```python
import torch

def _softmax(x, axis=-1):
    return torch.softmax(x, dim=axis)
def _gelu(x):
    return torch.nn.functional.gelu(x, approximate="tanh")
def _silu(x):
    return torch.nn.functional.silu(x)
def _sigmoid(x):
    return torch.sigmoid(x)
def _layernorm(x, axis=-1, eps=1e-5):
    m = x.mean(dim=axis, keepdim=True)
    v = x.var(dim=axis, keepdim=True, unbiased=False)
    return (x - m) / torch.sqrt(v + eps)
def _scatter_add(tgt, idx, src, axis=0):
    return tgt.clone().index_add_(axis, idx, src)
def _segment_sum(src, seg, n):
    out = torch.zeros((n,) + src.shape[1:], dtype=src.dtype)
    return out.index_add_(0, seg, src)
def _pad(x, pw):
    flat = tuple(v for pair in reversed(pw) for v in pair)
    return torch.nn.functional.pad(x, flat)

kernel_name = 'concat_heads__ssm_conv_s4__linear_attn_block__prompt'

def setup_inputs():

    _w = (lambda a: (lambda t: t.to(torch.bfloat16) if t.is_floating_point() else t)(torch.as_tensor(a)))
    def _A_setup():
        B, L, D, N = 1, 2048, 512, 128
        A_re = -(lambda _x: torch.exp(torch.as_tensor(_x)))((lambda *s: torch.randn(*s, dtype=torch.bfloat16) * 6.4)(D, N))
        A_im = torch.pi * (lambda *s: torch.randn(*s, dtype=torch.bfloat16) * 0.05)(D, N)
        B_re = (lambda *s: torch.randn(*s, dtype=torch.bfloat16) * 0.1)(D, N)
        B_im = (lambda *s: torch.randn(*s, dtype=torch.bfloat16) * 0.1)(D, N)
        C_re = (lambda *s: torch.randn(*s, dtype=torch.bfloat16) * 0.1)(D, N)
        C_im = (lambda *s: torch.randn(*s, dtype=torch.bfloat16) * 0.1)(D, N)
        log_dt = (lambda *s: torch.randn(*s, dtype=torch.bfloat16) * 0.05)(D) * 0.5 - 4.0
        Dskip = (lambda *s: torch.randn(*s, dtype=torch.bfloat16) * 0.05)(D)
        return {
            "u": _w((lambda *s: torch.randn(*s, dtype=torch.bfloat16) * 0.05)(B, L, D)),
            "A_re": _w(A_re),
            "A_im": _w(A_im),
            "B_re": _w(B_re),
            "B_im": _w(B_im),
            "C_re": _w(C_re),
            "C_im": _w(C_im),
            "log_dt": _w(log_dt),
            "Dskip": _w(Dskip),
        }
    _A_in = _A_setup()

    def _B_setup():
        B, S, D = 1, 2048, 512
        return {
            "x": _w((lambda *s: torch.randn(*s, dtype=torch.bfloat16) * 0.05)(B, S, D)),
            "wqkv": _w((lambda *s: torch.randn(*s, dtype=torch.bfloat16) * 0.4)(D, 3 * D)),
            "wo": _w((lambda *s: torch.randn(*s, dtype=torch.bfloat16) * 0.05)(D, D)),
        }
    _B_in = _B_setup()

    return {
        "A_u": _A_in["u"],
        "A_A_re": _A_in["A_re"],
        "A_A_im": _A_in["A_im"],
        "A_B_re": _A_in["B_re"],
        "A_B_im": _A_in["B_im"],
        "A_C_re": _A_in["C_re"],
        "A_C_im": _A_in["C_im"],
        "A_log_dt": _A_in["log_dt"],
        "A_Dskip": _A_in["Dskip"],
        "B_x": _B_in["x"],
        "B_wqkv": _B_in["wqkv"],
        "B_wo": _B_in["wo"],
    }

def reference(A_u, A_A_re, A_A_im, A_B_re, A_B_im, A_C_re, A_C_im, A_log_dt, A_Dskip, B_x, B_wqkv, B_wo):
    def _A_ref(u, A_re, A_im, B_re, B_im, C_re, C_im, log_dt, Dskip):
        Bsz, L, D = u.shape
        dt = torch.exp(log_dt)[:, None]
        A = A_re + 1j * A_im
        Bc = B_re + 1j * B_im
        Cc = C_re + 1j * C_im
        logdA = dt * A
        dB = dt * Bc
        l = (lambda x, dt: x.to(dt))(torch.arange(L), A_re.dtype)
        P = torch.exp(logdA[:, :, None] * l[None, None, :])
        K = torch.einsum("dn,dnl,dn->dl", Cc, P, dB).real
        L2 = 2 * L
        Kp = _pad(K, ((0, 0), (0, L)))
        up = (lambda x, *d: x.permute(*d))(u, 0, 2, 1)
        up = _pad(up, ((0, 0), (0, 0), (0, L)))
        Kf = (lambda x, axes=(-2,-1): torch.fft.rfft2(x.float(), dim=axes))(Kp[:, None, :], axes=(-2, -1))
        Uf = (lambda x, axes=(-2,-1): torch.fft.rfft2(x.float(), dim=axes))(up[:, :, None, :], axes=(-2, -1))
        Yf = Uf * Kf[None, :, :, :]
        y = (lambda x, s, axes=(-2,-1): torch.fft.irfft2(x, s=s, dim=axes).to(torch.bfloat16))(Yf, (1, L2), axes=(-2, -1))[:, :, 0, :L]
        y = (lambda x, *d: x.permute(*d))(y, 0, 2, 1) + u * Dskip[None, None, :]
        return y

    def _B_ref(x, wqkv, wo):
        B, S, D = x.shape
        H = 32; Dh = D // H
        qkv = (lambda x, *d: x.permute(*d))((x @ wqkv).reshape(B, S, 3, H, Dh), 2, 0, 3, 1, 4)
        q, k, v = qkv[0], qkv[1], qkv[2]
        phi = lambda t: torch.where(t > 0, t + 1, torch.exp(t)) + 1e-6
        pq, pk = phi(q), phi(k)
        kv = torch.einsum("bhsd,bhse->bhde", pk, v)
        z = torch.einsum("bhsd->bhd", pk)
        num = torch.einsum("bhqd,bhde->bhqe", pq, kv)
        den = torch.einsum("bhqd,bhd->bhq", pq, z)[..., None] + 1e-6
        o = num / den
        return (lambda x, *d: x.permute(*d))(o, 0, 2, 1, 3).reshape(B, S, D) @ wo

    a = _A_ref(A_u, A_A_re, A_A_im, A_B_re, A_B_im, A_C_re, A_C_im, A_log_dt, A_Dskip)
    b = _B_ref(B_x, B_wqkv, B_wo)
    return torch.concatenate([a, b], axis=-1)
```

```cpp
#include <cuda_runtime.h>
#include <cuda_bf16.h>
#include <cuda_fp16.h>
#include <cuda.h>
#include <stdint.h>

#define DEVI __device__ __forceinline__

namespace s4la {

constexpr int NTHREADS = 512;
constexpr int NCTA = 128;

constexpr uint32_t STG_BYTES = 40960, STG_X = 0, STG_W = 16384;
constexpr uint32_t SM_WO = 0;
constexpr uint32_t SM_BOUT = 65536;
constexpr uint32_t SM_PK = 81920;
constexpr uint32_t SM_VS = 98304;
constexpr uint32_t SM_TIN2 = 81920, SM_TOUT2 = 98304;
constexpr uint32_t SM_U = 122880, U_BYTES = 4352;
constexpr uint32_t SM_P = 140288, P_BYTES = 4096;
constexpr uint32_t SM_TIN1 = SM_U, SM_TOUT1 = SM_P;
constexpr uint32_t SM_VV = 156672, VV_BYTES = 13312;
constexpr uint32_t VV_U5 = 0, VV_U3 = 3712, VV_U9 = 7424, VV_U7 = 10112;
constexpr uint32_t VV_KF = 8192;
constexpr uint32_t SM_BAR = 209920;
constexpr uint32_t SM_MISC = SM_BAR + 256;
constexpr uint32_t SM_TOTAL = SM_MISC + 128;
constexpr int PADV = 12;

enum { B_FULL = 0, B_EMPTY = 3, B_WO = 6, B_UTILE = 7, B_YTILE = 8, B_UCH = 9, B_QKVDONE = 13,
       B_CONVDONE = 14, B_TRDONE = 15, B_PKVFREE = 16, B_COUNT = 17 };

constexpr int PD_OFF = 0, P2_OFF = 544, P3_OFF = 768;

__device__ __nv_bfloat16 g_uT[512 * 2048];
__device__ __nv_bfloat16 g_yT[512 * 2048];
__device__ uint4 g_ofrag[16 * 8 * 32 * 32];
__device__ float g_kv[2][8][4][272];
__device__ unsigned g_cnt[64 * 32];
__device__ unsigned g_epoch;
#define TS(slot) do { } while (0)
enum { C_U = 0, C_KV = 8, C_O = 16, C_Y = 32 };

struct Maps {
  CUtensorMap x, w, wo, u, uT, yT, out;
};
struct Ptrs {
  const __nv_bfloat16 *A_re, *A_im, *B_re, *B_im, *C_re, *C_im, *log_dt, *Dskip;
  const __nv_bfloat16 *x, *wqkv, *wo;
  __nv_bfloat16 *uT, *yT;
};

DEVI uint32_t s2u(const void* p) { return (uint32_t)__cvta_generic_to_shared(p); }
DEVI void mbar_init(uint32_t b, uint32_t c) { asm volatile("mbarrier.init.shared::cta.b64 [%0], %1;" ::"r"(b), "r"(c) : "memory"); }
DEVI void mbar_expect_tx(uint32_t b, uint32_t bytes) {
  asm volatile("mbarrier.arrive.expect_tx.shared::cta.b64 _, [%0], %1;" ::"r"(b), "r"(bytes) : "memory");
}
DEVI void mbar_arrive(uint32_t b) { asm volatile("mbarrier.arrive.shared::cta.b64 _, [%0];" ::"r"(b) : "memory"); }
DEVI void mbar_arrive_cluster(uint32_t b, uint32_t cta) {
  asm volatile("{\n.reg .b32 r;\nmapa.shared::cluster.u32 r, %0, %1;\nmbarrier.arrive.shared::cluster.b64 _, [r];\n}"
               ::"r"(b), "r"(cta) : "memory");
}
DEVI void mbar_wait(uint32_t b, uint32_t parity) {
  asm volatile("{\n.reg .pred p;\nLAB_WAIT:\nmbarrier.try_wait.parity.shared::cta.b64 p, [%0], %1;\n@p bra LAB_DONE;\nbra LAB_WAIT;\nLAB_DONE:\n}"
               ::"r"(b), "r"(parity) : "memory");
}
DEVI void mbar_wait_cluster(uint32_t b, uint32_t parity) {
  asm volatile("{\n.reg .pred p;\nLAB_WAIT:\nmbarrier.try_wait.parity.shared::cta.b64 p, [%0], %1;\n@p bra LAB_DONE;\nbra LAB_WAIT;\nLAB_DONE:\n}"
               ::"r"(b), "r"(parity) : "memory");
}
DEVI void bar_sync(int id, int n) { asm volatile("bar.sync %0, %1;" ::"r"(id), "r"(n) : "memory"); }
DEVI void fence_async_smem() { asm volatile("fence.proxy.async.shared::cta;" ::: "memory"); }
DEVI void fence_async_all() { asm volatile("fence.proxy.async;" ::: "memory"); }
DEVI void cluster_arrive() { asm volatile("barrier.cluster.arrive.relaxed.aligned;" ::: "memory"); }
DEVI void cluster_wait() { asm volatile("barrier.cluster.wait.aligned;" ::: "memory"); }

DEVI void tma_load_2d(uint32_t dst, const CUtensorMap* m, int c0, int c1, uint32_t bar) {
  asm volatile("cp.async.bulk.tensor.2d.shared::cluster.global.mbarrier::complete_tx::bytes [%0], [%1, {%3, %4}], [%2];"
               ::"r"(dst), "l"(m), "r"(bar), "r"(c0), "r"(c1) : "memory");
}
DEVI void tma_load_2d_mc(uint32_t dst, const CUtensorMap* m, int c0, int c1, uint32_t bar, uint16_t mask) {
  asm volatile("cp.async.bulk.tensor.2d.shared::cluster.global.mbarrier::complete_tx::bytes.multicast::cluster [%0], [%1, {%3, %4}], [%2], %5;"
               ::"r"(dst), "l"(m), "r"(bar), "r"(c0), "r"(c1), "h"(mask) : "memory");
}
DEVI void tma_store_2d(const CUtensorMap* m, uint32_t src, int c0, int c1) {
  asm volatile("cp.async.bulk.tensor.2d.global.shared::cta.bulk_group [%0, {%2, %3}], [%1];"
               ::"l"(m), "r"(src), "r"(c0), "r"(c1) : "memory");
}
DEVI void bulk_load(uint32_t dst, const void* src, uint32_t bytes, uint32_t bar) {
  asm volatile("cp.async.bulk.shared::cluster.global.mbarrier::complete_tx::bytes [%0], [%1], %2, [%3];"
               ::"r"(dst), "l"(src), "r"(bytes), "r"(bar) : "memory");
}
DEVI void bulk_store(void* dst, uint32_t src, uint32_t bytes) {
  asm volatile("cp.async.bulk.global.shared::cta.bulk_group [%0], [%1], %2;" ::"l"(dst), "r"(src), "r"(bytes) : "memory");
}
DEVI void bulk_commit() { asm volatile("cp.async.bulk.commit_group;" ::: "memory"); }
DEVI void bulk_wait0() { asm volatile("cp.async.bulk.wait_group 0;" ::: "memory"); }
DEVI void l2_prefetch(const void* p, uint32_t bytes) {
  asm volatile("cp.async.bulk.prefetch.L2.global [%0], %1;" ::"l"(p), "r"(bytes) : "memory");
}
DEVI void prefetch_tmap(const CUtensorMap* m) { asm volatile("prefetch.tensormap [%0];" ::"l"(m) : "memory"); }

DEVI void red_release_add(unsigned* p, unsigned v) {
  asm volatile("red.release.gpu.global.add.u32 [%0], %1;" ::"l"(p), "r"(v) : "memory");
}
DEVI unsigned ld_acquire(const unsigned* p) {
  unsigned v;
  asm volatile("ld.acquire.gpu.global.u32 %0, [%1];" : "=r"(v) : "l"(p) : "memory");
  return v;
}
DEVI void wait_counter(const unsigned* p, unsigned target) {
#pragma unroll 1
  for (int it = 0; it < (1 << 22); ++it) {
    if ((int)(ld_acquire(p) - target) >= 0) return;
    __nanosleep(32);
  }
  __trap();
}

DEVI void ldsm_x4(uint32_t (&r)[4], uint32_t a) {
  asm volatile("ldmatrix.sync.aligned.m8n8.x4.shared.b16 {%0,%1,%2,%3}, [%4];"
               : "=r"(r[0]), "=r"(r[1]), "=r"(r[2]), "=r"(r[3]) : "r"(a) : "memory");
}
DEVI void ldsm_x4_t(uint32_t (&r)[4], uint32_t a) {
  asm volatile("ldmatrix.sync.aligned.m8n8.x4.trans.shared.b16 {%0,%1,%2,%3}, [%4];"
               : "=r"(r[0]), "=r"(r[1]), "=r"(r[2]), "=r"(r[3]) : "r"(a) : "memory");
}
DEVI void ldsm_x2_t(uint32_t& r0, uint32_t& r1, uint32_t a) {
  asm volatile("ldmatrix.sync.aligned.m8n8.x2.trans.shared.b16 {%0,%1}, [%2];" : "=r"(r0), "=r"(r1) : "r"(a) : "memory");
}
DEVI void stsm_x4(uint32_t a, uint32_t r0, uint32_t r1, uint32_t r2, uint32_t r3) {
  asm volatile("stmatrix.sync.aligned.m8n8.x4.shared.b16 [%0], {%1,%2,%3,%4};"
               ::"r"(a), "r"(r0), "r"(r1), "r"(r2), "r"(r3) : "memory");
}
DEVI void stsm_x4_t(uint32_t a, uint32_t r0, uint32_t r1, uint32_t r2, uint32_t r3) {
  asm volatile("stmatrix.sync.aligned.m8n8.x4.trans.shared.b16 [%0], {%1,%2,%3,%4};"
               ::"r"(a), "r"(r0), "r"(r1), "r"(r2), "r"(r3) : "memory");
}
DEVI uint32_t lds32(uint32_t a) { uint32_t v; asm volatile("ld.shared.b32 %0, [%1];" : "=r"(v) : "r"(a) : "memory"); return v; }
DEVI float lds_f32(uint32_t a) { float v; asm volatile("ld.shared.f32 %0, [%1];" : "=f"(v) : "r"(a) : "memory"); return v; }
DEVI void sts32(uint32_t a, uint32_t v) { asm volatile("st.shared.b32 [%0], %1;" ::"r"(a), "r"(v) : "memory"); }
DEVI void sts_f32(uint32_t a, float v) { asm volatile("st.shared.f32 [%0], %1;" ::"r"(a), "f"(v) : "memory"); }
DEVI void sts_f32x2(uint32_t a, float x, float y) { asm volatile("st.shared.v2.f32 [%0], {%1,%2};" ::"r"(a), "f"(x), "f"(y) : "memory"); }
DEVI uint4 lds128(uint32_t a) {
  uint4 v;
  asm volatile("ld.shared.v4.b32 {%0,%1,%2,%3}, [%4];" : "=r"(v.x), "=r"(v.y), "=r"(v.z), "=r"(v.w) : "r"(a) : "memory");
  return v;
}
DEVI void sts128(uint32_t a, uint32_t x, uint32_t y, uint32_t z, uint32_t w) {
  asm volatile("st.shared.v4.b32 [%0], {%1,%2,%3,%4};" ::"r"(a), "r"(x), "r"(y), "r"(z), "r"(w) : "memory");
}

DEVI void mma_bf16(float (&d)[4], uint32_t a0, uint32_t a1, uint32_t a2, uint32_t a3, uint32_t b0, uint32_t b1) {
  asm("mma.sync.aligned.m16n8k16.row.col.f32.bf16.bf16.f32 {%0,%1,%2,%3}, {%4,%5,%6,%7}, {%8,%9}, {%0,%1,%2,%3};"
      : "+f"(d[0]), "+f"(d[1]), "+f"(d[2]), "+f"(d[3])
      : "r"(a0), "r"(a1), "r"(a2), "r"(a3), "r"(b0), "r"(b1));
}
DEVI uint32_t pack_bf16(float lo, float hi) {
  uint32_t r;
  asm("cvt.rn.bf16x2.f32 %0, %1, %2;" : "=r"(r) : "f"(hi), "f"(lo));
  return r;
}
DEVI uint32_t pack_f16(float lo, float hi) {
  uint32_t r;
  asm("cvt.rn.f16x2.f32 %0, %1, %2;" : "=r"(r) : "f"(hi), "f"(lo));
  return r;
}
DEVI float bf_lo(uint32_t v) { return __uint_as_float(v << 16); }
DEVI float bf_hi(uint32_t v) { return __uint_as_float(v & 0xffff0000u); }
DEVI float bf2f(__nv_bfloat16 v) { return __bfloat162float(v); }
DEVI float round_bf16(float v) { return __bfloat162float(__float2bfloat16_rn(v)); }
DEVI float ex2(float x) { float r; asm("ex2.approx.ftz.f32 %0, %1;" : "=f"(r) : "f"(x)); return r; }

DEVI void wg_fence() { asm volatile("wgmma.fence.sync.aligned;" ::: "memory"); }
DEVI void wg_commit() { asm volatile("wgmma.commit_group.sync.aligned;" ::: "memory"); }
template <int N> DEVI void wg_wait() { asm volatile("wgmma.wait_group.sync.aligned %0;" ::"n"(N) : "memory"); }
DEVI uint64_t mkdesc(uint32_t saddr, uint32_t lbo, uint32_t sbo) {
  return (uint64_t)((saddr & 0x3FFFF) >> 4) | ((uint64_t)(lbo >> 4) << 16) | ((uint64_t)(sbo >> 4) << 32) | (1ull << 62);
}

#define R8(b) "%" #b
DEVI void wgmma_n192(float (&d)[96], uint64_t da, uint64_t db, int scale_d) {
  asm volatile(
      "{\n.reg .pred p;\nsetp.ne.b32 p, %98, 0;\n"
      "wgmma.mma_async.sync.aligned.m64n192k16.f32.bf16.bf16 "
      "{%0,%1,%2,%3,%4,%5,%6,%7,%8,%9,%10,%11,%12,%13,%14,%15,"
      "%16,%17,%18,%19,%20,%21,%22,%23,%24,%25,%26,%27,%28,%29,%30,%31,"
      "%32,%33,%34,%35,%36,%37,%38,%39,%40,%41,%42,%43,%44,%45,%46,%47,"
      "%48,%49,%50,%51,%52,%53,%54,%55,%56,%57,%58,%59,%60,%61,%62,%63,"
      "%64,%65,%66,%67,%68,%69,%70,%71,%72,%73,%74,%75,%76,%77,%78,%79,"
      "%80,%81,%82,%83,%84,%85,%86,%87,%88,%89,%90,%91,%92,%93,%94,%95}, "
      "%96, %97, p, 1, 1, 0, 1;\n}"
      : "+f"(d[0]), "+f"(d[1]), "+f"(d[2]), "+f"(d[3]), "+f"(d[4]), "+f"(d[5]), "+f"(d[6]), "+f"(d[7]),
        "+f"(d[8]), "+f"(d[9]), "+f"(d[10]), "+f"(d[11]), "+f"(d[12]), "+f"(d[13]), "+f"(d[14]), "+f"(d[15]),
        "+f"(d[16]), "+f"(d[17]), "+f"(d[18]), "+f"(d[19]), "+f"(d[20]), "+f"(d[21]), "+f"(d[22]), "+f"(d[23]),
        "+f"(d[24]), "+f"(d[25]), "+f"(d[26]), "+f"(d[27]), "+f"(d[28]), "+f"(d[29]), "+f"(d[30]), "+f"(d[31]),
        "+f"(d[32]), "+f"(d[33]), "+f"(d[34]), "+f"(d[35]), "+f"(d[36]), "+f"(d[37]), "+f"(d[38]), "+f"(d[39]),
        "+f"(d[40]), "+f"(d[41]), "+f"(d[42]), "+f"(d[43]), "+f"(d[44]), "+f"(d[45]), "+f"(d[46]), "+f"(d[47]),
        "+f"(d[48]), "+f"(d[49]), "+f"(d[50]), "+f"(d[51]), "+f"(d[52]), "+f"(d[53]), "+f"(d[54]), "+f"(d[55]),
        "+f"(d[56]), "+f"(d[57]), "+f"(d[58]), "+f"(d[59]), "+f"(d[60]), "+f"(d[61]), "+f"(d[62]), "+f"(d[63]),
        "+f"(d[64]), "+f"(d[65]), "+f"(d[66]), "+f"(d[67]), "+f"(d[68]), "+f"(d[69]), "+f"(d[70]), "+f"(d[71]),
        "+f"(d[72]), "+f"(d[73]), "+f"(d[74]), "+f"(d[75]), "+f"(d[76]), "+f"(d[77]), "+f"(d[78]), "+f"(d[79]),
        "+f"(d[80]), "+f"(d[81]), "+f"(d[82]), "+f"(d[83]), "+f"(d[84]), "+f"(d[85]), "+f"(d[86]), "+f"(d[87]),
        "+f"(d[88]), "+f"(d[89]), "+f"(d[90]), "+f"(d[91]), "+f"(d[92]), "+f"(d[93]), "+f"(d[94]), "+f"(d[95])
      : "l"(da), "l"(db), "r"(scale_d));
}
DEVI void wgmma_n64_rs(float (&d)[32], const uint4& a, uint64_t db, int scale_d) {
  asm volatile(
      "{\n.reg .pred p;\nsetp.ne.b32 p, %37, 0;\n"
      "wgmma.mma_async.sync.aligned.m64n64k16.f32.bf16.bf16 "
      "{%0,%1,%2,%3,%4,%5,%6,%7,%8,%9,%10,%11,%12,%13,%14,%15,"
      "%16,%17,%18,%19,%20,%21,%22,%23,%24,%25,%26,%27,%28,%29,%30,%31}, "
      "{%32,%33,%34,%35}, %36, p, 1, 1, 1;\n}"
      : "+f"(d[0]), "+f"(d[1]), "+f"(d[2]), "+f"(d[3]), "+f"(d[4]), "+f"(d[5]), "+f"(d[6]), "+f"(d[7]),
        "+f"(d[8]), "+f"(d[9]), "+f"(d[10]), "+f"(d[11]), "+f"(d[12]), "+f"(d[13]), "+f"(d[14]), "+f"(d[15]),
        "+f"(d[16]), "+f"(d[17]), "+f"(d[18]), "+f"(d[19]), "+f"(d[20]), "+f"(d[21]), "+f"(d[22]), "+f"(d[23]),
        "+f"(d[24]), "+f"(d[25]), "+f"(d[26]), "+f"(d[27]), "+f"(d[28]), "+f"(d[29]), "+f"(d[30]), "+f"(d[31])
      : "r"(a.x), "r"(a.y), "r"(a.z), "r"(a.w), "l"(db), "r"(scale_d));
}
DEVI void wgmma_n16_f16(float (&d)[8], uint64_t da, uint64_t db, int scale_d) {
  asm volatile(
      "{\n.reg .pred p;\nsetp.ne.b32 p, %10, 0;\n"
      "wgmma.mma_async.sync.aligned.m64n16k16.f32.f16.f16 {%0,%1,%2,%3,%4,%5,%6,%7}, %8, %9, p, 1, 1, 0, 0;\n}"
      : "+f"(d[0]), "+f"(d[1]), "+f"(d[2]), "+f"(d[3]), "+f"(d[4]), "+f"(d[5]), "+f"(d[6]), "+f"(d[7])
      : "l"(da), "l"(db), "r"(scale_d));
}

template <int MODE>
DEVI void transpose_tile(uint32_t src, uint32_t dst, int lane) {
  const int m = lane >> 3, r = lane & 7;
#pragma unroll 4
  for (int it = 0; it < 32; ++it) {
    uint32_t v[4];
    if (MODE == 0) {
      const int tb = it >> 1, cb0 = (it & 1) * 4;
      const int row = tb * 8 + r;
      ldsm_x4_t(v, src + row * 128 + (((cb0 + m) ^ r) << 4));
      const int b = tb >> 3;
      const int ch = (cb0 + m) * 8 + r;
      const int chunk = (tb & 7) ^ b;
      stsm_x4(dst + b * 8192 + ch * 128 + ((chunk ^ r) << 4), v[0], v[1], v[2], v[3]);
    } else {
      const int cb = it & 7, tb = (it >> 3) * 4 + m;
      const int b = tb >> 3;
      const int ch = cb * 8 + r;
      ldsm_x4_t(v, src + b * 8192 + ch * 128 + (((tb & 7) ^ r) << 4));
      const int t = tb * 8 + r;
      stsm_x4(dst + t * 128 + ((cb ^ r) << 4), v[0], v[1], v[2], v[3]);
    }
  }
}

struct C32 { float re, im; };
DEVI C32 csq(C32 a) { return {a.re * a.re - a.im * a.im, 2.f * a.re * a.im}; }
DEVI C32 cmul(C32 a, C32 b) { return {a.re * b.re - a.im * b.im, a.re * b.im + a.im * b.re}; }
DEVI C32 cfresh(float zl, float zi, float m) {
  float mag = ex2(zl * m), ph = zi * m;
  return {mag * __cosf(ph), mag * __sinf(ph)};
}
struct HMul { uint32_t b, bp; };
DEVI HMul mk_mul(float re, float im) { return {pack_f16(re, im), pack_f16(-im, re)}; }
DEVI uint32_t hcmul(uint32_t a, const HMul& m) {
  __half2 ah = *reinterpret_cast<__half2*>(&a);
  __half2 b = *reinterpret_cast<const __half2*>(&m.b), bp = *reinterpret_cast<const __half2*>(&m.bp);
  __half2 r = __hfma2(__high2half2(ah), bp, __hmul2(__low2half2(ah), b));
  return *reinterpret_cast<uint32_t*>(&r);
}

DEVI int kidx(int l) {
  int r = (l >> 3) & 15, y;
  if (l < 256) y = (l & 7) + ((l >> 7) << 3);
  else if (l < 512) y = 16 + (((l - 256) >> 7) << 2) + ((l & 7) >> 1);
  else if (l < 1024) y = 24 + (((l - 512) >> 7) << 1) + ((l >> 2) & 1);
  else y = 32 + ((l - 1024) >> 7);
  return y * 16 + r;
}
DEVI int kidx_l(int y, int r) {
  int lo;
  if (y < 16) lo = (y & 7) + ((y >> 3) << 7);
  else if (y < 24) lo = 256 + (((y - 16) >> 2) << 7) + ((y & 3) << 1);
  else if (y < 32) lo = 512 + (((y - 24) >> 1) << 7) + ((y & 1) << 2);
  else lo = 1024 + ((y - 32) << 7);
  return lo + 8 * r;
}

template <int EXTRA>
DEVI void conv_direct(float (&acc)[16][4], uint32_t pd_lane, uint32_t u_base, int rho, int lane, uint32_t h127,
                      uint32_t h128) {
  uint32_t A[4][3];
#pragma unroll
  for (int i = 0; i < 4; ++i) {
    uint32_t a = pd_lane + (uint32_t)(2 * rho + 16 * i) * 32;
    A[i][0] = lds32(a);
    A[i][1] = lds32(a + 32);
    A[i][2] = lds32(a - 32);
  }
  uint32_t h63 = 0, h64 = 0;
  if (EXTRA == 1) { h63 = lds32(pd_lane + 63 * 32); h64 = lds32(pd_lane + 64 * 32); }
  const int prow = 8 - rho + (lane & 7) + ((lane >> 4) << 3);
  const uint32_t la = u_base + prow * 32 + ((((lane >> 3) & 1) ^ ((prow >> 2) & 1)) << 4);
  uint32_t B[2][4];
  ldsm_x4(B[0], la);
#pragma unroll
  for (int m2 = 0; m2 < 8; ++m2) {
    if (m2 < 7) ldsm_x4(B[(m2 + 1) & 1], la + (m2 + 1) * 512);
#pragma unroll
    for (int h = 0; h < 2; ++h) {
      const int m = 2 * m2 + h;
      const uint32_t b0 = B[m2 & 1][2 * h], b1 = B[m2 & 1][2 * h + 1];
#pragma unroll
      for (int i = 0; i < 4; ++i)
        if (m + i < 16) mma_bf16(acc[m + i], A[i][0], A[i][1], A[i][2], A[i][0], b0, b1);
      if (EXTRA == 1) {
        if (m + 4 < 16) mma_bf16(acc[m + 4], h64, 0u, h63, h64, b0, b1);
        if (m + 8 < 16) mma_bf16(acc[m + 8], h128, 0u, h127, h128, b0, b1);
      }
      if (EXTRA == 2) {
        if (m + 7 < 16) mma_bf16(acc[m + 7], 0u, h127, 0u, 0u, b0, b1);
      }
    }
  }
}

template <int MU0, int NMU, int DMAX>
DEVI void conv_tail(float (&acc)[16][4], uint32_t p_lane, uint32_t v_base, int back, bool edge, int lane) {
  uint32_t H[2 * NMU];
#pragma unroll
  for (int i = 0; i < 2 * NMU; ++i) H[i] = lds32(p_lane + (uint32_t)(MU0 - 1 + i) * 32);
  const int hsel = (lane >> 3) & 1;
  int row = (lane & 7) + ((lane >> 4) << 3) + PADV;
  int half = hsel;
  if (back) { half = hsel ^ 1; row -= (hsel == 0) ? 1 : 0; }
  row -= 8;
  const uint32_t la = v_base + row * 32 + ((half ^ ((row >> 2) & 1)) << 4);
  constexpr int NLD = (DMAX + 3 + 1) / 2;
  uint32_t M[2][4];
  uint32_t p0 = 0, p1 = 0;
  ldsm_x4_t(M[0], la);
#pragma unroll
  for (int ld = 0; ld < NLD; ++ld) {
    if (ld + 1 < NLD) ldsm_x4_t(M[(ld + 1) & 1], la + (ld + 1) * 512);
    const uint32_t* c = M[ld & 1];
#pragma unroll
    for (int s = 0; s < 2; ++s) {
      const int delta = 2 * ld - 2 + s;
      if (delta > DMAX) continue;
      if (delta == -2 && !edge) continue;
      const uint32_t a0 = s ? c[0] : p0, a1 = s ? c[1] : p1, a2 = s ? c[2] : c[0], a3 = s ? c[3] : c[1];
#pragma unroll
      for (int k = 0; k < NMU; ++k) {
        const int nb = delta + MU0 + 2 * k;
        if (nb < 16) mma_bf16(acc[nb], a0, a1, a2, a3, H[2 * k + 1], H[2 * k]);
      }
    }
    p0 = c[2]; p1 = c[3];
  }
}

__global__ void __cluster_dims__(2, 1, 1) __launch_bounds__(NTHREADS, 1)
fused_kernel(const __grid_constant__ Maps maps, const Ptrs p, __nv_bfloat16* __restrict__ out) {
  extern __shared__ __align__(1024) uint8_t smem[];
  const uint32_t sb = s2u(smem);
  const int tid = threadIdx.x, warp = tid >> 5, lane = tid & 31;
  const int cta = blockIdx.x;
  const uint32_t rank = cta & 1;
  const int c2 = cta >> 1;
  const int ti = 2 * (c2 >> 3) + rank;
  const int tj = c2 & 7;
  auto bar = [&](int i) { return sb + SM_BAR + 8 * i; };

  if (tid == 0) {
    TS(0);
    for (int s = 0; s < 3; ++s) { mbar_init(bar(B_FULL + s), 1); mbar_init(bar(B_EMPTY + s), 16); }
    mbar_init(bar(B_WO), 1); mbar_init(bar(B_UTILE), 1); mbar_init(bar(B_YTILE), 1);
    for (int c = 0; c < 4; ++c) mbar_init(bar(B_UCH + c), 1);
    mbar_init(bar(B_QKVDONE), 8); mbar_init(bar(B_CONVDONE), 4); mbar_init(bar(B_TRDONE), 1);
    mbar_init(bar(B_PKVFREE), 8);
    asm volatile("fence.mbarrier_init.release.cluster;" ::: "memory");
  }
  if (tid == 32) {
    l2_prefetch((const char*)p.x + (size_t)cta * 16384, 16384);
    l2_prefetch((const char*)p.wqkv + (size_t)cta * 12288, 12288);
    l2_prefetch((const char*)p.wo + (size_t)cta * 4096, 4096);
  }
  if (tid == 384) {
    prefetch_tmap(&maps.x); prefetch_tmap(&maps.w); prefetch_tmap(&maps.u); prefetch_tmap(&maps.wo);
    prefetch_tmap(&maps.uT); prefetch_tmap(&maps.yT); prefetch_tmap(&maps.out);
  }
  __syncthreads();
  cluster_arrive();
  cluster_wait();
  const unsigned epoch = *(volatile unsigned*)&g_epoch;

  if (warp < 4) {
    asm volatile("setmaxnreg.inc.sync.aligned.u32 152;");
    const int ch = warp;
    const int d = cta * 4 + ch;
    const uint32_t vv = sb + SM_VV + ch * VV_BYTES;
    const uint32_t ub = sb + SM_U + ch * U_BYTES;
    const uint32_t pb = sb + SM_P + ch * P_BYTES;
    const uint32_t misc = sb + SM_MISC;
    const int g = lane >> 2, q = lane & 3;

    const size_t po = (size_t)d * 128 + lane * 4;
    const uint2 rAr = *(const uint2*)(p.A_re + po), rAi = *(const uint2*)(p.A_im + po);
    const uint2 rBr = *(const uint2*)(p.B_re + po), rBi = *(const uint2*)(p.B_im + po);
    const uint2 rCr = *(const uint2*)(p.C_re + po), rCi = *(const uint2*)(p.C_im + po);
    const float dt = round_bf16(expf(bf2f(p.log_dt[d])));
    const float dskip = bf2f(p.Dskip[d]);
    float zr[4], zi[4], wr[4], wi[4];
    {
      auto el = [](const uint2& v, int i) { uint32_t w = (i & 2) ? v.y : v.x; return (i & 1) ? bf_hi(w) : bf_lo(w); };
      float mz = 0.f, mw = 0.f;
#pragma unroll
      for (int i = 0; i < 4; ++i) {
        zr[i] = dt * el(rAr, i); zi[i] = dt * el(rAi, i);
        float br = dt * el(rBr, i), bi = dt * el(rBi, i), cr = el(rCr, i), ci = el(rCi, i);
        wr[i] = cr * br - ci * bi; wi[i] = cr * bi + ci * br;
        mz = fmaxf(mz, zr[i]); mw = fmaxf(mw, fmaxf(fabsf(wr[i]), fabsf(wi[i])));
      }
#pragma unroll
      for (int o = 16; o > 0; o >>= 1) {
        mz = fmaxf(mz, __shfl_xor_sync(0xffffffffu, mz, o));
        mw = fmaxf(mw, __shfl_xor_sync(0xffffffffu, mw, o));
      }
      int E = (__float_as_int(mw) >> 23) & 255;
      float sc = 1.f, inv = 1.f;
      if (E > 0 && E < 253) { sc = __int_as_float((253 - E) << 23); inv = __int_as_float((E + 1) << 23); }
#pragma unroll
      for (int i = 0; i < 4; ++i) { zr[i] = (zr[i] - mz) * 1.4426950408889634f; wr[i] *= sc; wi[i] *= sc; }
      if (lane == 0) { sts_f32(misc + ch * 4, inv); sts_f32(misc + 16 + ch * 4, mz * 1.4426950408889634f); }
    }
    if (lane == 0) TS(1);

    float Dk[4][8];
    float k2048 = 0.f;
    uint32_t laneoff[8];
#pragma unroll
    for (int i = 0; i < 8; ++i) laneoff[i] = vv + ((((lane >> 2) ^ i) << 4) | ((lane & 3) << 2));
#pragma unroll 1
    for (int rd = 0; rd < 4; ++rd) {
      const float zl = rd == 0 ? zr[0] : rd == 1 ? zr[1] : rd == 2 ? zr[2] : zr[3];
      const float zim = rd == 0 ? zi[0] : rd == 1 ? zi[1] : rd == 2 ? zi[2] : zi[3];
      const float w_r = rd == 0 ? wr[0] : rd == 1 ? wr[1] : rd == 2 ? wr[2] : wr[3];
      const float w_i = rd == 0 ? wi[0] : rd == 1 ? wi[1] : rd == 2 ? wi[2] : wi[3];
      uint32_t val[56];
      {
        C32 e1 = cfresh(zl, zim, 1.f), e2 = csq(e1), e4 = csq(e2), e8 = csq(e4);
        C32 e16 = cfresh(zl, zim, 16.f), e32 = csq(e16), e64 = csq(e32), e128 = csq(e64);
        C32 e256 = cfresh(zl, zim, 256.f), e512 = csq(e256), e1024 = csq(e512), e2048 = csq(e1024);
        k2048 += w_r * e2048.re - w_i * e2048.im;
        HMul m16 = mk_mul(e16.re, e16.im), m32 = mk_mul(e32.re, e32.im), m64 = mk_mul(e64.re, e64.im);
        uint32_t* X = val + 40;
        X[0] = 0x00003c00u;
        X[1] = pack_f16(e8.re, e8.im); X[2] = m16.b; X[4] = m32.b; X[8] = m64.b;
        X[3] = hcmul(X[1], m16); X[5] = hcmul(X[1], m32); X[6] = hcmul(X[2], m32); X[7] = hcmul(X[3], m32);
#pragma unroll
        for (int r = 1; r < 8; ++r) X[8 + r] = hcmul(X[r], m64);
        HMul c1 = mk_mul(e1.re, -e1.im), c2 = mk_mul(e2.re, -e2.im), c4 = mk_mul(e4.re, -e4.im);
        uint32_t W[8];
        W[0] = pack_f16(w_r, -w_i);
        W[1] = hcmul(W[0], c1); W[2] = hcmul(W[0], c2); W[3] = hcmul(W[1], c2);
        W[4] = hcmul(W[0], c4); W[5] = hcmul(W[1], c4); W[6] = hcmul(W[2], c4); W[7] = hcmul(W[3], c4);
        C32 e384 = cmul(e256, e128), e640 = cmul(e512, e128), e768 = cmul(e512, e256), e896 = cmul(e768, e128);
        HMul c128 = mk_mul(e128.re, -e128.im), c256 = mk_mul(e256.re, -e256.im), c384 = mk_mul(e384.re, -e384.im);
        HMul c512 = mk_mul(e512.re, -e512.im), c640 = mk_mul(e640.re, -e640.im), c768 = mk_mul(e768.re, -e768.im);
        HMul c896 = mk_mul(e896.re, -e896.im), c1024 = mk_mul(e1024.re, -e1024.im);
#pragma unroll
        for (int i = 0; i < 8; ++i) { val[i] = W[i]; val[8 + i] = hcmul(W[i], c128); }
#pragma unroll
        for (int i = 0; i < 4; ++i) { val[16 + i] = hcmul(W[2 * i], c256); val[20 + i] = hcmul(W[2 * i], c384); }
        val[24] = hcmul(W[0], c512); val[25] = hcmul(W[4], c512);
        val[26] = hcmul(W[0], c640); val[27] = hcmul(W[4], c640);
        val[28] = hcmul(W[0], c768); val[29] = hcmul(W[4], c768);
        val[30] = hcmul(W[0], c896); val[31] = hcmul(W[4], c896);
        const uint32_t v0 = hcmul(W[0], c1024);
        val[32] = v0; val[33] = hcmul(v0, c128); val[34] = hcmul(v0, c256); val[35] = hcmul(v0, c384);
        val[36] = hcmul(v0, c512); val[37] = hcmul(v0, c640); val[38] = hcmul(v0, c768); val[39] = hcmul(v0, c896);
      }
      if (rd > 0) { wg_wait<0>(); bar_sync(2, 128); }
#pragma unroll
      for (int r = 0; r < 56; ++r) sts32(laneoff[r & 7] + r * 128, val[r]);
      fence_async_smem();
      bar_sync(2, 128);
      wg_fence();
#pragma unroll
      for (int c = 0; c < 4; ++c) {
        const uint32_t tb = sb + SM_VV + c * VV_BYTES;
        const uint64_t da = mkdesc(tb, 16, 1024), db = mkdesc(tb + 5120, 16, 1024);
#pragma unroll
        for (int k = 0; k < 4; ++k) wgmma_n16_f16(Dk[c], da + 2 * k, db + 2 * k, (rd | k) != 0);
      }
      wg_commit();
    }
    wg_wait<0>();
    bar_sync(2, 128);
    if (warp < 3) {
#pragma unroll
      for (int c = 0; c < 4; ++c) {
        const float inv = lds_f32(misc + c * 4), zt = lds_f32(misc + 16 + c * 4);
        const uint32_t kf = sb + SM_VV + c * VV_BYTES + VV_KF;
#pragma unroll
        for (int hh = 0; hh < 2; ++hh) {
          const int y = 16 * warp + g + 8 * hh;
          if (y < 40) {
#pragma unroll
            for (int i = 0; i < 2; ++i) {
              const int r = 8 * i + 2 * q;
              float a = Dk[c][4 * i + 2 * hh] * inv, b = Dk[c][4 * i + 2 * hh + 1] * inv;
              if (zt > 0.f) { a *= ex2(zt * kidx_l(y, r)); b *= ex2(zt * kidx_l(y, r + 1)); }
              sts_f32x2(kf + (y * 16 + r) * 4, a, b);
            }
          }
        }
      }
    }
#pragma unroll
    for (int o = 16; o > 0; o >>= 1) k2048 += __shfl_xor_sync(0xffffffffu, k2048, o);
    {
      const float zt = lds_f32(misc + 16 + ch * 4);
      k2048 *= lds_f32(misc + ch * 4);
      if (zt > 0.f) k2048 *= ex2(zt * 2048.f);
    }
    if (lane == 0) TS(2);
    mbar_wait(bar(B_TRDONE), 0);
    bar_sync(2, 128);
    if (lane == 0) {
      wait_counter(&g_cnt[(C_U + (cta >> 4)) * 32], (epoch + 1) * 16);
      fence_async_all();
      mbar_expect_tx(bar(B_UCH + ch), 4096);
      bulk_load(ub + 256, p.uT + (size_t)d * 2048, 4096, bar(B_UCH + ch));
      TS(3);
    }
    if (lane < 16) sts128(ub + lane * 16, 0, 0, 0, 0);
    const uint32_t kf = vv + VV_KF;
    float k1024;
    {
      const float k512 = lds_f32(kf + kidx(512) * 4);
      k1024 = lds_f32(kf + kidx(1024) * 4);
      auto kd = [&](int l) -> float {
        if (l < 0 || l > 510) return 0.f;
        int lr = l < 256 ? l : ((l + ((l >> 1) & 1)) & ~1);
        float v = lds_f32(kf + kidx(lr) * 4);
        if (l == 510) v -= k512;
        if (l == 0) v += dskip;
        return v;
      };
      int x = -16 + 17 * lane;
      float prev = kd(x - 1);
#pragma unroll 1
      for (int i = 0; i < 17; ++i, ++x) {
        float cur = kd(x);
        sts32(pb + (PD_OFF + x + 16) * 4, pack_bf16(cur, prev));
        prev = cur;
      }
      {
        const int v = lane >> 3;
        auto k2 = [&](int k) -> float { return (k >= 32 && k < 64) ? lds_f32(kf + kidx(16 * k + 4 * v) * 4) : 0.f; };
        int xx = 16 + 7 * (lane & 7);
        float pv = k2(xx - 1);
#pragma unroll 1
        for (int i = 0; i < 7; ++i, ++xx) {
          float cur = k2(xx);
          sts32(pb + (P2_OFF + 56 * v + xx - 16) * 4, pack_bf16(cur, pv));
          pv = cur;
        }
      }
      {
        const int pi = lane >> 4;
        auto k3 = [&](int k) -> float {
          if (k >= 64 && k < 128) return lds_f32(kf + kidx(16 * k + 8 * pi) * 4);
          return (k == 128 && pi == 0) ? k2048 : 0.f;
        };
        int xx = 48 + 6 * (lane & 15);
        float pv = k3(xx - 1);
#pragma unroll 1
        for (int i = 0; i < 6; ++i, ++xx) {
          float cur = k3(xx);
          if (xx < 136) sts32(pb + (P3_OFF + 88 * pi + xx - 48) * 4, pack_bf16(cur, pv));
          pv = cur;
        }
      }
    }
    __syncwarp();
    if (lane == 0) TS(4);
    mbar_wait(bar(B_UCH + ch), 0);
    if (lane == 0) TS(5);
    {
      auto uaddr = [&](int k) { int r = (k >> 1) + 8; return ub + r * 32 + (((k & 1) ^ ((r >> 2) & 1)) << 4); };
      auto vaddr = [&](uint32_t base, int k) { int r = (k >> 1) + PADV; return vv + base + r * 32 + (((k & 1) ^ ((r >> 2) & 1)) << 4); };
#pragma unroll 1
      for (int it = 0; it < 8; ++it) {
        const int k = -18 + it * 32 + lane;
        const int kr = k < -2 ? -2 : (k > 208 ? 208 : k);
        const uint4 c0 = lds128(uaddr(kr - 1)), c1 = lds128(uaddr(kr)), c2 = lds128(uaddr(kr + 1));
        float x[17];
        x[0] = bf_hi(c0.y); x[1] = bf_lo(c0.z); x[2] = bf_hi(c0.z); x[3] = bf_lo(c0.w); x[4] = bf_hi(c0.w);
        x[5] = bf_lo(c1.x); x[6] = bf_hi(c1.x); x[7] = bf_lo(c1.y); x[8] = bf_hi(c1.y);
        x[9] = bf_lo(c1.z); x[10] = bf_hi(c1.z); x[11] = bf_lo(c1.w); x[12] = bf_hi(c1.w);
        x[13] = bf_lo(c2.x); x[14] = bf_hi(c2.x); x[15] = bf_lo(c2.y); x[16] = bf_hi(c2.y);
        float s3[12];
#pragma unroll
        for (int i = 0; i < 12; ++i) s3[i] = (x[i] + x[i + 2]) + x[i + 1];
        float s5[8];
#pragma unroll
        for (int i = 0; i < 8; ++i) s5[i] = s3[i + 4] + (x[i + 3] + x[i + 7]);
        if (k < 208) {
          sts128(vaddr(VV_U3, k), pack_bf16(s3[0], s3[1]), pack_bf16(s3[2], s3[3]), pack_bf16(s3[4], s3[5]), pack_bf16(s3[6], s3[7]));
          sts128(vaddr(VV_U5, k), pack_bf16(s5[0], s5[1]), pack_bf16(s5[2], s5[3]), pack_bf16(s5[4], s5[5]), pack_bf16(s5[6], s5[7]));
        }
        if (it < 6) {
          float s7[8], s9[8];
#pragma unroll
          for (int i = 0; i < 8; ++i) s7[i] = s5[i] + (x[i + 2] + x[i + 8]);
#pragma unroll
          for (int i = 0; i < 8; ++i) s9[i] = s7[i] + (x[i + 1] + x[i + 9]);
          if (k < 144) {
            sts128(vaddr(VV_U7, k), pack_bf16(s7[0], s7[1]), pack_bf16(s7[2], s7[3]), pack_bf16(s7[4], s7[5]), pack_bf16(s7[6], s7[7]));
            sts128(vaddr(VV_U9, k), pack_bf16(s9[0], s9[1]), pack_bf16(s9[2], s9[3]), pack_bf16(s9[4], s9[5]), pack_bf16(s9[6], s9[7]));
          }
        }
      }
    }
    __syncwarp();
    if (lane == 0) TS(6);
    mbar_wait(bar(B_QKVDONE), 0);
    if (lane == 0) TS(7);
    float acc[16][4];
#pragma unroll
    for (int i = 0; i < 16; ++i) { acc[i][0] = acc[i][1] = acc[i][2] = acc[i][3] = 0.f; }
    {
      const int gq = g - 2 * q;
      const uint32_t pd_lane = pb + (PD_OFF + 16 + gq) * 4;
      const float kfix = -round_bf16(k1024);
      auto kc = [&](int x) { return (x == 1020 || x == 1021) ? kfix : 0.f; };
      const uint32_t h127 = pack_bf16(kc(1016 + gq), kc(1015 + gq));
      const uint32_t h128 = pack_bf16(kc(1024 + gq), kc(1023 + gq));
      conv_direct<1>(acc, pd_lane, ub, 0, lane, h127, h128);
#pragma unroll 1
      for (int rho = 1; rho < 7; ++rho) conv_direct<0>(acc, pd_lane, ub, rho, lane, h127, h128);
      conv_direct<2>(acc, pd_lane, ub, 7, lane, h127, h128);
#pragma unroll 1
      for (int v = 0; v < 4; ++v)
        conv_tail<4, 3, 11>(acc, pb + (P2_OFF + 56 * v + gq - 16) * 4, vv + ((v & 1) ? VV_U3 : VV_U5), v >> 1, v == 0, lane);
#pragma unroll 1
      for (int pi = 0; pi < 2; ++pi)
        conv_tail<8, 5, 7>(acc, pb + (P3_OFF + 88 * pi + gq - 48) * 4, vv + (pi ? VV_U7 : VV_U9), pi, pi == 0, lane);
    }
    __syncwarp();
    if (lane == 0) { mbar_arrive(bar(B_CONVDONE)); TS(8); }
#pragma unroll
    for (int ab = 0; ab < 16; ab += 2) {
      const int mt = lane >> 3;
      const uint32_t a = vv + (128 * (ab + (mt >> 1)) + 16 * (lane & 7) + 8 * (mt & 1)) * 2;
      stsm_x4_t(a, pack_bf16(acc[ab][0], acc[ab][1]), pack_bf16(acc[ab][2], acc[ab][3]),
                pack_bf16(acc[ab + 1][0], acc[ab + 1][1]), pack_bf16(acc[ab + 1][2], acc[ab + 1][3]));
    }
    fence_async_smem();
    __syncwarp();
    if (lane == 0) {
      bulk_store(p.yT + (size_t)d * 2048, vv, 4096);
      bulk_commit();
      bulk_wait0();
      fence_async_all();
      red_release_add(&g_cnt[(C_Y + (cta >> 4)) * 32], 1);
      TS(9);
    }
  } else if (warp < 12) {
    asm volatile("setmaxnreg.inc.sync.aligned.u32 160;");
    const int wgc = (warp - 4) >> 2;
    const int w8 = warp - 4;
    const int g = lane >> 2, q = lane & 3;
    float acc[96];
#pragma unroll 1
    for (int ks = 0; ks < 8; ++ks) {
      const int s = ks % 3;
      mbar_wait_cluster(bar(B_FULL + s), (ks / 3) & 1);
      if (ks == 0 && tid == 128) TS(16);
      const uint32_t st = sb + s * STG_BYTES;
      const uint64_t da = mkdesc(st + STG_X + wgc * 8192, 16, 1024);
      const uint64_t db = mkdesc(st + STG_W, 8192, 1024);
      wg_fence();
#pragma unroll
      for (int k = 0; k < 4; ++k) wgmma_n192(acc, da + 2 * k, db + 128 * k, (ks | k) != 0);
      wg_commit();
      if (ks > 0) {
        wg_wait<1>();
        if (lane == 0) { const uint32_t e = bar(B_EMPTY + (ks - 1) % 3); mbar_arrive_cluster(e, 0); mbar_arrive_cluster(e, 1); }
      }
    }
    wg_wait<0>();
    if (lane == 0) {
      const uint32_t e = bar(B_EMPTY + 1);
      mbar_arrive_cluster(e, 0); mbar_arrive_cluster(e, 1);
      mbar_arrive(bar(B_QKVDONE));
    }
    if (tid == 128) TS(17);
    auto phi2 = [](float a, float b) -> uint32_t {
      const uint32_t t = pack_bf16(a, b);
      const __nv_bfloat162 tb = *reinterpret_cast<const __nv_bfloat162*>(&t);
      const __nv_bfloat162 p1 = __hadd2(tb, __floats2bfloat162_rn(1.f, 1.f));
      const uint32_t e = pack_bf16(ex2(bf_lo(t) * 1.4426950408889634f), ex2(bf_hi(t) * 1.4426950408889634f));
      const uint32_t m = __hgt2_mask(tb, __floats2bfloat162_rn(0.f, 0.f));
      const uint32_t sel = (*reinterpret_cast<const uint32_t*>(&p1) & m) | (e & ~m);
      const float lo = bf_lo(sel) + 1e-6f, hi = bf_hi(sel) + 1e-6f;
      return pack_bf16(lo, hi);
    };
    uint32_t pk[8][2], vr[8][2];
#pragma unroll
    for (int i = 0; i < 8; ++i) {
      pk[i][0] = phi2(acc[32 + 4 * i], acc[32 + 4 * i + 1]);
      pk[i][1] = phi2(acc[32 + 4 * i + 2], acc[32 + 4 * i + 3]);
      vr[i][0] = pack_bf16(acc[64 + 4 * i], acc[64 + 4 * i + 1]);
      vr[i][1] = pack_bf16(acc[64 + 4 * i + 2], acc[64 + 4 * i + 3]);
    }
    bar_sync(1, 256);
    {
      const int row = w8 * 16 + (lane & 7) + (((lane >> 3) & 1) << 3);
#pragma unroll
      for (int i = 0; i < 8; i += 2) {
        const uint32_t off = row * 128 + (((i + (lane >> 4)) ^ (row & 7)) << 4);
        stsm_x4(sb + SM_PK + off, pk[i][0], pk[i][1], pk[i + 1][0], pk[i + 1][1]);
        stsm_x4(sb + SM_VS + off, vr[i][0], vr[i][1], vr[i + 1][0], vr[i + 1][1]);
      }
    }
    bar_sync(1, 256);
    const unsigned par = epoch & 1;
    {
      const int hh = w8 >> 1, dtile = w8 & 1;
      float kv[4] = {0.f, 0.f, 0.f, 0.f}, zz[4] = {0.f, 0.f, 0.f, 0.f};
#pragma unroll
      for (int ks = 0; ks < 8; ++ks) {
        uint32_t a[4], b0, b1;
        const int m = lane >> 3;
        const int ra = 16 * ks + (lane & 7) + ((m >> 1) << 3);
        ldsm_x4_t(a, sb + SM_VS + ra * 128 + (((2 * hh + (m & 1)) ^ (ra & 7)) << 4));
        const int rb = 16 * ks + (lane & 15);
        ldsm_x2_t(b0, b1, sb + SM_PK + rb * 128 + (((2 * hh + dtile) ^ (rb & 7)) << 4));
        mma_bf16(kv, a[0], a[1], a[2], a[3], b0, b1);
        mma_bf16(zz, 0x3f803f80u, 0x3f803f80u, 0x3f803f80u, 0x3f803f80u, b0, b1);
      }
      float* dst = &g_kv[par][tj][hh][0];
      asm volatile("red.global.add.v4.f32 [%0], {%1,%2,%3,%4};" ::"l"(dst + dtile * 128 + lane * 4), "f"(kv[0]), "f"(kv[1]),
                   "f"(kv[2]), "f"(kv[3]) : "memory");
      if (g == 0)
        asm volatile("red.global.add.v2.f32 [%0], {%1,%2};" ::"l"(dst + 256 + dtile * 8 + 2 * q), "f"(zz[0]), "f"(zz[1]) : "memory");
    }
    bar_sync(1, 256);
    if (lane == 0) mbar_arrive(bar(B_PKVFREE));
    if (tid == 128) { red_release_add(&g_cnt[(C_KV + tj) * 32], 1); TS(18); }
    if (ti == 0) {
      float* z = &g_kv[par ^ 1][tj][0][0];
      for (int i = tid - 128; i < 4 * 272; i += 256) z[i] = 0.f;
    }
    uint32_t pq[4][4];
#pragma unroll
    for (int h = 0; h < 4; ++h) {
      pq[h][0] = phi2(acc[8 * h + 0], acc[8 * h + 1]);
      pq[h][1] = phi2(acc[8 * h + 2], acc[8 * h + 3]);
      pq[h][2] = phi2(acc[8 * h + 4], acc[8 * h + 5]);
      pq[h][3] = phi2(acc[8 * h + 6], acc[8 * h + 7]);
    }
    if (tid == 128) { wait_counter(&g_cnt[(C_KV + tj) * 32], (epoch + 1) * 16); TS(19); }
    bar_sync(1, 256);
#pragma unroll
    for (int h = 0; h < 4; ++h) {
      const float* src = &g_kv[par][tj][h][0];
      const float4 k0 = __ldcg((const float4*)(src + lane * 4)), k1 = __ldcg((const float4*)(src + 128 + lane * 4));
      const float2 z0 = __ldcg((const float2*)(src + 256 + 2 * q)), z1 = __ldcg((const float2*)(src + 264 + 2 * q));
      float n0[4] = {0.f, 0.f, 0.f, 0.f}, n1[4] = {0.f, 0.f, 0.f, 0.f}, dn[4] = {0.f, 0.f, 0.f, 0.f};
      mma_bf16(n0, pq[h][0], pq[h][1], pq[h][2], pq[h][3], pack_bf16(k0.x, k0.y), pack_bf16(k1.x, k1.y));
      mma_bf16(n1, pq[h][0], pq[h][1], pq[h][2], pq[h][3], pack_bf16(k0.z, k0.w), pack_bf16(k1.z, k1.w));
      mma_bf16(dn, pq[h][0], pq[h][1], pq[h][2], pq[h][3], pack_bf16(z0.x, z0.y), pack_bf16(z1.x, z1.y));
      const float d0 = round_bf16(round_bf16(dn[0]) + 1e-6f), d1 = round_bf16(round_bf16(dn[2]) + 1e-6f);
      uint4 o;
      o.x = pack_bf16(__fdividef(round_bf16(n0[0]), d0), __fdividef(round_bf16(n0[1]), d0));
      o.y = pack_bf16(__fdividef(round_bf16(n0[2]), d1), __fdividef(round_bf16(n0[3]), d1));
      o.z = pack_bf16(__fdividef(round_bf16(n1[0]), d0), __fdividef(round_bf16(n1[1]), d0));
      o.w = pack_bf16(__fdividef(round_bf16(n1[2]), d1), __fdividef(round_bf16(n1[3]), d1));
      g_ofrag[((ti * 8 + w8) * 32 + 4 * tj + h) * 32 + lane] = o;
    }
    bar_sync(1, 256);
    if (tid == 128) {
      red_release_add(&g_cnt[(C_O + ti) * 32], 1);
      TS(20);
      wait_counter(&g_cnt[(C_O + ti) * 32], (epoch + 1) * 8);
      if (cta == 0) g_epoch = epoch + 1;
      TS(21);
    }
    bar_sync(1, 256);
    {
      const uint4* src = &g_ofrag[((ti * 8 + w8) * 32) * 32 + lane];
      uint4 A0[8], A1[8], A2[8];
#pragma unroll
      for (int h = 0; h < 8; ++h) A0[h] = __ldcg(src + h * 32);
#pragma unroll
      for (int h = 0; h < 8; ++h) A1[h] = __ldcg(src + (8 + h) * 32);
#pragma unroll
      for (int h = 0; h < 8; ++h) A2[h] = __ldcg(src + (16 + h) * 32);
      mbar_wait_cluster(bar(B_WO), 0);
      mbar_wait(bar(B_CONVDONE), 0);
      if (tid == 128) TS(22);
      float o[32];
      const uint64_t db = mkdesc(sb + SM_WO, 8192, 1024);
      wg_fence();
#pragma unroll
      for (int h = 0; h < 8; ++h) wgmma_n64_rs(o, A0[h], db + h * 128, h != 0);
      wg_commit();
      wg_wait<0>();
#pragma unroll
      for (int h = 0; h < 8; ++h) A0[h] = __ldcg(src + (24 + h) * 32);
      wg_fence();
#pragma unroll
      for (int h = 0; h < 8; ++h) wgmma_n64_rs(o, A1[h], db + (8 + h) * 128, 1);
#pragma unroll
      for (int h = 0; h < 8; ++h) wgmma_n64_rs(o, A2[h], db + (16 + h) * 128, 1);
      wg_commit();
      wg_fence();
#pragma unroll
      for (int h = 0; h < 8; ++h) wgmma_n64_rs(o, A0[h], db + (24 + h) * 128, 1);
      wg_commit();
      wg_wait<0>();
      const int row = w8 * 16 + (lane & 7) + (((lane >> 3) & 1) << 3);
#pragma unroll
      for (int i = 0; i < 8; i += 2) {
        const uint32_t off = row * 128 + (((i + (lane >> 4)) ^ (row & 7)) << 4);
        stsm_x4(sb + SM_BOUT + off, pack_bf16(o[4 * i], o[4 * i + 1]), pack_bf16(o[4 * i + 2], o[4 * i + 3]),
                pack_bf16(o[4 * i + 4], o[4 * i + 5]), pack_bf16(o[4 * i + 6], o[4 * i + 7]));
      }
      fence_async_smem();
      bar_sync(1, 256);
      if (tid == 128) {
        tma_store_2d(&maps.out, sb + SM_BOUT, 512 + 64 * tj, 128 * ti);
        bulk_commit();
        bulk_wait0();
        TS(23);
      }
    }
  } else {
    asm volatile("setmaxnreg.dec.sync.aligned.u32 40;");
    if (warp == 12) {
      if (lane == 0) {
#pragma unroll 1
        for (int ks = 0; ks < 8; ++ks) {
          const int s = ks % 3;
          if (ks >= 3) mbar_wait_cluster(bar(B_EMPTY + s), ((ks / 3) - 1) & 1);
          const uint32_t st = sb + s * STG_BYTES, fb = bar(B_FULL + s);
          mbar_expect_tx(fb, STG_BYTES);
          tma_load_2d(st + STG_X, &maps.x, ks * 64, ti * 128, fb);
#pragma unroll
          for (int nb = 0; nb < 3; ++nb)
            tma_load_2d_mc(st + STG_W + nb * 8192 + rank * 4096, &maps.w, nb * 512 + tj * 64, ks * 64 + rank * 32, fb, 3);
        }
        TS(24);
        mbar_wait_cluster(bar(B_EMPTY + 0), 0);
        mbar_wait_cluster(bar(B_EMPTY + 1), 0);
        mbar_expect_tx(bar(B_WO), 65536);
        tma_load_2d_mc(sb + SM_WO + rank * 32768, &maps.wo, tj * 64, rank * 256, bar(B_WO), 3);
      }
    } else if (warp == 13) {
      if (lane == 0) {
        mbar_expect_tx(bar(B_UTILE), 16384);
        tma_load_2d(sb + SM_TIN1, &maps.u, tj * 64, ti * 128, bar(B_UTILE));
      }
      mbar_wait(bar(B_UTILE), 0);
      if (lane == 0) TS(26);
      transpose_tile<0>(sb + SM_TIN1, sb + SM_TOUT1, lane);
      fence_async_smem();
      __syncwarp();
      if (lane == 0) {
        tma_store_2d(&maps.uT, sb + SM_TOUT1, ti * 128, tj * 64);
        tma_store_2d(&maps.uT, sb + SM_TOUT1 + 8192, ti * 128 + 64, tj * 64);
        bulk_commit();
        bulk_wait0();
        fence_async_all();
        red_release_add(&g_cnt[(C_U + tj) * 32], 1);
        mbar_arrive(bar(B_TRDONE));
        TS(27);
        mbar_wait(bar(B_PKVFREE), 0);
        wait_counter(&g_cnt[(C_Y + tj) * 32], (epoch + 1) * 64);
        fence_async_all();
        TS(28);
        mbar_expect_tx(bar(B_YTILE), 16384);
        tma_load_2d(sb + SM_TIN2, &maps.yT, ti * 128, tj * 64, bar(B_YTILE));
        tma_load_2d(sb + SM_TIN2 + 8192, &maps.yT, ti * 128 + 64, tj * 64, bar(B_YTILE));
      }
      __syncwarp();
      mbar_wait(bar(B_YTILE), 0);
      transpose_tile<1>(sb + SM_TIN2, sb + SM_TOUT2, lane);
      fence_async_smem();
      __syncwarp();
      if (lane == 0) {
        tma_store_2d(&maps.out, sb + SM_TOUT2, 64 * tj, 128 * ti);
        bulk_commit();
        bulk_wait0();
        TS(29);
      }
    }
  }
  __syncwarp();
  cluster_arrive();
  cluster_wait();
  if (tid == 0) TS(31);
}

typedef CUresult (*EncodeFn)(CUtensorMap*, CUtensorMapDataType, cuuint32_t, void*, const cuuint64_t*, const cuuint64_t*,
                             const cuuint32_t*, const cuuint32_t*, CUtensorMapInterleave, CUtensorMapSwizzle,
                             CUtensorMapL2promotion, CUtensorMapFloatOOBfill);

static void make_map(EncodeFn enc, CUtensorMap* m, const void* base, uint64_t inner, uint64_t outer, uint32_t box_in,
                     uint32_t box_out) {
  cuuint64_t gd[2] = {inner, outer};
  cuuint64_t gs[1] = {inner * 2};
  cuuint32_t bd[2] = {box_in, box_out};
  cuuint32_t es[2] = {1, 1};
  enc(m, CU_TENSOR_MAP_DATA_TYPE_BFLOAT16, 2, const_cast<void*>(base), gd, gs, bd, es, CU_TENSOR_MAP_INTERLEAVE_NONE,
      CU_TENSOR_MAP_SWIZZLE_128B, CU_TENSOR_MAP_L2_PROMOTION_L2_128B, CU_TENSOR_MAP_FLOAT_OOB_FILL_NONE);
}

}

extern "C" void kernel_launch(void* const* d_in, const int* in_sizes, int n_in, void* d_out, int out_size) {
  using namespace s4la;
  (void)in_sizes; (void)n_in; (void)out_size;
  static EncodeFn enc = nullptr;
  static void *uT = nullptr, *yT = nullptr;
  if (!enc) {
    void* fn = nullptr;
    cudaDriverEntryPointQueryResult qr;
    cudaGetDriverEntryPoint("cuTensorMapEncodeTiled", &fn, cudaEnableDefault, &qr);
    enc = (EncodeFn)fn;
    cudaGetSymbolAddress(&uT, g_uT);
    cudaGetSymbolAddress(&yT, g_yT);
    cudaFuncSetAttribute(fused_kernel, cudaFuncAttributeMaxDynamicSharedMemorySize, SM_TOTAL);
  }
  const __nv_bfloat16* const* in = (const __nv_bfloat16* const*)d_in;
  Maps maps;
  make_map(enc, &maps.x, in[9], 512, 2048, 64, 128);
  make_map(enc, &maps.w, in[10], 1536, 512, 64, 32);
  make_map(enc, &maps.wo, in[11], 512, 512, 64, 256);
  make_map(enc, &maps.u, in[0], 512, 2048, 64, 128);
  make_map(enc, &maps.uT, uT, 2048, 512, 64, 64);
  make_map(enc, &maps.yT, yT, 2048, 512, 64, 64);
  make_map(enc, &maps.out, d_out, 1024, 2048, 64, 128);
  Ptrs p;
  p.A_re = in[1]; p.A_im = in[2]; p.B_re = in[3]; p.B_im = in[4]; p.C_re = in[5]; p.C_im = in[6];
  p.log_dt = in[7]; p.Dskip = in[8]; p.x = in[9]; p.wqkv = in[10]; p.wo = in[11];
  p.uT = (__nv_bfloat16*)uT; p.yT = (__nv_bfloat16*)yT;
  fused_kernel<<<NCTA, NTHREADS, SM_TOTAL, cudaStreamPerThread>>>(maps, p, (__nv_bfloat16*)d_out);
}
```

```cpp
#include <cuda_runtime.h>
#include <cuda_bf16.h>
#include <cuda_fp16.h>
#include <cuda.h>
#include <stdint.h>

#define DEVI __device__ __forceinline__

namespace s4la {

constexpr int NTHREADS = 512;
constexpr int NCTA = 128;

constexpr uint32_t STG_BYTES = 40960, STG_X = 0, STG_W = 16384;
constexpr uint32_t SM_WO = 0;
constexpr uint32_t SM_QS = 65536;
constexpr uint32_t SM_BOUT = 65536;
constexpr uint32_t SM_PK = 81920;
constexpr uint32_t SM_VS = 98304;
constexpr uint32_t SM_KVB = 114688;
constexpr uint32_t SM_TIN2 = 81920, SM_TOUT2 = 98304;
constexpr uint32_t SM_U = 122880, U_BYTES = 4352;
constexpr uint32_t SM_P = 140288, P_BYTES = 4096;
constexpr uint32_t SM_TIN1 = SM_U, SM_TOUT1 = SM_P;
constexpr uint32_t SM_VV = 156672, VV_BYTES = 13312;
constexpr uint32_t VV_U5 = 0, VV_U3 = 3712, VV_U9 = 7424, VV_U7 = 10112;
constexpr uint32_t VV_KF = 8192;
constexpr uint32_t SM_BAR = 209920;
constexpr uint32_t SM_MISC = SM_BAR + 256;
constexpr uint32_t SM_PTAB = SM_MISC + 128;
constexpr uint32_t SM_TOTAL = SM_PTAB + 3840;
constexpr int PADV = 12;

enum { B_FULL = 0, B_EMPTY = 3, B_WO = 6, B_UTILE = 7, B_YTILE = 8, B_UCH = 9, B_QKVDONE = 13,
       B_CONVDONE = 14, B_TRDONE = 15, B_PKVFREE = 16, B_COUNT = 17 };

constexpr int PD_OFF = 0, P2_OFF = 544, P3_OFF = 768;

constexpr int SL_K2048 = 640, SL_ZERO = 641, SL_510 = 642, SL_0 = 643;
__host__ __device__ constexpr int kidx_c(int l) {
  int r = (l >> 3) & 15, y = 0;
  if (l < 256) y = (l & 7) + ((l >> 7) << 3);
  else if (l < 512) y = 16 + (((l - 256) >> 7) << 2) + ((l & 7) >> 1);
  else if (l < 1024) y = 24 + (((l - 512) >> 7) << 1) + ((l >> 2) & 1);
  else y = 32 + ((l - 1024) >> 7);
  return y * 16 + r;
}
constexpr int slot_direct(int l) {
  if (l < 0 || l > 510) return SL_ZERO;
  if (l == 510) return SL_510;
  if (l == 0) return SL_0;
  return kidx_c(l < 256 ? l : ((l + ((l >> 1) & 1)) & ~1));
}
constexpr int slot_seg2(int v, int k) { return (k >= 32 && k < 64) ? kidx_c(16 * k + 4 * v) : SL_ZERO; }
constexpr int slot_seg3(int pi, int k) {
  return (k >= 64 && k < 128) ? kidx_c(16 * k + 8 * pi) : ((k == 128 && pi == 0) ? SL_K2048 : SL_ZERO);
}
struct PTab { uint32_t v[960]; };
constexpr PTab make_ptab() {
  PTab t{};
  for (int w = 0; w < 960; ++w) t.v[w] = (SL_ZERO * 4) | ((SL_ZERO * 4) << 16);
  for (int w = 0; w < 544; ++w) t.v[w] = (slot_direct(w - 16) * 4) | ((slot_direct(w - 17) * 4) << 16);
  for (int v = 0; v < 4; ++v)
    for (int x = 16; x < 72; ++x) t.v[544 + 56 * v + x - 16] = (slot_seg2(v, x) * 4) | ((slot_seg2(v, x - 1) * 4) << 16);
  for (int pi = 0; pi < 2; ++pi)
    for (int x = 48; x < 136; ++x) t.v[768 + 88 * pi + x - 48] = (slot_seg3(pi, x) * 4) | ((slot_seg3(pi, x - 1) * 4) << 16);
  return t;
}
__device__ const PTab g_ptab = make_ptab();

__device__ __nv_bfloat16 g_uT[512 * 2048];
__device__ __nv_bfloat16 g_yT[512 * 2048];
__device__ uint4 g_ofrag[16 * 8 * 32 * 32];
__device__ float g_kv[2][8][4][272];
__device__ unsigned g_cnt[64 * 32];
__device__ unsigned g_epoch;
#define TS(slot) do { } while (0)
enum { C_U = 0, C_KV = 8, C_O = 16, C_Y = 32 };

struct Maps {
  CUtensorMap x, w, wo, u, uT, yT, out;
};
struct Ptrs {
  const __nv_bfloat16 *A_re, *A_im, *B_re, *B_im, *C_re, *C_im, *log_dt, *Dskip;
  const __nv_bfloat16 *x, *wqkv, *wo;
  __nv_bfloat16 *uT, *yT;
};

DEVI uint32_t s2u(const void* p) { return (uint32_t)__cvta_generic_to_shared(p); }
DEVI void mbar_init(uint32_t b, uint32_t c) { asm volatile("mbarrier.init.shared::cta.b64 [%0], %1;" ::"r"(b), "r"(c) : "memory"); }
DEVI void mbar_expect_tx(uint32_t b, uint32_t bytes) {
  asm volatile("mbarrier.arrive.expect_tx.shared::cta.b64 _, [%0], %1;" ::"r"(b), "r"(bytes) : "memory");
}
DEVI void mbar_arrive(uint32_t b) { asm volatile("mbarrier.arrive.shared::cta.b64 _, [%0];" ::"r"(b) : "memory"); }
DEVI void mbar_arrive_cluster(uint32_t b, uint32_t cta) {
  asm volatile("{\n.reg .b32 r;\nmapa.shared::cluster.u32 r, %0, %1;\nmbarrier.arrive.shared::cluster.b64 _, [r];\n}"
               ::"r"(b), "r"(cta) : "memory");
}
DEVI void mbar_wait(uint32_t b, uint32_t parity) {
  asm volatile("{\n.reg .pred p;\nLAB_WAIT:\nmbarrier.try_wait.parity.shared::cta.b64 p, [%0], %1, 0x989680;\n@p bra LAB_DONE;\nbra LAB_WAIT;\nLAB_DONE:\n}"
               ::"r"(b), "r"(parity) : "memory");
}
#define mbar_wait_cluster mbar_wait
DEVI void bar_sync(int id, int n) { asm volatile("bar.sync %0, %1;" ::"r"(id), "r"(n) : "memory"); }
DEVI void fence_async_smem() { asm volatile("fence.proxy.async.shared::cta;" ::: "memory"); }
DEVI void fence_async_all() { asm volatile("fence.proxy.async;" ::: "memory"); }
DEVI void cluster_arrive() { asm volatile("barrier.cluster.arrive.relaxed.aligned;" ::: "memory"); }
DEVI void cluster_wait() { asm volatile("barrier.cluster.wait.aligned;" ::: "memory"); }

DEVI void tma_load_2d(uint32_t dst, const CUtensorMap* m, int c0, int c1, uint32_t bar) {
  asm volatile("cp.async.bulk.tensor.2d.shared::cluster.global.mbarrier::complete_tx::bytes [%0], [%1, {%3, %4}], [%2];"
               ::"r"(dst), "l"(m), "r"(bar), "r"(c0), "r"(c1) : "memory");
}
DEVI void tma_load_2d_mc(uint32_t dst, const CUtensorMap* m, int c0, int c1, uint32_t bar, uint16_t mask) {
  asm volatile("cp.async.bulk.tensor.2d.shared::cluster.global.mbarrier::complete_tx::bytes.multicast::cluster [%0], [%1, {%3, %4}], [%2], %5;"
               ::"r"(dst), "l"(m), "r"(bar), "r"(c0), "r"(c1), "h"(mask) : "memory");
}
DEVI void tma_store_2d(const CUtensorMap* m, uint32_t src, int c0, int c1) {
  asm volatile("cp.async.bulk.tensor.2d.global.shared::cta.bulk_group [%0, {%2, %3}], [%1];"
               ::"l"(m), "r"(src), "r"(c0), "r"(c1) : "memory");
}
DEVI void bulk_load(uint32_t dst, const void* src, uint32_t bytes, uint32_t bar) {
  asm volatile("cp.async.bulk.shared::cluster.global.mbarrier::complete_tx::bytes [%0], [%1], %2, [%3];"
               ::"r"(dst), "l"(src), "r"(bytes), "r"(bar) : "memory");
}
DEVI void bulk_store(void* dst, uint32_t src, uint32_t bytes) {
  asm volatile("cp.async.bulk.global.shared::cta.bulk_group [%0], [%1], %2;" ::"l"(dst), "r"(src), "r"(bytes) : "memory");
}
DEVI void bulk_commit() { asm volatile("cp.async.bulk.commit_group;" ::: "memory"); }
DEVI void bulk_wait0() { asm volatile("cp.async.bulk.wait_group 0;" ::: "memory"); }
DEVI void l2_prefetch(const void* p, uint32_t bytes) {
  asm volatile("cp.async.bulk.prefetch.L2.global [%0], %1;" ::"l"(p), "r"(bytes) : "memory");
}
DEVI void prefetch_tmap(const CUtensorMap* m) { asm volatile("prefetch.tensormap [%0];" ::"l"(m) : "memory"); }

DEVI void red_release_add(unsigned* p, unsigned v) {
  asm volatile("red.release.gpu.global.add.u32 [%0], %1;" ::"l"(p), "r"(v) : "memory");
}
DEVI void red_relaxed_add(unsigned* p, unsigned v) {
  asm volatile("red.relaxed.gpu.global.add.u32 [%0], %1;" ::"l"(p), "r"(v) : "memory");
}
DEVI unsigned ld_relaxed(const unsigned* p) {
  unsigned v;
  asm volatile("ld.relaxed.gpu.global.u32 %0, [%1];" : "=r"(v) : "l"(p) : "memory");
  return v;
}
DEVI void wait_counter(const unsigned* p, unsigned target) {
#pragma unroll 1
  for (int it = 0; (int)(ld_relaxed(p) - target) < 0; ++it)
    if (it > (1 << 22)) __trap();
  asm volatile("fence.acq_rel.gpu;" ::: "memory");
}

DEVI void ldsm_x4(uint32_t (&r)[4], uint32_t a) {
  asm volatile("ldmatrix.sync.aligned.m8n8.x4.shared.b16 {%0,%1,%2,%3}, [%4];"
               : "=r"(r[0]), "=r"(r[1]), "=r"(r[2]), "=r"(r[3]) : "r"(a) : "memory");
}
DEVI void ldsm_x4_t(uint32_t (&r)[4], uint32_t a) {
  asm volatile("ldmatrix.sync.aligned.m8n8.x4.trans.shared.b16 {%0,%1,%2,%3}, [%4];"
               : "=r"(r[0]), "=r"(r[1]), "=r"(r[2]), "=r"(r[3]) : "r"(a) : "memory");
}
DEVI void ldsm_x2_t(uint32_t& r0, uint32_t& r1, uint32_t a) {
  asm volatile("ldmatrix.sync.aligned.m8n8.x2.trans.shared.b16 {%0,%1}, [%2];" : "=r"(r0), "=r"(r1) : "r"(a) : "memory");
}
DEVI void stsm_x4(uint32_t a, uint32_t r0, uint32_t r1, uint32_t r2, uint32_t r3) {
  asm volatile("stmatrix.sync.aligned.m8n8.x4.shared.b16 [%0], {%1,%2,%3,%4};"
               ::"r"(a), "r"(r0), "r"(r1), "r"(r2), "r"(r3) : "memory");
}
DEVI void stsm_x4_t(uint32_t a, uint32_t r0, uint32_t r1, uint32_t r2, uint32_t r3) {
  asm volatile("stmatrix.sync.aligned.m8n8.x4.trans.shared.b16 [%0], {%1,%2,%3,%4};"
               ::"r"(a), "r"(r0), "r"(r1), "r"(r2), "r"(r3) : "memory");
}
DEVI uint32_t lds32(uint32_t a) { uint32_t v; asm volatile("ld.shared.b32 %0, [%1];" : "=r"(v) : "r"(a) : "memory"); return v; }
DEVI float lds_f32(uint32_t a) { float v; asm volatile("ld.shared.f32 %0, [%1];" : "=f"(v) : "r"(a) : "memory"); return v; }
DEVI void sts32(uint32_t a, uint32_t v) { asm volatile("st.shared.b32 [%0], %1;" ::"r"(a), "r"(v) : "memory"); }
DEVI void sts_f32(uint32_t a, float v) { asm volatile("st.shared.f32 [%0], %1;" ::"r"(a), "f"(v) : "memory"); }
DEVI void sts_f32x2(uint32_t a, float x, float y) { asm volatile("st.shared.v2.f32 [%0], {%1,%2};" ::"r"(a), "f"(x), "f"(y) : "memory"); }
DEVI uint4 lds128(uint32_t a) {
  uint4 v;
  asm volatile("ld.shared.v4.b32 {%0,%1,%2,%3}, [%4];" : "=r"(v.x), "=r"(v.y), "=r"(v.z), "=r"(v.w) : "r"(a) : "memory");
  return v;
}
DEVI void sts128(uint32_t a, uint32_t x, uint32_t y, uint32_t z, uint32_t w) {
  asm volatile("st.shared.v4.b32 [%0], {%1,%2,%3,%4};" ::"r"(a), "r"(x), "r"(y), "r"(z), "r"(w) : "memory");
}

DEVI void mma_bf16(float (&d)[4], uint32_t a0, uint32_t a1, uint32_t a2, uint32_t a3, uint32_t b0, uint32_t b1) {
  asm("mma.sync.aligned.m16n8k16.row.col.f32.bf16.bf16.f32 {%0,%1,%2,%3}, {%4,%5,%6,%7}, {%8,%9}, {%0,%1,%2,%3};"
      : "+f"(d[0]), "+f"(d[1]), "+f"(d[2]), "+f"(d[3])
      : "r"(a0), "r"(a1), "r"(a2), "r"(a3), "r"(b0), "r"(b1));
}
DEVI uint32_t pack_bf16(float lo, float hi) {
  uint32_t r;
  asm("cvt.rn.bf16x2.f32 %0, %1, %2;" : "=r"(r) : "f"(hi), "f"(lo));
  return r;
}
DEVI uint32_t pack_f16(float lo, float hi) {
  uint32_t r;
  asm("cvt.rn.f16x2.f32 %0, %1, %2;" : "=r"(r) : "f"(hi), "f"(lo));
  return r;
}
DEVI float bf_lo(uint32_t v) { return __uint_as_float(v << 16); }
DEVI float bf_hi(uint32_t v) { return __uint_as_float(v & 0xffff0000u); }
DEVI float bf2f(__nv_bfloat16 v) { return __bfloat162float(v); }
DEVI float round_bf16(float v) { return __bfloat162float(__float2bfloat16_rn(v)); }
DEVI float rcp(float x) { float r; asm("rcp.approx.ftz.f32 %0, %1;" : "=f"(r) : "f"(x)); return r; }
DEVI float ex2(float x) { float r; asm("ex2.approx.ftz.f32 %0, %1;" : "=f"(r) : "f"(x)); return r; }

DEVI void wg_fence() { asm volatile("wgmma.fence.sync.aligned;" ::: "memory"); }
DEVI void wg_commit() { asm volatile("wgmma.commit_group.sync.aligned;" ::: "memory"); }
template <int N> DEVI void wg_wait() { asm volatile("wgmma.wait_group.sync.aligned %0;" ::"n"(N) : "memory"); }
DEVI uint64_t mkdesc(uint32_t saddr, uint32_t lbo, uint32_t sbo) {
  return (uint64_t)((saddr & 0x3FFFF) >> 4) | ((uint64_t)(lbo >> 4) << 16) | ((uint64_t)(sbo >> 4) << 32) | (1ull << 62);
}

#define R8(b) "%" #b
DEVI void wgmma_n192(float (&d)[96], uint64_t da, uint64_t db, int scale_d) {
  asm volatile(
      "{\n.reg .pred p;\nsetp.ne.b32 p, %98, 0;\n"
      "wgmma.mma_async.sync.aligned.m64n192k16.f32.bf16.bf16 "
      "{%0,%1,%2,%3,%4,%5,%6,%7,%8,%9,%10,%11,%12,%13,%14,%15,"
      "%16,%17,%18,%19,%20,%21,%22,%23,%24,%25,%26,%27,%28,%29,%30,%31,"
      "%32,%33,%34,%35,%36,%37,%38,%39,%40,%41,%42,%43,%44,%45,%46,%47,"
      "%48,%49,%50,%51,%52,%53,%54,%55,%56,%57,%58,%59,%60,%61,%62,%63,"
      "%64,%65,%66,%67,%68,%69,%70,%71,%72,%73,%74,%75,%76,%77,%78,%79,"
      "%80,%81,%82,%83,%84,%85,%86,%87,%88,%89,%90,%91,%92,%93,%94,%95}, "
      "%96, %97, p, 1, 1, 0, 1;\n}"
      : "+f"(d[0]), "+f"(d[1]), "+f"(d[2]), "+f"(d[3]), "+f"(d[4]), "+f"(d[5]), "+f"(d[6]), "+f"(d[7]),
        "+f"(d[8]), "+f"(d[9]), "+f"(d[10]), "+f"(d[11]), "+f"(d[12]), "+f"(d[13]), "+f"(d[14]), "+f"(d[15]),
        "+f"(d[16]), "+f"(d[17]), "+f"(d[18]), "+f"(d[19]), "+f"(d[20]), "+f"(d[21]), "+f"(d[22]), "+f"(d[23]),
        "+f"(d[24]), "+f"(d[25]), "+f"(d[26]), "+f"(d[27]), "+f"(d[28]), "+f"(d[29]), "+f"(d[30]), "+f"(d[31]),
        "+f"(d[32]), "+f"(d[33]), "+f"(d[34]), "+f"(d[35]), "+f"(d[36]), "+f"(d[37]), "+f"(d[38]), "+f"(d[39]),
        "+f"(d[40]), "+f"(d[41]), "+f"(d[42]), "+f"(d[43]), "+f"(d[44]), "+f"(d[45]), "+f"(d[46]), "+f"(d[47]),
        "+f"(d[48]), "+f"(d[49]), "+f"(d[50]), "+f"(d[51]), "+f"(d[52]), "+f"(d[53]), "+f"(d[54]), "+f"(d[55]),
        "+f"(d[56]), "+f"(d[57]), "+f"(d[58]), "+f"(d[59]), "+f"(d[60]), "+f"(d[61]), "+f"(d[62]), "+f"(d[63]),
        "+f"(d[64]), "+f"(d[65]), "+f"(d[66]), "+f"(d[67]), "+f"(d[68]), "+f"(d[69]), "+f"(d[70]), "+f"(d[71]),
        "+f"(d[72]), "+f"(d[73]), "+f"(d[74]), "+f"(d[75]), "+f"(d[76]), "+f"(d[77]), "+f"(d[78]), "+f"(d[79]),
        "+f"(d[80]), "+f"(d[81]), "+f"(d[82]), "+f"(d[83]), "+f"(d[84]), "+f"(d[85]), "+f"(d[86]), "+f"(d[87]),
        "+f"(d[88]), "+f"(d[89]), "+f"(d[90]), "+f"(d[91]), "+f"(d[92]), "+f"(d[93]), "+f"(d[94]), "+f"(d[95])
      : "l"(da), "l"(db), "r"(scale_d));
}
DEVI void wgmma_n64_rs(float (&d)[32], const uint4& a, uint64_t db, int scale_d) {
  asm volatile(
      "{\n.reg .pred p;\nsetp.ne.b32 p, %37, 0;\n"
      "wgmma.mma_async.sync.aligned.m64n64k16.f32.bf16.bf16 "
      "{%0,%1,%2,%3,%4,%5,%6,%7,%8,%9,%10,%11,%12,%13,%14,%15,"
      "%16,%17,%18,%19,%20,%21,%22,%23,%24,%25,%26,%27,%28,%29,%30,%31}, "
      "{%32,%33,%34,%35}, %36, p, 1, 1, 1;\n}"
      : "+f"(d[0]), "+f"(d[1]), "+f"(d[2]), "+f"(d[3]), "+f"(d[4]), "+f"(d[5]), "+f"(d[6]), "+f"(d[7]),
        "+f"(d[8]), "+f"(d[9]), "+f"(d[10]), "+f"(d[11]), "+f"(d[12]), "+f"(d[13]), "+f"(d[14]), "+f"(d[15]),
        "+f"(d[16]), "+f"(d[17]), "+f"(d[18]), "+f"(d[19]), "+f"(d[20]), "+f"(d[21]), "+f"(d[22]), "+f"(d[23]),
        "+f"(d[24]), "+f"(d[25]), "+f"(d[26]), "+f"(d[27]), "+f"(d[28]), "+f"(d[29]), "+f"(d[30]), "+f"(d[31])
      : "r"(a.x), "r"(a.y), "r"(a.z), "r"(a.w), "l"(db), "r"(scale_d));
}
DEVI void wgmma_n16_f16(float (&d)[8], uint64_t da, uint64_t db, int scale_d) {
  asm volatile(
      "{\n.reg .pred p;\nsetp.ne.b32 p, %10, 0;\n"
      "wgmma.mma_async.sync.aligned.m64n16k16.f32.f16.f16 {%0,%1,%2,%3,%4,%5,%6,%7}, %8, %9, p, 1, 1, 0, 0;\n}"
      : "+f"(d[0]), "+f"(d[1]), "+f"(d[2]), "+f"(d[3]), "+f"(d[4]), "+f"(d[5]), "+f"(d[6]), "+f"(d[7])
      : "l"(da), "l"(db), "r"(scale_d));
}

template <int MODE>
DEVI void transpose_tile(uint32_t src, uint32_t dst, int lane) {
  const int m = lane >> 3, r = lane & 7;
#pragma unroll 2
  for (int it = 0; it < 32; ++it) {
    uint32_t v[4];
    if (MODE == 0) {
      const int tb = it >> 1, cb = (it & 1) * 4 + m;
      ldsm_x4_t(v, src + (tb * 8 + r) * 128 + ((cb ^ r) << 4));
      const int b = tb >> 3;
      stsm_x4(dst + b * 8192 + (cb * 8 + r) * 128 + (((tb & 7) ^ b ^ r) << 4), v[0], v[1], v[2], v[3]);
    } else {
      const int cb = it & 7, tb = (it >> 3) * 4 + m;
      ldsm_x4_t(v, src + (tb >> 3) * 8192 + (cb * 8 + r) * 128 + (((tb & 7) ^ r) << 4));
      stsm_x4(dst + (tb * 8 + r) * 128 + ((cb ^ r) << 4), v[0], v[1], v[2], v[3]);
    }
  }
}

struct C32 { float re, im; };
DEVI C32 csq(C32 a) { return {a.re * a.re - a.im * a.im, 2.f * a.re * a.im}; }
DEVI C32 cmul(C32 a, C32 b) { return {a.re * b.re - a.im * b.im, a.re * b.im + a.im * b.re}; }
DEVI C32 cfresh(float zl, float zi, float m) {
  float mag = ex2(zl * m), ph = zi * m;
  return {mag * __cosf(ph), mag * __sinf(ph)};
}
struct HMul { uint32_t b, bp; };
DEVI HMul mk_mul(float re, float im) { return {pack_f16(re, im), pack_f16(-im, re)}; }
DEVI uint32_t hcmul(uint32_t a, const HMul& m) {
  __half2 ah = *reinterpret_cast<__half2*>(&a);
  __half2 b = *reinterpret_cast<const __half2*>(&m.b), bp = *reinterpret_cast<const __half2*>(&m.bp);
  __half2 r = __hfma2(__high2half2(ah), bp, __hmul2(__low2half2(ah), b));
  return *reinterpret_cast<uint32_t*>(&r);
}
DEVI uint32_t badd(uint32_t a, uint32_t b) {
  __nv_bfloat162 r = __hadd2(*reinterpret_cast<__nv_bfloat162*>(&a), *reinterpret_cast<__nv_bfloat162*>(&b));
  return *reinterpret_cast<uint32_t*>(&r);
}
DEVI int kidx_l(int i) {
  const int y = i >> 4, r = i & 15;
  int lo;
  if (y < 16) lo = (y & 7) + ((y >> 3) << 7);
  else if (y < 24) lo = 256 + (((y - 16) >> 2) << 7) + ((y & 3) << 1);
  else if (y < 32) lo = 512 + (((y - 24) >> 1) << 7) + ((y & 1) << 2);
  else lo = 1024 + ((y - 32) << 7);
  return lo + 8 * r;
}

template <int MU0, int NMU, int DMAX>
DEVI void conv_tail(float (&acc)[16][4], uint32_t p_lane, uint32_t v_base, int back, bool edge, int lane) {
  uint32_t H[2 * NMU];
#pragma unroll
  for (int i = 0; i < 2 * NMU; ++i) H[i] = lds32(p_lane + (uint32_t)(MU0 - 1 + i) * 32);
  const int hsel = (lane >> 3) & 1;
  const int row = (lane & 7) + ((lane >> 4) << 3) + PADV - 8 - (back & (hsel ^ 1));
  const uint32_t la = v_base + row * 32 + (((hsel ^ back) ^ ((row >> 2) & 1)) << 4);
  constexpr int NLD = (DMAX + 4) / 2;
  uint32_t M[2][4];
  uint32_t p0 = 0, p1 = 0;
  ldsm_x4_t(M[0], la);
#pragma unroll
  for (int ld = 0; ld < NLD; ++ld) {
    if (ld + 1 < NLD) ldsm_x4_t(M[(ld + 1) & 1], la + (ld + 1) * 512);
    const uint32_t* c = M[ld & 1];
#pragma unroll
    for (int s = 0; s < 2; ++s) {
      const int delta = 2 * ld - 2 + s;
      if (delta > DMAX) continue;
      if (delta == -2 && !edge) continue;
      const uint32_t a0 = s ? c[0] : p0, a1 = s ? c[1] : p1, a2 = s ? c[2] : c[0], a3 = s ? c[3] : c[1];
#pragma unroll
      for (int k = 0; k < NMU; ++k) {
        const int nb = delta + MU0 + 2 * k;
        if (nb < 16 && !(delta == -2 && k == 0)) mma_bf16(acc[nb], a0, a1, a2, a3, H[2 * k + 1], H[2 * k]);
      }
    }
    p0 = c[2]; p1 = c[3];
  }
}

__global__ void __cluster_dims__(2, 1, 1) __launch_bounds__(NTHREADS, 1)
fused_kernel(const __grid_constant__ Maps maps, const Ptrs p) {
  extern __shared__ __align__(1024) uint8_t smem[];
  const uint32_t sb = s2u(smem);
  const int tid = threadIdx.x, warp = tid >> 5, lane = tid & 31;
  const int cta = blockIdx.x;
  const uint32_t rank = cta & 1;
  const int ti = 2 * (cta >> 4) + rank;
  const int tj = (cta >> 1) & 7;
  const uint32_t bars = sb + SM_BAR;
#define BAR(i) (bars + 8 * (i))

  if (tid == 384) {
    TS(0);
#pragma unroll
    for (int i = 0; i < B_COUNT; ++i)
      mbar_init(BAR(i), i < 3 ? 1 : i < 6 ? 16 : i < B_QKVDONE ? 1 : i == B_CONVDONE ? 4 : i == B_TRDONE ? 3 : 8);
    asm volatile("fence.mbarrier_init.release.cluster;" ::: "memory");
    prefetch_tmap(&maps.x); prefetch_tmap(&maps.w); prefetch_tmap(&maps.u);
  }
  if (tid == 384) TS(32);
  __syncthreads();
  if (tid == 384) TS(33);
  cluster_arrive();
  if (tid == 384) TS(34);

  if (warp < 4) {
    asm volatile("setmaxnreg.inc.sync.aligned.u32 152;");
    const unsigned epoch = __ldcg(&g_epoch);
    const int ch = warp;
    const int d = cta * 4 + ch;
    const uint32_t vv = sb + SM_VV + ch * VV_BYTES;
    const uint32_t ub = sb + SM_U + ch * U_BYTES;
    const uint32_t pb = sb + SM_P + ch * P_BYTES;
    const uint32_t kf = vv + VV_KF;
    const int g = lane >> 2, q = lane & 3;

    float inv, sc, zeta, dskip;
    {
      const size_t po = (size_t)d * 128 + lane * 4;
      uint2 raw[6];
      raw[0] = __ldg((const uint2*)(p.A_re + po)); raw[1] = __ldg((const uint2*)(p.A_im + po));
      raw[2] = __ldg((const uint2*)(p.B_re + po)); raw[3] = __ldg((const uint2*)(p.B_im + po));
      raw[4] = __ldg((const uint2*)(p.C_re + po)); raw[5] = __ldg((const uint2*)(p.C_im + po));
      const float dt = round_bf16(expf(bf2f(p.log_dt[d])));
      dskip = bf2f(p.Dskip[d]);
      float mz = 0.f, mw = 0.f;
#pragma unroll 1
      for (int rd = 0; rd < 4; ++rd) {
        float v[6];
#pragma unroll
        for (int a = 0; a < 6; ++a) {
          v[a] = bf_lo(raw[a].x);
          raw[a].x = __funnelshift_r(raw[a].x, raw[a].y, 16);
          raw[a].y >>= 16;
        }
        const float zr = dt * v[0], zi = dt * v[1], br = dt * v[2], bi = dt * v[3];
        const float wr = v[4] * br - v[5] * bi, wi = v[4] * bi + v[5] * br;
        mz = fmaxf(mz, zr); mw = fmaxf(mw, fmaxf(fabsf(wr), fabsf(wi)));
        sts128(kf + (rd * 32 + lane) * 16, __float_as_uint(zr), __float_as_uint(zi), __float_as_uint(wr), __float_as_uint(wi));
      }
#pragma unroll 1
      for (int o = 16; o > 0; o >>= 1) {
        mz = fmaxf(mz, __shfl_xor_sync(0xffffffffu, mz, o));
        mw = fmaxf(mw, __shfl_xor_sync(0xffffffffu, mw, o));
      }
      const int E = min(max((__float_as_int(mw) >> 23) & 255, 1), 252);
      sc = __int_as_float((253 - E) << 23);
      inv = __int_as_float((E + 1) << 23);
      zeta = mz;
    }
    if (lane == 0) TS(1);

    float Dk[4][8];
    float k2048 = 0.f;
    const uint32_t laneoff = ((lane >> 2) << 4) | ((lane & 3) << 2);
#pragma unroll 1
    for (int rd = 0; rd < 4; ++rd) {
      uint32_t val[56];
      {
        const uint4 zw = lds128(kf + (rd * 32 + lane) * 16);
        const float zl = (__uint_as_float(zw.x) - zeta) * 1.4426950408889634f, zim = __uint_as_float(zw.y);
        const float w_r = __uint_as_float(zw.z) * sc, w_i = __uint_as_float(zw.w) * sc;
        C32 e1 = cfresh(zl, zim, 1.f), e2 = csq(e1), e4 = csq(e2), e8 = csq(e4);
        C32 e16 = cfresh(zl, zim, 16.f), e32 = csq(e16), e64 = csq(e32), e128 = csq(e64);
        C32 e256 = cfresh(zl, zim, 256.f), e512 = csq(e256), e1024 = csq(e512), e2048 = csq(e1024);
        k2048 += w_r * e2048.re - w_i * e2048.im;
        HMul m16 = mk_mul(e16.re, e16.im), m32 = mk_mul(e32.re, e32.im), m64 = mk_mul(e64.re, e64.im);
        uint32_t* X = val + 40;
        X[0] = 0x00003c00u;
        X[1] = pack_f16(e8.re, e8.im); X[2] = m16.b; X[4] = m32.b; X[8] = m64.b;
        X[3] = hcmul(X[1], m16); X[5] = hcmul(X[1], m32); X[6] = hcmul(X[2], m32); X[7] = hcmul(X[3], m32);
#pragma unroll
        for (int r = 1; r < 8; ++r) X[8 + r] = hcmul(X[r], m64);
        HMul c1 = mk_mul(e1.re, -e1.im), c2 = mk_mul(e2.re, -e2.im), c4 = mk_mul(e4.re, -e4.im);
        uint32_t W[8];
        W[0] = pack_f16(w_r, -w_i);
        W[1] = hcmul(W[0], c1); W[2] = hcmul(W[0], c2); W[3] = hcmul(W[1], c2);
        W[4] = hcmul(W[0], c4); W[5] = hcmul(W[1], c4); W[6] = hcmul(W[2], c4); W[7] = hcmul(W[3], c4);
        C32 e384 = cmul(e256, e128), e640 = cmul(e512, e128), e768 = cmul(e512, e256), e896 = cmul(e768, e128);
        HMul c128 = mk_mul(e128.re, -e128.im), c256 = mk_mul(e256.re, -e256.im), c384 = mk_mul(e384.re, -e384.im);
        HMul c512 = mk_mul(e512.re, -e512.im), c640 = mk_mul(e640.re, -e640.im), c768 = mk_mul(e768.re, -e768.im);
        HMul c896 = mk_mul(e896.re, -e896.im), c1024 = mk_mul(e1024.re, -e1024.im);
#pragma unroll
        for (int i = 0; i < 8; ++i) { val[i] = W[i]; val[8 + i] = hcmul(W[i], c128); }
#pragma unroll
        for (int i = 0; i < 4; ++i) { val[16 + i] = hcmul(W[2 * i], c256); val[20 + i] = hcmul(W[2 * i], c384); }
        val[24] = hcmul(W[0], c512); val[25] = hcmul(W[4], c512);
        val[26] = hcmul(W[0], c640); val[27] = hcmul(W[4], c640);
        val[28] = hcmul(W[0], c768); val[29] = hcmul(W[4], c768);
        val[30] = hcmul(W[0], c896); val[31] = hcmul(W[4], c896);
        const uint32_t v0 = hcmul(W[0], c1024);
        val[32] = v0; val[33] = hcmul(v0, c128); val[34] = hcmul(v0, c256); val[35] = hcmul(v0, c384);
        val[36] = hcmul(v0, c512); val[37] = hcmul(v0, c640); val[38] = hcmul(v0, c768); val[39] = hcmul(v0, c896);
      }
      if (tid == 0) TS(36 + rd * 3);
      if (rd > 0) { wg_wait<0>(); bar_sync(2, 128); }
      if (tid == 0) TS(37 + rd * 3);
#pragma unroll
      for (int r = 0; r < 56; ++r) sts32(vv + r * 128 + (laneoff ^ ((r & 7) << 4)), val[r]);
      fence_async_smem();
      bar_sync(2, 128);
      wg_fence();
#pragma unroll
      for (int c = 0; c < 4; ++c) {
        const uint64_t da = mkdesc(sb + SM_VV + c * VV_BYTES, 16, 1024);
#pragma unroll
        for (int k = 0; k < 4; ++k) wgmma_n16_f16(Dk[c], da + 2 * k, da + 320 + 2 * k, (rd | k) != 0);
      }
      wg_commit();
      if (tid == 0) TS(38 + rd * 3);
    }
    wg_wait<0>();
    if (tid == 0) TS(48);
    bar_sync(2, 128);
    if (warp < 3) {
#pragma unroll
      for (int c = 0; c < 4; ++c) {
        const uint32_t a = sb + SM_VV + c * VV_BYTES + VV_KF + ((16 * warp + g) * 16 + 2 * q) * 4;
        sts_f32x2(a, Dk[c][0], Dk[c][1]);
        sts_f32x2(a + 32, Dk[c][4], Dk[c][5]);
        if (warp < 2) {
          sts_f32x2(a + 512, Dk[c][2], Dk[c][3]);
          sts_f32x2(a + 544, Dk[c][6], Dk[c][7]);
        }
      }
    }
#pragma unroll 1
    for (int o = 16; o > 0; o >>= 1) k2048 += __shfl_xor_sync(0xffffffffu, k2048, o);
    if (lane == 0) TS(2);
    mbar_wait(BAR(B_TRDONE), 0);
    bar_sync(2, 128);
    if (lane == 0) {
      TS(50);
      wait_counter(&g_cnt[(C_U + (cta >> 4)) * 32], (epoch + 1) * 16);
      fence_async_all();
      mbar_expect_tx(BAR(B_UCH + ch), 4096);
      bulk_load(ub + 256, p.uT + (size_t)d * 2048, 4096, BAR(B_UCH + ch));
      TS(3);
    }
    __syncwarp();
    if (lane < 16) sts128(ub + lane * 16, 0, 0, 0, 0);
    if (zeta > 0.f) {
      const float zt = zeta * 1.4426950408889634f;
#pragma unroll 1
      for (int i = lane; i < 640; i += 32) sts_f32(kf + i * 4, lds_f32(kf + i * 4) * ex2(zt * kidx_l(i)));
      k2048 *= ex2(zt * 2048.f);
      __syncwarp();
    }
    const float k1024 = lds_f32(kf + kidx_c(1024) * 4) * inv;
    if (lane == 0) {
      sts_f32(kf + SL_K2048 * 4, k2048);
      sts_f32(kf + SL_ZERO * 4, 0.f);
      sts_f32(kf + SL_510 * 4, lds_f32(kf + kidx_c(510) * 4) - lds_f32(kf + kidx_c(512) * 4));
      sts_f32(kf + SL_0 * 4, lds_f32(kf) + dskip * sc);
    }
    __syncwarp();
#pragma unroll 5
    for (int i = 0; i < 30; ++i) {
      const uint32_t e = lds32(sb + SM_PTAB + (i * 32 + lane) * 4);
      sts32(pb + (i * 32 + lane) * 4, pack_bf16(lds_f32(kf + (e & 0xffff)) * inv, lds_f32(kf + (e >> 16)) * inv));
    }
    __syncwarp();
    if (lane == 0) TS(4);
    mbar_wait(BAR(B_UCH + ch), 0);
    if (lane == 0) TS(5);
#pragma unroll 1
    for (int it = 0; it < 8; ++it) {
      const int k = -18 + it * 32 + lane;
      const int kr = min(max(k, -2), 208);
      uint32_t E[12];
#pragma unroll
      for (int c = 0; c < 3; ++c) {
        const int kk = kr - 1 + c, r = (kk >> 1) + 8;
        const uint4 t = lds128(ub + r * 32 + (((kk & 1) ^ ((r >> 2) & 1)) << 4));
        E[4 * c] = t.x; E[4 * c + 1] = t.y; E[4 * c + 2] = t.z; E[4 * c + 3] = t.w;
      }
      uint32_t O[8];
#pragma unroll
      for (int j = 0; j < 8; ++j) O[j] = __byte_perm(E[j + 1], E[j + 2], 0x5432);
      uint32_t s3[6], s5[4], s7[4], s9[4];
#pragma unroll
      for (int j = 0; j < 6; ++j) s3[j] = badd(badd(O[j], O[j + 1]), E[j + 2]);
#pragma unroll
      for (int j = 0; j < 4; ++j) {
        s5[j] = badd(s3[j + 2], badd(E[j + 3], E[j + 5]));
        s7[j] = badd(s5[j], badd(O[j + 1], O[j + 4]));
        s9[j] = badd(s7[j], badd(E[j + 2], E[j + 6]));
      }
      const int r = (k >> 1) + PADV;
      const uint32_t a = vv + r * 32 + (((k & 1) ^ ((r >> 2) & 1)) << 4);
      if (k < 208) { sts128(a + VV_U3, s3[0], s3[1], s3[2], s3[3]); sts128(a + VV_U5, s5[0], s5[1], s5[2], s5[3]); }
      if (k < 144) { sts128(a + VV_U7, s7[0], s7[1], s7[2], s7[3]); sts128(a + VV_U9, s9[0], s9[1], s9[2], s9[3]); }
    }
    __syncwarp();
    if (lane == 0) TS(6);
    mbar_wait(BAR(B_QKVDONE), 0);
    if (lane == 0) TS(7);
    float acc[16][4];
#pragma unroll
    for (int i = 0; i < 16; ++i) { acc[i][0] = acc[i][1] = acc[i][2] = acc[i][3] = 0.f; }
    {
      const int gq = g - 2 * q;
      const uint32_t pd_lane = pb + (PD_OFF + 16 + gq) * 4;
      const int prow0 = 8 + (lane & 7) + ((lane >> 4) << 3), hs = (lane >> 3) & 1;
#pragma unroll 1
      for (int rho = 0; rho < 8; ++rho) {
        uint32_t A[4][3];
#pragma unroll
        for (int i = 0; i < 4; ++i) {
          const uint32_t a = pd_lane + (uint32_t)(2 * rho + 16 * i) * 32;
          A[i][0] = lds32(a); A[i][1] = lds32(a + 32); A[i][2] = lds32(a - 32);
        }
        const int prow = prow0 - rho;
        const uint32_t la = ub + prow * 32 + ((hs ^ ((prow >> 2) & 1)) << 4);
        uint32_t B[2][4];
        ldsm_x4(B[0], la);
#pragma unroll
        for (int m2 = 0; m2 < 8; ++m2) {
          if (m2 < 7) ldsm_x4(B[(m2 + 1) & 1], la + (m2 + 1) * 512);
#pragma unroll
          for (int h = 0; h < 2; ++h)
#pragma unroll
            for (int i = 0; i < 4; ++i)
              if (2 * m2 + h + i < 16)
                mma_bf16(acc[2 * m2 + h + i], A[i][0], A[i][1], A[i][2], A[i][0], B[m2 & 1][2 * h], B[m2 & 1][2 * h + 1]);
        }
      }
      {
        const float kfix = -round_bf16(k1024);
        const uint32_t kf2 = pack_bf16(kfix, kfix);
        auto hfix = [&](int x) { return (x == 1020 ? kf2 & 0xffffu : x == 1021 ? kf2 : x == 1022 ? kf2 & 0xffff0000u : 0u); };
        const uint32_t h127 = hfix(1016 + gq), h128 = hfix(1024 + gq);
        const uint32_t h63 = lds32(pd_lane + 63 * 32), h64 = lds32(pd_lane + 64 * 32);
        const uint32_t la0 = ub + prow0 * 32 + ((hs ^ ((prow0 >> 2) & 1)) << 4);
        const uint32_t la7 = ub + (prow0 - 7) * 32 + ((hs ^ (((prow0 - 7) >> 2) & 1)) << 4);
#pragma unroll
        for (int m2 = 0; m2 < 6; ++m2) {
          uint32_t B0[4], B7[4];
          ldsm_x4(B0, la0 + m2 * 512);
          if (m2 < 5) ldsm_x4(B7, la7 + m2 * 512);
#pragma unroll
          for (int h = 0; h < 2; ++h) {
            const int m = 2 * m2 + h;
            mma_bf16(acc[m + 4], h64, 0u, h63, h64, B0[2 * h], B0[2 * h + 1]);
            if (m + 8 < 16) mma_bf16(acc[m + 8], h128, 0u, h127, h128, B0[2 * h], B0[2 * h + 1]);
            if (m + 7 < 16) mma_bf16(acc[m + 7], 0u, h127, 0u, 0u, B7[2 * h], B7[2 * h + 1]);
          }
        }
      }
#pragma unroll 1
      for (int v = 0; v < 4; ++v)
        conv_tail<4, 3, 11>(acc, pb + (P2_OFF + 56 * v + gq - 16) * 4, vv + ((v & 1) ? VV_U3 : VV_U5), v >> 1, v == 0, lane);
#pragma unroll 1
      for (int pi = 0; pi < 2; ++pi)
        conv_tail<8, 5, 7>(acc, pb + (P3_OFF + 88 * pi + gq - 48) * 4, vv + (pi ? VV_U7 : VV_U9), pi, pi == 0, lane);
    }
    __syncwarp();
    if (lane == 0) { mbar_arrive(BAR(B_CONVDONE)); TS(8); }
    {
      const int mt = lane >> 3;
      const uint32_t a = vv + (128 * (mt >> 1) + 16 * (lane & 7) + 8 * (mt & 1)) * 2;
#pragma unroll
      for (int ab = 0; ab < 16; ab += 2)
        stsm_x4_t(a + ab * 256, pack_bf16(acc[ab][0], acc[ab][1]), pack_bf16(acc[ab][2], acc[ab][3]),
                  pack_bf16(acc[ab + 1][0], acc[ab + 1][1]), pack_bf16(acc[ab + 1][2], acc[ab + 1][3]));
    }
    fence_async_smem();
    __syncwarp();
    if (lane == 0) {
      bulk_store(p.yT + (size_t)d * 2048, vv, 4096);
      bulk_commit();
      bulk_wait0();
      red_release_add(&g_cnt[(C_Y + (cta >> 4)) * 32], 1);
      TS(9);
    }
    cluster_wait();
  } else if (warp < 12) {
    asm volatile("setmaxnreg.inc.sync.aligned.u32 160;");
    const unsigned epoch = __ldcg(&g_epoch);
    const int w8 = warp - 4;
    const int g = lane >> 2, q = lane & 3;
    cluster_wait();
    {
      float acc[96];
#pragma unroll 1
      for (int ks = 0, s = 0, ph = 0; ks < 8; ++ks) {
        mbar_wait(BAR(B_FULL + s), ph);
        if (ks == 0 && tid == 128) TS(16);
        const uint32_t st = sb + s * STG_BYTES;
        const uint64_t da = mkdesc(st + STG_X + (w8 >> 2) * 8192, 16, 1024);
        const uint64_t db = mkdesc(st + STG_W, 8192, 1024);
        wg_fence();
#pragma unroll
        for (int k = 0; k < 4; ++k) wgmma_n192(acc, da + 2 * k, db + 128 * k, (ks | k) != 0);
        wg_commit();
        const uint32_t eprev = BAR(B_EMPTY + (s == 0 ? 2 : s - 1));
        if (++s == 3) { s = 0; ph ^= 1; }
        if (ks > 0) {
          wg_wait<1>();
          if (lane < 2) mbar_arrive_cluster(eprev, lane);
        }
      }
      wg_wait<0>();
      if (lane < 2) mbar_arrive_cluster(BAR(B_EMPTY + 1), lane);
      if (lane == 0) mbar_arrive(BAR(B_QKVDONE));
      if (tid == 128) TS(17);
      bar_sync(1, 256);
      const int row = w8 * 16 + (lane & 7) + (((lane >> 3) & 1) << 3);
      const uint32_t ra = sb + SM_QS + row * 128;
#pragma unroll
      for (int i = 0; i < 24; i += 2)
        stsm_x4(ra + (i >> 3) * 16384 + ((((i & 7) + (lane >> 4)) ^ (row & 7)) << 4), pack_bf16(acc[4 * i], acc[4 * i + 1]),
                pack_bf16(acc[4 * i + 2], acc[4 * i + 3]), pack_bf16(acc[4 * i + 4], acc[4 * i + 5]),
                pack_bf16(acc[4 * i + 6], acc[4 * i + 7]));
    }
    __syncwarp();
    const unsigned par = epoch & 1;
    const int hh = w8 >> 1, dtile = w8 & 1;
    float* kvg = &g_kv[par][tj][hh][0];
#pragma unroll 1
    for (int part = 1; part >= 0; --part) {
      const uint32_t pa = sb + SM_QS + part * 16384 + w8 * 2048 + lane * 16;
#pragma unroll 1
      for (int it = 0; it < 4; ++it) {
        uint4 t = lds128(pa + it * 512);
        uint32_t* tw = &t.x;
#pragma unroll
        for (int j = 0; j < 4; ++j) {
          const uint32_t x = tw[j];
          const __nv_bfloat162 xb = *reinterpret_cast<const __nv_bfloat162*>(&x);
          const uint32_t e = pack_bf16(ex2(bf_lo(x) * 1.4426950408889634f), ex2(bf_hi(x) * 1.4426950408889634f));
          const uint32_t m = __hgt2_mask(xb, __floats2bfloat162_rn(0.f, 0.f));
          const uint32_t sel = (badd(x, 0x3f803f80u) & m) | (e & ~m);
          tw[j] = pack_bf16(bf_lo(sel) + 1e-6f, bf_hi(sel) + 1e-6f);
        }
        sts128(pa + it * 512, t.x, t.y, t.z, t.w);
      }
      if (part == 1) {
        if (tid == 128) TS(53);
        bar_sync(1, 256);
        float kv[4] = {0.f, 0.f, 0.f, 0.f}, zz[4] = {0.f, 0.f, 0.f, 0.f};
        const int m = lane >> 3;
        const uint32_t aa = sb + SM_VS + ((lane & 7) + ((m >> 1) << 3)) * 128 + (((2 * hh + (m & 1)) ^ (lane & 7)) << 4);
        const uint32_t ab = sb + SM_PK + (lane & 15) * 128 + (((2 * hh + dtile) ^ (lane & 7)) << 4);
#pragma unroll 2
        for (int ks = 0; ks < 8; ++ks) {
          uint32_t a[4], b0, b1;
          ldsm_x4_t(a, aa + ks * 2048);
          ldsm_x2_t(b0, b1, ab + ks * 2048);
          mma_bf16(kv, a[0], a[1], a[2], a[3], b0, b1);
          mma_bf16(zz, 0x3f803f80u, 0x3f803f80u, 0x3f803f80u, 0x3f803f80u, b0, b1);
        }
        asm volatile("red.global.add.v4.f32 [%0], {%1,%2,%3,%4};" ::"l"(kvg + dtile * 128 + lane * 4), "f"(kv[0]), "f"(kv[1]),
                     "f"(kv[2]), "f"(kv[3]) : "memory");
        if (g == 0)
          asm volatile("red.global.add.v2.f32 [%0], {%1,%2};" ::"l"(kvg + 256 + dtile * 8 + 2 * q), "f"(zz[0]), "f"(zz[1]) : "memory");
        if (tid == 128) TS(55);
        bar_sync(1, 256);
        if (lane == 0) mbar_arrive(BAR(B_PKVFREE));
        if (tid == 128) { red_release_add(&g_cnt[(C_KV + tj) * 32], 1); TS(18); }
        if (ti == 0) {
          float4* z = (float4*)&g_kv[par ^ 1][tj][0][0];
          for (int i = tid - 128; i < 272; i += 256) z[i] = make_float4(0.f, 0.f, 0.f, 0.f);
        }
      }
    }
    if (tid == 128) { TS(56); wait_counter(&g_cnt[(C_KV + tj) * 32], (epoch + 1) * 16); TS(19); }
    bar_sync(1, 256);
    {
      const float4 k4 = __ldcg((const float4*)(kvg + dtile * 128 + lane * 4));
      const float2 z2 = __ldcg((const float2*)(kvg + 256 + dtile * 8 + 2 * q));
      const uint32_t a = sb + SM_KVB + hh * 512 + lane * 16 + dtile * 4;
      sts32(a, pack_bf16(k4.x, k4.y));
      sts32(a + 8, pack_bf16(k4.z, k4.w));
      if (g == 0) sts32(sb + SM_KVB + 2048 + hh * 32 + q * 8 + dtile * 4, pack_bf16(z2.x, z2.y));
    }
    bar_sync(1, 256);
    {
      const int row = w8 * 16 + (lane & 7) + (((lane >> 3) & 1) << 3);
      uint4* dst = &g_ofrag[((ti * 8 + w8) * 32 + 4 * tj) * 32 + lane];
#pragma unroll 1
      for (int h = 0; h < 4; ++h) {
        uint32_t a[4];
        ldsm_x4(a, sb + SM_QS + row * 128 + (((2 * h + (lane >> 4)) ^ (row & 7)) << 4));
        const uint4 kb = lds128(sb + SM_KVB + h * 512 + lane * 16);
        const uint32_t zb0 = lds32(sb + SM_KVB + 2048 + h * 32 + q * 8), zb1 = lds32(sb + SM_KVB + 2048 + h * 32 + q * 8 + 4);
        float n0[4] = {0.f, 0.f, 0.f, 0.f}, n1[4] = {0.f, 0.f, 0.f, 0.f}, dn[4] = {0.f, 0.f, 0.f, 0.f};
        mma_bf16(n0, a[0], a[1], a[2], a[3], kb.x, kb.y);
        mma_bf16(n1, a[0], a[1], a[2], a[3], kb.z, kb.w);
        mma_bf16(dn, a[0], a[1], a[2], a[3], zb0, zb1);
        const uint32_t dd = pack_bf16(dn[0], dn[2]);
        const uint32_t d2 = pack_bf16(bf_lo(dd) + 1e-6f, bf_hi(dd) + 1e-6f);
        const float r0 = rcp(bf_lo(d2)), r1 = rcp(bf_hi(d2));
        const uint32_t x0 = pack_bf16(n0[0], n0[1]), x1 = pack_bf16(n0[2], n0[3]);
        const uint32_t x2 = pack_bf16(n1[0], n1[1]), x3 = pack_bf16(n1[2], n1[3]);
        dst[h * 32] = make_uint4(pack_bf16(bf_lo(x0) * r0, bf_hi(x0) * r0), pack_bf16(bf_lo(x1) * r1, bf_hi(x1) * r1),
                                 pack_bf16(bf_lo(x2) * r0, bf_hi(x2) * r0), pack_bf16(bf_lo(x3) * r1, bf_hi(x3) * r1));
      }
    }
    if (tid == 128) TS(57);
    bar_sync(1, 256);
    if (tid == 128) {
      red_release_add(&g_cnt[(C_O + ti) * 32], 1);
      TS(20);
      wait_counter(&g_cnt[(C_O + ti) * 32], (epoch + 1) * 8);
      if (cta == 0) g_epoch = epoch + 1;
      TS(21);
    }
    bar_sync(1, 256);
    {
      const uint4* src = &g_ofrag[((ti * 8 + w8) * 32) * 32 + lane];
      uint4 A0[8], A1[8];
#pragma unroll
      for (int h = 0; h < 8; ++h) A0[h] = __ldcg(src + h * 32);
#pragma unroll
      for (int h = 0; h < 8; ++h) A1[h] = __ldcg(src + (8 + h) * 32);
      mbar_wait(BAR(B_WO), 0);
      mbar_wait(BAR(B_CONVDONE), 0);
      if (tid == 128) TS(22);
      float o[32];
      const uint64_t db = mkdesc(sb + SM_WO, 8192, 1024);
#pragma unroll 1
      for (int it = 0; it < 2; ++it) {
        wg_fence();
#pragma unroll
        for (int h = 0; h < 8; ++h) wgmma_n64_rs(o, A0[h], db + (16 * it + h) * 128, (it | h) != 0);
        wg_commit();
        wg_wait<0>();
        if (it == 0) {
#pragma unroll
          for (int h = 0; h < 8; ++h) A0[h] = __ldcg(src + (16 + h) * 32);
        }
        wg_fence();
#pragma unroll
        for (int h = 0; h < 8; ++h) wgmma_n64_rs(o, A1[h], db + (16 * it + 8 + h) * 128, 1);
        wg_commit();
        wg_wait<0>();
        if (it == 0) {
#pragma unroll
          for (int h = 0; h < 8; ++h) A1[h] = __ldcg(src + (24 + h) * 32);
        }
      }
      const int row = w8 * 16 + (lane & 7) + (((lane >> 3) & 1) << 3);
#pragma unroll
      for (int i = 0; i < 8; i += 2)
        stsm_x4(sb + SM_BOUT + row * 128 + (((i + (lane >> 4)) ^ (row & 7)) << 4), pack_bf16(o[4 * i], o[4 * i + 1]),
                pack_bf16(o[4 * i + 2], o[4 * i + 3]), pack_bf16(o[4 * i + 4], o[4 * i + 5]), pack_bf16(o[4 * i + 6], o[4 * i + 7]));
      fence_async_smem();
      bar_sync(1, 256);
      if (tid == 128) {
        tma_store_2d(&maps.out, sb + SM_BOUT, 512 + 64 * tj, 128 * ti);
        bulk_commit();
        bulk_wait0();
        TS(23);
      }
    }
  } else {
    asm volatile("setmaxnreg.dec.sync.aligned.u32 40;");
    if (tid == 384) TS(49);
    if (warp == 13 && lane == 0) {
      mbar_expect_tx(BAR(B_UTILE), 16384);
      tma_load_2d(sb + SM_TIN1, &maps.u, tj * 64, ti * 128, BAR(B_UTILE));
    }
    if (warp >= 14) {
      const int t = tid - 448;
#pragma unroll
      for (int i = 0; i < 4; ++i)
        if (t + 64 * i < 240) {
          const uint4 v = __ldg((const uint4*)g_ptab.v + t + 64 * i);
          sts128(sb + SM_PTAB + (t + 64 * i) * 16, v.x, v.y, v.z, v.w);
        }
      __syncwarp();
      if (lane == 0) mbar_arrive(BAR(B_TRDONE));
    }
    if (tid == 384) TS(51);
    cluster_wait();
    if (tid == 384) TS(52);
    if (warp == 12) {
      if (lane == 0) {
#pragma unroll 1
        for (int ks = 0, s = 0, ph = 1; ks < 8; ++ks) {
          if (ks >= 3) mbar_wait(BAR(B_EMPTY + s), ph);
          const uint32_t st = sb + s * STG_BYTES, fb = BAR(B_FULL + s);
          if (ks == 0) TS(61);
          mbar_expect_tx(fb, STG_BYTES);
          tma_load_2d(st + STG_X, &maps.x, ks * 64, ti * 128, fb);
#pragma unroll 1
          for (int nb = 0; nb < 3; ++nb)
            tma_load_2d_mc(st + STG_W + nb * 8192 + rank * 4096, &maps.w, nb * 512 + tj * 64, ks * 64 + rank * 32, fb, 3);
          if (ks == 2) {
            l2_prefetch((const char*)p.wqkv + 192 * 3072 + cta * 7680, 7680);
            l2_prefetch((const char*)p.x + (size_t)cta * 16384, 16384);
            l2_prefetch((const char*)p.wo + (size_t)cta * 4096, 4096);
            prefetch_tmap(&maps.wo); prefetch_tmap(&maps.uT); prefetch_tmap(&maps.yT); prefetch_tmap(&maps.out);
          }
          if (++s == 3) { s = 0; ph ^= 1; }
        }
        TS(24);
        mbar_wait(BAR(B_EMPTY + 0), 0);
        mbar_wait(BAR(B_EMPTY + 1), 0);
        mbar_expect_tx(BAR(B_WO), 65536);
        tma_load_2d_mc(sb + SM_WO + rank * 32768, &maps.wo, tj * 64, rank * 256, BAR(B_WO), 3);
      }
    } else if (warp == 13) {
      const unsigned epoch = __ldcg(&g_epoch);
      mbar_wait(BAR(B_UTILE), 0);
      if (lane == 0) TS(26);
      transpose_tile<0>(sb + SM_TIN1, sb + SM_TOUT1, lane);
      if (lane == 0) TS(58);
      fence_async_smem();
      __syncwarp();
      if (lane == 0) {
        tma_store_2d(&maps.uT, sb + SM_TOUT1, ti * 128, tj * 64);
        tma_store_2d(&maps.uT, sb + SM_TOUT1 + 8192, ti * 128 + 64, tj * 64);
        bulk_commit();
        bulk_wait0();
        TS(59);
        red_release_add(&g_cnt[(C_U + tj) * 32], 1);
        mbar_arrive(BAR(B_TRDONE));
        TS(27);
        mbar_wait(BAR(B_PKVFREE), 0);
        wait_counter(&g_cnt[(C_Y + tj) * 32], (epoch + 1) * 64);
        fence_async_all();
        TS(28);
        mbar_expect_tx(BAR(B_YTILE), 16384);
        tma_load_2d(sb + SM_TIN2, &maps.yT, ti * 128, tj * 64, BAR(B_YTILE));
        tma_load_2d(sb + SM_TIN2 + 8192, &maps.yT, ti * 128 + 64, tj * 64, BAR(B_YTILE));
      }
      __syncwarp();
      mbar_wait(BAR(B_YTILE), 0);
      transpose_tile<1>(sb + SM_TIN2, sb + SM_TOUT2, lane);
      fence_async_smem();
      __syncwarp();
      if (lane == 0) {
        tma_store_2d(&maps.out, sb + SM_TOUT2, 64 * tj, 128 * ti);
        bulk_commit();
        bulk_wait0();
        TS(29);
      }
    }
  }
  __syncwarp();
  cluster_arrive();
  cluster_wait();
  if (tid == 0) TS(31);
#undef BAR
}

typedef CUresult (*EncodeFn)(CUtensorMap*, CUtensorMapDataType, cuuint32_t, void*, const cuuint64_t*, const cuuint64_t*,
                             const cuuint32_t*, const cuuint32_t*, CUtensorMapInterleave, CUtensorMapSwizzle,
                             CUtensorMapL2promotion, CUtensorMapFloatOOBfill);

static void make_map(EncodeFn enc, CUtensorMap* m, const void* base, uint64_t inner, uint64_t outer, uint32_t box_in,
                     uint32_t box_out) {
  cuuint64_t gd[2] = {inner, outer};
  cuuint64_t gs[1] = {inner * 2};
  cuuint32_t bd[2] = {box_in, box_out};
  cuuint32_t es[2] = {1, 1};
  enc(m, CU_TENSOR_MAP_DATA_TYPE_BFLOAT16, 2, const_cast<void*>(base), gd, gs, bd, es, CU_TENSOR_MAP_INTERLEAVE_NONE,
      CU_TENSOR_MAP_SWIZZLE_128B, CU_TENSOR_MAP_L2_PROMOTION_L2_128B, CU_TENSOR_MAP_FLOAT_OOB_FILL_NONE);
}

}

extern "C" void kernel_launch(void* const* d_in, const int* in_sizes, int n_in, void* d_out, int out_size) {
  using namespace s4la;
  (void)in_sizes; (void)n_in; (void)out_size;
  static EncodeFn enc = nullptr;
  static void *uT = nullptr, *yT = nullptr;
  if (!enc) {
    void* fn = nullptr;
    cudaDriverEntryPointQueryResult qr;
    cudaGetDriverEntryPoint("cuTensorMapEncodeTiled", &fn, cudaEnableDefault, &qr);
    enc = (EncodeFn)fn;
    cudaGetSymbolAddress(&uT, g_uT);
    cudaGetSymbolAddress(&yT, g_yT);
    cudaFuncSetAttribute(fused_kernel, cudaFuncAttributeMaxDynamicSharedMemorySize, SM_TOTAL);
  }
  const __nv_bfloat16* const* in = (const __nv_bfloat16* const*)d_in;
  Maps maps;
  make_map(enc, &maps.x, in[9], 512, 2048, 64, 128);
  make_map(enc, &maps.w, in[10], 1536, 512, 64, 32);
  make_map(enc, &maps.wo, in[11], 512, 512, 64, 256);
  make_map(enc, &maps.u, in[0], 512, 2048, 64, 128);
  make_map(enc, &maps.uT, uT, 2048, 512, 64, 64);
  make_map(enc, &maps.yT, yT, 2048, 512, 64, 64);
  make_map(enc, &maps.out, d_out, 1024, 2048, 64, 128);
  Ptrs p;
  p.A_re = in[1]; p.A_im = in[2]; p.B_re = in[3]; p.B_im = in[4]; p.C_re = in[5]; p.C_im = in[6];
  p.log_dt = in[7]; p.Dskip = in[8]; p.x = in[9]; p.wqkv = in[10]; p.wo = in[11];
  p.uT = (__nv_bfloat16*)uT; p.yT = (__nv_bfloat16*)yT;
  fused_kernel<<<NCTA, NTHREADS, SM_TOTAL, cudaStreamPerThread>>>(maps, p);
}
```

```cpp
#include <cuda_runtime.h>
#include <cuda_bf16.h>
#include <cuda_fp16.h>
#include <cuda.h>
#include <stdint.h>

#define DEVI __device__ __forceinline__

namespace s4la {

constexpr int NTHREADS = 512;
constexpr int NCTA = 128;

constexpr uint32_t STG_BYTES = 40960, STG_X = 0, STG_W = 16384;
constexpr uint32_t SM_WO = 0;
constexpr uint32_t SM_QS = 65536;
constexpr uint32_t SM_BOUT = 65536;
constexpr uint32_t SM_PK = 81920;
constexpr uint32_t SM_VS = 98304;
constexpr uint32_t SM_KVB = 114688;
constexpr uint32_t SM_TIN2 = 81920, SM_TOUT2 = 98304;
constexpr uint32_t SM_U = 122880, U_BYTES = 4352;
constexpr uint32_t SM_P = 140288, P_BYTES = 4096;
constexpr uint32_t SM_TIN1 = SM_U, SM_TOUT1 = SM_P;
constexpr uint32_t SM_VV = 156672, VV_BYTES = 13312;
constexpr uint32_t VV_U5 = 0, VV_U3 = 3712, VV_U9 = 7424, VV_U7 = 10112;
constexpr uint32_t VV_KF = 8192;
constexpr uint32_t SM_BAR = 209920;
constexpr uint32_t SM_MISC = SM_BAR + 256;
constexpr uint32_t SM_PTAB = SM_MISC + 128;
constexpr uint32_t SM_TOTAL = SM_PTAB + 3840;
constexpr int PADV = 12;

enum { B_FULL = 0, B_EMPTY = 3, B_WO = 6, B_UTILE = 7, B_YTILE = 8, B_UCH = 9, B_QKVDONE = 13,
       B_CONVDONE = 14, B_TRDONE = 15, B_PKVFREE = 16, B_COUNT = 17 };

constexpr int PD_OFF = 0, P2_OFF = 544, P3_OFF = 768;

constexpr int SL_K2048 = 640, SL_ZERO = 641, SL_510 = 642, SL_0 = 643;
__host__ __device__ constexpr int kidx_c(int l) {
  int r = (l >> 3) & 15, y = 0;
  if (l < 256) y = (l & 7) + ((l >> 7) << 3);
  else if (l < 512) y = 16 + (((l - 256) >> 7) << 2) + ((l & 7) >> 1);
  else if (l < 1024) y = 24 + (((l - 512) >> 7) << 1) + ((l >> 2) & 1);
  else y = 32 + ((l - 1024) >> 7);
  return y * 16 + r;
}
constexpr int slot_direct(int l) {
  if (l < 0 || l > 510) return SL_ZERO;
  if (l == 510) return SL_510;
  if (l == 0) return SL_0;
  return kidx_c(l < 256 ? l : ((l + ((l >> 1) & 1)) & ~1));
}
constexpr int slot_seg2(int v, int k) { return (k >= 32 && k < 64) ? kidx_c(16 * k + 4 * v) : SL_ZERO; }
constexpr int slot_seg3(int pi, int k) {
  return (k >= 64 && k < 128) ? kidx_c(16 * k + 8 * pi) : ((k == 128 && pi == 0) ? SL_K2048 : SL_ZERO);
}
struct PTab { uint32_t v[960]; };
constexpr PTab make_ptab() {
  PTab t{};
  for (int w = 0; w < 960; ++w) t.v[w] = (SL_ZERO * 4) | ((SL_ZERO * 4) << 16);
  for (int w = 0; w < 544; ++w) t.v[w] = (slot_direct(w - 16) * 4) | ((slot_direct(w - 17) * 4) << 16);
  for (int v = 0; v < 4; ++v)
    for (int x = 16; x < 72; ++x) t.v[544 + 56 * v + x - 16] = (slot_seg2(v, x) * 4) | ((slot_seg2(v, x - 1) * 4) << 16);
  for (int pi = 0; pi < 2; ++pi)
    for (int x = 48; x < 136; ++x) t.v[768 + 88 * pi + x - 48] = (slot_seg3(pi, x) * 4) | ((slot_seg3(pi, x - 1) * 4) << 16);
  return t;
}
__device__ const PTab g_ptab = make_ptab();

__device__ __nv_bfloat16 g_uT[512 * 2048];
__device__ __nv_bfloat16 g_yT[512 * 2048];
__device__ uint4 g_ofrag[16 * 8 * 32 * 32];
__device__ float g_kv[2][8][4][272];
__device__ unsigned g_cnt[64 * 32];
__device__ unsigned g_epoch;
#define TS(slot) do { } while (0)
enum { C_U = 0, C_KV = 8, C_O = 16, C_Y = 32 };

struct Maps {
  CUtensorMap x, w, wo, u, uT, yT, out;
};
struct Ptrs {
  const __nv_bfloat16 *A_re, *A_im, *B_re, *B_im, *C_re, *C_im, *log_dt, *Dskip;
  const __nv_bfloat16 *x, *wqkv, *wo;
  __nv_bfloat16 *uT, *yT;
};

DEVI uint32_t s2u(const void* p) { return (uint32_t)__cvta_generic_to_shared(p); }
DEVI void mbar_init(uint32_t b, uint32_t c) { asm volatile("mbarrier.init.shared::cta.b64 [%0], %1;" ::"r"(b), "r"(c) : "memory"); }
DEVI void mbar_expect_tx(uint32_t b, uint32_t bytes) {
  asm volatile("mbarrier.arrive.expect_tx.shared::cta.b64 _, [%0], %1;" ::"r"(b), "r"(bytes) : "memory");
}
DEVI void mbar_arrive(uint32_t b) { asm volatile("mbarrier.arrive.shared::cta.b64 _, [%0];" ::"r"(b) : "memory"); }
DEVI void mbar_arrive_cluster(uint32_t b, uint32_t cta) {
  asm volatile("{\n.reg .b32 r;\nmapa.shared::cluster.u32 r, %0, %1;\nmbarrier.arrive.shared::cluster.b64 _, [r];\n}"
               ::"r"(b), "r"(cta) : "memory");
}
DEVI void mbar_wait(uint32_t b, uint32_t parity) {
  asm volatile("{\n.reg .pred p;\nLAB_WAIT:\nmbarrier.try_wait.parity.shared::cta.b64 p, [%0], %1, 0x989680;\n@p bra LAB_DONE;\nbra LAB_WAIT;\nLAB_DONE:\n}"
               ::"r"(b), "r"(parity) : "memory");
}
#define mbar_wait_cluster mbar_wait
DEVI void bar_sync(int id, int n) { asm volatile("bar.sync %0, %1;" ::"r"(id), "r"(n) : "memory"); }
DEVI void fence_async_smem() { asm volatile("fence.proxy.async.shared::cta;" ::: "memory"); }
DEVI void fence_async_all() { asm volatile("fence.proxy.async;" ::: "memory"); }
DEVI void cluster_arrive() { asm volatile("barrier.cluster.arrive.relaxed.aligned;" ::: "memory"); }
DEVI void cluster_wait() { asm volatile("barrier.cluster.wait.aligned;" ::: "memory"); }

DEVI void tma_load_2d(uint32_t dst, const CUtensorMap* m, int c0, int c1, uint32_t bar) {
  asm volatile("cp.async.bulk.tensor.2d.shared::cluster.global.mbarrier::complete_tx::bytes [%0], [%1, {%3, %4}], [%2];"
               ::"r"(dst), "l"(m), "r"(bar), "r"(c0), "r"(c1) : "memory");
}
DEVI void tma_load_2d_mc(uint32_t dst, const CUtensorMap* m, int c0, int c1, uint32_t bar, uint16_t mask) {
  asm volatile("cp.async.bulk.tensor.2d.shared::cluster.global.mbarrier::complete_tx::bytes.multicast::cluster [%0], [%1, {%3, %4}], [%2], %5;"
               ::"r"(dst), "l"(m), "r"(bar), "r"(c0), "r"(c1), "h"(mask) : "memory");
}
DEVI void tma_store_2d(const CUtensorMap* m, uint32_t src, int c0, int c1) {
  asm volatile("cp.async.bulk.tensor.2d.global.shared::cta.bulk_group [%0, {%2, %3}], [%1];"
               ::"l"(m), "r"(src), "r"(c0), "r"(c1) : "memory");
}
DEVI void bulk_load(uint32_t dst, const void* src, uint32_t bytes, uint32_t bar) {
  asm volatile("cp.async.bulk.shared::cluster.global.mbarrier::complete_tx::bytes [%0], [%1], %2, [%3];"
               ::"r"(dst), "l"(src), "r"(bytes), "r"(bar) : "memory");
}
DEVI void bulk_store(void* dst, uint32_t src, uint32_t bytes) {
  asm volatile("cp.async.bulk.global.shared::cta.bulk_group [%0], [%1], %2;" ::"l"(dst), "r"(src), "r"(bytes) : "memory");
}
DEVI void bulk_commit() { asm volatile("cp.async.bulk.commit_group;" ::: "memory"); }
DEVI void bulk_wait0() { asm volatile("cp.async.bulk.wait_group 0;" ::: "memory"); }
DEVI void l2_prefetch(const void* p, uint32_t bytes) {
  asm volatile("cp.async.bulk.prefetch.L2.global [%0], %1;" ::"l"(p), "r"(bytes) : "memory");
}
DEVI void prefetch_tmap(const CUtensorMap* m) { asm volatile("prefetch.tensormap [%0];" ::"l"(m) : "memory"); }

DEVI void red_release_add(unsigned* p, unsigned v) {
  asm volatile("red.release.gpu.global.add.u32 [%0], %1;" ::"l"(p), "r"(v) : "memory");
}
DEVI void red_relaxed_add(unsigned* p, unsigned v) {
  asm volatile("red.relaxed.gpu.global.add.u32 [%0], %1;" ::"l"(p), "r"(v) : "memory");
}
DEVI unsigned ld_relaxed(const unsigned* p) {
  unsigned v;
  asm volatile("ld.relaxed.gpu.global.u32 %0, [%1];" : "=r"(v) : "l"(p) : "memory");
  return v;
}
DEVI void wait_counter(const unsigned* p, unsigned target) {
#pragma unroll 1
  for (int it = 0; (int)(ld_relaxed(p) - target) < 0; ++it)
    if (it > (1 << 22)) __trap();
}

DEVI void ldsm_x4(uint32_t (&r)[4], uint32_t a) {
  asm volatile("ldmatrix.sync.aligned.m8n8.x4.shared.b16 {%0,%1,%2,%3}, [%4];"
               : "=r"(r[0]), "=r"(r[1]), "=r"(r[2]), "=r"(r[3]) : "r"(a) : "memory");
}
DEVI void ldsm_x4_t(uint32_t (&r)[4], uint32_t a) {
  asm volatile("ldmatrix.sync.aligned.m8n8.x4.trans.shared.b16 {%0,%1,%2,%3}, [%4];"
               : "=r"(r[0]), "=r"(r[1]), "=r"(r[2]), "=r"(r[3]) : "r"(a) : "memory");
}
DEVI void ldsm_x2_t(uint32_t& r0, uint32_t& r1, uint32_t a) {
  asm volatile("ldmatrix.sync.aligned.m8n8.x2.trans.shared.b16 {%0,%1}, [%2];" : "=r"(r0), "=r"(r1) : "r"(a) : "memory");
}
DEVI void stsm_x4(uint32_t a, uint32_t r0, uint32_t r1, uint32_t r2, uint32_t r3) {
  asm volatile("stmatrix.sync.aligned.m8n8.x4.shared.b16 [%0], {%1,%2,%3,%4};"
               ::"r"(a), "r"(r0), "r"(r1), "r"(r2), "r"(r3) : "memory");
}
DEVI void stsm_x4_t(uint32_t a, uint32_t r0, uint32_t r1, uint32_t r2, uint32_t r3) {
  asm volatile("stmatrix.sync.aligned.m8n8.x4.trans.shared.b16 [%0], {%1,%2,%3,%4};"
               ::"r"(a), "r"(r0), "r"(r1), "r"(r2), "r"(r3) : "memory");
}
DEVI uint32_t lds32(uint32_t a) { uint32_t v; asm volatile("ld.shared.b32 %0, [%1];" : "=r"(v) : "r"(a) : "memory"); return v; }
DEVI float lds_f32(uint32_t a) { float v; asm volatile("ld.shared.f32 %0, [%1];" : "=f"(v) : "r"(a) : "memory"); return v; }
DEVI void sts32(uint32_t a, uint32_t v) { asm volatile("st.shared.b32 [%0], %1;" ::"r"(a), "r"(v) : "memory"); }
DEVI void sts_f32(uint32_t a, float v) { asm volatile("st.shared.f32 [%0], %1;" ::"r"(a), "f"(v) : "memory"); }
DEVI void sts_f32x2(uint32_t a, float x, float y) { asm volatile("st.shared.v2.f32 [%0], {%1,%2};" ::"r"(a), "f"(x), "f"(y) : "memory"); }
DEVI uint4 lds128(uint32_t a) {
  uint4 v;
  asm volatile("ld.shared.v4.b32 {%0,%1,%2,%3}, [%4];" : "=r"(v.x), "=r"(v.y), "=r"(v.z), "=r"(v.w) : "r"(a) : "memory");
  return v;
}
DEVI void sts128(uint32_t a, uint32_t x, uint32_t y, uint32_t z, uint32_t w) {
  asm volatile("st.shared.v4.b32 [%0], {%1,%2,%3,%4};" ::"r"(a), "r"(x), "r"(y), "r"(z), "r"(w) : "memory");
}

DEVI void mma_bf16(float (&d)[4], uint32_t a0, uint32_t a1, uint32_t a2, uint32_t a3, uint32_t b0, uint32_t b1) {
  asm("mma.sync.aligned.m16n8k16.row.col.f32.bf16.bf16.f32 {%0,%1,%2,%3}, {%4,%5,%6,%7}, {%8,%9}, {%0,%1,%2,%3};"
      : "+f"(d[0]), "+f"(d[1]), "+f"(d[2]), "+f"(d[3])
      : "r"(a0), "r"(a1), "r"(a2), "r"(a3), "r"(b0), "r"(b1));
}
DEVI uint32_t pack_bf16(float lo, float hi) {
  uint32_t r;
  asm("cvt.rn.bf16x2.f32 %0, %1, %2;" : "=r"(r) : "f"(hi), "f"(lo));
  return r;
}
DEVI uint32_t pack_f16(float lo, float hi) {
  uint32_t r;
  asm("cvt.rn.f16x2.f32 %0, %1, %2;" : "=r"(r) : "f"(hi), "f"(lo));
  return r;
}
DEVI float bf_lo(uint32_t v) { return __uint_as_float(v << 16); }
DEVI float bf_hi(uint32_t v) { return __uint_as_float(v & 0xffff0000u); }
DEVI float bf2f(__nv_bfloat16 v) { return __bfloat162float(v); }
DEVI float round_bf16(float v) { return __bfloat162float(__float2bfloat16_rn(v)); }
DEVI float rcp(float x) { float r; asm("rcp.approx.ftz.f32 %0, %1;" : "=f"(r) : "f"(x)); return r; }
DEVI float ex2(float x) { float r; asm("ex2.approx.ftz.f32 %0, %1;" : "=f"(r) : "f"(x)); return r; }

DEVI void wg_fence() { asm volatile("wgmma.fence.sync.aligned;" ::: "memory"); }
DEVI void wg_commit() { asm volatile("wgmma.commit_group.sync.aligned;" ::: "memory"); }
template <int N> DEVI void wg_wait() { asm volatile("wgmma.wait_group.sync.aligned %0;" ::"n"(N) : "memory"); }
constexpr uint32_t DESC_HI = (1u << 30) | (1024 >> 4);
DEVI uint32_t mkdesc(uint32_t saddr, uint32_t lbo) { return ((saddr & 0x3FFFF) >> 4) | ((lbo >> 4) << 16); }

#define R8(b) "%" #b
DEVI void wgmma_n192(float (&d)[96], uint32_t da, uint32_t db, int scale_d) {
  asm volatile(
      "{\n.reg .pred p;\n.reg .b64 da, db;\nsetp.ne.b32 p, %98, 0;\nmov.b64 da, {%96, %99};\nmov.b64 db, {%97, %99};\n"
      "wgmma.mma_async.sync.aligned.m64n192k16.f32.bf16.bf16 "
      "{%0,%1,%2,%3,%4,%5,%6,%7,%8,%9,%10,%11,%12,%13,%14,%15,"
      "%16,%17,%18,%19,%20,%21,%22,%23,%24,%25,%26,%27,%28,%29,%30,%31,"
      "%32,%33,%34,%35,%36,%37,%38,%39,%40,%41,%42,%43,%44,%45,%46,%47,"
      "%48,%49,%50,%51,%52,%53,%54,%55,%56,%57,%58,%59,%60,%61,%62,%63,"
      "%64,%65,%66,%67,%68,%69,%70,%71,%72,%73,%74,%75,%76,%77,%78,%79,"
      "%80,%81,%82,%83,%84,%85,%86,%87,%88,%89,%90,%91,%92,%93,%94,%95}, "
      "da, db, p, 1, 1, 0, 1;\n}"
      : "+f"(d[0]), "+f"(d[1]), "+f"(d[2]), "+f"(d[3]), "+f"(d[4]), "+f"(d[5]), "+f"(d[6]), "+f"(d[7]),
        "+f"(d[8]), "+f"(d[9]), "+f"(d[10]), "+f"(d[11]), "+f"(d[12]), "+f"(d[13]), "+f"(d[14]), "+f"(d[15]),
        "+f"(d[16]), "+f"(d[17]), "+f"(d[18]), "+f"(d[19]), "+f"(d[20]), "+f"(d[21]), "+f"(d[22]), "+f"(d[23]),
        "+f"(d[24]), "+f"(d[25]), "+f"(d[26]), "+f"(d[27]), "+f"(d[28]), "+f"(d[29]), "+f"(d[30]), "+f"(d[31]),
        "+f"(d[32]), "+f"(d[33]), "+f"(d[34]), "+f"(d[35]), "+f"(d[36]), "+f"(d[37]), "+f"(d[38]), "+f"(d[39]),
        "+f"(d[40]), "+f"(d[41]), "+f"(d[42]), "+f"(d[43]), "+f"(d[44]), "+f"(d[45]), "+f"(d[46]), "+f"(d[47]),
        "+f"(d[48]), "+f"(d[49]), "+f"(d[50]), "+f"(d[51]), "+f"(d[52]), "+f"(d[53]), "+f"(d[54]), "+f"(d[55]),
        "+f"(d[56]), "+f"(d[57]), "+f"(d[58]), "+f"(d[59]), "+f"(d[60]), "+f"(d[61]), "+f"(d[62]), "+f"(d[63]),
        "+f"(d[64]), "+f"(d[65]), "+f"(d[66]), "+f"(d[67]), "+f"(d[68]), "+f"(d[69]), "+f"(d[70]), "+f"(d[71]),
        "+f"(d[72]), "+f"(d[73]), "+f"(d[74]), "+f"(d[75]), "+f"(d[76]), "+f"(d[77]), "+f"(d[78]), "+f"(d[79]),
        "+f"(d[80]), "+f"(d[81]), "+f"(d[82]), "+f"(d[83]), "+f"(d[84]), "+f"(d[85]), "+f"(d[86]), "+f"(d[87]),
        "+f"(d[88]), "+f"(d[89]), "+f"(d[90]), "+f"(d[91]), "+f"(d[92]), "+f"(d[93]), "+f"(d[94]), "+f"(d[95])
      : "r"(da), "r"(db), "r"(scale_d), "n"(DESC_HI));
}
DEVI void wgmma_n64_rs(float (&d)[32], const uint4& a, uint32_t db, int scale_d) {
  asm volatile(
      "{\n.reg .pred p;\n.reg .b64 db;\nsetp.ne.b32 p, %37, 0;\nmov.b64 db, {%36, %38};\n"
      "wgmma.mma_async.sync.aligned.m64n64k16.f32.bf16.bf16 "
      "{%0,%1,%2,%3,%4,%5,%6,%7,%8,%9,%10,%11,%12,%13,%14,%15,"
      "%16,%17,%18,%19,%20,%21,%22,%23,%24,%25,%26,%27,%28,%29,%30,%31}, "
      "{%32,%33,%34,%35}, db, p, 1, 1, 1;\n}"
      : "+f"(d[0]), "+f"(d[1]), "+f"(d[2]), "+f"(d[3]), "+f"(d[4]), "+f"(d[5]), "+f"(d[6]), "+f"(d[7]),
        "+f"(d[8]), "+f"(d[9]), "+f"(d[10]), "+f"(d[11]), "+f"(d[12]), "+f"(d[13]), "+f"(d[14]), "+f"(d[15]),
        "+f"(d[16]), "+f"(d[17]), "+f"(d[18]), "+f"(d[19]), "+f"(d[20]), "+f"(d[21]), "+f"(d[22]), "+f"(d[23]),
        "+f"(d[24]), "+f"(d[25]), "+f"(d[26]), "+f"(d[27]), "+f"(d[28]), "+f"(d[29]), "+f"(d[30]), "+f"(d[31])
      : "r"(a.x), "r"(a.y), "r"(a.z), "r"(a.w), "r"(db), "r"(scale_d), "n"(DESC_HI));
}
DEVI void wgmma_n16_f16(float (&d)[8], uint32_t da, uint32_t db, int scale_d) {
  asm volatile(
      "{\n.reg .pred p;\n.reg .b64 da, db;\nsetp.ne.b32 p, %10, 0;\nmov.b64 da, {%8, %11};\nmov.b64 db, {%9, %11};\n"
      "wgmma.mma_async.sync.aligned.m64n16k16.f32.f16.f16 {%0,%1,%2,%3,%4,%5,%6,%7}, da, db, p, 1, 1, 0, 0;\n}"
      : "+f"(d[0]), "+f"(d[1]), "+f"(d[2]), "+f"(d[3]), "+f"(d[4]), "+f"(d[5]), "+f"(d[6]), "+f"(d[7])
      : "r"(da), "r"(db), "r"(scale_d), "n"(DESC_HI));
}

template <int MODE>
DEVI void transpose_tile(uint32_t src, uint32_t dst, int lane) {
  const int m = lane >> 3, r = lane & 7;
#pragma unroll 2
  for (int it = 0; it < 32; ++it) {
    uint32_t v[4];
    if (MODE == 0) {
      const int tb = it >> 1, cb = (it & 1) * 4 + m;
      ldsm_x4_t(v, src + (tb * 8 + r) * 128 + ((cb ^ r) << 4));
      const int b = tb >> 3;
      stsm_x4(dst + b * 8192 + (cb * 8 + r) * 128 + (((tb & 7) ^ b ^ r) << 4), v[0], v[1], v[2], v[3]);
    } else {
      const int cb = it & 7, tb = (it >> 3) * 4 + m;
      ldsm_x4_t(v, src + (tb >> 3) * 8192 + (cb * 8 + r) * 128 + (((tb & 7) ^ r) << 4));
      stsm_x4(dst + (tb * 8 + r) * 128 + ((cb ^ r) << 4), v[0], v[1], v[2], v[3]);
    }
  }
}

struct C32 { float re, im; };
DEVI C32 csq(C32 a) { return {a.re * a.re - a.im * a.im, 2.f * a.re * a.im}; }
DEVI C32 cmul(C32 a, C32 b) { return {a.re * b.re - a.im * b.im, a.re * b.im + a.im * b.re}; }
DEVI C32 cfresh(float zl, float zi, float m) {
  float mag = ex2(zl * m), ph = zi * m;
  return {mag * __cosf(ph), mag * __sinf(ph)};
}
struct HMul { uint32_t b, bp; };
DEVI HMul mk_mul(float re, float im) { return {pack_f16(re, im), pack_f16(-im, re)}; }
DEVI uint32_t hcmul(uint32_t a, const HMul& m) {
  __half2 ah = *reinterpret_cast<__half2*>(&a);
  __half2 b = *reinterpret_cast<const __half2*>(&m.b), bp = *reinterpret_cast<const __half2*>(&m.bp);
  __half2 r = __hfma2(__high2half2(ah), bp, __hmul2(__low2half2(ah), b));
  return *reinterpret_cast<uint32_t*>(&r);
}
DEVI uint32_t badd(uint32_t a, uint32_t b) {
  __nv_bfloat162 r = __hadd2(*reinterpret_cast<__nv_bfloat162*>(&a), *reinterpret_cast<__nv_bfloat162*>(&b));
  return *reinterpret_cast<uint32_t*>(&r);
}
DEVI int kidx_l(int i) {
  const int y = i >> 4, r = i & 15;
  int lo;
  if (y < 16) lo = (y & 7) + ((y >> 3) << 7);
  else if (y < 24) lo = 256 + (((y - 16) >> 2) << 7) + ((y & 3) << 1);
  else if (y < 32) lo = 512 + (((y - 24) >> 1) << 7) + ((y & 1) << 2);
  else lo = 1024 + ((y - 32) << 7);
  return lo + 8 * r;
}

template <int MU0, int NMU, int DMAX>
DEVI void conv_tail(float (&acc)[16][4], uint32_t p_lane, uint32_t v_base, int back, bool edge, int lane) {
  uint32_t H[2 * NMU];
#pragma unroll
  for (int i = 0; i < 2 * NMU; ++i) H[i] = lds32(p_lane + (uint32_t)(MU0 - 1 + i) * 32);
  const int hsel = (lane >> 3) & 1;
  const int row = (lane & 7) + ((lane >> 4) << 3) + PADV - 8 - (back & (hsel ^ 1));
  const uint32_t la = v_base + row * 32 + (((hsel ^ back) ^ ((row >> 2) & 1)) << 4);
  constexpr int NLD = (DMAX + 4) / 2;
  uint32_t M[2][4];
  uint32_t p0 = 0, p1 = 0;
  ldsm_x4_t(M[0], la);
#pragma unroll
  for (int ld = 0; ld < NLD; ++ld) {
    if (ld + 1 < NLD) ldsm_x4_t(M[(ld + 1) & 1], la + (ld + 1) * 512);
    const uint32_t* c = M[ld & 1];
#pragma unroll
    for (int s = 0; s < 2; ++s) {
      const int delta = 2 * ld - 2 + s;
      if (delta > DMAX) continue;
      if (delta == -2 && !edge) continue;
      const uint32_t a0 = s ? c[0] : p0, a1 = s ? c[1] : p1, a2 = s ? c[2] : c[0], a3 = s ? c[3] : c[1];
#pragma unroll
      for (int k = 0; k < NMU; ++k) {
        const int nb = delta + MU0 + 2 * k;
        if (nb < 16 && !(delta == -2 && k == 0)) mma_bf16(acc[nb], a0, a1, a2, a3, H[2 * k + 1], H[2 * k]);
      }
    }
    p0 = c[2]; p1 = c[3];
  }
}

__global__ void __cluster_dims__(2, 1, 1) __launch_bounds__(NTHREADS, 1)
fused_kernel(const __grid_constant__ Maps maps, const Ptrs p) {
  extern __shared__ __align__(1024) uint8_t smem[];
  const uint32_t sb = s2u(smem);
  const int tid = threadIdx.x, lane = tid & 31;
  const int warp = __shfl_sync(0xffffffffu, tid >> 5, 0);
  const int cta = blockIdx.x;
  const uint32_t rank = cta & 1;
  const int ti = 2 * (cta >> 4) + rank;
  const int tj = (cta >> 1) & 7;
  const uint32_t bars = sb + SM_BAR;
#define BAR(i) (bars + 8 * (i))

  if (tid == 384) {
    TS(0);
#pragma unroll
    for (int i = 0; i < B_COUNT; ++i)
      mbar_init(BAR(i), i < 3 ? 1 : i < 6 ? 16 : i < B_QKVDONE ? 1 : i == B_CONVDONE ? 4 : i == B_TRDONE ? 3 : 8);
    asm volatile("fence.mbarrier_init.release.cluster;" ::: "memory");
    prefetch_tmap(&maps.x); prefetch_tmap(&maps.w); prefetch_tmap(&maps.u);
  }
  if (tid == 384) TS(32);
  __syncthreads();
  if (tid == 384) TS(33);
  cluster_arrive();
  if (tid == 384) TS(34);

  if (warp < 4) {
    asm volatile("setmaxnreg.inc.sync.aligned.u32 152;");
    const unsigned epoch = __ldcg(&g_epoch);
    const int ch = warp;
    const int d = cta * 4 + ch;
    const uint32_t vv = sb + SM_VV + ch * VV_BYTES;
    const uint32_t ub = sb + SM_U + ch * U_BYTES;
    const uint32_t pb = sb + SM_P + ch * P_BYTES;
    const uint32_t kf = vv + VV_KF;
    const int g = lane >> 2, q = lane & 3;

    float inv, sc, zeta, dskip;
    {
      const size_t po = (size_t)d * 128 + lane * 4;
      uint2 raw[6];
      raw[0] = __ldg((const uint2*)(p.A_re + po)); raw[1] = __ldg((const uint2*)(p.A_im + po));
      raw[2] = __ldg((const uint2*)(p.B_re + po)); raw[3] = __ldg((const uint2*)(p.B_im + po));
      raw[4] = __ldg((const uint2*)(p.C_re + po)); raw[5] = __ldg((const uint2*)(p.C_im + po));
      const float dt = round_bf16(expf(bf2f(p.log_dt[d])));
      dskip = bf2f(p.Dskip[d]);
      float mz = 0.f, mw = 0.f;
#pragma unroll 1
      for (int rd = 0; rd < 4; ++rd) {
        float v[6];
#pragma unroll
        for (int a = 0; a < 6; ++a) {
          v[a] = bf_lo(raw[a].x);
          raw[a].x = __funnelshift_r(raw[a].x, raw[a].y, 16);
          raw[a].y >>= 16;
        }
        const float zr = dt * v[0], zi = dt * v[1], br = dt * v[2], bi = dt * v[3];
        const float wr = v[4] * br - v[5] * bi, wi = v[4] * bi + v[5] * br;
        mz = fmaxf(mz, zr); mw = fmaxf(mw, fmaxf(fabsf(wr), fabsf(wi)));
        sts128(kf + (rd * 32 + lane) * 16, __float_as_uint(zr), __float_as_uint(zi), __float_as_uint(wr), __float_as_uint(wi));
      }
#pragma unroll 1
      for (int o = 16; o > 0; o >>= 1) {
        mz = fmaxf(mz, __shfl_xor_sync(0xffffffffu, mz, o));
        mw = fmaxf(mw, __shfl_xor_sync(0xffffffffu, mw, o));
      }
      const int E = min(max((__float_as_int(mw) >> 23) & 255, 1), 252);
      sc = __int_as_float((253 - E) << 23);
      inv = __int_as_float((E + 1) << 23);
      zeta = mz;
    }
    if (lane == 0) TS(1);

    float Dk[4][8];
    float k2048 = 0.f;
    const uint32_t laneoff = ((lane >> 2) << 4) | ((lane & 3) << 2);
#pragma unroll 1
    for (int rd = 0; rd < 4; ++rd) {
      uint32_t val[56];
      {
        const uint4 zw = lds128(kf + (rd * 32 + lane) * 16);
        const float zl = (__uint_as_float(zw.x) - zeta) * 1.4426950408889634f, zim = __uint_as_float(zw.y);
        const float w_r = __uint_as_float(zw.z) * sc, w_i = __uint_as_float(zw.w) * sc;
        C32 e1 = cfresh(zl, zim, 1.f), e2 = csq(e1), e4 = csq(e2), e8 = csq(e4);
        C32 e16 = cfresh(zl, zim, 16.f), e32 = csq(e16), e64 = csq(e32), e128 = csq(e64);
        C32 e256 = cfresh(zl, zim, 256.f), e512 = csq(e256), e1024 = csq(e512), e2048 = csq(e1024);
        k2048 += w_r * e2048.re - w_i * e2048.im;
        HMul m16 = mk_mul(e16.re, e16.im), m32 = mk_mul(e32.re, e32.im), m64 = mk_mul(e64.re, e64.im);
        uint32_t* X = val + 40;
        X[0] = 0x00003c00u;
        X[1] = pack_f16(e8.re, e8.im); X[2] = m16.b; X[4] = m32.b; X[8] = m64.b;
        X[3] = hcmul(X[1], m16); X[5] = hcmul(X[1], m32); X[6] = hcmul(X[2], m32); X[7] = hcmul(X[3], m32);
#pragma unroll
        for (int r = 1; r < 8; ++r) X[8 + r] = hcmul(X[r], m64);
        HMul c1 = mk_mul(e1.re, -e1.im), c2 = mk_mul(e2.re, -e2.im), c4 = mk_mul(e4.re, -e4.im);
        uint32_t W[8];
        W[0] = pack_f16(w_r, -w_i);
        W[1] = hcmul(W[0], c1); W[2] = hcmul(W[0], c2); W[3] = hcmul(W[1], c2);
        W[4] = hcmul(W[0], c4); W[5] = hcmul(W[1], c4); W[6] = hcmul(W[2], c4); W[7] = hcmul(W[3], c4);
        C32 e384 = cmul(e256, e128), e640 = cmul(e512, e128), e768 = cmul(e512, e256), e896 = cmul(e768, e128);
        HMul c128 = mk_mul(e128.re, -e128.im), c256 = mk_mul(e256.re, -e256.im), c384 = mk_mul(e384.re, -e384.im);
        HMul c512 = mk_mul(e512.re, -e512.im), c640 = mk_mul(e640.re, -e640.im), c768 = mk_mul(e768.re, -e768.im);
        HMul c896 = mk_mul(e896.re, -e896.im), c1024 = mk_mul(e1024.re, -e1024.im);
#pragma unroll
        for (int i = 0; i < 8; ++i) { val[i] = W[i]; val[8 + i] = hcmul(W[i], c128); }
#pragma unroll
        for (int i = 0; i < 4; ++i) { val[16 + i] = hcmul(W[2 * i], c256); val[20 + i] = hcmul(W[2 * i], c384); }
        val[24] = hcmul(W[0], c512); val[25] = hcmul(W[4], c512);
        val[26] = hcmul(W[0], c640); val[27] = hcmul(W[4], c640);
        val[28] = hcmul(W[0], c768); val[29] = hcmul(W[4], c768);
        val[30] = hcmul(W[0], c896); val[31] = hcmul(W[4], c896);
        const uint32_t v0 = hcmul(W[0], c1024);
        val[32] = v0; val[33] = hcmul(v0, c128); val[34] = hcmul(v0, c256); val[35] = hcmul(v0, c384);
        val[36] = hcmul(v0, c512); val[37] = hcmul(v0, c640); val[38] = hcmul(v0, c768); val[39] = hcmul(v0, c896);
      }
      if (tid == 0) TS(36 + rd * 3);
      if (rd > 0) { wg_wait<0>(); bar_sync(2, 128); }
      if (tid == 0) TS(37 + rd * 3);
#pragma unroll
      for (int r = 0; r < 56; ++r) sts32(vv + r * 128 + (laneoff ^ ((r & 7) << 4)), val[r]);
      fence_async_smem();
      bar_sync(2, 128);
      wg_fence();
#pragma unroll
      for (int c = 0; c < 4; ++c) {
        const uint32_t da = mkdesc(sb + SM_VV + c * VV_BYTES, 16);
#pragma unroll
        for (int k = 0; k < 4; ++k) wgmma_n16_f16(Dk[c], da + 2 * k, da + 320 + 2 * k, (rd | k) != 0);
      }
      wg_commit();
      if (tid == 0) TS(38 + rd * 3);
    }
    wg_wait<0>();
    if (tid == 0) TS(48);
    bar_sync(2, 128);
    if (warp < 3) {
#pragma unroll
      for (int c = 0; c < 4; ++c) {
        const uint32_t a = sb + SM_VV + c * VV_BYTES + VV_KF + ((16 * warp + g) * 16 + 2 * q) * 4;
        sts_f32x2(a, Dk[c][0], Dk[c][1]);
        sts_f32x2(a + 32, Dk[c][4], Dk[c][5]);
        if (warp < 2) {
          sts_f32x2(a + 512, Dk[c][2], Dk[c][3]);
          sts_f32x2(a + 544, Dk[c][6], Dk[c][7]);
        }
      }
    }
#pragma unroll 1
    for (int o = 16; o > 0; o >>= 1) k2048 += __shfl_xor_sync(0xffffffffu, k2048, o);
    if (lane == 0) TS(2);
    mbar_wait(BAR(B_TRDONE), 0);
    bar_sync(2, 128);
    if (lane == 0) {
      TS(50);
      wait_counter(&g_cnt[(C_U + (cta >> 4)) * 32], (epoch + 1) * 16);
      mbar_expect_tx(BAR(B_UCH + ch), 4096);
      bulk_load(ub + 256, p.uT + (size_t)d * 2048, 4096, BAR(B_UCH + ch));
      TS(3);
    }
    __syncwarp();
    if (lane < 16) sts128(ub + lane * 16, 0, 0, 0, 0);
    if (zeta > 0.f) {
      const float zt = zeta * 1.4426950408889634f;
#pragma unroll 1
      for (int i = lane; i < 640; i += 32) sts_f32(kf + i * 4, lds_f32(kf + i * 4) * ex2(zt * kidx_l(i)));
      k2048 *= ex2(zt * 2048.f);
      __syncwarp();
    }
    const float k1024 = lds_f32(kf + kidx_c(1024) * 4) * inv;
    if (lane == 0) {
      sts_f32(kf + SL_K2048 * 4, k2048);
      sts_f32(kf + SL_ZERO * 4, 0.f);
      sts_f32(kf + SL_510 * 4, lds_f32(kf + kidx_c(510) * 4) - lds_f32(kf + kidx_c(512) * 4));
      sts_f32(kf + SL_0 * 4, lds_f32(kf) + dskip * sc);
    }
    __syncwarp();
#pragma unroll 1
    for (int i0 = 0; i0 < 30; i0 += 6) {
      uint32_t e[6];
      float a[6], b[6];
#pragma unroll
      for (int i = 0; i < 6; ++i) e[i] = lds32(sb + SM_PTAB + ((i0 + i) * 32 + lane) * 4);
#pragma unroll
      for (int i = 0; i < 6; ++i) { a[i] = lds_f32(kf + (e[i] & 0xffff)); b[i] = lds_f32(kf + (e[i] >> 16)); }
#pragma unroll
      for (int i = 0; i < 6; ++i) sts32(pb + ((i0 + i) * 32 + lane) * 4, pack_bf16(a[i] * inv, b[i] * inv));
    }
    __syncwarp();
    if (lane == 0) TS(4);
    mbar_wait(BAR(B_UCH + ch), 0);
    if (lane == 0) TS(5);
#pragma unroll 1
    for (int it = 0; it < 8; ++it) {
      const int k = -18 + it * 32 + lane;
      const int kr = min(max(k, -2), 208);
      uint32_t E[12];
#pragma unroll
      for (int c = 0; c < 3; ++c) {
        const int kk = kr - 1 + c, r = (kk >> 1) + 8;
        const uint4 t = lds128(ub + r * 32 + (((kk & 1) ^ ((r >> 2) & 1)) << 4));
        E[4 * c] = t.x; E[4 * c + 1] = t.y; E[4 * c + 2] = t.z; E[4 * c + 3] = t.w;
      }
      uint32_t O[8];
#pragma unroll
      for (int j = 0; j < 8; ++j) O[j] = __byte_perm(E[j + 1], E[j + 2], 0x5432);
      uint32_t s3[6], s5[4], s7[4], s9[4];
#pragma unroll
      for (int j = 0; j < 6; ++j) s3[j] = badd(badd(O[j], O[j + 1]), E[j + 2]);
#pragma unroll
      for (int j = 0; j < 4; ++j) {
        s5[j] = badd(s3[j + 2], badd(E[j + 3], E[j + 5]));
        s7[j] = badd(s5[j], badd(O[j + 1], O[j + 4]));
        s9[j] = badd(s7[j], badd(E[j + 2], E[j + 6]));
      }
      const int r = (k >> 1) + PADV;
      const uint32_t a = vv + r * 32 + (((k & 1) ^ ((r >> 2) & 1)) << 4);
      if (k < 208) { sts128(a + VV_U3, s3[0], s3[1], s3[2], s3[3]); sts128(a + VV_U5, s5[0], s5[1], s5[2], s5[3]); }
      if (k < 144) { sts128(a + VV_U7, s7[0], s7[1], s7[2], s7[3]); sts128(a + VV_U9, s9[0], s9[1], s9[2], s9[3]); }
    }
    __syncwarp();
    if (lane == 0) TS(6);
    mbar_wait(BAR(B_QKVDONE), 0);
    if (lane == 0) TS(7);
    float acc[16][4];
#pragma unroll
    for (int i = 0; i < 16; ++i) { acc[i][0] = acc[i][1] = acc[i][2] = acc[i][3] = 0.f; }
    {
      const int gq = g - 2 * q;
      const uint32_t pd_lane = pb + (PD_OFF + 16 + gq) * 4;
      const int prow0 = 8 + (lane & 7) + ((lane >> 4) << 3), hs = (lane >> 3) & 1;
      uint32_t B[8][4];
      {
        const uint32_t la = ub + prow0 * 32 + ((hs ^ ((prow0 >> 2) & 1)) << 4);
#pragma unroll
        for (int m2 = 0; m2 < 8; ++m2) ldsm_x4(B[m2], la + m2 * 512);
      }
#pragma unroll 1
      for (int rho = 0; rho < 8; ++rho) {
        uint32_t A[4][3];
#pragma unroll
        for (int i = 0; i < 4; ++i) {
          const uint32_t a = pd_lane + (uint32_t)(2 * rho + 16 * i) * 32;
          A[i][0] = lds32(a); A[i][1] = lds32(a + 32); A[i][2] = lds32(a - 32);
        }
        const int prow = prow0 - min(rho + 1, 7);
        const uint32_t la = ub + prow * 32 + ((hs ^ ((prow >> 2) & 1)) << 4);
#pragma unroll
        for (int i = 0; i < 4; ++i)
#pragma unroll
          for (int m2 = 0; m2 < 8; ++m2) {
#pragma unroll
            for (int h = 0; h < 2; ++h)
              if (2 * m2 + h + i < 16)
                mma_bf16(acc[2 * m2 + h + i], A[i][0], A[i][1], A[i][2], A[i][0], B[m2][2 * h], B[m2][2 * h + 1]);
            if (i == 3) ldsm_x4(B[m2], la + m2 * 512);
          }
      }
      {
        const float kfix = -round_bf16(k1024);
        const uint32_t kf2 = pack_bf16(kfix, kfix);
        auto hfix = [&](int x) { return (x == 1020 ? kf2 & 0xffffu : x == 1021 ? kf2 : x == 1022 ? kf2 & 0xffff0000u : 0u); };
        const uint32_t h127 = hfix(1016 + gq), h128 = hfix(1024 + gq);
        const uint32_t h63 = lds32(pd_lane + 63 * 32), h64 = lds32(pd_lane + 64 * 32);
        const uint32_t la0 = ub + prow0 * 32 + ((hs ^ ((prow0 >> 2) & 1)) << 4);
#pragma unroll
        for (int m = 0; m < 9; ++m) mma_bf16(acc[m + 7], 0u, h127, 0u, 0u, B[m >> 1][2 * (m & 1)], B[m >> 1][2 * (m & 1) + 1]);
#pragma unroll
        for (int m2 = 0; m2 < 6; ++m2) ldsm_x4(B[m2], la0 + m2 * 512);
#pragma unroll
        for (int m = 0; m < 12; ++m) mma_bf16(acc[m + 4], h64, 0u, h63, h64, B[m >> 1][2 * (m & 1)], B[m >> 1][2 * (m & 1) + 1]);
#pragma unroll
        for (int m = 0; m < 8; ++m) mma_bf16(acc[m + 8], h128, 0u, h127, h128, B[m >> 1][2 * (m & 1)], B[m >> 1][2 * (m & 1) + 1]);
      }
#pragma unroll 1
      for (int v = 0; v < 4; ++v)
        conv_tail<4, 3, 11>(acc, pb + (P2_OFF + 56 * v + gq - 16) * 4, vv + ((v & 1) ? VV_U3 : VV_U5), v >> 1, v == 0, lane);
#pragma unroll 1
      for (int pi = 0; pi < 2; ++pi)
        conv_tail<8, 5, 7>(acc, pb + (P3_OFF + 88 * pi + gq - 48) * 4, vv + (pi ? VV_U7 : VV_U9), pi, pi == 0, lane);
    }
    __syncwarp();
    if (lane == 0) { mbar_arrive(BAR(B_CONVDONE)); TS(8); }
    {
      const int mt = lane >> 3;
      const uint32_t a = vv + (128 * (mt >> 1) + 16 * (lane & 7) + 8 * (mt & 1)) * 2;
#pragma unroll
      for (int ab = 0; ab < 16; ab += 2)
        stsm_x4_t(a + ab * 256, pack_bf16(acc[ab][0], acc[ab][1]), pack_bf16(acc[ab][2], acc[ab][3]),
                  pack_bf16(acc[ab + 1][0], acc[ab + 1][1]), pack_bf16(acc[ab + 1][2], acc[ab + 1][3]));
    }
    fence_async_smem();
    __syncwarp();
    if (lane == 0) {
      bulk_store(p.yT + (size_t)d * 2048, vv, 4096);
      bulk_commit();
      bulk_wait0();
      red_relaxed_add(&g_cnt[(C_Y + (cta >> 4)) * 32], 1);
      TS(9);
    }
    cluster_wait();
  } else if (warp < 12) {
    asm volatile("setmaxnreg.inc.sync.aligned.u32 160;");
    const unsigned epoch = __ldcg(&g_epoch);
    const int w8 = warp - 4;
    const int g = lane >> 2, q = lane & 3;
    cluster_wait();
    {
      float acc[96];
#pragma unroll 1
      for (int ks = 0, s = 0, ph = 0; ks < 8; ++ks) {
        mbar_wait(BAR(B_FULL + s), ph);
        if (ks == 0 && tid == 128) TS(16);
        const uint32_t st = sb + s * STG_BYTES;
        const uint32_t da = mkdesc(st + STG_X + (w8 >> 2) * 8192, 16);
        const uint32_t db = mkdesc(st + STG_W, 8192);
        wg_fence();
#pragma unroll
        for (int k = 0; k < 4; ++k) wgmma_n192(acc, da + 2 * k, db + 128 * k, (ks | k) != 0);
        wg_commit();
        const uint32_t eprev = BAR(B_EMPTY + (s == 0 ? 2 : s - 1));
        if (++s == 3) { s = 0; ph ^= 1; }
        if (ks > 0) {
          wg_wait<1>();
          if (lane < 2) mbar_arrive_cluster(eprev, lane);
        }
      }
      wg_wait<0>();
      if (lane < 2) mbar_arrive_cluster(BAR(B_EMPTY + 1), lane);
      if (lane == 0) mbar_arrive(BAR(B_QKVDONE));
      if (tid == 128) TS(17);
      bar_sync(1, 256);
      const int row = w8 * 16 + (lane & 7) + (((lane >> 3) & 1) << 3);
      const uint32_t ra = sb + SM_QS + row * 128;
#pragma unroll
      for (int i = 0; i < 24; i += 2)
        stsm_x4(ra + (i >> 3) * 16384 + ((((i & 7) + (lane >> 4)) ^ (row & 7)) << 4), pack_bf16(acc[4 * i], acc[4 * i + 1]),
                pack_bf16(acc[4 * i + 2], acc[4 * i + 3]), pack_bf16(acc[4 * i + 4], acc[4 * i + 5]),
                pack_bf16(acc[4 * i + 6], acc[4 * i + 7]));
    }
    __syncwarp();
    const unsigned par = epoch & 1;
    const int hh = w8 >> 1, dtile = w8 & 1;
    float* kvg = &g_kv[par][tj][hh][0];
#pragma unroll 1
    for (int part = 1; part >= 0; --part) {
      const uint32_t pa = sb + SM_QS + part * 16384 + w8 * 2048 + lane * 16;
#pragma unroll 1
      for (int it = 0; it < 4; ++it) {
        uint4 t = lds128(pa + it * 512);
        uint32_t* tw = &t.x;
#pragma unroll
        for (int j = 0; j < 4; ++j) {
          const uint32_t x = tw[j];
          const __nv_bfloat162 xb = *reinterpret_cast<const __nv_bfloat162*>(&x);
          const uint32_t e = pack_bf16(ex2(bf_lo(x) * 1.4426950408889634f), ex2(bf_hi(x) * 1.4426950408889634f));
          const uint32_t m = __hgt2_mask(xb, __floats2bfloat162_rn(0.f, 0.f));
          const uint32_t sel = (badd(x, 0x3f803f80u) & m) | (e & ~m);
          tw[j] = pack_bf16(bf_lo(sel) + 1e-6f, bf_hi(sel) + 1e-6f);
        }
        sts128(pa + it * 512, t.x, t.y, t.z, t.w);
      }
      if (part == 1) {
        if (tid == 128) TS(53);
        bar_sync(1, 256);
        float kv[4] = {0.f, 0.f, 0.f, 0.f}, zz[4] = {0.f, 0.f, 0.f, 0.f};
        const int m = lane >> 3;
        const uint32_t aa = sb + SM_VS + ((lane & 7) + ((m >> 1) << 3)) * 128 + (((2 * hh + (m & 1)) ^ (lane & 7)) << 4);
        const uint32_t ab = sb + SM_PK + (lane & 15) * 128 + (((2 * hh + dtile) ^ (lane & 7)) << 4);
#pragma unroll 2
        for (int ks = 0; ks < 8; ++ks) {
          uint32_t a[4], b0, b1;
          ldsm_x4_t(a, aa + ks * 2048);
          ldsm_x2_t(b0, b1, ab + ks * 2048);
          mma_bf16(kv, a[0], a[1], a[2], a[3], b0, b1);
          mma_bf16(zz, 0x3f803f80u, 0x3f803f80u, 0x3f803f80u, 0x3f803f80u, b0, b1);
        }
        asm volatile("red.global.add.v4.f32 [%0], {%1,%2,%3,%4};" ::"l"(kvg + dtile * 128 + lane * 4), "f"(kv[0]), "f"(kv[1]),
                     "f"(kv[2]), "f"(kv[3]) : "memory");
        if (g == 0)
          asm volatile("red.global.add.v2.f32 [%0], {%1,%2};" ::"l"(kvg + 256 + dtile * 8 + 2 * q), "f"(zz[0]), "f"(zz[1]) : "memory");
        if (tid == 128) TS(55);
        bar_sync(1, 256);
        if (lane == 0) mbar_arrive(BAR(B_PKVFREE));
        if (tid == 128) { red_release_add(&g_cnt[(C_KV + tj) * 32], 1); TS(18); }
        if (ti == 0) {
          float4* z = (float4*)&g_kv[par ^ 1][tj][0][0];
          for (int i = tid - 128; i < 272; i += 256) z[i] = make_float4(0.f, 0.f, 0.f, 0.f);
        }
      }
    }
    if (tid == 128) { TS(56); wait_counter(&g_cnt[(C_KV + tj) * 32], (epoch + 1) * 16); TS(19); }
    bar_sync(1, 256);
    {
      const float4 k4 = __ldcg((const float4*)(kvg + dtile * 128 + lane * 4));
      const float2 z2 = __ldcg((const float2*)(kvg + 256 + dtile * 8 + 2 * q));
      const uint32_t a = sb + SM_KVB + hh * 512 + lane * 16 + dtile * 4;
      sts32(a, pack_bf16(k4.x, k4.y));
      sts32(a + 8, pack_bf16(k4.z, k4.w));
      if (g == 0) sts32(sb + SM_KVB + 2048 + hh * 32 + q * 8 + dtile * 4, pack_bf16(z2.x, z2.y));
    }
    bar_sync(1, 256);
    {
      const int row = w8 * 16 + (lane & 7) + (((lane >> 3) & 1) << 3);
      uint4* dst = &g_ofrag[((ti * 8 + w8) * 32 + 4 * tj) * 32 + lane];
#pragma unroll 1
      for (int h = 0; h < 4; ++h) {
        uint32_t a[4];
        ldsm_x4(a, sb + SM_QS + row * 128 + (((2 * h + (lane >> 4)) ^ (row & 7)) << 4));
        const uint4 kb = lds128(sb + SM_KVB + h * 512 + lane * 16);
        const uint32_t zb0 = lds32(sb + SM_KVB + 2048 + h * 32 + q * 8), zb1 = lds32(sb + SM_KVB + 2048 + h * 32 + q * 8 + 4);
        float n0[4] = {0.f, 0.f, 0.f, 0.f}, n1[4] = {0.f, 0.f, 0.f, 0.f}, dn[4] = {0.f, 0.f, 0.f, 0.f};
        mma_bf16(n0, a[0], a[1], a[2], a[3], kb.x, kb.y);
        mma_bf16(n1, a[0], a[1], a[2], a[3], kb.z, kb.w);
        mma_bf16(dn, a[0], a[1], a[2], a[3], zb0, zb1);
        const uint32_t dd = pack_bf16(dn[0], dn[2]);
        const uint32_t d2 = pack_bf16(bf_lo(dd) + 1e-6f, bf_hi(dd) + 1e-6f);
        const float r0 = rcp(bf_lo(d2)), r1 = rcp(bf_hi(d2));
        const uint32_t x0 = pack_bf16(n0[0], n0[1]), x1 = pack_bf16(n0[2], n0[3]);
        const uint32_t x2 = pack_bf16(n1[0], n1[1]), x3 = pack_bf16(n1[2], n1[3]);
        dst[h * 32] = make_uint4(pack_bf16(bf_lo(x0) * r0, bf_hi(x0) * r0), pack_bf16(bf_lo(x1) * r1, bf_hi(x1) * r1),
                                 pack_bf16(bf_lo(x2) * r0, bf_hi(x2) * r0), pack_bf16(bf_lo(x3) * r1, bf_hi(x3) * r1));
      }
    }
    if (tid == 128) TS(57);
    bar_sync(1, 256);
    if (tid == 128) {
      red_release_add(&g_cnt[(C_O + ti) * 32], 1);
      TS(20);
      wait_counter(&g_cnt[(C_O + ti) * 32], (epoch + 1) * 8);
      if (cta == 0) g_epoch = epoch + 1;
      TS(21);
    }
    bar_sync(1, 256);
    {
      const uint4* src = &g_ofrag[((ti * 8 + w8) * 32) * 32 + lane];
      uint4 A0[8], A1[8];
#pragma unroll
      for (int h = 0; h < 8; ++h) A0[h] = __ldcg(src + h * 32);
#pragma unroll
      for (int h = 0; h < 8; ++h) A1[h] = __ldcg(src + (8 + h) * 32);
      mbar_wait(BAR(B_WO), 0);
      mbar_wait(BAR(B_CONVDONE), 0);
      if (tid == 128) TS(22);
      float o[32];
      const uint32_t db = mkdesc(sb + SM_WO, 8192);
#pragma unroll 1
      for (int it = 0; it < 2; ++it) {
        wg_fence();
#pragma unroll
        for (int h = 0; h < 8; ++h) wgmma_n64_rs(o, A0[h], db + (16 * it + h) * 128, (it | h) != 0);
        wg_commit();
        wg_wait<0>();
        if (it == 0) {
#pragma unroll
          for (int h = 0; h < 8; ++h) A0[h] = __ldcg(src + (16 + h) * 32);
        }
        wg_fence();
#pragma unroll
        for (int h = 0; h < 8; ++h) wgmma_n64_rs(o, A1[h], db + (16 * it + 8 + h) * 128, 1);
        wg_commit();
        wg_wait<0>();
        if (it == 0) {
#pragma unroll
          for (int h = 0; h < 8; ++h) A1[h] = __ldcg(src + (24 + h) * 32);
        }
      }
      const int row = w8 * 16 + (lane & 7) + (((lane >> 3) & 1) << 3);
#pragma unroll
      for (int i = 0; i < 8; i += 2)
        stsm_x4(sb + SM_BOUT + row * 128 + (((i + (lane >> 4)) ^ (row & 7)) << 4), pack_bf16(o[4 * i], o[4 * i + 1]),
                pack_bf16(o[4 * i + 2], o[4 * i + 3]), pack_bf16(o[4 * i + 4], o[4 * i + 5]), pack_bf16(o[4 * i + 6], o[4 * i + 7]));
      fence_async_smem();
      bar_sync(1, 256);
      if (tid == 128) {
        tma_store_2d(&maps.out, sb + SM_BOUT, 512 + 64 * tj, 128 * ti);
        bulk_commit();
        bulk_wait0();
        TS(23);
      }
    }
  } else {
    asm volatile("setmaxnreg.dec.sync.aligned.u32 40;");
    if (tid == 384) TS(49);
    if (warp == 13 && lane == 0) {
      mbar_expect_tx(BAR(B_UTILE), 16384);
      tma_load_2d(sb + SM_TIN1, &maps.u, tj * 64, ti * 128, BAR(B_UTILE));
    }
    if (warp >= 14) {
      const int t = tid - 448;
#pragma unroll
      for (int i = 0; i < 4; ++i)
        if (t + 64 * i < 240) {
          const uint4 v = __ldg((const uint4*)g_ptab.v + t + 64 * i);
          sts128(sb + SM_PTAB + (t + 64 * i) * 16, v.x, v.y, v.z, v.w);
        }
      __syncwarp();
      if (lane == 0) mbar_arrive(BAR(B_TRDONE));
    }
    if (tid == 384) TS(51);
    cluster_wait();
    if (tid == 384) TS(52);
    if (warp == 12) {
      if (lane == 0) {
#pragma unroll 1
        for (int ks = 0, s = 0, ph = 1; ks < 8; ++ks) {
          if (ks >= 3) mbar_wait(BAR(B_EMPTY + s), ph);
          const uint32_t st = sb + s * STG_BYTES, fb = BAR(B_FULL + s);
          if (ks == 0) TS(61);
          mbar_expect_tx(fb, STG_BYTES);
          tma_load_2d(st + STG_X, &maps.x, ks * 64, ti * 128, fb);
#pragma unroll 1
          for (int nb = 0; nb < 3; ++nb)
            tma_load_2d_mc(st + STG_W + nb * 8192 + rank * 4096, &maps.w, nb * 512 + tj * 64, ks * 64 + rank * 32, fb, 3);
          if (ks == 2) {
            l2_prefetch((const char*)p.wqkv + 192 * 3072 + cta * 7680, 7680);
            l2_prefetch((const char*)p.x + (size_t)cta * 16384, 16384);
            l2_prefetch((const char*)p.wo + (size_t)cta * 4096, 4096);
            prefetch_tmap(&maps.wo); prefetch_tmap(&maps.uT); prefetch_tmap(&maps.yT); prefetch_tmap(&maps.out);
          }
          if (++s == 3) { s = 0; ph ^= 1; }
        }
        TS(24);
        mbar_wait(BAR(B_EMPTY + 0), 0);
        mbar_wait(BAR(B_EMPTY + 1), 0);
        mbar_expect_tx(BAR(B_WO), 65536);
        tma_load_2d_mc(sb + SM_WO + rank * 32768, &maps.wo, tj * 64, rank * 256, BAR(B_WO), 3);
      }
    } else if (warp == 13) {
      const unsigned epoch = __ldcg(&g_epoch);
      mbar_wait(BAR(B_UTILE), 0);
      if (lane == 0) TS(26);
      transpose_tile<0>(sb + SM_TIN1, sb + SM_TOUT1, lane);
      if (lane == 0) TS(58);
      fence_async_smem();
      __syncwarp();
      if (lane == 0) {
        tma_store_2d(&maps.uT, sb + SM_TOUT1, ti * 128, tj * 64);
        tma_store_2d(&maps.uT, sb + SM_TOUT1 + 8192, ti * 128 + 64, tj * 64);
        bulk_commit();
        bulk_wait0();
        TS(59);
        red_relaxed_add(&g_cnt[(C_U + tj) * 32], 1);
        mbar_arrive(BAR(B_TRDONE));
        TS(27);
        mbar_wait(BAR(B_PKVFREE), 0);
        wait_counter(&g_cnt[(C_Y + tj) * 32], (epoch + 1) * 64);
        TS(28);
        mbar_expect_tx(BAR(B_YTILE), 16384);
        tma_load_2d(sb + SM_TIN2, &maps.yT, ti * 128, tj * 64, BAR(B_YTILE));
        tma_load_2d(sb + SM_TIN2 + 8192, &maps.yT, ti * 128 + 64, tj * 64, BAR(B_YTILE));
      }
      __syncwarp();
      mbar_wait(BAR(B_YTILE), 0);
      transpose_tile<1>(sb + SM_TIN2, sb + SM_TOUT2, lane);
      fence_async_smem();
      __syncwarp();
      if (lane == 0) {
        tma_store_2d(&maps.out, sb + SM_TOUT2, 64 * tj, 128 * ti);
        bulk_commit();
        bulk_wait0();
        TS(29);
      }
    }
  }
  __syncwarp();
  cluster_arrive();
  cluster_wait();
  if (tid == 0) TS(31);
#undef BAR
}

typedef CUresult (*EncodeFn)(CUtensorMap*, CUtensorMapDataType, cuuint32_t, void*, const cuuint64_t*, const cuuint64_t*,
                             const cuuint32_t*, const cuuint32_t*, CUtensorMapInterleave, CUtensorMapSwizzle,
                             CUtensorMapL2promotion, CUtensorMapFloatOOBfill);

static void make_map(EncodeFn enc, CUtensorMap* m, const void* base, uint64_t inner, uint64_t outer, uint32_t box_in,
                     uint32_t box_out) {
  cuuint64_t gd[2] = {inner, outer};
  cuuint64_t gs[1] = {inner * 2};
  cuuint32_t bd[2] = {box_in, box_out};
  cuuint32_t es[2] = {1, 1};
  enc(m, CU_TENSOR_MAP_DATA_TYPE_BFLOAT16, 2, const_cast<void*>(base), gd, gs, bd, es, CU_TENSOR_MAP_INTERLEAVE_NONE,
      CU_TENSOR_MAP_SWIZZLE_128B, CU_TENSOR_MAP_L2_PROMOTION_L2_128B, CU_TENSOR_MAP_FLOAT_OOB_FILL_NONE);
}

}

extern "C" void kernel_launch(void* const* d_in, const int* in_sizes, int n_in, void* d_out, int out_size) {
  using namespace s4la;
  (void)in_sizes; (void)n_in; (void)out_size;
  static EncodeFn enc = nullptr;
  static void *uT = nullptr, *yT = nullptr;
  if (!enc) {
    void* fn = nullptr;
    cudaDriverEntryPointQueryResult qr;
    cudaGetDriverEntryPoint("cuTensorMapEncodeTiled", &fn, cudaEnableDefault, &qr);
    enc = (EncodeFn)fn;
    cudaGetSymbolAddress(&uT, g_uT);
    cudaGetSymbolAddress(&yT, g_yT);
    cudaFuncSetAttribute(fused_kernel, cudaFuncAttributeMaxDynamicSharedMemorySize, SM_TOTAL);
  }
  const __nv_bfloat16* const* in = (const __nv_bfloat16* const*)d_in;
  Maps maps;
  make_map(enc, &maps.x, in[9], 512, 2048, 64, 128);
  make_map(enc, &maps.w, in[10], 1536, 512, 64, 32);
  make_map(enc, &maps.wo, in[11], 512, 512, 64, 256);
  make_map(enc, &maps.u, in[0], 512, 2048, 64, 128);
  make_map(enc, &maps.uT, uT, 2048, 512, 64, 64);
  make_map(enc, &maps.yT, yT, 2048, 512, 64, 64);
  make_map(enc, &maps.out, d_out, 1024, 2048, 64, 128);
  Ptrs p;
  p.A_re = in[1]; p.A_im = in[2]; p.B_re = in[3]; p.B_im = in[4]; p.C_re = in[5]; p.C_im = in[6];
  p.log_dt = in[7]; p.Dskip = in[8]; p.x = in[9]; p.wqkv = in[10]; p.wo = in[11];
  p.uT = (__nv_bfloat16*)uT; p.yT = (__nv_bfloat16*)yT;
  fused_kernel<<<NCTA, NTHREADS, SM_TOTAL, cudaStreamPerThread>>>(maps, p);
}
```

```cpp
#include <cuda_runtime.h>
#include <cuda_bf16.h>
#include <cuda_fp16.h>
#include <cuda.h>
#include <stdint.h>

#define DEVI __device__ __forceinline__

namespace s4la {

constexpr int NTHREADS = 512;
constexpr int NCTA = 128;

constexpr uint32_t STG_BYTES = 40960, STG_X = 0, STG_W = 16384;
constexpr uint32_t SM_WO = 0;
constexpr uint32_t SM_QS = 65536;
constexpr uint32_t SM_BOUT = 65536;
constexpr uint32_t SM_PK = 81920;
constexpr uint32_t SM_VS = 98304;
constexpr uint32_t SM_KVB = 114688;
constexpr uint32_t SM_TIN2 = 81920, SM_TOUT2 = 98304;
constexpr uint32_t SM_U = 122880, U_BYTES = 4352;
constexpr uint32_t SM_P = 140288, P_BYTES = 4096;
constexpr uint32_t SM_TIN1 = SM_U, SM_TOUT1 = SM_P;
constexpr uint32_t SM_VV = 156672, VV_BYTES = 13312;
constexpr uint32_t VV_U5 = 0, VV_U3 = 3712, VV_U9 = 7424, VV_U7 = 10112;
constexpr uint32_t VV_KF = 8192;
constexpr uint32_t SM_BAR = 209920;
constexpr uint32_t SM_MISC = SM_BAR + 256;
constexpr uint32_t SM_PTAB = SM_MISC + 128;
constexpr uint32_t SM_TOTAL = SM_PTAB + 3840;
constexpr int PADV = 12;

enum { B_FULL = 0, B_EMPTY = 3, B_WO = 6, B_UTILE = 7, B_YTILE = 8, B_UCH = 9, B_QKVDONE = 13,
       B_CONVDONE = 14, B_TRDONE = 15, B_PKVFREE = 16, B_COUNT = 17 };

constexpr int PD_OFF = 0, P2_OFF = 544, P3_OFF = 768;

constexpr int SL_K2048 = 640, SL_ZERO = 641, SL_510 = 642, SL_0 = 643;
__host__ __device__ constexpr int kidx_c(int l) {
  int r = (l >> 3) & 15, y = 0;
  if (l < 256) y = (l & 7) + ((l >> 7) << 3);
  else if (l < 512) y = 16 + (((l - 256) >> 7) << 2) + ((l & 7) >> 1);
  else if (l < 1024) y = 24 + (((l - 512) >> 7) << 1) + ((l >> 2) & 1);
  else y = 32 + ((l - 1024) >> 7);
  return y * 16 + r;
}
constexpr int slot_direct(int l) {
  if (l < 0 || l > 510) return SL_ZERO;
  if (l == 510) return SL_510;
  if (l == 0) return SL_0;
  return kidx_c(l < 256 ? l : ((l + ((l >> 1) & 1)) & ~1));
}
constexpr int slot_seg2(int v, int k) { return (k >= 32 && k < 64) ? kidx_c(16 * k + 4 * v) : SL_ZERO; }
constexpr int slot_seg3(int pi, int k) {
  return (k >= 64 && k < 128) ? kidx_c(16 * k + 8 * pi) : ((k == 128 && pi == 0) ? SL_K2048 : SL_ZERO);
}
struct PTab { uint32_t v[960]; };
constexpr PTab make_ptab() {
  PTab t{};
  for (int w = 0; w < 960; ++w) t.v[w] = (SL_ZERO * 4) | ((SL_ZERO * 4) << 16);
  for (int w = 0; w < 544; ++w) t.v[w] = (slot_direct(w - 16) * 4) | ((slot_direct(w - 17) * 4) << 16);
  for (int v = 0; v < 4; ++v)
    for (int x = 16; x < 72; ++x) t.v[544 + 56 * v + x - 16] = (slot_seg2(v, x) * 4) | ((slot_seg2(v, x - 1) * 4) << 16);
  for (int pi = 0; pi < 2; ++pi)
    for (int x = 48; x < 136; ++x) t.v[768 + 88 * pi + x - 48] = (slot_seg3(pi, x) * 4) | ((slot_seg3(pi, x - 1) * 4) << 16);
  return t;
}
__device__ const PTab g_ptab = make_ptab();

__device__ __nv_bfloat16 g_uT[512 * 2048];
__device__ __nv_bfloat16 g_yT[512 * 2048];
__device__ uint4 g_ofrag[16 * 8 * 32 * 32];
__device__ float g_kv[2][8][4][272];
__device__ unsigned g_cnt[64 * 32];
__device__ unsigned g_epoch;
#define TS(slot) do { } while (0)
enum { C_U = 0, C_KV = 8, C_O = 16, C_Y = 32 };

struct Maps {
  CUtensorMap x, w, wo, u, uT, yT, out;
};
struct Ptrs {
  const __nv_bfloat16 *A_re, *A_im, *B_re, *B_im, *C_re, *C_im, *log_dt, *Dskip;
  const __nv_bfloat16 *x, *wqkv, *wo;
  __nv_bfloat16 *uT, *yT;
};

DEVI uint32_t s2u(const void* p) { return (uint32_t)__cvta_generic_to_shared(p); }
DEVI void mbar_init(uint32_t b, uint32_t c) { asm volatile("mbarrier.init.shared::cta.b64 [%0], %1;" ::"r"(b), "r"(c) : "memory"); }
DEVI void mbar_expect_tx(uint32_t b, uint32_t bytes) {
  asm volatile("mbarrier.arrive.expect_tx.shared::cta.b64 _, [%0], %1;" ::"r"(b), "r"(bytes) : "memory");
}
DEVI void mbar_arrive(uint32_t b) { asm volatile("mbarrier.arrive.shared::cta.b64 _, [%0];" ::"r"(b) : "memory"); }
DEVI void mbar_arrive_cluster(uint32_t b, uint32_t cta) {
  asm volatile("{\n.reg .b32 r;\nmapa.shared::cluster.u32 r, %0, %1;\nmbarrier.arrive.shared::cluster.b64 _, [r];\n}"
               ::"r"(b), "r"(cta) : "memory");
}
DEVI void mbar_wait(uint32_t b, uint32_t parity) {
  asm volatile("{\n.reg .pred p;\nLAB_WAIT:\nmbarrier.try_wait.parity.shared::cta.b64 p, [%0], %1, 0x989680;\n@p bra LAB_DONE;\nbra LAB_WAIT;\nLAB_DONE:\n}"
               ::"r"(b), "r"(parity) : "memory");
}
#define mbar_wait_cluster mbar_wait
DEVI void bar_sync(int id, int n) { asm volatile("bar.sync %0, %1;" ::"r"(id), "r"(n) : "memory"); }
DEVI void bar_arrive(int id, int n) { asm volatile("bar.arrive %0, %1;" ::"r"(id), "r"(n) : "memory"); }
DEVI void fence_async_smem() { asm volatile("fence.proxy.async.shared::cta;" ::: "memory"); }
DEVI void fence_async_all() { asm volatile("fence.proxy.async;" ::: "memory"); }
DEVI void cluster_arrive() { asm volatile("barrier.cluster.arrive.relaxed.aligned;" ::: "memory"); }
DEVI void cluster_wait() { asm volatile("barrier.cluster.wait.aligned;" ::: "memory"); }

DEVI void tma_load_2d(uint32_t dst, const CUtensorMap* m, int c0, int c1, uint32_t bar) {
  asm volatile("cp.async.bulk.tensor.2d.shared::cluster.global.mbarrier::complete_tx::bytes [%0], [%1, {%3, %4}], [%2];"
               ::"r"(dst), "l"(m), "r"(bar), "r"(c0), "r"(c1) : "memory");
}
DEVI void tma_load_2d_mc(uint32_t dst, const CUtensorMap* m, int c0, int c1, uint32_t bar, uint16_t mask) {
  asm volatile("cp.async.bulk.tensor.2d.shared::cluster.global.mbarrier::complete_tx::bytes.multicast::cluster [%0], [%1, {%3, %4}], [%2], %5;"
               ::"r"(dst), "l"(m), "r"(bar), "r"(c0), "r"(c1), "h"(mask) : "memory");
}
DEVI void tma_store_2d(const CUtensorMap* m, uint32_t src, int c0, int c1) {
  asm volatile("cp.async.bulk.tensor.2d.global.shared::cta.bulk_group [%0, {%2, %3}], [%1];"
               ::"l"(m), "r"(src), "r"(c0), "r"(c1) : "memory");
}
DEVI void bulk_load(uint32_t dst, const void* src, uint32_t bytes, uint32_t bar) {
  asm volatile("cp.async.bulk.shared::cluster.global.mbarrier::complete_tx::bytes [%0], [%1], %2, [%3];"
               ::"r"(dst), "l"(src), "r"(bytes), "r"(bar) : "memory");
}
DEVI void bulk_store(void* dst, uint32_t src, uint32_t bytes) {
  asm volatile("cp.async.bulk.global.shared::cta.bulk_group [%0], [%1], %2;" ::"l"(dst), "r"(src), "r"(bytes) : "memory");
}
DEVI void bulk_commit() { asm volatile("cp.async.bulk.commit_group;" ::: "memory"); }
DEVI void bulk_wait0() { asm volatile("cp.async.bulk.wait_group 0;" ::: "memory"); }
DEVI void l2_prefetch(const void* p, uint32_t bytes) {
  asm volatile("cp.async.bulk.prefetch.L2.global [%0], %1;" ::"l"(p), "r"(bytes) : "memory");
}
DEVI void prefetch_tmap(const CUtensorMap* m) { asm volatile("prefetch.tensormap [%0];" ::"l"(m) : "memory"); }

DEVI void red_release_add(unsigned* p, unsigned v) {
  asm volatile("red.release.gpu.global.add.u32 [%0], %1;" ::"l"(p), "r"(v) : "memory");
}
DEVI void red_relaxed_add(unsigned* p, unsigned v) {
  asm volatile("red.relaxed.gpu.global.add.u32 [%0], %1;" ::"l"(p), "r"(v) : "memory");
}
DEVI unsigned ld_relaxed(const unsigned* p) {
  unsigned v;
  asm volatile("ld.relaxed.gpu.global.u32 %0, [%1];" : "=r"(v) : "l"(p) : "memory");
  return v;
}
DEVI void wait_counter(const unsigned* p, unsigned target) {
#pragma unroll 1
  for (int it = 0; (int)(ld_relaxed(p) - target) < 0; ++it)
    if (it > (1 << 22)) __trap();
}

DEVI void ldsm_x4(uint32_t (&r)[4], uint32_t a) {
  asm volatile("ldmatrix.sync.aligned.m8n8.x4.shared.b16 {%0,%1,%2,%3}, [%4];"
               : "=r"(r[0]), "=r"(r[1]), "=r"(r[2]), "=r"(r[3]) : "r"(a) : "memory");
}
DEVI void ldsm_x4_t(uint32_t (&r)[4], uint32_t a) {
  asm volatile("ldmatrix.sync.aligned.m8n8.x4.trans.shared.b16 {%0,%1,%2,%3}, [%4];"
               : "=r"(r[0]), "=r"(r[1]), "=r"(r[2]), "=r"(r[3]) : "r"(a) : "memory");
}
DEVI void ldsm_x2_t(uint32_t& r0, uint32_t& r1, uint32_t a) {
  asm volatile("ldmatrix.sync.aligned.m8n8.x2.trans.shared.b16 {%0,%1}, [%2];" : "=r"(r0), "=r"(r1) : "r"(a) : "memory");
}
DEVI void stsm_x4(uint32_t a, uint32_t r0, uint32_t r1, uint32_t r2, uint32_t r3) {
  asm volatile("stmatrix.sync.aligned.m8n8.x4.shared.b16 [%0], {%1,%2,%3,%4};"
               ::"r"(a), "r"(r0), "r"(r1), "r"(r2), "r"(r3) : "memory");
}
DEVI void stsm_x4_t(uint32_t a, uint32_t r0, uint32_t r1, uint32_t r2, uint32_t r3) {
  asm volatile("stmatrix.sync.aligned.m8n8.x4.trans.shared.b16 [%0], {%1,%2,%3,%4};"
               ::"r"(a), "r"(r0), "r"(r1), "r"(r2), "r"(r3) : "memory");
}
DEVI uint32_t lds32(uint32_t a) { uint32_t v; asm volatile("ld.shared.b32 %0, [%1];" : "=r"(v) : "r"(a) : "memory"); return v; }
DEVI float lds_f32(uint32_t a) { float v; asm volatile("ld.shared.f32 %0, [%1];" : "=f"(v) : "r"(a) : "memory"); return v; }
DEVI void sts32(uint32_t a, uint32_t v) { asm volatile("st.shared.b32 [%0], %1;" ::"r"(a), "r"(v) : "memory"); }
DEVI void sts_f32(uint32_t a, float v) { asm volatile("st.shared.f32 [%0], %1;" ::"r"(a), "f"(v) : "memory"); }
DEVI void sts_f32x2(uint32_t a, float x, float y) { asm volatile("st.shared.v2.f32 [%0], {%1,%2};" ::"r"(a), "f"(x), "f"(y) : "memory"); }
DEVI uint4 lds128(uint32_t a) {
  uint4 v;
  asm volatile("ld.shared.v4.b32 {%0,%1,%2,%3}, [%4];" : "=r"(v.x), "=r"(v.y), "=r"(v.z), "=r"(v.w) : "r"(a) : "memory");
  return v;
}
DEVI void sts128(uint32_t a, uint32_t x, uint32_t y, uint32_t z, uint32_t w) {
  asm volatile("st.shared.v4.b32 [%0], {%1,%2,%3,%4};" ::"r"(a), "r"(x), "r"(y), "r"(z), "r"(w) : "memory");
}

DEVI void mma_bf16(float (&d)[4], uint32_t a0, uint32_t a1, uint32_t a2, uint32_t a3, uint32_t b0, uint32_t b1) {
  asm("mma.sync.aligned.m16n8k16.row.col.f32.bf16.bf16.f32 {%0,%1,%2,%3}, {%4,%5,%6,%7}, {%8,%9}, {%0,%1,%2,%3};"
      : "+f"(d[0]), "+f"(d[1]), "+f"(d[2]), "+f"(d[3])
      : "r"(a0), "r"(a1), "r"(a2), "r"(a3), "r"(b0), "r"(b1));
}
DEVI uint32_t pack_bf16(float lo, float hi) {
  uint32_t r;
  asm("cvt.rn.bf16x2.f32 %0, %1, %2;" : "=r"(r) : "f"(hi), "f"(lo));
  return r;
}
DEVI uint32_t pack_f16(float lo, float hi) {
  uint32_t r;
  asm("cvt.rn.f16x2.f32 %0, %1, %2;" : "=r"(r) : "f"(hi), "f"(lo));
  return r;
}
DEVI float bf_lo(uint32_t v) { return __uint_as_float(v << 16); }
DEVI float bf_hi(uint32_t v) { return __uint_as_float(v & 0xffff0000u); }
DEVI float bf2f(__nv_bfloat16 v) { return __bfloat162float(v); }
DEVI float round_bf16(float v) { return __bfloat162float(__float2bfloat16_rn(v)); }
DEVI float rcp(float x) { float r; asm("rcp.approx.ftz.f32 %0, %1;" : "=f"(r) : "f"(x)); return r; }
DEVI float ex2(float x) { float r; asm("ex2.approx.ftz.f32 %0, %1;" : "=f"(r) : "f"(x)); return r; }

DEVI void wg_fence() { asm volatile("wgmma.fence.sync.aligned;" ::: "memory"); }
DEVI void wg_commit() { asm volatile("wgmma.commit_group.sync.aligned;" ::: "memory"); }
template <int N> DEVI void wg_wait() { asm volatile("wgmma.wait_group.sync.aligned %0;" ::"n"(N) : "memory"); }
constexpr uint32_t DESC_HI = (1u << 30) | (1024 >> 4);
DEVI uint32_t mkdesc(uint32_t saddr, uint32_t lbo) { return ((saddr & 0x3FFFF) >> 4) | ((lbo >> 4) << 16); }

#define R8(b) "%" #b
DEVI void wgmma_n192(float (&d)[96], uint32_t da, uint32_t db, int scale_d) {
  asm volatile(
      "{\n.reg .pred p;\n.reg .b64 da, db;\nsetp.ne.b32 p, %98, 0;\nmov.b64 da, {%96, %99};\nmov.b64 db, {%97, %99};\n"
      "wgmma.mma_async.sync.aligned.m64n192k16.f32.bf16.bf16 "
      "{%0,%1,%2,%3,%4,%5,%6,%7,%8,%9,%10,%11,%12,%13,%14,%15,"
      "%16,%17,%18,%19,%20,%21,%22,%23,%24,%25,%26,%27,%28,%29,%30,%31,"
      "%32,%33,%34,%35,%36,%37,%38,%39,%40,%41,%42,%43,%44,%45,%46,%47,"
      "%48,%49,%50,%51,%52,%53,%54,%55,%56,%57,%58,%59,%60,%61,%62,%63,"
      "%64,%65,%66,%67,%68,%69,%70,%71,%72,%73,%74,%75,%76,%77,%78,%79,"
      "%80,%81,%82,%83,%84,%85,%86,%87,%88,%89,%90,%91,%92,%93,%94,%95}, "
      "da, db, p, 1, 1, 0, 1;\n}"
      : "+f"(d[0]), "+f"(d[1]), "+f"(d[2]), "+f"(d[3]), "+f"(d[4]), "+f"(d[5]), "+f"(d[6]), "+f"(d[7]),
        "+f"(d[8]), "+f"(d[9]), "+f"(d[10]), "+f"(d[11]), "+f"(d[12]), "+f"(d[13]), "+f"(d[14]), "+f"(d[15]),
        "+f"(d[16]), "+f"(d[17]), "+f"(d[18]), "+f"(d[19]), "+f"(d[20]), "+f"(d[21]), "+f"(d[22]), "+f"(d[23]),
        "+f"(d[24]), "+f"(d[25]), "+f"(d[26]), "+f"(d[27]), "+f"(d[28]), "+f"(d[29]), "+f"(d[30]), "+f"(d[31]),
        "+f"(d[32]), "+f"(d[33]), "+f"(d[34]), "+f"(d[35]), "+f"(d[36]), "+f"(d[37]), "+f"(d[38]), "+f"(d[39]),
        "+f"(d[40]), "+f"(d[41]), "+f"(d[42]), "+f"(d[43]), "+f"(d[44]), "+f"(d[45]), "+f"(d[46]), "+f"(d[47]),
        "+f"(d[48]), "+f"(d[49]), "+f"(d[50]), "+f"(d[51]), "+f"(d[52]), "+f"(d[53]), "+f"(d[54]), "+f"(d[55]),
        "+f"(d[56]), "+f"(d[57]), "+f"(d[58]), "+f"(d[59]), "+f"(d[60]), "+f"(d[61]), "+f"(d[62]), "+f"(d[63]),
        "+f"(d[64]), "+f"(d[65]), "+f"(d[66]), "+f"(d[67]), "+f"(d[68]), "+f"(d[69]), "+f"(d[70]), "+f"(d[71]),
        "+f"(d[72]), "+f"(d[73]), "+f"(d[74]), "+f"(d[75]), "+f"(d[76]), "+f"(d[77]), "+f"(d[78]), "+f"(d[79]),
        "+f"(d[80]), "+f"(d[81]), "+f"(d[82]), "+f"(d[83]), "+f"(d[84]), "+f"(d[85]), "+f"(d[86]), "+f"(d[87]),
        "+f"(d[88]), "+f"(d[89]), "+f"(d[90]), "+f"(d[91]), "+f"(d[92]), "+f"(d[93]), "+f"(d[94]), "+f"(d[95])
      : "r"(da), "r"(db), "r"(scale_d), "n"(DESC_HI));
}
DEVI void wgmma_n64_rs(float (&d)[32], const uint4& a, uint32_t db, int scale_d) {
  asm volatile(
      "{\n.reg .pred p;\n.reg .b64 db;\nsetp.ne.b32 p, %37, 0;\nmov.b64 db, {%36, %38};\n"
      "wgmma.mma_async.sync.aligned.m64n64k16.f32.bf16.bf16 "
      "{%0,%1,%2,%3,%4,%5,%6,%7,%8,%9,%10,%11,%12,%13,%14,%15,"
      "%16,%17,%18,%19,%20,%21,%22,%23,%24,%25,%26,%27,%28,%29,%30,%31}, "
      "{%32,%33,%34,%35}, db, p, 1, 1, 1;\n}"
      : "+f"(d[0]), "+f"(d[1]), "+f"(d[2]), "+f"(d[3]), "+f"(d[4]), "+f"(d[5]), "+f"(d[6]), "+f"(d[7]),
        "+f"(d[8]), "+f"(d[9]), "+f"(d[10]), "+f"(d[11]), "+f"(d[12]), "+f"(d[13]), "+f"(d[14]), "+f"(d[15]),
        "+f"(d[16]), "+f"(d[17]), "+f"(d[18]), "+f"(d[19]), "+f"(d[20]), "+f"(d[21]), "+f"(d[22]), "+f"(d[23]),
        "+f"(d[24]), "+f"(d[25]), "+f"(d[26]), "+f"(d[27]), "+f"(d[28]), "+f"(d[29]), "+f"(d[30]), "+f"(d[31])
      : "r"(a.x), "r"(a.y), "r"(a.z), "r"(a.w), "r"(db), "r"(scale_d), "n"(DESC_HI));
}
DEVI void wgmma_n16_f16(float (&d)[8], uint32_t da, uint32_t db, int scale_d) {
  asm volatile(
      "{\n.reg .pred p;\n.reg .b64 da, db;\nsetp.ne.b32 p, %10, 0;\nmov.b64 da, {%8, %11};\nmov.b64 db, {%9, %11};\n"
      "wgmma.mma_async.sync.aligned.m64n16k16.f32.f16.f16 {%0,%1,%2,%3,%4,%5,%6,%7}, da, db, p, 1, 1, 0, 0;\n}"
      : "+f"(d[0]), "+f"(d[1]), "+f"(d[2]), "+f"(d[3]), "+f"(d[4]), "+f"(d[5]), "+f"(d[6]), "+f"(d[7])
      : "r"(da), "r"(db), "r"(scale_d), "n"(DESC_HI));
}

template <int MODE>
DEVI void transpose_tile(uint32_t src, uint32_t dst, int lane) {
  const int m = lane >> 3, r = lane & 7;
#pragma unroll 2
  for (int it = 0; it < 32; ++it) {
    uint32_t v[4];
    if (MODE == 0) {
      const int tb = it >> 1, cb = (it & 1) * 4 + m;
      ldsm_x4_t(v, src + (tb * 8 + r) * 128 + ((cb ^ r) << 4));
      const int b = tb >> 3;
      stsm_x4(dst + b * 8192 + (cb * 8 + r) * 128 + (((tb & 7) ^ b ^ r) << 4), v[0], v[1], v[2], v[3]);
    } else {
      const int cb = it & 7, tb = (it >> 3) * 4 + m;
      ldsm_x4_t(v, src + (tb >> 3) * 8192 + (cb * 8 + r) * 128 + (((tb & 7) ^ r) << 4));
      stsm_x4(dst + (tb * 8 + r) * 128 + ((cb ^ r) << 4), v[0], v[1], v[2], v[3]);
    }
  }
}

struct C32 { float re, im; };
DEVI C32 csq(C32 a) { return {a.re * a.re - a.im * a.im, 2.f * a.re * a.im}; }
DEVI C32 cmul(C32 a, C32 b) { return {a.re * b.re - a.im * b.im, a.re * b.im + a.im * b.re}; }
DEVI C32 cfresh(float zl, float zi, float m) {
  float mag = ex2(zl * m), ph = zi * m;
  return {mag * __cosf(ph), mag * __sinf(ph)};
}
struct HMul { uint32_t b, bp; };
DEVI HMul mk_mul(float re, float im) { return {pack_f16(re, im), pack_f16(-im, re)}; }
DEVI uint32_t hcmul(uint32_t a, const HMul& m) {
  __half2 ah = *reinterpret_cast<__half2*>(&a);
  __half2 b = *reinterpret_cast<const __half2*>(&m.b), bp = *reinterpret_cast<const __half2*>(&m.bp);
  __half2 r = __hfma2(__high2half2(ah), bp, __hmul2(__low2half2(ah), b));
  return *reinterpret_cast<uint32_t*>(&r);
}
DEVI uint32_t badd(uint32_t a, uint32_t b) {
  __nv_bfloat162 r = __hadd2(*reinterpret_cast<__nv_bfloat162*>(&a), *reinterpret_cast<__nv_bfloat162*>(&b));
  return *reinterpret_cast<uint32_t*>(&r);
}
DEVI int kidx_l(int i) {
  const int y = i >> 4, r = i & 15;
  int lo;
  if (y < 16) lo = (y & 7) + ((y >> 3) << 7);
  else if (y < 24) lo = 256 + (((y - 16) >> 2) << 7) + ((y & 3) << 1);
  else if (y < 32) lo = 512 + (((y - 24) >> 1) << 7) + ((y & 1) << 2);
  else lo = 1024 + ((y - 32) << 7);
  return lo + 8 * r;
}

template <int MU0, int NMU, int DMAX>
DEVI void conv_tail(float (&acc)[16][4], uint32_t p_lane, uint32_t v_base, int back, bool edge, int lane) {
  uint32_t H[2 * NMU];
#pragma unroll
  for (int i = 0; i < 2 * NMU; ++i) H[i] = lds32(p_lane + (uint32_t)(MU0 - 1 + i) * 32);
  const int hsel = (lane >> 3) & 1;
  const int row = (lane & 7) + ((lane >> 4) << 3) + PADV - 8 - (back & (hsel ^ 1));
  const uint32_t la = v_base + row * 32 + (((hsel ^ back) ^ ((row >> 2) & 1)) << 4);
  constexpr int NLD = (DMAX + 4) / 2;
  uint32_t M[2][4];
  uint32_t p0 = 0, p1 = 0;
  ldsm_x4_t(M[0], la);
#pragma unroll
  for (int ld = 0; ld < NLD; ++ld) {
    if (ld + 1 < NLD) ldsm_x4_t(M[(ld + 1) & 1], la + (ld + 1) * 512);
    const uint32_t* c = M[ld & 1];
#pragma unroll
    for (int s = 0; s < 2; ++s) {
      const int delta = 2 * ld - 2 + s;
      if (delta > DMAX) continue;
      if (delta == -2 && !edge) continue;
      const uint32_t a0 = s ? c[0] : p0, a1 = s ? c[1] : p1, a2 = s ? c[2] : c[0], a3 = s ? c[3] : c[1];
#pragma unroll
      for (int k = 0; k < NMU; ++k) {
        const int nb = delta + MU0 + 2 * k;
        if (nb < 16 && !(delta == -2 && k == 0)) mma_bf16(acc[nb], a0, a1, a2, a3, H[2 * k + 1], H[2 * k]);
      }
    }
    p0 = c[2]; p1 = c[3];
  }
}

__global__ void __cluster_dims__(2, 1, 1) __launch_bounds__(NTHREADS, 1)
fused_kernel(const __grid_constant__ Maps maps, const Ptrs p) {
  extern __shared__ __align__(1024) uint8_t smem[];
  const uint32_t sb = s2u(smem);
  const int tid = threadIdx.x, lane = tid & 31;
  const int warp = __shfl_sync(0xffffffffu, tid >> 5, 0);
  const int cta = blockIdx.x;
  const uint32_t rank = cta & 1;
  const int ti = 2 * (cta >> 4) + rank;
  const int tj = (cta >> 1) & 7;
  const uint32_t bars = sb + SM_BAR;
#define BAR(i) (bars + 8 * (i))

  if (tid == 384) {
    TS(0);
#pragma unroll
    for (int i = 0; i < B_COUNT; ++i)
      mbar_init(BAR(i), i < 3 ? 1 : i < 6 ? 16 : i < B_QKVDONE ? 1 : i == B_CONVDONE ? 4 : i == B_TRDONE ? 3 : 8);
    asm volatile("fence.mbarrier_init.release.cluster;" ::: "memory");
    prefetch_tmap(&maps.x); prefetch_tmap(&maps.w); prefetch_tmap(&maps.u);
  }
  if (tid == 384) TS(32);
  __syncthreads();
  if (tid == 384) TS(33);
  cluster_arrive();
  if (tid == 384) TS(34);

  if (warp < 4) {
    asm volatile("setmaxnreg.inc.sync.aligned.u32 152;");
    const unsigned epoch = __ldcg(&g_epoch);
    const int ch = warp;
    const int d = cta * 4 + ch;
    const uint32_t vv = sb + SM_VV + ch * VV_BYTES;
    const uint32_t ub = sb + SM_U + ch * U_BYTES;
    const uint32_t pb = sb + SM_P + ch * P_BYTES;
    const uint32_t kf = vv + VV_KF;
    const int g = lane >> 2, q = lane & 3;

    float inv, sc, zeta, dskip;
    {
      const size_t po = (size_t)d * 128 + lane * 4;
      uint2 raw[6];
      raw[0] = __ldg((const uint2*)(p.A_re + po)); raw[1] = __ldg((const uint2*)(p.A_im + po));
      raw[2] = __ldg((const uint2*)(p.B_re + po)); raw[3] = __ldg((const uint2*)(p.B_im + po));
      raw[4] = __ldg((const uint2*)(p.C_re + po)); raw[5] = __ldg((const uint2*)(p.C_im + po));
      const float dt = round_bf16(expf(bf2f(p.log_dt[d])));
      dskip = bf2f(p.Dskip[d]);
      float mz = 0.f, mw = 0.f;
#pragma unroll 1
      for (int rd = 0; rd < 4; ++rd) {
        float v[6];
#pragma unroll
        for (int a = 0; a < 6; ++a) {
          v[a] = bf_lo(raw[a].x);
          raw[a].x = __funnelshift_r(raw[a].x, raw[a].y, 16);
          raw[a].y >>= 16;
        }
        const float zr = dt * v[0], zi = dt * v[1], br = dt * v[2], bi = dt * v[3];
        const float wr = v[4] * br - v[5] * bi, wi = v[4] * bi + v[5] * br;
        mz = fmaxf(mz, zr); mw = fmaxf(mw, fmaxf(fabsf(wr), fabsf(wi)));
        sts128(kf + (rd * 32 + lane) * 16, __float_as_uint(zr), __float_as_uint(zi), __float_as_uint(wr), __float_as_uint(wi));
      }
#pragma unroll 1
      for (int o = 16; o > 0; o >>= 1) {
        mz = fmaxf(mz, __shfl_xor_sync(0xffffffffu, mz, o));
        mw = fmaxf(mw, __shfl_xor_sync(0xffffffffu, mw, o));
      }
      const int E = min(max((__float_as_int(mw) >> 23) & 255, 1), 252);
      sc = __int_as_float((253 - E) << 23);
      inv = __int_as_float((E + 1) << 23);
      zeta = mz;
    }
    if (lane == 0) TS(1);

    float Dk[4][8];
    float k2048 = 0.f;
    const uint32_t laneoff = ((lane >> 2) << 4) | ((lane & 3) << 2);
#pragma unroll 1
    for (int rd = 0; rd < 4; ++rd) {
      uint32_t val[56];
      {
        const uint4 zw = lds128(kf + (rd * 32 + lane) * 16);
        const float zl = (__uint_as_float(zw.x) - zeta) * 1.4426950408889634f, zim = __uint_as_float(zw.y);
        const float w_r = __uint_as_float(zw.z) * sc, w_i = __uint_as_float(zw.w) * sc;
        C32 e1 = cfresh(zl, zim, 1.f), e2 = csq(e1), e4 = csq(e2), e8 = csq(e4);
        C32 e16 = cfresh(zl, zim, 16.f), e32 = csq(e16), e64 = csq(e32), e128 = csq(e64);
        C32 e256 = cfresh(zl, zim, 256.f), e512 = csq(e256), e1024 = csq(e512), e2048 = csq(e1024);
        k2048 += w_r * e2048.re - w_i * e2048.im;
        HMul m16 = mk_mul(e16.re, e16.im), m32 = mk_mul(e32.re, e32.im), m64 = mk_mul(e64.re, e64.im);
        uint32_t* X = val + 40;
        X[0] = 0x00003c00u;
        X[1] = pack_f16(e8.re, e8.im); X[2] = m16.b; X[4] = m32.b; X[8] = m64.b;
        X[3] = hcmul(X[1], m16); X[5] = hcmul(X[1], m32); X[6] = hcmul(X[2], m32); X[7] = hcmul(X[3], m32);
#pragma unroll
        for (int r = 1; r < 8; ++r) X[8 + r] = hcmul(X[r], m64);
        HMul c1 = mk_mul(e1.re, -e1.im), c2 = mk_mul(e2.re, -e2.im), c4 = mk_mul(e4.re, -e4.im);
        uint32_t W[8];
        W[0] = pack_f16(w_r, -w_i);
        W[1] = hcmul(W[0], c1); W[2] = hcmul(W[0], c2); W[3] = hcmul(W[1], c2);
        W[4] = hcmul(W[0], c4); W[5] = hcmul(W[1], c4); W[6] = hcmul(W[2], c4); W[7] = hcmul(W[3], c4);
        C32 e384 = cmul(e256, e128), e640 = cmul(e512, e128), e768 = cmul(e512, e256), e896 = cmul(e768, e128);
        HMul c128 = mk_mul(e128.re, -e128.im), c256 = mk_mul(e256.re, -e256.im), c384 = mk_mul(e384.re, -e384.im);
        HMul c512 = mk_mul(e512.re, -e512.im), c640 = mk_mul(e640.re, -e640.im), c768 = mk_mul(e768.re, -e768.im);
        HMul c896 = mk_mul(e896.re, -e896.im), c1024 = mk_mul(e1024.re, -e1024.im);
#pragma unroll
        for (int i = 0; i < 8; ++i) { val[i] = W[i]; val[8 + i] = hcmul(W[i], c128); }
#pragma unroll
        for (int i = 0; i < 4; ++i) { val[16 + i] = hcmul(W[2 * i], c256); val[20 + i] = hcmul(W[2 * i], c384); }
        val[24] = hcmul(W[0], c512); val[25] = hcmul(W[4], c512);
        val[26] = hcmul(W[0], c640); val[27] = hcmul(W[4], c640);
        val[28] = hcmul(W[0], c768); val[29] = hcmul(W[4], c768);
        val[30] = hcmul(W[0], c896); val[31] = hcmul(W[4], c896);
        const uint32_t v0 = hcmul(W[0], c1024);
        val[32] = v0; val[33] = hcmul(v0, c128); val[34] = hcmul(v0, c256); val[35] = hcmul(v0, c384);
        val[36] = hcmul(v0, c512); val[37] = hcmul(v0, c640); val[38] = hcmul(v0, c768); val[39] = hcmul(v0, c896);
      }
      if (tid == 0) TS(36 + rd * 3);
      if (rd > 0) { wg_wait<0>(); bar_sync(2, 128); }
      if (tid == 0) TS(37 + rd * 3);
#pragma unroll
      for (int r = 0; r < 56; ++r) sts32(vv + r * 128 + (laneoff ^ ((r & 7) << 4)), val[r]);
      fence_async_smem();
      bar_sync(2, 128);
      wg_fence();
#pragma unroll
      for (int c = 0; c < 4; ++c) {
        const uint32_t da = mkdesc(sb + SM_VV + c * VV_BYTES, 16);
#pragma unroll
        for (int k = 0; k < 4; ++k) wgmma_n16_f16(Dk[c], da + 2 * k, da + 320 + 2 * k, (rd | k) != 0);
      }
      wg_commit();
      if (tid == 0) TS(38 + rd * 3);
    }
    wg_wait<0>();
    if (tid == 0) TS(48);
    bar_sync(2, 128);
    if (warp < 3) {
#pragma unroll
      for (int c = 0; c < 4; ++c) {
        const uint32_t a = sb + SM_VV + c * VV_BYTES + VV_KF + ((16 * warp + g) * 16 + 2 * q) * 4;
        sts_f32x2(a, Dk[c][0], Dk[c][1]);
        sts_f32x2(a + 32, Dk[c][4], Dk[c][5]);
        if (warp < 2) {
          sts_f32x2(a + 512, Dk[c][2], Dk[c][3]);
          sts_f32x2(a + 544, Dk[c][6], Dk[c][7]);
        }
      }
    }
#pragma unroll 1
    for (int o = 16; o > 0; o >>= 1) k2048 += __shfl_xor_sync(0xffffffffu, k2048, o);
    if (lane == 0) TS(2);
    mbar_wait(BAR(B_TRDONE), 0);
    bar_sync(2, 128);
    if (lane == 0) {
      TS(50);
      wait_counter(&g_cnt[(C_U + (cta >> 4)) * 32], (epoch + 1) * 16);
      mbar_expect_tx(BAR(B_UCH + ch), 4096);
      bulk_load(ub + 256, p.uT + (size_t)d * 2048, 4096, BAR(B_UCH + ch));
      TS(3);
    }
    __syncwarp();
    if (lane < 16) sts128(ub + lane * 16, 0, 0, 0, 0);
    if (zeta > 0.f) {
      const float zt = zeta * 1.4426950408889634f;
#pragma unroll 1
      for (int i = lane; i < 640; i += 32) sts_f32(kf + i * 4, lds_f32(kf + i * 4) * ex2(zt * kidx_l(i)));
      k2048 *= ex2(zt * 2048.f);
      __syncwarp();
    }
    const float k1024 = lds_f32(kf + kidx_c(1024) * 4) * inv;
    if (lane == 0) {
      sts_f32(kf + SL_K2048 * 4, k2048);
      sts_f32(kf + SL_ZERO * 4, 0.f);
      sts_f32(kf + SL_510 * 4, lds_f32(kf + kidx_c(510) * 4) - lds_f32(kf + kidx_c(512) * 4));
      sts_f32(kf + SL_0 * 4, lds_f32(kf) + dskip * sc);
    }
    __syncwarp();
#pragma unroll 1
    for (int i0 = 0; i0 < 30; i0 += 6) {
      uint32_t e[6];
      float a[6], b[6];
#pragma unroll
      for (int i = 0; i < 6; ++i) e[i] = lds32(sb + SM_PTAB + ((i0 + i) * 32 + lane) * 4);
#pragma unroll
      for (int i = 0; i < 6; ++i) { a[i] = lds_f32(kf + (e[i] & 0xffff)); b[i] = lds_f32(kf + (e[i] >> 16)); }
#pragma unroll
      for (int i = 0; i < 6; ++i) sts32(pb + ((i0 + i) * 32 + lane) * 4, pack_bf16(a[i] * inv, b[i] * inv));
    }
    __syncwarp();
    if (lane == 0) TS(4);
    mbar_wait(BAR(B_UCH + ch), 0);
    if (lane == 0) TS(5);
#pragma unroll 1
    for (int it = 0; it < 8; ++it) {
      const int k = -18 + it * 32 + lane;
      const int kr = min(max(k, -2), 208);
      uint32_t E[12];
#pragma unroll
      for (int c = 0; c < 3; ++c) {
        const int kk = kr - 1 + c, r = (kk >> 1) + 8;
        const uint4 t = lds128(ub + r * 32 + (((kk & 1) ^ ((r >> 2) & 1)) << 4));
        E[4 * c] = t.x; E[4 * c + 1] = t.y; E[4 * c + 2] = t.z; E[4 * c + 3] = t.w;
      }
      uint32_t O[8];
#pragma unroll
      for (int j = 0; j < 8; ++j) O[j] = __byte_perm(E[j + 1], E[j + 2], 0x5432);
      uint32_t s3[6], s5[4], s7[4], s9[4];
#pragma unroll
      for (int j = 0; j < 6; ++j) s3[j] = badd(badd(O[j], O[j + 1]), E[j + 2]);
#pragma unroll
      for (int j = 0; j < 4; ++j) {
        s5[j] = badd(s3[j + 2], badd(E[j + 3], E[j + 5]));
        s7[j] = badd(s5[j], badd(O[j + 1], O[j + 4]));
        s9[j] = badd(s7[j], badd(E[j + 2], E[j + 6]));
      }
      const int r = (k >> 1) + PADV;
      const uint32_t a = vv + r * 32 + (((k & 1) ^ ((r >> 2) & 1)) << 4);
      if (k < 208) { sts128(a + VV_U3, s3[0], s3[1], s3[2], s3[3]); sts128(a + VV_U5, s5[0], s5[1], s5[2], s5[3]); }
      if (k < 144) { sts128(a + VV_U7, s7[0], s7[1], s7[2], s7[3]); sts128(a + VV_U9, s9[0], s9[1], s9[2], s9[3]); }
    }
    __syncwarp();
    if (lane == 0) TS(6);
    bar_sync(4, 384);
    if (lane == 0) TS(7);
    float acc[16][4];
#pragma unroll
    for (int i = 0; i < 16; ++i) { acc[i][0] = acc[i][1] = acc[i][2] = acc[i][3] = 0.f; }
    {
      const int gq = g - 2 * q;
      const uint32_t pd_lane = pb + (PD_OFF + 16 + gq) * 4;
      const int prow0 = 8 + (lane & 7) + ((lane >> 4) << 3), hs = (lane >> 3) & 1;
      uint32_t B[8][4];
      {
        const uint32_t la = ub + prow0 * 32 + ((hs ^ ((prow0 >> 2) & 1)) << 4);
#pragma unroll
        for (int m2 = 0; m2 < 8; ++m2) ldsm_x4(B[m2], la + m2 * 512);
      }
#pragma unroll 1
      for (int rho = 0; rho < 8; ++rho) {
        uint32_t A[4][3];
#pragma unroll
        for (int i = 0; i < 4; ++i) {
          const uint32_t a = pd_lane + (uint32_t)(2 * rho + 16 * i) * 32;
          A[i][0] = lds32(a); A[i][1] = lds32(a + 32); A[i][2] = lds32(a - 32);
        }
        const int prow = prow0 - min(rho + 1, 7);
        const uint32_t la = ub + prow * 32 + ((hs ^ ((prow >> 2) & 1)) << 4);
#pragma unroll
        for (int i = 0; i < 4; ++i)
#pragma unroll
          for (int m2 = 0; m2 < 8; ++m2) {
#pragma unroll
            for (int h = 0; h < 2; ++h)
              if (2 * m2 + h + i < 16)
                mma_bf16(acc[2 * m2 + h + i], A[i][0], A[i][1], A[i][2], A[i][0], B[m2][2 * h], B[m2][2 * h + 1]);
            if (i == 3) ldsm_x4(B[m2], la + m2 * 512);
          }
      }
      {
        const float kfix = -round_bf16(k1024);
        const uint32_t kf2 = pack_bf16(kfix, kfix);
        auto hfix = [&](int x) { return (x == 1020 ? kf2 & 0xffffu : x == 1021 ? kf2 : x == 1022 ? kf2 & 0xffff0000u : 0u); };
        const uint32_t h127 = hfix(1016 + gq), h128 = hfix(1024 + gq);
        const uint32_t h63 = lds32(pd_lane + 63 * 32), h64 = lds32(pd_lane + 64 * 32);
        const uint32_t la0 = ub + prow0 * 32 + ((hs ^ ((prow0 >> 2) & 1)) << 4);
#pragma unroll
        for (int m = 0; m < 9; ++m) mma_bf16(acc[m + 7], 0u, h127, 0u, 0u, B[m >> 1][2 * (m & 1)], B[m >> 1][2 * (m & 1) + 1]);
#pragma unroll
        for (int m2 = 0; m2 < 6; ++m2) ldsm_x4(B[m2], la0 + m2 * 512);
#pragma unroll
        for (int m = 0; m < 12; ++m) mma_bf16(acc[m + 4], h64, 0u, h63, h64, B[m >> 1][2 * (m & 1)], B[m >> 1][2 * (m & 1) + 1]);
#pragma unroll
        for (int m = 0; m < 8; ++m) mma_bf16(acc[m + 8], h128, 0u, h127, h128, B[m >> 1][2 * (m & 1)], B[m >> 1][2 * (m & 1) + 1]);
      }
#pragma unroll 1
      for (int v = 0; v < 4; ++v)
        conv_tail<4, 3, 11>(acc, pb + (P2_OFF + 56 * v + gq - 16) * 4, vv + ((v & 1) ? VV_U3 : VV_U5), v >> 1, v == 0, lane);
#pragma unroll 1
      for (int pi = 0; pi < 2; ++pi)
        conv_tail<8, 5, 7>(acc, pb + (P3_OFF + 88 * pi + gq - 48) * 4, vv + (pi ? VV_U7 : VV_U9), pi, pi == 0, lane);
    }
    bar_arrive(3, 384);
    if (lane == 0) TS(8);
    {
      const int mt = lane >> 3;
      const uint32_t a = vv + (128 * (mt >> 1) + 16 * (lane & 7) + 8 * (mt & 1)) * 2;
#pragma unroll
      for (int ab = 0; ab < 16; ab += 2)
        stsm_x4_t(a + ab * 256, pack_bf16(acc[ab][0], acc[ab][1]), pack_bf16(acc[ab][2], acc[ab][3]),
                  pack_bf16(acc[ab + 1][0], acc[ab + 1][1]), pack_bf16(acc[ab + 1][2], acc[ab + 1][3]));
    }
    fence_async_smem();
    __syncwarp();
    if (lane == 0) {
      bulk_store(p.yT + (size_t)d * 2048, vv, 4096);
      bulk_commit();
      bulk_wait0();
      red_relaxed_add(&g_cnt[(C_Y + (cta >> 4)) * 32], 1);
      TS(9);
    }
    cluster_wait();
  } else if (warp < 12) {
    asm volatile("setmaxnreg.inc.sync.aligned.u32 160;");
    const unsigned epoch = __ldcg(&g_epoch);
    const int w8 = warp - 4;
    const int g = lane >> 2, q = lane & 3;
    cluster_wait();
    {
      float acc[96];
#pragma unroll 1
      for (int ks = 0, s = 0, ph = 0; ks < 8; ++ks) {
        mbar_wait(BAR(B_FULL + s), ph);
        if (ks == 0 && tid == 128) TS(16);
        const uint32_t st = sb + s * STG_BYTES;
        const uint32_t da = mkdesc(st + STG_X + (w8 >> 2) * 8192, 16);
        const uint32_t db = mkdesc(st + STG_W, 8192);
        wg_fence();
#pragma unroll
        for (int k = 0; k < 4; ++k) wgmma_n192(acc, da + 2 * k, db + 128 * k, (ks | k) != 0);
        wg_commit();
        const uint32_t eprev = BAR(B_EMPTY + (s == 0 ? 2 : s - 1));
        if (++s == 3) { s = 0; ph ^= 1; }
        if (ks > 0) {
          wg_wait<1>();
          if (lane < 2) mbar_arrive_cluster(eprev, lane);
        }
      }
      wg_wait<0>();
      if (lane < 2) mbar_arrive_cluster(BAR(B_EMPTY + 1), lane);
      bar_arrive(4, 384);
      if (tid == 128) TS(17);
      bar_sync(1, 256);
      const int row = w8 * 16 + (lane & 7) + (((lane >> 3) & 1) << 3);
      const uint32_t ra = sb + SM_QS + row * 128;
#pragma unroll
      for (int i = 0; i < 24; i += 2)
        stsm_x4(ra + (i >> 3) * 16384 + ((((i & 7) + (lane >> 4)) ^ (row & 7)) << 4), pack_bf16(acc[4 * i], acc[4 * i + 1]),
                pack_bf16(acc[4 * i + 2], acc[4 * i + 3]), pack_bf16(acc[4 * i + 4], acc[4 * i + 5]),
                pack_bf16(acc[4 * i + 6], acc[4 * i + 7]));
    }
    __syncwarp();
    const unsigned par = epoch & 1;
    const int hh = w8 >> 1, dtile = w8 & 1;
    float* kvg = &g_kv[par][tj][hh][0];
#pragma unroll 1
    for (int part = 1; part >= 0; --part) {
      const uint32_t pa = sb + SM_QS + part * 16384 + w8 * 2048 + lane * 16;
#pragma unroll 1
      for (int it = 0; it < 4; ++it) {
        uint4 t = lds128(pa + it * 512);
        uint32_t* tw = &t.x;
#pragma unroll
        for (int j = 0; j < 4; ++j) {
          const uint32_t x = tw[j];
          const __nv_bfloat162 xb = *reinterpret_cast<const __nv_bfloat162*>(&x);
          const uint32_t e = pack_bf16(ex2(bf_lo(x) * 1.4426950408889634f), ex2(bf_hi(x) * 1.4426950408889634f));
          const uint32_t m = __hgt2_mask(xb, __floats2bfloat162_rn(0.f, 0.f));
          const uint32_t sel = (badd(x, 0x3f803f80u) & m) | (e & ~m);
          tw[j] = pack_bf16(bf_lo(sel) + 1e-6f, bf_hi(sel) + 1e-6f);
        }
        sts128(pa + it * 512, t.x, t.y, t.z, t.w);
      }
      if (part == 1) {
        if (tid == 128) TS(53);
        bar_sync(1, 256);
        float kv[4] = {0.f, 0.f, 0.f, 0.f}, zz[4] = {0.f, 0.f, 0.f, 0.f};
        const int m = lane >> 3;
        const uint32_t aa = sb + SM_VS + ((lane & 7) + ((m >> 1) << 3)) * 128 + (((2 * hh + (m & 1)) ^ (lane & 7)) << 4);
        const uint32_t ab = sb + SM_PK + (lane & 15) * 128 + (((2 * hh + dtile) ^ (lane & 7)) << 4);
#pragma unroll 2
        for (int ks = 0; ks < 8; ++ks) {
          uint32_t a[4], b0, b1;
          ldsm_x4_t(a, aa + ks * 2048);
          ldsm_x2_t(b0, b1, ab + ks * 2048);
          mma_bf16(kv, a[0], a[1], a[2], a[3], b0, b1);
          mma_bf16(zz, 0x3f803f80u, 0x3f803f80u, 0x3f803f80u, 0x3f803f80u, b0, b1);
        }
        asm volatile("red.global.add.v4.f32 [%0], {%1,%2,%3,%4};" ::"l"(kvg + dtile * 128 + lane * 4), "f"(kv[0]), "f"(kv[1]),
                     "f"(kv[2]), "f"(kv[3]) : "memory");
        if (g == 0)
          asm volatile("red.global.add.v2.f32 [%0], {%1,%2};" ::"l"(kvg + 256 + dtile * 8 + 2 * q), "f"(zz[0]), "f"(zz[1]) : "memory");
        if (tid == 128) TS(55);
        bar_sync(1, 256);
        if (lane == 0) mbar_arrive(BAR(B_PKVFREE));
        if (tid == 128) { red_release_add(&g_cnt[(C_KV + tj) * 32], 1); TS(18); }
        if (ti == 0) {
          float4* z = (float4*)&g_kv[par ^ 1][tj][0][0];
          for (int i = tid - 128; i < 272; i += 256) z[i] = make_float4(0.f, 0.f, 0.f, 0.f);
        }
      }
    }
    if (tid == 128) { TS(56); wait_counter(&g_cnt[(C_KV + tj) * 32], (epoch + 1) * 16); TS(19); }
    bar_sync(1, 256);
    {
      const float4 k4 = __ldcg((const float4*)(kvg + dtile * 128 + lane * 4));
      const float2 z2 = __ldcg((const float2*)(kvg + 256 + dtile * 8 + 2 * q));
      const uint32_t a = sb + SM_KVB + hh * 512 + lane * 16 + dtile * 4;
      sts32(a, pack_bf16(k4.x, k4.y));
      sts32(a + 8, pack_bf16(k4.z, k4.w));
      if (g == 0) sts32(sb + SM_KVB + 2048 + hh * 32 + q * 8 + dtile * 4, pack_bf16(z2.x, z2.y));
    }
    bar_sync(1, 256);
    {
      const int row = w8 * 16 + (lane & 7) + (((lane >> 3) & 1) << 3);
      uint4* dst = &g_ofrag[((ti * 8 + w8) * 32 + 4 * tj) * 32 + lane];
#pragma unroll 1
      for (int h = 0; h < 4; ++h) {
        uint32_t a[4];
        ldsm_x4(a, sb + SM_QS + row * 128 + (((2 * h + (lane >> 4)) ^ (row & 7)) << 4));
        const uint4 kb = lds128(sb + SM_KVB + h * 512 + lane * 16);
        const uint32_t zb0 = lds32(sb + SM_KVB + 2048 + h * 32 + q * 8), zb1 = lds32(sb + SM_KVB + 2048 + h * 32 + q * 8 + 4);
        float n0[4] = {0.f, 0.f, 0.f, 0.f}, n1[4] = {0.f, 0.f, 0.f, 0.f}, dn[4] = {0.f, 0.f, 0.f, 0.f};
        mma_bf16(n0, a[0], a[1], a[2], a[3], kb.x, kb.y);
        mma_bf16(n1, a[0], a[1], a[2], a[3], kb.z, kb.w);
        mma_bf16(dn, a[0], a[1], a[2], a[3], zb0, zb1);
        const uint32_t dd = pack_bf16(dn[0], dn[2]);
        const uint32_t d2 = pack_bf16(bf_lo(dd) + 1e-6f, bf_hi(dd) + 1e-6f);
        const float r0 = rcp(bf_lo(d2)), r1 = rcp(bf_hi(d2));
        const uint32_t x0 = pack_bf16(n0[0], n0[1]), x1 = pack_bf16(n0[2], n0[3]);
        const uint32_t x2 = pack_bf16(n1[0], n1[1]), x3 = pack_bf16(n1[2], n1[3]);
        dst[h * 32] = make_uint4(pack_bf16(bf_lo(x0) * r0, bf_hi(x0) * r0), pack_bf16(bf_lo(x1) * r1, bf_hi(x1) * r1),
                                 pack_bf16(bf_lo(x2) * r0, bf_hi(x2) * r0), pack_bf16(bf_lo(x3) * r1, bf_hi(x3) * r1));
      }
    }
    if (tid == 128) TS(57);
    bar_sync(1, 256);
    if (tid == 128) {
      red_release_add(&g_cnt[(C_O + ti) * 32], 1);
      TS(20);
      wait_counter(&g_cnt[(C_O + ti) * 32], (epoch + 1) * 8);
      if (cta == 0) g_epoch = epoch + 1;
      TS(21);
    }
    bar_sync(1, 256);
    {
      const uint4* src = &g_ofrag[((ti * 8 + w8) * 32) * 32 + lane];
      uint4 A0[8], A1[8];
#pragma unroll
      for (int h = 0; h < 8; ++h) A0[h] = __ldcg(src + h * 32);
#pragma unroll
      for (int h = 0; h < 8; ++h) A1[h] = __ldcg(src + (8 + h) * 32);
      mbar_wait(BAR(B_WO), 0);
      bar_sync(3, 384);
      if (tid == 128) TS(22);
      float o[32];
      const uint32_t db = mkdesc(sb + SM_WO, 8192);
#pragma unroll 1
      for (int it = 0; it < 2; ++it) {
        wg_fence();
#pragma unroll
        for (int h = 0; h < 8; ++h) wgmma_n64_rs(o, A0[h], db + (16 * it + h) * 128, (it | h) != 0);
        wg_commit();
        wg_wait<0>();
        if (it == 0) {
#pragma unroll
          for (int h = 0; h < 8; ++h) A0[h] = __ldcg(src + (16 + h) * 32);
        }
        wg_fence();
#pragma unroll
        for (int h = 0; h < 8; ++h) wgmma_n64_rs(o, A1[h], db + (16 * it + 8 + h) * 128, 1);
        wg_commit();
        wg_wait<0>();
        if (it == 0) {
#pragma unroll
          for (int h = 0; h < 8; ++h) A1[h] = __ldcg(src + (24 + h) * 32);
        }
      }
      const int row = w8 * 16 + (lane & 7) + (((lane >> 3) & 1) << 3);
#pragma unroll
      for (int i = 0; i < 8; i += 2)
        stsm_x4(sb + SM_BOUT + row * 128 + (((i + (lane >> 4)) ^ (row & 7)) << 4), pack_bf16(o[4 * i], o[4 * i + 1]),
                pack_bf16(o[4 * i + 2], o[4 * i + 3]), pack_bf16(o[4 * i + 4], o[4 * i + 5]), pack_bf16(o[4 * i + 6], o[4 * i + 7]));
      fence_async_smem();
      bar_sync(1, 256);
      if (tid == 128) {
        tma_store_2d(&maps.out, sb + SM_BOUT, 512 + 64 * tj, 128 * ti);
        bulk_commit();
        bulk_wait0();
        TS(23);
      }
    }
  } else {
    asm volatile("setmaxnreg.dec.sync.aligned.u32 40;");
    if (tid == 384) TS(49);
    if (warp == 13 && lane == 0) {
      mbar_expect_tx(BAR(B_UTILE), 16384);
      tma_load_2d(sb + SM_TIN1, &maps.u, tj * 64, ti * 128, BAR(B_UTILE));
    }
    if (warp >= 14) {
      const int t = tid - 448;
#pragma unroll
      for (int i = 0; i < 4; ++i)
        if (t + 64 * i < 240) {
          const uint4 v = __ldg((const uint4*)g_ptab.v + t + 64 * i);
          sts128(sb + SM_PTAB + (t + 64 * i) * 16, v.x, v.y, v.z, v.w);
        }
      __syncwarp();
      if (lane == 0) mbar_arrive(BAR(B_TRDONE));
    }
    if (tid == 384) TS(51);
    cluster_wait();
    if (tid == 384) TS(52);
    if (warp == 12) {
      if (lane == 0) {
#pragma unroll 1
        for (int ks = 0, s = 0, ph = 1; ks < 8; ++ks) {
          if (ks >= 3) mbar_wait(BAR(B_EMPTY + s), ph);
          const uint32_t st = sb + s * STG_BYTES, fb = BAR(B_FULL + s);
          if (ks == 0) TS(61);
          mbar_expect_tx(fb, STG_BYTES);
          tma_load_2d(st + STG_X, &maps.x, ks * 64, ti * 128, fb);
#pragma unroll 1
          for (int nb = 0; nb < 3; ++nb)
            tma_load_2d_mc(st + STG_W + nb * 8192 + rank * 4096, &maps.w, nb * 512 + tj * 64, ks * 64 + rank * 32, fb, 3);
          if (ks == 2) {
            l2_prefetch((const char*)p.wqkv + 192 * 3072 + cta * 7680, 7680);
            l2_prefetch((const char*)p.x + (size_t)cta * 16384, 16384);
            l2_prefetch((const char*)p.wo + (size_t)cta * 4096, 4096);
            prefetch_tmap(&maps.wo); prefetch_tmap(&maps.uT); prefetch_tmap(&maps.yT); prefetch_tmap(&maps.out);
          }
          if (++s == 3) { s = 0; ph ^= 1; }
        }
        TS(24);
        mbar_wait(BAR(B_EMPTY + 0), 0);
        mbar_wait(BAR(B_EMPTY + 1), 0);
        mbar_expect_tx(BAR(B_WO), 65536);
        tma_load_2d_mc(sb + SM_WO + rank * 32768, &maps.wo, tj * 64, rank * 256, BAR(B_WO), 3);
      }
    } else if (warp == 13) {
      const unsigned epoch = __ldcg(&g_epoch);
      mbar_wait(BAR(B_UTILE), 0);
      if (lane == 0) TS(26);
      transpose_tile<0>(sb + SM_TIN1, sb + SM_TOUT1, lane);
      if (lane == 0) TS(58);
      fence_async_smem();
      __syncwarp();
      if (lane == 0) {
        tma_store_2d(&maps.uT, sb + SM_TOUT1, ti * 128, tj * 64);
        tma_store_2d(&maps.uT, sb + SM_TOUT1 + 8192, ti * 128 + 64, tj * 64);
        bulk_commit();
        bulk_wait0();
        TS(59);
        red_relaxed_add(&g_cnt[(C_U + tj) * 32], 1);
        mbar_arrive(BAR(B_TRDONE));
        TS(27);
        mbar_wait(BAR(B_PKVFREE), 0);
        wait_counter(&g_cnt[(C_Y + tj) * 32], (epoch + 1) * 64);
        TS(28);
        mbar_expect_tx(BAR(B_YTILE), 16384);
        tma_load_2d(sb + SM_TIN2, &maps.yT, ti * 128, tj * 64, BAR(B_YTILE));
        tma_load_2d(sb + SM_TIN2 + 8192, &maps.yT, ti * 128 + 64, tj * 64, BAR(B_YTILE));
      }
      __syncwarp();
      mbar_wait(BAR(B_YTILE), 0);
      transpose_tile<1>(sb + SM_TIN2, sb + SM_TOUT2, lane);
      fence_async_smem();
      __syncwarp();
      if (lane == 0) {
        tma_store_2d(&maps.out, sb + SM_TOUT2, 64 * tj, 128 * ti);
        bulk_commit();
        bulk_wait0();
        TS(29);
      }
    }
  }
  __syncwarp();
  cluster_arrive();
  cluster_wait();
  if (tid == 0) TS(31);
#undef BAR
}

typedef CUresult (*EncodeFn)(CUtensorMap*, CUtensorMapDataType, cuuint32_t, void*, const cuuint64_t*, const cuuint64_t*,
                             const cuuint32_t*, const cuuint32_t*, CUtensorMapInterleave, CUtensorMapSwizzle,
                             CUtensorMapL2promotion, CUtensorMapFloatOOBfill);

static void make_map(EncodeFn enc, CUtensorMap* m, const void* base, uint64_t inner, uint64_t outer, uint32_t box_in,
                     uint32_t box_out) {
  cuuint64_t gd[2] = {inner, outer};
  cuuint64_t gs[1] = {inner * 2};
  cuuint32_t bd[2] = {box_in, box_out};
  cuuint32_t es[2] = {1, 1};
  enc(m, CU_TENSOR_MAP_DATA_TYPE_BFLOAT16, 2, const_cast<void*>(base), gd, gs, bd, es, CU_TENSOR_MAP_INTERLEAVE_NONE,
      CU_TENSOR_MAP_SWIZZLE_128B, CU_TENSOR_MAP_L2_PROMOTION_L2_128B, CU_TENSOR_MAP_FLOAT_OOB_FILL_NONE);
}

}

extern "C" void kernel_launch(void* const* d_in, const int* in_sizes, int n_in, void* d_out, int out_size) {
  using namespace s4la;
  (void)in_sizes; (void)n_in; (void)out_size;
  static EncodeFn enc = nullptr;
  static void *uT = nullptr, *yT = nullptr;
  if (!enc) {
    void* fn = nullptr;
    cudaDriverEntryPointQueryResult qr;
    cudaGetDriverEntryPoint("cuTensorMapEncodeTiled", &fn, cudaEnableDefault, &qr);
    enc = (EncodeFn)fn;
    cudaGetSymbolAddress(&uT, g_uT);
    cudaGetSymbolAddress(&yT, g_yT);
    cudaFuncSetAttribute(fused_kernel, cudaFuncAttributeMaxDynamicSharedMemorySize, SM_TOTAL);
  }
  const __nv_bfloat16* const* in = (const __nv_bfloat16* const*)d_in;
  Maps maps;
  make_map(enc, &maps.x, in[9], 512, 2048, 64, 128);
  make_map(enc, &maps.w, in[10], 1536, 512, 64, 32);
  make_map(enc, &maps.wo, in[11], 512, 512, 64, 256);
  make_map(enc, &maps.u, in[0], 512, 2048, 64, 128);
  make_map(enc, &maps.uT, uT, 2048, 512, 64, 64);
  make_map(enc, &maps.yT, yT, 2048, 512, 64, 64);
  make_map(enc, &maps.out, d_out, 1024, 2048, 64, 128);
  Ptrs p;
  p.A_re = in[1]; p.A_im = in[2]; p.B_re = in[3]; p.B_im = in[4]; p.C_re = in[5]; p.C_im = in[6];
  p.log_dt = in[7]; p.Dskip = in[8]; p.x = in[9]; p.wqkv = in[10]; p.wo = in[11];
  p.uT = (__nv_bfloat16*)uT; p.yT = (__nv_bfloat16*)yT;
  fused_kernel<<<NCTA, NTHREADS, SM_TOTAL, cudaStreamPerThread>>>(maps, p);
}
```

```cpp
#include <cuda_runtime.h>
#include <cuda_bf16.h>
#include <cuda_fp16.h>
#include <cuda.h>
#include <stdint.h>

#define DEVI __device__ __forceinline__

namespace s4la {

constexpr int NTHREADS = 512;
constexpr int NCTA = 128;

constexpr uint32_t STG_BYTES = 40960, STG_X = 0, STG_W = 16384;
constexpr uint32_t SM_WO = 0;
constexpr uint32_t SM_QS = 65536;
constexpr uint32_t SM_BOUT = 65536;
constexpr uint32_t SM_PK = 81920;
constexpr uint32_t SM_VS = 98304;
constexpr uint32_t SM_KVB = 114688;
constexpr uint32_t SM_TIN2 = 81920, SM_TOUT2 = 98304;
constexpr uint32_t SM_U = 122880, U_BYTES = 4352;
constexpr uint32_t SM_P = 140288, P_BYTES = 4096;
constexpr uint32_t SM_TIN1 = SM_U, SM_TOUT1 = SM_P;
constexpr uint32_t SM_VV = 156672, VV_BYTES = 12800;
constexpr uint32_t VV_U5 = 0, VV_U3 = 3712, VV_U9 = 7424, VV_U7 = 10112;
constexpr uint32_t KG_BYTES = 3200;
constexpr uint32_t SM_BAR = SM_VV + 4 * VV_BYTES;
constexpr uint32_t SM_PTAB = SM_BAR + 256;
constexpr uint32_t SM_TOTAL = SM_PTAB + 3840;
constexpr int PADV = 12;

enum { B_FULL = 0, B_EMPTY = 3, B_WO = 6, B_UTILE = 7, B_YTILE = 8, B_UCH = 9, B_QKVDONE = 13,
       B_CONVDONE = 14, B_TRDONE = 15, B_PKVFREE = 16, B_COUNT = 17 };

constexpr int PD_OFF = 0, P2_OFF = 544, P3_OFF = 768;

constexpr int SL_K2048 = 640, SL_ZERO = 641, SL_510 = 642, SL_0 = 643;
__host__ __device__ constexpr int kidx_c(int l) {
  int r = (l >> 3) & 15, y = 0;
  if (l < 256) y = (l & 7) + ((l >> 7) << 3);
  else if (l < 512) y = 16 + (((l - 256) >> 7) << 2) + ((l & 7) >> 1);
  else if (l < 1024) y = 24 + (((l - 512) >> 7) << 1) + ((l >> 2) & 1);
  else y = 32 + ((l - 1024) >> 7);
  return r * 40 + y;
}
constexpr int slot_direct(int l) {
  if (l < 0 || l > 510) return SL_ZERO;
  if (l == 510) return SL_510;
  if (l == 0) return SL_0;
  return kidx_c(l < 256 ? l : ((l + ((l >> 1) & 1)) & ~1));
}
constexpr int slot_seg2(int v, int k) { return (k >= 32 && k < 64) ? kidx_c(16 * k + 4 * v) : SL_ZERO; }
constexpr int slot_seg3(int pi, int k) {
  return (k >= 64 && k < 128) ? kidx_c(16 * k + 8 * pi) : ((k == 128 && pi == 0) ? SL_K2048 : SL_ZERO);
}
struct PTab { uint32_t v[960]; };
constexpr PTab make_ptab() {
  PTab t{};
  for (int w = 0; w < 960; ++w) t.v[w] = (SL_ZERO * 4) | ((SL_ZERO * 4) << 16);
  for (int w = 0; w < 544; ++w) t.v[w] = (slot_direct(w - 16) * 4) | ((slot_direct(w - 17) * 4) << 16);
  for (int v = 0; v < 4; ++v)
    for (int x = 16; x < 72; ++x) t.v[544 + 56 * v + x - 16] = (slot_seg2(v, x) * 4) | ((slot_seg2(v, x - 1) * 4) << 16);
  for (int pi = 0; pi < 2; ++pi)
    for (int x = 48; x < 136; ++x) t.v[768 + 88 * pi + x - 48] = (slot_seg3(pi, x) * 4) | ((slot_seg3(pi, x - 1) * 4) << 16);
  return t;
}
__device__ const PTab g_ptab = make_ptab();

__device__ __nv_bfloat16 g_uT[512 * 2048];
__device__ __nv_bfloat16 g_yT[512 * 2048];
__device__ uint4 g_ofrag[16 * 8 * 32 * 32];
__device__ float g_kv[2][8][4][272];
__device__ unsigned g_cnt[64 * 32];
__device__ unsigned g_epoch;
#define TS(slot) do { } while (0)
enum { C_U = 0, C_KV = 8, C_O = 16, C_Y = 32 };

struct Maps {
  CUtensorMap x, w, wo, u, uT, yT, out;
};
struct Ptrs {
  const __nv_bfloat16 *A_re, *A_im, *B_re, *B_im, *C_re, *C_im, *log_dt, *Dskip;
  const __nv_bfloat16 *x, *wqkv, *wo;
  __nv_bfloat16 *uT, *yT;
};

DEVI uint32_t s2u(const void* p) { return (uint32_t)__cvta_generic_to_shared(p); }
DEVI void mbar_init(uint32_t b, uint32_t c) { asm volatile("mbarrier.init.shared::cta.b64 [%0], %1;" ::"r"(b), "r"(c) : "memory"); }
DEVI void mbar_expect_tx(uint32_t b, uint32_t bytes) {
  asm volatile("mbarrier.arrive.expect_tx.shared::cta.b64 _, [%0], %1;" ::"r"(b), "r"(bytes) : "memory");
}
DEVI void mbar_arrive(uint32_t b) { asm volatile("mbarrier.arrive.shared::cta.b64 _, [%0];" ::"r"(b) : "memory"); }
DEVI void mbar_arrive_cluster(uint32_t b, uint32_t cta) {
  asm volatile("{\n.reg .b32 r;\nmapa.shared::cluster.u32 r, %0, %1;\nmbarrier.arrive.shared::cluster.b64 _, [r];\n}"
               ::"r"(b), "r"(cta) : "memory");
}
DEVI void mbar_wait(uint32_t b, uint32_t parity) {
  asm volatile("{\n.reg .pred p;\nLAB_WAIT:\nmbarrier.try_wait.parity.shared::cta.b64 p, [%0], %1, 0x989680;\n@p bra LAB_DONE;\nbra LAB_WAIT;\nLAB_DONE:\n}"
               ::"r"(b), "r"(parity) : "memory");
}
#define mbar_wait_cluster mbar_wait
DEVI void bar_sync(int id, int n) { asm volatile("bar.sync %0, %1;" ::"r"(id), "r"(n) : "memory"); }
DEVI void bar_arrive(int id, int n) { asm volatile("bar.arrive %0, %1;" ::"r"(id), "r"(n) : "memory"); }
DEVI void fence_async_smem() { asm volatile("fence.proxy.async.shared::cta;" ::: "memory"); }
DEVI void fence_async_all() { asm volatile("fence.proxy.async;" ::: "memory"); }
DEVI void cluster_arrive() { asm volatile("barrier.cluster.arrive.relaxed.aligned;" ::: "memory"); }
DEVI void cluster_wait() { asm volatile("barrier.cluster.wait.aligned;" ::: "memory"); }

DEVI void tma_load_2d(uint32_t dst, const CUtensorMap* m, int c0, int c1, uint32_t bar) {
  asm volatile("cp.async.bulk.tensor.2d.shared::cluster.global.mbarrier::complete_tx::bytes [%0], [%1, {%3, %4}], [%2];"
               ::"r"(dst), "l"(m), "r"(bar), "r"(c0), "r"(c1) : "memory");
}
DEVI void tma_load_2d_mc(uint32_t dst, const CUtensorMap* m, int c0, int c1, uint32_t bar, uint16_t mask) {
  asm volatile("cp.async.bulk.tensor.2d.shared::cluster.global.mbarrier::complete_tx::bytes.multicast::cluster [%0], [%1, {%3, %4}], [%2], %5;"
               ::"r"(dst), "l"(m), "r"(bar), "r"(c0), "r"(c1), "h"(mask) : "memory");
}
DEVI void tma_store_2d(const CUtensorMap* m, uint32_t src, int c0, int c1) {
  asm volatile("cp.async.bulk.tensor.2d.global.shared::cta.bulk_group [%0, {%2, %3}], [%1];"
               ::"l"(m), "r"(src), "r"(c0), "r"(c1) : "memory");
}
DEVI void bulk_load(uint32_t dst, const void* src, uint32_t bytes, uint32_t bar) {
  asm volatile("cp.async.bulk.shared::cluster.global.mbarrier::complete_tx::bytes [%0], [%1], %2, [%3];"
               ::"r"(dst), "l"(src), "r"(bytes), "r"(bar) : "memory");
}
DEVI void bulk_store(void* dst, uint32_t src, uint32_t bytes) {
  asm volatile("cp.async.bulk.global.shared::cta.bulk_group [%0], [%1], %2;" ::"l"(dst), "r"(src), "r"(bytes) : "memory");
}
DEVI void bulk_commit() { asm volatile("cp.async.bulk.commit_group;" ::: "memory"); }
DEVI void bulk_wait0() { asm volatile("cp.async.bulk.wait_group 0;" ::: "memory"); }
DEVI void bulk_wait_read0() { asm volatile("cp.async.bulk.wait_group.read 0;" ::: "memory"); }
DEVI void l2_prefetch(const void* p, uint32_t bytes) {
  asm volatile("cp.async.bulk.prefetch.L2.global [%0], %1;" ::"l"(p), "r"(bytes) : "memory");
}
DEVI void prefetch_tmap(const CUtensorMap* m) { asm volatile("prefetch.tensormap [%0];" ::"l"(m) : "memory"); }

DEVI void red_release_add(unsigned* p, unsigned v) {
  asm volatile("red.release.gpu.global.add.u32 [%0], %1;" ::"l"(p), "r"(v) : "memory");
}
DEVI void red_relaxed_add(unsigned* p, unsigned v) {
  asm volatile("red.relaxed.gpu.global.add.u32 [%0], %1;" ::"l"(p), "r"(v) : "memory");
}
DEVI unsigned ld_relaxed(const unsigned* p) {
  unsigned v;
  asm volatile("ld.relaxed.gpu.global.u32 %0, [%1];" : "=r"(v) : "l"(p) : "memory");
  return v;
}
DEVI void wait_counter(const unsigned* p, unsigned target) {
#pragma unroll 1
  for (int it = 0; (int)(ld_relaxed(p) - target) < 0; ++it)
    if (it > (1 << 22)) __trap();
}

DEVI void ldsm_x4(uint32_t (&r)[4], uint32_t a) {
  asm volatile("ldmatrix.sync.aligned.m8n8.x4.shared.b16 {%0,%1,%2,%3}, [%4];"
               : "=r"(r[0]), "=r"(r[1]), "=r"(r[2]), "=r"(r[3]) : "r"(a) : "memory");
}
DEVI void ldsm_x4_t(uint32_t (&r)[4], uint32_t a) {
  asm volatile("ldmatrix.sync.aligned.m8n8.x4.trans.shared.b16 {%0,%1,%2,%3}, [%4];"
               : "=r"(r[0]), "=r"(r[1]), "=r"(r[2]), "=r"(r[3]) : "r"(a) : "memory");
}
DEVI void ldsm_x2_t(uint32_t& r0, uint32_t& r1, uint32_t a) {
  asm volatile("ldmatrix.sync.aligned.m8n8.x2.trans.shared.b16 {%0,%1}, [%2];" : "=r"(r0), "=r"(r1) : "r"(a) : "memory");
}
DEVI void stsm_x4(uint32_t a, uint32_t r0, uint32_t r1, uint32_t r2, uint32_t r3) {
  asm volatile("stmatrix.sync.aligned.m8n8.x4.shared.b16 [%0], {%1,%2,%3,%4};"
               ::"r"(a), "r"(r0), "r"(r1), "r"(r2), "r"(r3) : "memory");
}
DEVI void stsm_x4_t(uint32_t a, uint32_t r0, uint32_t r1, uint32_t r2, uint32_t r3) {
  asm volatile("stmatrix.sync.aligned.m8n8.x4.trans.shared.b16 [%0], {%1,%2,%3,%4};"
               ::"r"(a), "r"(r0), "r"(r1), "r"(r2), "r"(r3) : "memory");
}
DEVI uint32_t lds32(uint32_t a) { uint32_t v; asm volatile("ld.shared.b32 %0, [%1];" : "=r"(v) : "r"(a) : "memory"); return v; }
DEVI float lds_f32(uint32_t a) { float v; asm volatile("ld.shared.f32 %0, [%1];" : "=f"(v) : "r"(a) : "memory"); return v; }
DEVI void sts32(uint32_t a, uint32_t v) { asm volatile("st.shared.b32 [%0], %1;" ::"r"(a), "r"(v) : "memory"); }
DEVI void sts_f32(uint32_t a, float v) { asm volatile("st.shared.f32 [%0], %1;" ::"r"(a), "f"(v) : "memory"); }
DEVI void sts_f32x2(uint32_t a, float x, float y) { asm volatile("st.shared.v2.f32 [%0], {%1,%2};" ::"r"(a), "f"(x), "f"(y) : "memory"); }
DEVI uint4 lds128(uint32_t a) {
  uint4 v;
  asm volatile("ld.shared.v4.b32 {%0,%1,%2,%3}, [%4];" : "=r"(v.x), "=r"(v.y), "=r"(v.z), "=r"(v.w) : "r"(a) : "memory");
  return v;
}
DEVI void sts128(uint32_t a, uint32_t x, uint32_t y, uint32_t z, uint32_t w) {
  asm volatile("st.shared.v4.b32 [%0], {%1,%2,%3,%4};" ::"r"(a), "r"(x), "r"(y), "r"(z), "r"(w) : "memory");
}

DEVI void mma_bf16(float (&d)[4], uint32_t a0, uint32_t a1, uint32_t a2, uint32_t a3, uint32_t b0, uint32_t b1) {
  asm("mma.sync.aligned.m16n8k16.row.col.f32.bf16.bf16.f32 {%0,%1,%2,%3}, {%4,%5,%6,%7}, {%8,%9}, {%0,%1,%2,%3};"
      : "+f"(d[0]), "+f"(d[1]), "+f"(d[2]), "+f"(d[3])
      : "r"(a0), "r"(a1), "r"(a2), "r"(a3), "r"(b0), "r"(b1));
}
DEVI void mma_f16(float (&d)[4], const uint32_t (&a)[4], uint32_t b0, uint32_t b1) {
  asm("mma.sync.aligned.m16n8k16.row.col.f32.f16.f16.f32 {%0,%1,%2,%3}, {%4,%5,%6,%7}, {%8,%9}, {%0,%1,%2,%3};"
      : "+f"(d[0]), "+f"(d[1]), "+f"(d[2]), "+f"(d[3])
      : "r"(a[0]), "r"(a[1]), "r"(a[2]), "r"(a[3]), "r"(b0), "r"(b1));
}
DEVI void mma_bf16v(float (&d)[4], const uint32_t (&a)[4], uint32_t b0, uint32_t b1) {
  asm volatile("mma.sync.aligned.m16n8k16.row.col.f32.bf16.bf16.f32 {%0,%1,%2,%3}, {%4,%5,%6,%7}, {%8,%9}, {%0,%1,%2,%3};"
               : "+f"(d[0]), "+f"(d[1]), "+f"(d[2]), "+f"(d[3])
               : "r"(a[0]), "r"(a[1]), "r"(a[2]), "r"(a[3]), "r"(b0), "r"(b1));
}
DEVI uint32_t pack_bf16(float lo, float hi) {
  uint32_t r;
  asm("cvt.rn.bf16x2.f32 %0, %1, %2;" : "=r"(r) : "f"(hi), "f"(lo));
  return r;
}
DEVI uint32_t pack_f16(float lo, float hi) {
  uint32_t r;
  asm("cvt.rn.f16x2.f32 %0, %1, %2;" : "=r"(r) : "f"(hi), "f"(lo));
  return r;
}
DEVI float bf_lo(uint32_t v) { return __uint_as_float(v << 16); }
DEVI float bf_hi(uint32_t v) { return __uint_as_float(v & 0xffff0000u); }
DEVI float bf2f(__nv_bfloat16 v) { return __bfloat162float(v); }
DEVI float round_bf16(float v) { return __bfloat162float(__float2bfloat16_rn(v)); }
DEVI float rcp(float x) { float r; asm("rcp.approx.ftz.f32 %0, %1;" : "=f"(r) : "f"(x)); return r; }
DEVI float ex2(float x) { float r; asm("ex2.approx.ftz.f32 %0, %1;" : "=f"(r) : "f"(x)); return r; }

DEVI void wg_fence() { asm volatile("wgmma.fence.sync.aligned;" ::: "memory"); }
DEVI void wg_commit() { asm volatile("wgmma.commit_group.sync.aligned;" ::: "memory"); }
template <int N> DEVI void wg_wait() { asm volatile("wgmma.wait_group.sync.aligned %0;" ::"n"(N) : "memory"); }
constexpr uint32_t DESC_HI = (1u << 30) | (1024 >> 4);
DEVI uint32_t mkdesc(uint32_t saddr, uint32_t lbo) { return ((saddr & 0x3FFFF) >> 4) | ((lbo >> 4) << 16); }

#define R8(b) "%" #b
DEVI void wgmma_n192(float (&d)[96], uint32_t da, uint32_t db, int scale_d) {
  asm volatile(
      "{\n.reg .pred p;\n.reg .b64 da, db;\nsetp.ne.b32 p, %98, 0;\nmov.b64 da, {%96, %99};\nmov.b64 db, {%97, %99};\n"
      "wgmma.mma_async.sync.aligned.m64n192k16.f32.bf16.bf16 "
      "{%0,%1,%2,%3,%4,%5,%6,%7,%8,%9,%10,%11,%12,%13,%14,%15,"
      "%16,%17,%18,%19,%20,%21,%22,%23,%24,%25,%26,%27,%28,%29,%30,%31,"
      "%32,%33,%34,%35,%36,%37,%38,%39,%40,%41,%42,%43,%44,%45,%46,%47,"
      "%48,%49,%50,%51,%52,%53,%54,%55,%56,%57,%58,%59,%60,%61,%62,%63,"
      "%64,%65,%66,%67,%68,%69,%70,%71,%72,%73,%74,%75,%76,%77,%78,%79,"
      "%80,%81,%82,%83,%84,%85,%86,%87,%88,%89,%90,%91,%92,%93,%94,%95}, "
      "da, db, p, 1, 1, 0, 1;\n}"
      : "+f"(d[0]), "+f"(d[1]), "+f"(d[2]), "+f"(d[3]), "+f"(d[4]), "+f"(d[5]), "+f"(d[6]), "+f"(d[7]),
        "+f"(d[8]), "+f"(d[9]), "+f"(d[10]), "+f"(d[11]), "+f"(d[12]), "+f"(d[13]), "+f"(d[14]), "+f"(d[15]),
        "+f"(d[16]), "+f"(d[17]), "+f"(d[18]), "+f"(d[19]), "+f"(d[20]), "+f"(d[21]), "+f"(d[22]), "+f"(d[23]),
        "+f"(d[24]), "+f"(d[25]), "+f"(d[26]), "+f"(d[27]), "+f"(d[28]), "+f"(d[29]), "+f"(d[30]), "+f"(d[31]),
        "+f"(d[32]), "+f"(d[33]), "+f"(d[34]), "+f"(d[35]), "+f"(d[36]), "+f"(d[37]), "+f"(d[38]), "+f"(d[39]),
        "+f"(d[40]), "+f"(d[41]), "+f"(d[42]), "+f"(d[43]), "+f"(d[44]), "+f"(d[45]), "+f"(d[46]), "+f"(d[47]),
        "+f"(d[48]), "+f"(d[49]), "+f"(d[50]), "+f"(d[51]), "+f"(d[52]), "+f"(d[53]), "+f"(d[54]), "+f"(d[55]),
        "+f"(d[56]), "+f"(d[57]), "+f"(d[58]), "+f"(d[59]), "+f"(d[60]), "+f"(d[61]), "+f"(d[62]), "+f"(d[63]),
        "+f"(d[64]), "+f"(d[65]), "+f"(d[66]), "+f"(d[67]), "+f"(d[68]), "+f"(d[69]), "+f"(d[70]), "+f"(d[71]),
        "+f"(d[72]), "+f"(d[73]), "+f"(d[74]), "+f"(d[75]), "+f"(d[76]), "+f"(d[77]), "+f"(d[78]), "+f"(d[79]),
        "+f"(d[80]), "+f"(d[81]), "+f"(d[82]), "+f"(d[83]), "+f"(d[84]), "+f"(d[85]), "+f"(d[86]), "+f"(d[87]),
        "+f"(d[88]), "+f"(d[89]), "+f"(d[90]), "+f"(d[91]), "+f"(d[92]), "+f"(d[93]), "+f"(d[94]), "+f"(d[95])
      : "r"(da), "r"(db), "r"(scale_d), "n"(DESC_HI));
}
DEVI void wgmma_n64_rs(float (&d)[32], const uint4& a, uint32_t db, int scale_d) {
  asm volatile(
      "{\n.reg .pred p;\n.reg .b64 db;\nsetp.ne.b32 p, %37, 0;\nmov.b64 db, {%36, %38};\n"
      "wgmma.mma_async.sync.aligned.m64n64k16.f32.bf16.bf16 "
      "{%0,%1,%2,%3,%4,%5,%6,%7,%8,%9,%10,%11,%12,%13,%14,%15,"
      "%16,%17,%18,%19,%20,%21,%22,%23,%24,%25,%26,%27,%28,%29,%30,%31}, "
      "{%32,%33,%34,%35}, db, p, 1, 1, 1;\n}"
      : "+f"(d[0]), "+f"(d[1]), "+f"(d[2]), "+f"(d[3]), "+f"(d[4]), "+f"(d[5]), "+f"(d[6]), "+f"(d[7]),
        "+f"(d[8]), "+f"(d[9]), "+f"(d[10]), "+f"(d[11]), "+f"(d[12]), "+f"(d[13]), "+f"(d[14]), "+f"(d[15]),
        "+f"(d[16]), "+f"(d[17]), "+f"(d[18]), "+f"(d[19]), "+f"(d[20]), "+f"(d[21]), "+f"(d[22]), "+f"(d[23]),
        "+f"(d[24]), "+f"(d[25]), "+f"(d[26]), "+f"(d[27]), "+f"(d[28]), "+f"(d[29]), "+f"(d[30]), "+f"(d[31])
      : "r"(a.x), "r"(a.y), "r"(a.z), "r"(a.w), "r"(db), "r"(scale_d), "n"(DESC_HI));
}
template <int MODE>
DEVI void transpose_tile(uint32_t src, uint32_t dst, int lane) {
  const int m = lane >> 3, r = lane & 7;
#pragma unroll 2
  for (int it = 0; it < 32; ++it) {
    uint32_t v[4];
    if (MODE == 0) {
      const int tb = it >> 1, cb = (it & 1) * 4 + m;
      ldsm_x4_t(v, src + (tb * 8 + r) * 128 + ((cb ^ r) << 4));
      const int b = tb >> 3;
      stsm_x4(dst + b * 8192 + (cb * 8 + r) * 128 + (((tb & 7) ^ b ^ r) << 4), v[0], v[1], v[2], v[3]);
    } else {
      const int cb = it & 7, tb = (it >> 3) * 4 + m;
      ldsm_x4_t(v, src + (tb >> 3) * 8192 + (cb * 8 + r) * 128 + (((tb & 7) ^ r) << 4));
      stsm_x4(dst + (tb * 8 + r) * 128 + ((cb ^ r) << 4), v[0], v[1], v[2], v[3]);
    }
  }
}

struct C32 { float re, im; };
DEVI C32 csq(C32 a) { return {a.re * a.re - a.im * a.im, 2.f * a.re * a.im}; }
DEVI C32 cmul(C32 a, C32 b) { return {a.re * b.re - a.im * b.im, a.re * b.im + a.im * b.re}; }
DEVI C32 cfresh(float zl, float zi, float m) {
  float mag = ex2(zl * m), ph = zi * m;
  return {mag * __cosf(ph), mag * __sinf(ph)};
}
struct HMul { uint32_t b, bp; };
DEVI HMul mk_mul(float re, float im) { return {pack_f16(re, im), pack_f16(-im, re)}; }
DEVI uint32_t hcmul(uint32_t a, const HMul& m) {
  __half2 ah = *reinterpret_cast<__half2*>(&a);
  __half2 b = *reinterpret_cast<const __half2*>(&m.b), bp = *reinterpret_cast<const __half2*>(&m.bp);
  __half2 r = __hfma2(__high2half2(ah), bp, __hmul2(__low2half2(ah), b));
  return *reinterpret_cast<uint32_t*>(&r);
}
DEVI uint32_t badd(uint32_t a, uint32_t b) {
  __nv_bfloat162 r = __hadd2(*reinterpret_cast<__nv_bfloat162*>(&a), *reinterpret_cast<__nv_bfloat162*>(&b));
  return *reinterpret_cast<uint32_t*>(&r);
}
DEVI int kidx_l(int i) {
  const int r = i / 40, y = i - 40 * r;
  int lo;
  if (y < 16) lo = (y & 7) + ((y >> 3) << 7);
  else if (y < 24) lo = 256 + (((y - 16) >> 2) << 7) + ((y & 3) << 1);
  else if (y < 32) lo = 512 + (((y - 24) >> 1) << 7) + ((y & 1) << 2);
  else lo = 1024 + ((y - 32) << 7);
  return lo + 8 * r;
}

template <int MU0, int NMU, int DMAX>
DEVI void conv_tail(float (&acc)[16][4], uint32_t p_lane, uint32_t v_base, int back, bool edge, int lane) {
  const int hsel = (lane >> 3) & 1;
  const int row = (lane & 7) + ((lane >> 4) << 3) + PADV - 8 - (back & (hsel ^ 1));
  const uint32_t la = v_base + row * 32 + (((hsel ^ back) ^ ((row >> 2) & 1)) << 4);
  uint32_t M[3][4];
  ldsm_x4_t(M[0], la);
  ldsm_x4_t(M[1], la + 256);
  uint32_t H[2 * NMU];
#pragma unroll
  for (int i = 0; i < 2 * NMU; ++i) H[i ^ 1] = lds32(p_lane + (uint32_t)(MU0 - 1 + i) * 32);
  if (edge) {
    const uint32_t a[4] = {0u, 0u, M[0][0], M[0][1]};
#pragma unroll
    for (int k = 1; k < NMU; ++k) mma_bf16v(acc[MU0 - 2 + 2 * k], a, H[2 * k], H[2 * k + 1]);
  }
#pragma unroll
  for (int delta = -1; delta <= DMAX; ++delta) {
    if (delta + 2 <= DMAX) ldsm_x4_t(M[(delta + 3) % 3], la + (delta + 3) * 256);
#pragma unroll
    for (int k = 0; k < NMU; ++k)
      if (delta + MU0 + 2 * k < 16) mma_bf16v(acc[delta + MU0 + 2 * k], M[(delta + 1) % 3], H[2 * k], H[2 * k + 1]);
  }
}

__global__ void __cluster_dims__(2, 1, 1) __launch_bounds__(NTHREADS, 1)
fused_kernel(const __grid_constant__ Maps maps, const Ptrs p) {
  extern __shared__ __align__(1024) uint8_t smem[];
  const uint32_t sb = s2u(smem);
  const int tid = threadIdx.x, lane = tid & 31;
  const int warp = __shfl_sync(0xffffffffu, tid >> 5, 0);
  const int cta = blockIdx.x;
  const uint32_t rank = cta & 1;
  const int ti = 2 * (cta >> 4) + rank;
  const int tj = (cta >> 1) & 7;
  const uint32_t bars = sb + SM_BAR;
#define BAR(i) (bars + 8 * (i))

  const int kch = warp & 3, krd = warp >> 2;
  float zr, zi, wr, wi;
  {
    const size_t po = (size_t)(cta * 4 + kch) * 128 + krd * 32 + lane;
    const float ar = bf2f(p.A_re[po]), ai = bf2f(p.A_im[po]), br = bf2f(p.B_re[po]), bi = bf2f(p.B_im[po]);
    const float cr = bf2f(p.C_re[po]), ci = bf2f(p.C_im[po]);
    const float ldt = bf2f(p.log_dt[cta * 4 + kch]);
    uint4 pt;
    if (tid < 240) pt = __ldg((const uint4*)g_ptab.v + tid);
    if (tid == 384) {
      TS(0);
#pragma unroll
      for (int i = 0; i < B_COUNT; ++i)
        mbar_init(BAR(i), i < 3 ? 1 : i < 6 ? 16 : i < B_TRDONE ? 1 : i == B_TRDONE ? 1 : 8);
      asm volatile("fence.mbarrier_init.release.cluster;" ::: "memory");
      prefetch_tmap(&maps.x); prefetch_tmap(&maps.w); prefetch_tmap(&maps.u);
    }
    __syncthreads();
    cluster_arrive();
    if (warp == 13 && lane == 0) {
      mbar_expect_tx(BAR(B_UTILE), 16384);
      tma_load_2d(sb + SM_TIN1, &maps.u, tj * 64, ti * 128, BAR(B_UTILE));
    }
    if (warp == 12) {
      cluster_wait();
      if (lane == 0) {
        TS(61);
#pragma unroll 1
        for (int ks = 0; ks < 3; ++ks) {
          const uint32_t st = sb + ks * STG_BYTES, fb = BAR(B_FULL + ks);
          mbar_expect_tx(fb, STG_BYTES);
          tma_load_2d(st + STG_X, &maps.x, ks * 64, ti * 128, fb);
#pragma unroll 1
          for (int nb = 0; nb < 3; ++nb)
            tma_load_2d_mc(st + STG_W + nb * 8192 + rank * 4096, &maps.w, nb * 512 + tj * 64, ks * 64 + rank * 32, fb, 3);
        }
        l2_prefetch((const char*)p.wqkv + 192 * 3072 + cta * 7680, 7680);
        l2_prefetch((const char*)p.x + (size_t)cta * 16384, 16384);
        l2_prefetch((const char*)p.wo + (size_t)cta * 4096, 4096);
        prefetch_tmap(&maps.wo); prefetch_tmap(&maps.uT); prefetch_tmap(&maps.yT); prefetch_tmap(&maps.out);
      }
      __syncwarp();
    }
    if (tid < 240) sts128(sb + SM_PTAB + tid * 16, pt.x, pt.y, pt.z, pt.w);
    const float dt = round_bf16(expf(ldt));
    zr = dt * ar; zi = dt * ai;
    const float dbr = dt * br, dbi = dt * bi;
    wr = cr * dbr - ci * dbi; wi = cr * dbi + ci * dbr;
  }
  if (tid == 0) TS(1);
  {
    float mz = fmaxf(zr, 0.f), mw = fmaxf(fabsf(wr), fabsf(wi));
#pragma unroll 1
    for (int o = 16; o > 0; o >>= 1) {
      mz = fmaxf(mz, __shfl_xor_sync(0xffffffffu, mz, o));
      mw = fmaxf(mw, __shfl_xor_sync(0xffffffffu, mw, o));
    }
    const int E = min(max((__float_as_int(mw) >> 23) & 255, 1), 252);
    const float sc = __int_as_float((253 - E) << 23), inv = __int_as_float((E + 1) << 23);
    const float zl = (zr - mz) * 1.4426950408889634f, w_r = wr * sc, w_i = wi * sc;
    const uint32_t tb = sb + SM_VV + kch * VV_BYTES + krd * KG_BYTES;
    const uint32_t sta = tb + (((lane >> 2) << 4) | ((lane & 3) << 2));
    auto put = [&](int r, uint32_t v) { sts32((sta ^ ((r & 7) << 4)) + r * 128, v); };
    const uint32_t lda = tb + ((lane & 7) + (((lane >> 3) & 1) << 3)) * 128;
    const uint32_t ldb = tb + ((lane & 7) + ((lane >> 4) << 3)) * 128;
    C32 e1 = cfresh(zl, zi, 1.f), e2 = csq(e1), e4 = csq(e2), e8 = csq(e4);
    C32 e16 = cfresh(zl, zi, 16.f), e32 = csq(e16), e64 = csq(e32), e128 = csq(e64);
    C32 e256 = cfresh(zl, zi, 256.f), e512 = csq(e256), e1024 = csq(e512), e2048 = csq(e1024);
    float k2048 = w_r * e2048.re - w_i * e2048.im;
    uint32_t XA[4][4];
    {
      const HMul m16 = mk_mul(e16.re, e16.im), m32 = mk_mul(e32.re, e32.im), m64 = mk_mul(e64.re, e64.im);
      uint32_t X[8];
      X[0] = 0x00003c00u; X[1] = pack_f16(e8.re, e8.im); X[2] = m16.b; X[4] = m32.b;
      X[3] = hcmul(X[1], m16); X[5] = hcmul(X[1], m32); X[6] = hcmul(X[2], m32); X[7] = hcmul(X[3], m32);
      put(8, m64.b);
#pragma unroll
      for (int r = 0; r < 8; ++r) { put(r, X[r]); if (r) put(8 + r, hcmul(X[r], m64)); }
      __syncwarp();
#pragma unroll
      for (int k = 0; k < 4; ++k) ldsm_x4(XA[k], lda + (((2 * k + (lane >> 4)) ^ (lane & 7)) << 4));
      __syncwarp();
    }
    float D[5][4];
#pragma unroll
    for (int t = 0; t < 5; ++t) D[t][0] = D[t][1] = D[t][2] = D[t][3] = 0.f;
    auto contract = [&](int t0, int nt) {
      __syncwarp();
#pragma unroll
      for (int k = 0; k < 4; ++k) {
        uint32_t b[4];
        ldsm_x4(b, ldb + (((2 * k + ((lane >> 3) & 1)) ^ (lane & 7)) << 4));
        mma_f16(D[t0], XA[k], b[0], b[1]);
        if (nt == 2) mma_f16(D[t0 + 1], XA[k], b[2], b[3]);
      }
      __syncwarp();
    };
    const HMul c1 = mk_mul(e1.re, -e1.im), c2 = mk_mul(e2.re, -e2.im), c4 = mk_mul(e4.re, -e4.im);
    uint32_t W[8];
    W[0] = pack_f16(w_r, -w_i);
    W[1] = hcmul(W[0], c1); W[2] = hcmul(W[0], c2); W[3] = hcmul(W[1], c2);
    W[4] = hcmul(W[0], c4); W[5] = hcmul(W[1], c4); W[6] = hcmul(W[2], c4); W[7] = hcmul(W[3], c4);
    const HMul c128 = mk_mul(e128.re, -e128.im), c256 = mk_mul(e256.re, -e256.im);
#pragma unroll
    for (int i = 0; i < 8; ++i) { put(i, W[i]); put(8 + i, hcmul(W[i], c128)); }
    contract(0, 2);
    const C32 e384 = cmul(e256, e128), e640 = cmul(e512, e128), e768 = cmul(e512, e256), e896 = cmul(e768, e128);
    const HMul c384 = mk_mul(e384.re, -e384.im), c512 = mk_mul(e512.re, -e512.im), c640 = mk_mul(e640.re, -e640.im);
    const HMul c768 = mk_mul(e768.re, -e768.im), c896 = mk_mul(e896.re, -e896.im), c1024 = mk_mul(e1024.re, -e1024.im);
#pragma unroll
    for (int i = 0; i < 4; ++i) { put(i, hcmul(W[2 * i], c256)); put(4 + i, hcmul(W[2 * i], c384)); }
    put(8, hcmul(W[0], c512)); put(9, hcmul(W[4], c512)); put(10, hcmul(W[0], c640)); put(11, hcmul(W[4], c640));
    put(12, hcmul(W[0], c768)); put(13, hcmul(W[4], c768)); put(14, hcmul(W[0], c896)); put(15, hcmul(W[4], c896));
    contract(2, 2);
    const uint32_t v0 = hcmul(W[0], c1024);
    put(0, v0); put(1, hcmul(v0, c128)); put(2, hcmul(v0, c256)); put(3, hcmul(v0, c384));
    put(4, hcmul(v0, c512)); put(5, hcmul(v0, c640)); put(6, hcmul(v0, c768)); put(7, hcmul(v0, c896));
    contract(4, 1);
    {
      const int g = lane >> 2, q = lane & 3;
#pragma unroll 1
      for (int o = 16; o > 0; o >>= 1) k2048 += __shfl_xor_sync(0xffffffffu, k2048, o);
      const uint32_t a = tb + (g * 40 + 2 * q) * 4;
#pragma unroll
      for (int t = 0; t < 5; ++t) {
        sts_f32x2(a + t * 32, D[t][0] * inv, D[t][1] * inv);
        sts_f32x2(a + t * 32 + 1280, D[t][2] * inv, D[t][3] * inv);
      }
      if (lane == 0) sts_f32(tb + SL_K2048 * 4, k2048 * inv);
      if (mz > 0.f) {
        const float zt = mz * 1.4426950408889634f;
        __syncwarp();
#pragma unroll 1
        for (int i = lane; i < 641; i += 32)
          sts_f32(tb + i * 4, lds_f32(tb + i * 4) * ex2(zt * (i < 640 ? kidx_l(i) : 2048)));
      }
    }
  }
  if (tid == 0) TS(2);
  if (warp != 12) cluster_wait();
  __syncthreads();
  if (tid == 0) TS(32);

  if (warp < 4) {
    asm volatile("setmaxnreg.inc.sync.aligned.u32 152;");
    const unsigned epoch = __ldcg(&g_epoch);
    const int ch = warp;
    const int d = cta * 4 + ch;
    const uint32_t vv = sb + SM_VV + ch * VV_BYTES;
    const uint32_t ub = sb + SM_U + ch * U_BYTES;
    const uint32_t pb = sb + SM_P + ch * P_BYTES;
    const uint32_t kf = vv;
    const int g = lane >> 2, q = lane & 3;
    const float dskip = bf2f(p.Dskip[d]);
#pragma unroll 1
    for (int i0 = 0; i0 < 21; i0 += 3) {
      float a[3][4];
#pragma unroll
      for (int i = 0; i < 3; ++i)
#pragma unroll
        for (int r = 0; r < 4; ++r) a[i][r] = lds_f32(kf + r * KG_BYTES + ((i0 + i) * 32 + lane) * 4);
#pragma unroll
      for (int i = 0; i < 3; ++i) sts_f32(kf + ((i0 + i) * 32 + lane) * 4, (a[i][0] + a[i][1]) + (a[i][2] + a[i][3]));
    }
    __syncwarp();
    const float k1024 = lds_f32(kf + kidx_c(1024) * 4);
    if (lane == 0) {
      sts_f32(kf + SL_ZERO * 4, 0.f);
      sts_f32(kf + SL_510 * 4, lds_f32(kf + kidx_c(510) * 4) - lds_f32(kf + kidx_c(512) * 4));
      sts_f32(kf + SL_0 * 4, lds_f32(kf) + dskip);
    }
    __syncwarp();
    mbar_wait(BAR(B_TRDONE), 0);
    if (lane == 0) TS(50);
    if (lane < 16) sts128(ub + lane * 16, 0, 0, 0, 0);
#pragma unroll 1
    for (int i0 = 0; i0 < 30; i0 += 6) {
      uint32_t e[6];
      float a[6], b[6];
#pragma unroll
      for (int i = 0; i < 6; ++i) e[i] = lds32(sb + SM_PTAB + ((i0 + i) * 32 + lane) * 4);
#pragma unroll
      for (int i = 0; i < 6; ++i) { a[i] = lds_f32(kf + (e[i] & 0xffff)); b[i] = lds_f32(kf + (e[i] >> 16)); }
#pragma unroll
      for (int i = 0; i < 6; ++i) sts32(pb + ((i0 + i) * 32 + lane) * 4, pack_bf16(a[i], b[i]));
    }
    if (lane == 0) {
      TS(4);
      wait_counter(&g_cnt[(C_U + (cta >> 4)) * 32], (epoch + 1) * 16);
      mbar_expect_tx(BAR(B_UCH + ch), 4096);
      bulk_load(ub + 256, p.uT + (size_t)d * 2048, 4096, BAR(B_UCH + ch));
      TS(3);
    }
    __syncwarp();
    mbar_wait(BAR(B_UCH + ch), 0);
    if (lane == 0) TS(5);
#pragma unroll 1
    for (int it = 0; it < 8; ++it) {
      const int k = -18 + it * 32 + lane;
      const int kr = min(max(k, -2), 208);
      uint32_t E[12];
#pragma unroll
      for (int c = 0; c < 3; ++c) {
        const int kk = kr - 1 + c, r = (kk >> 1) + 8;
        const uint4 t = lds128(ub + r * 32 + (((kk & 1) ^ ((r >> 2) & 1)) << 4));
        E[4 * c] = t.x; E[4 * c + 1] = t.y; E[4 * c + 2] = t.z; E[4 * c + 3] = t.w;
      }
      uint32_t O[8];
#pragma unroll
      for (int j = 0; j < 8; ++j) O[j] = __byte_perm(E[j + 1], E[j + 2], 0x5432);
      uint32_t s3[6], s5[4], s7[4], s9[4];
#pragma unroll
      for (int j = 0; j < 6; ++j) s3[j] = badd(badd(O[j], O[j + 1]), E[j + 2]);
#pragma unroll
      for (int j = 0; j < 4; ++j) {
        s5[j] = badd(s3[j + 2], badd(E[j + 3], E[j + 5]));
        s7[j] = badd(s5[j], badd(O[j + 1], O[j + 4]));
        s9[j] = badd(s7[j], badd(E[j + 2], E[j + 6]));
      }
      const int r = (k >> 1) + PADV;
      const uint32_t a = vv + r * 32 + (((k & 1) ^ ((r >> 2) & 1)) << 4);
      if (k < 208) { sts128(a + VV_U3, s3[0], s3[1], s3[2], s3[3]); sts128(a + VV_U5, s5[0], s5[1], s5[2], s5[3]); }
      if (k < 144) { sts128(a + VV_U7, s7[0], s7[1], s7[2], s7[3]); sts128(a + VV_U9, s9[0], s9[1], s9[2], s9[3]); }
    }
    __syncwarp();
    if (lane == 0) TS(6);
    const int gq = g - 2 * q;
    uint32_t h127, h128;
    {
      const uint32_t kf2 = pack_bf16(k1024, k1024) ^ 0x80008000u;
      h127 = (gq == 4 ? 0x0000ffffu : gq == 5 ? 0xffffffffu : gq == 6 ? 0xffff0000u : 0u) & kf2;
      h128 = (gq == -4 ? 0x0000ffffu : gq == -3 ? 0xffffffffu : gq == -2 ? 0xffff0000u : 0u) & kf2;
    }
    bar_sync(4, 384);
    if (lane == 0) TS(7);
    float acc[16][4];
#pragma unroll
    for (int i = 0; i < 16; ++i) { acc[i][0] = acc[i][1] = acc[i][2] = acc[i][3] = 0.f; }
    {
      const uint32_t pd_lane = pb + (PD_OFF + 16 + gq) * 4;
      const int prow0 = 8 + (lane & 7) + ((lane >> 4) << 3), hs = (lane >> 3) & 1;
      uint32_t B[2][4][4];
      uint32_t A[4][4];
      const uint32_t la0 = ub + prow0 * 32 + ((hs ^ ((prow0 >> 2) & 1)) << 4);
#pragma unroll
      for (int m2 = 0; m2 < 4; ++m2) ldsm_x4(B[0][m2], la0 + m2 * 512);
#pragma unroll
      for (int i = 0; i < 4; ++i) {
        const uint32_t a = pd_lane + i * 512;
        A[i][0] = lds32(a); A[i][1] = lds32(a + 32); A[i][2] = lds32(a - 32); A[i][3] = A[i][0];
      }
      uint32_t la = la0;
#pragma unroll 1
      for (int rho = 0; rho < 8; ++rho) {
#pragma unroll
        for (int m2 = 0; m2 < 4; ++m2) ldsm_x4(B[1][m2], la + (4 + m2) * 512);
#pragma unroll
        for (int i = 0; i < 4; ++i)
#pragma unroll
          for (int m = 0; m < 8; ++m) mma_bf16v(acc[m + i], A[i], B[0][m >> 1][2 * (m & 1)], B[0][m >> 1][2 * (m & 1) + 1]);
        const int prow = prow0 - min(rho + 1, 7);
        la = ub + prow * 32 + ((hs ^ ((prow >> 2) & 1)) << 4);
#pragma unroll
        for (int m2 = 0; m2 < 4; ++m2) ldsm_x4(B[0][m2], la + m2 * 512);
        const uint32_t pa = pd_lane + (rho + 1) * 64;
#pragma unroll
        for (int i = 0; i < 4; ++i) {
#pragma unroll
          for (int m = 0; m < 8 - i; ++m)
            mma_bf16v(acc[8 + m + i], A[i], B[1][m >> 1][2 * (m & 1)], B[1][m >> 1][2 * (m & 1) + 1]);
          A[i][0] = lds32(pa + i * 512); A[i][1] = lds32(pa + i * 512 + 32); A[i][2] = lds32(pa + i * 512 - 32);
          A[i][3] = A[i][0];
        }
      }
      {
        uint32_t b8[4];
        ldsm_x4(b8, la + 4 * 512);
        const uint32_t h63 = lds32(pd_lane + 63 * 32), h64 = lds32(pd_lane + 64 * 32);
        const uint32_t a63[4] = {0u, h127, 0u, 0u}, a32[4] = {h64, 0u, h63, h64}, a64[4] = {h128, 0u, h127, h128};
#pragma unroll
        for (int m2 = 0; m2 < 4; ++m2) ldsm_x4(B[1][m2], la0 + m2 * 512);
#pragma unroll
        for (int m = 0; m < 8; ++m) mma_bf16v(acc[m + 7], a63, B[0][m >> 1][2 * (m & 1)], B[0][m >> 1][2 * (m & 1) + 1]);
#pragma unroll
        for (int m2 = 0; m2 < 2; ++m2) ldsm_x4(B[0][m2], la0 + (4 + m2) * 512);
#pragma unroll
        for (int m = 0; m < 8; ++m) mma_bf16v(acc[m + 4], a32, B[1][m >> 1][2 * (m & 1)], B[1][m >> 1][2 * (m & 1) + 1]);
        mma_bf16v(acc[15], a63, b8[0], b8[1]);
#pragma unroll
        for (int m = 0; m < 8; ++m) mma_bf16v(acc[m + 8], a64, B[1][m >> 1][2 * (m & 1)], B[1][m >> 1][2 * (m & 1) + 1]);
#pragma unroll
        for (int m = 0; m < 4; ++m) mma_bf16v(acc[m + 12], a32, B[0][m >> 1][2 * (m & 1)], B[0][m >> 1][2 * (m & 1) + 1]);
      }
#pragma unroll 1
      for (int v = 0; v < 4; ++v)
        conv_tail<4, 3, 11>(acc, pb + (P2_OFF + 56 * v + gq - 16) * 4, vv + ((v & 1) ? VV_U3 : VV_U5), v >> 1, v == 0, lane);
#pragma unroll 1
      for (int pi = 0; pi < 2; ++pi)
        conv_tail<8, 5, 7>(acc, pb + (P3_OFF + 88 * pi + gq - 48) * 4, vv + (pi ? VV_U7 : VV_U9), pi, pi == 0, lane);
    }
    bar_arrive(3, 384);
    if (lane == 0) TS(8);
    {
      const int mt = lane >> 3;
      const uint32_t a = vv + (128 * (mt >> 1) + 16 * (lane & 7) + 8 * (mt & 1)) * 2;
#pragma unroll
      for (int ab = 0; ab < 16; ab += 2)
        stsm_x4_t(a + ab * 256, pack_bf16(acc[ab][0], acc[ab][1]), pack_bf16(acc[ab][2], acc[ab][3]),
                  pack_bf16(acc[ab + 1][0], acc[ab + 1][1]), pack_bf16(acc[ab + 1][2], acc[ab + 1][3]));
    }
    fence_async_smem();
    __syncwarp();
    if (lane == 0) {
      bulk_store(p.yT + (size_t)d * 2048, vv, 4096);
      bulk_commit();
      bulk_wait0();
      red_relaxed_add(&g_cnt[(C_Y + (cta >> 4)) * 32], 1);
      TS(9);
    }
  } else if (warp < 12) {
    asm volatile("setmaxnreg.inc.sync.aligned.u32 160;");
    const unsigned epoch = __ldcg(&g_epoch);
    const int w8 = warp - 4;
    const int g = lane >> 2, q = lane & 3;
    {
      float acc[96];
#pragma unroll 1
      for (int ks = 0, s = 0, ph = 0; ks < 8; ++ks) {
        mbar_wait(BAR(B_FULL + s), ph);
        if (tid == 128) TS(ks == 0 ? 16 : 9 + ks + (ks > 6 ? 46 : 0));
        const uint32_t st = sb + s * STG_BYTES;
        const uint32_t da = mkdesc(st + STG_X + (w8 >> 2) * 8192, 16);
        const uint32_t db = mkdesc(st + STG_W, 8192);
        wg_fence();
#pragma unroll
        for (int k = 0; k < 4; ++k) wgmma_n192(acc, da + 2 * k, db + 128 * k, (ks | k) != 0);
        wg_commit();
        const uint32_t eprev = BAR(B_EMPTY + (s == 0 ? 2 : s - 1));
        if (++s == 3) { s = 0; ph ^= 1; }
        if (ks > 0) {
          wg_wait<1>();
          if (lane < 2) mbar_arrive_cluster(eprev, lane);
        }
      }
      wg_wait<0>();
      if (lane < 2) mbar_arrive_cluster(BAR(B_EMPTY + 1), lane);
      bar_arrive(4, 384);
      if (tid == 128) TS(17);
      bar_sync(1, 256);
      const int row = w8 * 16 + (lane & 7) + (((lane >> 3) & 1) << 3);
      const uint32_t ra = sb + SM_QS + row * 128;
#pragma unroll
      for (int i = 0; i < 24; i += 2)
        stsm_x4(ra + (i >> 3) * 16384 + ((((i & 7) + (lane >> 4)) ^ (row & 7)) << 4), pack_bf16(acc[4 * i], acc[4 * i + 1]),
                pack_bf16(acc[4 * i + 2], acc[4 * i + 3]), pack_bf16(acc[4 * i + 4], acc[4 * i + 5]),
                pack_bf16(acc[4 * i + 6], acc[4 * i + 7]));
    }
    __syncwarp();
    const unsigned par = epoch & 1;
    const int hh = w8 >> 1, dtile = w8 & 1;
    float* kvg = &g_kv[par][tj][hh][0];
#pragma unroll 1
    for (int part = 1; part >= 0; --part) {
      const uint32_t pa = sb + SM_QS + part * 16384 + w8 * 2048 + lane * 16;
#pragma unroll 1
      for (int it = 0; it < 4; ++it) {
        uint4 t = lds128(pa + it * 512);
        uint32_t* tw = &t.x;
#pragma unroll
        for (int j = 0; j < 4; ++j) {
          const uint32_t x = tw[j];
          const __nv_bfloat162 xb = *reinterpret_cast<const __nv_bfloat162*>(&x);
          const uint32_t e = pack_bf16(ex2(bf_lo(x) * 1.4426950408889634f), ex2(bf_hi(x) * 1.4426950408889634f));
          const uint32_t m = __hgt2_mask(xb, __floats2bfloat162_rn(0.f, 0.f));
          const uint32_t sel = (badd(x, 0x3f803f80u) & m) | (e & ~m);
          tw[j] = pack_bf16(bf_lo(sel) + 1e-6f, bf_hi(sel) + 1e-6f);
        }
        sts128(pa + it * 512, t.x, t.y, t.z, t.w);
      }
      if (part == 1) {
        if (tid == 128) TS(53);
        bar_sync(1, 256);
        float kv[4] = {0.f, 0.f, 0.f, 0.f}, zz[4] = {0.f, 0.f, 0.f, 0.f};
        const int m = lane >> 3;
        const uint32_t aa = sb + SM_VS + ((lane & 7) + ((m >> 1) << 3)) * 128 + (((2 * hh + (m & 1)) ^ (lane & 7)) << 4);
        const uint32_t ab = sb + SM_PK + (lane & 15) * 128 + (((2 * hh + dtile) ^ (lane & 7)) << 4);
#pragma unroll 2
        for (int ks = 0; ks < 8; ++ks) {
          uint32_t a[4], b0, b1;
          ldsm_x4_t(a, aa + ks * 2048);
          ldsm_x2_t(b0, b1, ab + ks * 2048);
          mma_bf16(kv, a[0], a[1], a[2], a[3], b0, b1);
          mma_bf16(zz, 0x3f803f80u, 0x3f803f80u, 0x3f803f80u, 0x3f803f80u, b0, b1);
        }
        asm volatile("red.global.add.v4.f32 [%0], {%1,%2,%3,%4};" ::"l"(kvg + dtile * 128 + lane * 4), "f"(kv[0]), "f"(kv[1]),
                     "f"(kv[2]), "f"(kv[3]) : "memory");
        if (g == 0)
          asm volatile("red.global.add.v2.f32 [%0], {%1,%2};" ::"l"(kvg + 256 + dtile * 8 + 2 * q), "f"(zz[0]), "f"(zz[1]) : "memory");
        if (tid == 128) TS(55);
        bar_sync(1, 256);
        if (lane == 0) mbar_arrive(BAR(B_PKVFREE));
        if (tid == 128) { red_release_add(&g_cnt[(C_KV + tj) * 32], 1); TS(18); }
        if (ti == 0) {
          float4* z = (float4*)&g_kv[par ^ 1][tj][0][0];
          for (int i = tid - 128; i < 272; i += 256) z[i] = make_float4(0.f, 0.f, 0.f, 0.f);
        }
      }
    }
    if (tid == 128) { TS(56); wait_counter(&g_cnt[(C_KV + tj) * 32], (epoch + 1) * 16); TS(19); }
    bar_sync(1, 256);
    {
      const float4 k4 = __ldcg((const float4*)(kvg + dtile * 128 + lane * 4));
      const float2 z2 = __ldcg((const float2*)(kvg + 256 + dtile * 8 + 2 * q));
      const uint32_t a = sb + SM_KVB + hh * 512 + lane * 16 + dtile * 4;
      sts32(a, pack_bf16(k4.x, k4.y));
      sts32(a + 8, pack_bf16(k4.z, k4.w));
      if (g == 0) sts32(sb + SM_KVB + 2048 + hh * 32 + q * 8 + dtile * 4, pack_bf16(z2.x, z2.y));
    }
    bar_sync(1, 256);
    {
      const int row = w8 * 16 + (lane & 7) + (((lane >> 3) & 1) << 3);
      uint4* dst = &g_ofrag[((ti * 8 + w8) * 32 + 4 * tj) * 32 + lane];
#pragma unroll 1
      for (int h = 0; h < 4; ++h) {
        uint32_t a[4];
        ldsm_x4(a, sb + SM_QS + row * 128 + (((2 * h + (lane >> 4)) ^ (row & 7)) << 4));
        const uint4 kb = lds128(sb + SM_KVB + h * 512 + lane * 16);
        const uint32_t zb0 = lds32(sb + SM_KVB + 2048 + h * 32 + q * 8), zb1 = lds32(sb + SM_KVB + 2048 + h * 32 + q * 8 + 4);
        float n0[4] = {0.f, 0.f, 0.f, 0.f}, n1[4] = {0.f, 0.f, 0.f, 0.f}, dn[4] = {0.f, 0.f, 0.f, 0.f};
        mma_bf16(n0, a[0], a[1], a[2], a[3], kb.x, kb.y);
        mma_bf16(n1, a[0], a[1], a[2], a[3], kb.z, kb.w);
        mma_bf16(dn, a[0], a[1], a[2], a[3], zb0, zb1);
        const uint32_t dd = pack_bf16(dn[0], dn[2]);
        const uint32_t d2 = pack_bf16(bf_lo(dd) + 1e-6f, bf_hi(dd) + 1e-6f);
        const float r0 = rcp(bf_lo(d2)), r1 = rcp(bf_hi(d2));
        const uint32_t x0 = pack_bf16(n0[0], n0[1]), x1 = pack_bf16(n0[2], n0[3]);
        const uint32_t x2 = pack_bf16(n1[0], n1[1]), x3 = pack_bf16(n1[2], n1[3]);
        dst[h * 32] = make_uint4(pack_bf16(bf_lo(x0) * r0, bf_hi(x0) * r0), pack_bf16(bf_lo(x1) * r1, bf_hi(x1) * r1),
                                 pack_bf16(bf_lo(x2) * r0, bf_hi(x2) * r0), pack_bf16(bf_lo(x3) * r1, bf_hi(x3) * r1));
      }
    }
    if (tid == 128) TS(57);
    bar_sync(1, 256);
    if (tid == 128) {
      red_release_add(&g_cnt[(C_O + ti) * 32], 1);
      TS(20);
      wait_counter(&g_cnt[(C_O + ti) * 32], (epoch + 1) * 8);
      if (cta == 0) g_epoch = epoch + 1;
      TS(21);
    }
    bar_sync(1, 256);
    {
      const uint4* src = &g_ofrag[((ti * 8 + w8) * 32) * 32 + lane];
      uint4 A0[8], A1[8];
#pragma unroll
      for (int h = 0; h < 8; ++h) A0[h] = __ldcg(src + h * 32);
#pragma unroll
      for (int h = 0; h < 8; ++h) A1[h] = __ldcg(src + (8 + h) * 32);
      mbar_wait(BAR(B_WO), 0);
      bar_sync(3, 384);
      if (tid == 128) TS(22);
      float o[32];
      const uint32_t db = mkdesc(sb + SM_WO, 8192);
#pragma unroll 1
      for (int it = 0; it < 2; ++it) {
        wg_fence();
#pragma unroll
        for (int h = 0; h < 8; ++h) wgmma_n64_rs(o, A0[h], db + (16 * it + h) * 128, (it | h) != 0);
        wg_commit();
        wg_wait<0>();
        if (it == 0) {
#pragma unroll
          for (int h = 0; h < 8; ++h) A0[h] = __ldcg(src + (16 + h) * 32);
        }
        wg_fence();
#pragma unroll
        for (int h = 0; h < 8; ++h) wgmma_n64_rs(o, A1[h], db + (16 * it + 8 + h) * 128, 1);
        wg_commit();
        wg_wait<0>();
        if (it == 0) {
#pragma unroll
          for (int h = 0; h < 8; ++h) A1[h] = __ldcg(src + (24 + h) * 32);
        }
      }
      const int row = w8 * 16 + (lane & 7) + (((lane >> 3) & 1) << 3);
#pragma unroll
      for (int i = 0; i < 8; i += 2)
        stsm_x4(sb + SM_BOUT + row * 128 + (((i + (lane >> 4)) ^ (row & 7)) << 4), pack_bf16(o[4 * i], o[4 * i + 1]),
                pack_bf16(o[4 * i + 2], o[4 * i + 3]), pack_bf16(o[4 * i + 4], o[4 * i + 5]), pack_bf16(o[4 * i + 6], o[4 * i + 7]));
      fence_async_smem();
      bar_sync(1, 256);
      if (tid == 128) {
        tma_store_2d(&maps.out, sb + SM_BOUT, 512 + 64 * tj, 128 * ti);
        bulk_commit();
        bulk_wait_read0();
        TS(23);
      }
    }
  } else {
    asm volatile("setmaxnreg.dec.sync.aligned.u32 40;");
    if (tid == 384) TS(49);
    if (warp == 12) {
      if (lane == 0) {
#pragma unroll 1
        for (int ks = 3, s = 0, ph = 0; ks < 8; ++ks) {
          mbar_wait(BAR(B_EMPTY + s), ph);
          const uint32_t st = sb + s * STG_BYTES, fb = BAR(B_FULL + s);
          mbar_expect_tx(fb, STG_BYTES);
          tma_load_2d(st + STG_X, &maps.x, ks * 64, ti * 128, fb);
#pragma unroll 1
          for (int nb = 0; nb < 3; ++nb)
            tma_load_2d_mc(st + STG_W + nb * 8192 + rank * 4096, &maps.w, nb * 512 + tj * 64, ks * 64 + rank * 32, fb, 3);
          if (++s == 3) { s = 0; ph ^= 1; }
        }
        TS(24);
        mbar_wait(BAR(B_EMPTY + 0), 0);
        mbar_wait(BAR(B_EMPTY + 1), 0);
        mbar_expect_tx(BAR(B_WO), 65536);
        tma_load_2d_mc(sb + SM_WO + rank * 32768, &maps.wo, tj * 64, rank * 256, BAR(B_WO), 3);
      }
    } else if (warp == 13) {
      const unsigned epoch = __ldcg(&g_epoch);
      mbar_wait(BAR(B_UTILE), 0);
      if (lane == 0) TS(26);
      transpose_tile<0>(sb + SM_TIN1, sb + SM_TOUT1, lane);
      if (lane == 0) TS(58);
      fence_async_smem();
      __syncwarp();
      if (lane == 0) {
        tma_store_2d(&maps.uT, sb + SM_TOUT1, ti * 128, tj * 64);
        tma_store_2d(&maps.uT, sb + SM_TOUT1 + 8192, ti * 128 + 64, tj * 64);
        bulk_commit();
        bulk_wait0();
        TS(59);
        red_relaxed_add(&g_cnt[(C_U + tj) * 32], 1);
        mbar_arrive(BAR(B_TRDONE));
        TS(27);
        mbar_wait(BAR(B_PKVFREE), 0);
        wait_counter(&g_cnt[(C_Y + tj) * 32], (epoch + 1) * 64);
        TS(28);
        mbar_expect_tx(BAR(B_YTILE), 16384);
        tma_load_2d(sb + SM_TIN2, &maps.yT, ti * 128, tj * 64, BAR(B_YTILE));
        tma_load_2d(sb + SM_TIN2 + 8192, &maps.yT, ti * 128 + 64, tj * 64, BAR(B_YTILE));
      }
      __syncwarp();
      mbar_wait(BAR(B_YTILE), 0);
      transpose_tile<1>(sb + SM_TIN2, sb + SM_TOUT2, lane);
      fence_async_smem();
      __syncwarp();
      if (lane == 0) {
        tma_store_2d(&maps.out, sb + SM_TOUT2, 64 * tj, 128 * ti);
        bulk_commit();
        bulk_wait_read0();
        TS(29);
      }
    }
  }
  __syncwarp();
  cluster_arrive();
  cluster_wait();
  if (tid == 0) TS(31);
#undef BAR
}

typedef CUresult (*EncodeFn)(CUtensorMap*, CUtensorMapDataType, cuuint32_t, void*, const cuuint64_t*, const cuuint64_t*,
                             const cuuint32_t*, const cuuint32_t*, CUtensorMapInterleave, CUtensorMapSwizzle,
                             CUtensorMapL2promotion, CUtensorMapFloatOOBfill);

static void make_map(EncodeFn enc, CUtensorMap* m, const void* base, uint64_t inner, uint64_t outer, uint32_t box_in,
                     uint32_t box_out) {
  cuuint64_t gd[2] = {inner, outer};
  cuuint64_t gs[1] = {inner * 2};
  cuuint32_t bd[2] = {box_in, box_out};
  cuuint32_t es[2] = {1, 1};
  enc(m, CU_TENSOR_MAP_DATA_TYPE_BFLOAT16, 2, const_cast<void*>(base), gd, gs, bd, es, CU_TENSOR_MAP_INTERLEAVE_NONE,
      CU_TENSOR_MAP_SWIZZLE_128B, CU_TENSOR_MAP_L2_PROMOTION_L2_128B, CU_TENSOR_MAP_FLOAT_OOB_FILL_NONE);
}

}

extern "C" void kernel_launch(void* const* d_in, const int* in_sizes, int n_in, void* d_out, int out_size) {
  using namespace s4la;
  (void)in_sizes; (void)n_in; (void)out_size;
  static EncodeFn enc = nullptr;
  static void *uT = nullptr, *yT = nullptr;
  if (!enc) {
    void* fn = nullptr;
    cudaDriverEntryPointQueryResult qr;
    cudaGetDriverEntryPoint("cuTensorMapEncodeTiled", &fn, cudaEnableDefault, &qr);
    enc = (EncodeFn)fn;
    cudaGetSymbolAddress(&uT, g_uT);
    cudaGetSymbolAddress(&yT, g_yT);
    cudaFuncSetAttribute(fused_kernel, cudaFuncAttributeMaxDynamicSharedMemorySize, SM_TOTAL);
  }
  const __nv_bfloat16* const* in = (const __nv_bfloat16* const*)d_in;
  Maps maps;
  make_map(enc, &maps.x, in[9], 512, 2048, 64, 128);
  make_map(enc, &maps.w, in[10], 1536, 512, 64, 32);
  make_map(enc, &maps.wo, in[11], 512, 512, 64, 256);
  make_map(enc, &maps.u, in[0], 512, 2048, 64, 128);
  make_map(enc, &maps.uT, uT, 2048, 512, 64, 64);
  make_map(enc, &maps.yT, yT, 2048, 512, 64, 64);
  make_map(enc, &maps.out, d_out, 1024, 2048, 64, 128);
  Ptrs p;
  p.A_re = in[1]; p.A_im = in[2]; p.B_re = in[3]; p.B_im = in[4]; p.C_re = in[5]; p.C_im = in[6];
  p.log_dt = in[7]; p.Dskip = in[8]; p.x = in[9]; p.wqkv = in[10]; p.wo = in[11];
  p.uT = (__nv_bfloat16*)uT; p.yT = (__nv_bfloat16*)yT;
  fused_kernel<<<NCTA, NTHREADS, SM_TOTAL, cudaStreamPerThread>>>(maps, p);
}
```

```cpp
#include <cuda_runtime.h>
#include <cuda_bf16.h>
#include <cuda_fp16.h>
#include <cuda.h>
#include <stdint.h>

#define DEVI __device__ __forceinline__

namespace s4la {

constexpr int NTHREADS = 512;
constexpr int NCTA = 128;

constexpr uint32_t STG_BYTES = 40960, STG_X = 0, STG_W = 16384;
constexpr uint32_t SM_WO = 0;
constexpr uint32_t SM_QS = 65536;
constexpr uint32_t SM_BOUT = 65536;
constexpr uint32_t SM_PK = 81920;
constexpr uint32_t SM_VS = 98304;
constexpr uint32_t SM_KVB = 114688;
constexpr uint32_t SM_TIN2 = 81920, SM_TOUT2 = 98304;
constexpr uint32_t SM_U = 122880, U_BYTES = 4352;
constexpr uint32_t SM_P = 140288, P_BYTES = 4096;
constexpr uint32_t SM_TIN1 = SM_U, SM_TOUT1 = SM_P;
constexpr uint32_t SM_VV = 156672, VV_BYTES = 12800;
constexpr uint32_t VV_U5 = 0, VV_U3 = 3712, VV_U9 = 7424, VV_U7 = 10112;
constexpr uint32_t KG_BYTES = 3200;
constexpr uint32_t SM_BAR = SM_VV + 4 * VV_BYTES;
constexpr uint32_t SM_PTAB = SM_BAR + 256;
constexpr uint32_t SM_TOTAL = SM_PTAB + 3840;
constexpr int PADV = 12;

enum { B_FULL = 0, B_EMPTY = 3, B_WO = 6, B_UTILE = 7, B_YTILE = 8, B_UCH = 9, B_QKVDONE = 13,
       B_CONVDONE = 14, B_TRDONE = 15, B_PKVFREE = 16, B_COUNT = 17 };

constexpr int PD_OFF = 0, P2_OFF = 544, P3_OFF = 768;

constexpr int SL_K2048 = 640, SL_ZERO = 641, SL_510 = 642, SL_0 = 643;
__host__ __device__ constexpr int kidx_c(int l) {
  int r = (l >> 3) & 15, y = 0;
  if (l < 256) y = (l & 7) + ((l >> 7) << 3);
  else if (l < 512) y = 16 + (((l - 256) >> 7) << 2) + ((l & 7) >> 1);
  else if (l < 1024) y = 24 + (((l - 512) >> 7) << 1) + ((l >> 2) & 1);
  else y = 32 + ((l - 1024) >> 7);
  return r * 40 + y;
}
constexpr int slot_direct(int l) {
  if (l < 0 || l > 510) return SL_ZERO;
  if (l == 510) return SL_510;
  if (l == 0) return SL_0;
  return kidx_c(l < 256 ? l : ((l + ((l >> 1) & 1)) & ~1));
}
constexpr int slot_seg2(int v, int k) { return (k >= 32 && k < 64) ? kidx_c(16 * k + 4 * v) : SL_ZERO; }
constexpr int slot_seg3(int pi, int k) {
  return (k >= 64 && k < 128) ? kidx_c(16 * k + 8 * pi) : ((k == 128 && pi == 0) ? SL_K2048 : SL_ZERO);
}
struct PTab { uint32_t v[960]; };
constexpr PTab make_ptab() {
  PTab t{};
  for (int w = 0; w < 960; ++w) t.v[w] = (SL_ZERO * 4) | ((SL_ZERO * 4) << 16);
  for (int w = 0; w < 544; ++w) t.v[w] = (slot_direct(w - 16) * 4) | ((slot_direct(w - 17) * 4) << 16);
  for (int v = 0; v < 4; ++v)
    for (int x = 16; x < 72; ++x) t.v[544 + 56 * v + x - 16] = (slot_seg2(v, x) * 4) | ((slot_seg2(v, x - 1) * 4) << 16);
  for (int pi = 0; pi < 2; ++pi)
    for (int x = 48; x < 136; ++x) t.v[768 + 88 * pi + x - 48] = (slot_seg3(pi, x) * 4) | ((slot_seg3(pi, x - 1) * 4) << 16);
  return t;
}
__device__ const PTab g_ptab = make_ptab();

__device__ __nv_bfloat16 g_uT[512 * 2048];
__device__ __nv_bfloat16 g_yT[512 * 2048];
__device__ uint4 g_ofrag[16 * 8 * 32 * 32];
__device__ float g_kv[2][8][4][272];
__device__ unsigned g_cnt[64 * 32];
__device__ unsigned g_epoch;
#define TS(slot) do { } while (0)
#define TSD(slot, v) do { } while (0)
enum { C_U = 0, C_KV = 8, C_O = 16, C_Y = 32 };

struct Maps {
  CUtensorMap x, w, wo, u, uT, yT, out;
};
struct Ptrs {
  const __nv_bfloat16 *A_re, *A_im, *B_re, *B_im, *C_re, *C_im, *log_dt, *Dskip;
  const __nv_bfloat16 *x, *wqkv, *wo;
  __nv_bfloat16 *uT, *yT;
};

DEVI uint32_t s2u(const void* p) { return (uint32_t)__cvta_generic_to_shared(p); }
DEVI void mbar_init(uint32_t b, uint32_t c) { asm volatile("mbarrier.init.shared::cta.b64 [%0], %1;" ::"r"(b), "r"(c) : "memory"); }
DEVI void mbar_expect_tx(uint32_t b, uint32_t bytes) {
  asm volatile("mbarrier.arrive.expect_tx.shared::cta.b64 _, [%0], %1;" ::"r"(b), "r"(bytes) : "memory");
}
DEVI void mbar_arrive(uint32_t b) { asm volatile("mbarrier.arrive.shared::cta.b64 _, [%0];" ::"r"(b) : "memory"); }
DEVI void mbar_arrive_cluster(uint32_t b, uint32_t cta) {
  asm volatile("{\n.reg .b32 r;\nmapa.shared::cluster.u32 r, %0, %1;\nmbarrier.arrive.shared::cluster.b64 _, [r];\n}"
               ::"r"(b), "r"(cta) : "memory");
}
DEVI void mbar_wait(uint32_t b, uint32_t parity) {
  asm volatile("{\n.reg .pred p;\nLAB_WAIT:\nmbarrier.try_wait.parity.shared::cta.b64 p, [%0], %1, 0x989680;\n@p bra LAB_DONE;\nbra LAB_WAIT;\nLAB_DONE:\n}"
               ::"r"(b), "r"(parity) : "memory");
}
#define mbar_wait_cluster mbar_wait
DEVI void bar_sync(int id, int n) { asm volatile("bar.sync %0, %1;" ::"r"(id), "r"(n) : "memory"); }
DEVI void bar_arrive(int id, int n) { asm volatile("bar.arrive %0, %1;" ::"r"(id), "r"(n) : "memory"); }
DEVI void fence_async_smem() { asm volatile("fence.proxy.async.shared::cta;" ::: "memory"); }
DEVI void fence_async_all() { asm volatile("fence.proxy.async;" ::: "memory"); }
DEVI void cluster_arrive() { asm volatile("barrier.cluster.arrive.relaxed.aligned;" ::: "memory"); }
DEVI void cluster_wait() { asm volatile("barrier.cluster.wait.aligned;" ::: "memory"); }

DEVI void tma_load_2d(uint32_t dst, const CUtensorMap* m, int c0, int c1, uint32_t bar) {
  asm volatile("cp.async.bulk.tensor.2d.shared::cluster.global.mbarrier::complete_tx::bytes [%0], [%1, {%3, %4}], [%2];"
               ::"r"(dst), "l"(m), "r"(bar), "r"(c0), "r"(c1) : "memory");
}
DEVI void tma_load_2d_mc(uint32_t dst, const CUtensorMap* m, int c0, int c1, uint32_t bar, uint16_t mask) {
  asm volatile("cp.async.bulk.tensor.2d.shared::cluster.global.mbarrier::complete_tx::bytes.multicast::cluster [%0], [%1, {%3, %4}], [%2], %5;"
               ::"r"(dst), "l"(m), "r"(bar), "r"(c0), "r"(c1), "h"(mask) : "memory");
}
DEVI void tma_store_2d(const CUtensorMap* m, uint32_t src, int c0, int c1) {
  asm volatile("cp.async.bulk.tensor.2d.global.shared::cta.bulk_group [%0, {%2, %3}], [%1];"
               ::"l"(m), "r"(src), "r"(c0), "r"(c1) : "memory");
}
DEVI void bulk_load(uint32_t dst, const void* src, uint32_t bytes, uint32_t bar) {
  asm volatile("cp.async.bulk.shared::cluster.global.mbarrier::complete_tx::bytes [%0], [%1], %2, [%3];"
               ::"r"(dst), "l"(src), "r"(bytes), "r"(bar) : "memory");
}
DEVI void bulk_store(void* dst, uint32_t src, uint32_t bytes) {
  asm volatile("cp.async.bulk.global.shared::cta.bulk_group [%0], [%1], %2;" ::"l"(dst), "r"(src), "r"(bytes) : "memory");
}
DEVI void bulk_commit() { asm volatile("cp.async.bulk.commit_group;" ::: "memory"); }
DEVI void bulk_wait0() { asm volatile("cp.async.bulk.wait_group 0;" ::: "memory"); }
DEVI void bulk_wait_read0() { asm volatile("cp.async.bulk.wait_group.read 0;" ::: "memory"); }
DEVI void l2_prefetch(const void* p, uint32_t bytes) {
  asm volatile("cp.async.bulk.prefetch.L2.global [%0], %1;" ::"l"(p), "r"(bytes) : "memory");
}
DEVI void prefetch_tmap(const CUtensorMap* m) { asm volatile("prefetch.tensormap [%0];" ::"l"(m) : "memory"); }

DEVI void red_release_add(unsigned* p, unsigned v) {
  asm volatile("red.release.gpu.global.add.u32 [%0], %1;" ::"l"(p), "r"(v) : "memory");
}
DEVI void red_relaxed_add(unsigned* p, unsigned v) {
  asm volatile("red.relaxed.gpu.global.add.u32 [%0], %1;" ::"l"(p), "r"(v) : "memory");
}
DEVI unsigned ld_relaxed(const unsigned* p) {
  unsigned v;
  asm volatile("ld.relaxed.gpu.global.u32 %0, [%1];" : "=r"(v) : "l"(p) : "memory");
  return v;
}
DEVI void wait_counter(const unsigned* p, unsigned target) {
#pragma unroll 1
  for (int it = 0; (int)(ld_relaxed(p) - target) < 0; ++it)
    if (it > (1 << 22)) __trap();
}

DEVI void ldsm_x4(uint32_t (&r)[4], uint32_t a) {
  asm volatile("ldmatrix.sync.aligned.m8n8.x4.shared.b16 {%0,%1,%2,%3}, [%4];"
               : "=r"(r[0]), "=r"(r[1]), "=r"(r[2]), "=r"(r[3]) : "r"(a) : "memory");
}
DEVI void ldsm_x4_t(uint32_t (&r)[4], uint32_t a) {
  asm volatile("ldmatrix.sync.aligned.m8n8.x4.trans.shared.b16 {%0,%1,%2,%3}, [%4];"
               : "=r"(r[0]), "=r"(r[1]), "=r"(r[2]), "=r"(r[3]) : "r"(a) : "memory");
}
DEVI void ldsm_x2_t(uint32_t& r0, uint32_t& r1, uint32_t a) {
  asm volatile("ldmatrix.sync.aligned.m8n8.x2.trans.shared.b16 {%0,%1}, [%2];" : "=r"(r0), "=r"(r1) : "r"(a) : "memory");
}
DEVI void stsm_x4(uint32_t a, uint32_t r0, uint32_t r1, uint32_t r2, uint32_t r3) {
  asm volatile("stmatrix.sync.aligned.m8n8.x4.shared.b16 [%0], {%1,%2,%3,%4};"
               ::"r"(a), "r"(r0), "r"(r1), "r"(r2), "r"(r3) : "memory");
}
DEVI void stsm_x4_t(uint32_t a, uint32_t r0, uint32_t r1, uint32_t r2, uint32_t r3) {
  asm volatile("stmatrix.sync.aligned.m8n8.x4.trans.shared.b16 [%0], {%1,%2,%3,%4};"
               ::"r"(a), "r"(r0), "r"(r1), "r"(r2), "r"(r3) : "memory");
}
DEVI uint32_t lds32(uint32_t a) { uint32_t v; asm volatile("ld.shared.b32 %0, [%1];" : "=r"(v) : "r"(a) : "memory"); return v; }
DEVI float lds_f32(uint32_t a) { float v; asm volatile("ld.shared.f32 %0, [%1];" : "=f"(v) : "r"(a) : "memory"); return v; }
DEVI void sts32(uint32_t a, uint32_t v) { asm volatile("st.shared.b32 [%0], %1;" ::"r"(a), "r"(v) : "memory"); }
DEVI void sts_f32(uint32_t a, float v) { asm volatile("st.shared.f32 [%0], %1;" ::"r"(a), "f"(v) : "memory"); }
DEVI void sts_f32x2(uint32_t a, float x, float y) { asm volatile("st.shared.v2.f32 [%0], {%1,%2};" ::"r"(a), "f"(x), "f"(y) : "memory"); }
DEVI uint4 lds128(uint32_t a) {
  uint4 v;
  asm volatile("ld.shared.v4.b32 {%0,%1,%2,%3}, [%4];" : "=r"(v.x), "=r"(v.y), "=r"(v.z), "=r"(v.w) : "r"(a) : "memory");
  return v;
}
DEVI void sts128(uint32_t a, uint32_t x, uint32_t y, uint32_t z, uint32_t w) {
  asm volatile("st.shared.v4.b32 [%0], {%1,%2,%3,%4};" ::"r"(a), "r"(x), "r"(y), "r"(z), "r"(w) : "memory");
}

DEVI void mma_bf16(float (&d)[4], uint32_t a0, uint32_t a1, uint32_t a2, uint32_t a3, uint32_t b0, uint32_t b1) {
  asm("mma.sync.aligned.m16n8k16.row.col.f32.bf16.bf16.f32 {%0,%1,%2,%3}, {%4,%5,%6,%7}, {%8,%9}, {%0,%1,%2,%3};"
      : "+f"(d[0]), "+f"(d[1]), "+f"(d[2]), "+f"(d[3])
      : "r"(a0), "r"(a1), "r"(a2), "r"(a3), "r"(b0), "r"(b1));
}
DEVI void mma_f16(float (&d)[4], const uint32_t (&a)[4], uint32_t b0, uint32_t b1) {
  asm("mma.sync.aligned.m16n8k16.row.col.f32.f16.f16.f32 {%0,%1,%2,%3}, {%4,%5,%6,%7}, {%8,%9}, {%0,%1,%2,%3};"
      : "+f"(d[0]), "+f"(d[1]), "+f"(d[2]), "+f"(d[3])
      : "r"(a[0]), "r"(a[1]), "r"(a[2]), "r"(a[3]), "r"(b0), "r"(b1));
}
DEVI void mma_bf16v(float (&d)[4], const uint32_t (&a)[4], uint32_t b0, uint32_t b1) {
  asm volatile("mma.sync.aligned.m16n8k16.row.col.f32.bf16.bf16.f32 {%0,%1,%2,%3}, {%4,%5,%6,%7}, {%8,%9}, {%0,%1,%2,%3};"
               : "+f"(d[0]), "+f"(d[1]), "+f"(d[2]), "+f"(d[3])
               : "r"(a[0]), "r"(a[1]), "r"(a[2]), "r"(a[3]), "r"(b0), "r"(b1));
}
DEVI uint32_t pack_bf16(float lo, float hi) {
  uint32_t r;
  asm("cvt.rn.bf16x2.f32 %0, %1, %2;" : "=r"(r) : "f"(hi), "f"(lo));
  return r;
}
DEVI uint32_t pack_f16(float lo, float hi) {
  uint32_t r;
  asm("cvt.rn.f16x2.f32 %0, %1, %2;" : "=r"(r) : "f"(hi), "f"(lo));
  return r;
}
DEVI uint32_t ldg16(const __nv_bfloat16* p) {
  uint32_t v;
  asm volatile("ld.global.nc.u16 %0, [%1];" : "=r"(v) : "l"(p));
  return v;
}
DEVI bool elect_one() {
  uint32_t pred;
  asm volatile("{\n.reg .pred p;\nelect.sync _|p, 0xffffffff;\nselp.u32 %0, 1, 0, p;\n}" : "=r"(pred));
  return pred != 0;
}
DEVI float bf_lo(uint32_t v) { return __uint_as_float(v << 16); }
DEVI float bf_hi(uint32_t v) { return __uint_as_float(v & 0xffff0000u); }
DEVI float bf2f(__nv_bfloat16 v) { return __bfloat162float(v); }
DEVI float round_bf16(float v) { return __bfloat162float(__float2bfloat16_rn(v)); }
DEVI float rcp(float x) { float r; asm("rcp.approx.ftz.f32 %0, %1;" : "=f"(r) : "f"(x)); return r; }
DEVI float ex2(float x) { float r; asm("ex2.approx.ftz.f32 %0, %1;" : "=f"(r) : "f"(x)); return r; }

DEVI void wg_fence() { asm volatile("wgmma.fence.sync.aligned;" ::: "memory"); }
DEVI void wg_commit() { asm volatile("wgmma.commit_group.sync.aligned;" ::: "memory"); }
template <int N> DEVI void wg_wait() { asm volatile("wgmma.wait_group.sync.aligned %0;" ::"n"(N) : "memory"); }
constexpr uint32_t DESC_HI = (1u << 30) | (1024 >> 4);
DEVI uint32_t mkdesc(uint32_t saddr, uint32_t lbo) { return ((saddr & 0x3FFFF) >> 4) | ((lbo >> 4) << 16); }

#define R8(b) "%" #b
DEVI void wgmma_n192(float (&d)[96], uint32_t da, uint32_t db, int scale_d) {
  asm volatile(
      "{\n.reg .pred p;\n.reg .b64 da, db;\nsetp.ne.b32 p, %98, 0;\nmov.b64 da, {%96, %99};\nmov.b64 db, {%97, %99};\n"
      "wgmma.mma_async.sync.aligned.m64n192k16.f32.bf16.bf16 "
      "{%0,%1,%2,%3,%4,%5,%6,%7,%8,%9,%10,%11,%12,%13,%14,%15,"
      "%16,%17,%18,%19,%20,%21,%22,%23,%24,%25,%26,%27,%28,%29,%30,%31,"
      "%32,%33,%34,%35,%36,%37,%38,%39,%40,%41,%42,%43,%44,%45,%46,%47,"
      "%48,%49,%50,%51,%52,%53,%54,%55,%56,%57,%58,%59,%60,%61,%62,%63,"
      "%64,%65,%66,%67,%68,%69,%70,%71,%72,%73,%74,%75,%76,%77,%78,%79,"
      "%80,%81,%82,%83,%84,%85,%86,%87,%88,%89,%90,%91,%92,%93,%94,%95}, "
      "da, db, p, 1, 1, 0, 1;\n}"
      : "+f"(d[0]), "+f"(d[1]), "+f"(d[2]), "+f"(d[3]), "+f"(d[4]), "+f"(d[5]), "+f"(d[6]), "+f"(d[7]),
        "+f"(d[8]), "+f"(d[9]), "+f"(d[10]), "+f"(d[11]), "+f"(d[12]), "+f"(d[13]), "+f"(d[14]), "+f"(d[15]),
        "+f"(d[16]), "+f"(d[17]), "+f"(d[18]), "+f"(d[19]), "+f"(d[20]), "+f"(d[21]), "+f"(d[22]), "+f"(d[23]),
        "+f"(d[24]), "+f"(d[25]), "+f"(d[26]), "+f"(d[27]), "+f"(d[28]), "+f"(d[29]), "+f"(d[30]), "+f"(d[31]),
        "+f"(d[32]), "+f"(d[33]), "+f"(d[34]), "+f"(d[35]), "+f"(d[36]), "+f"(d[37]), "+f"(d[38]), "+f"(d[39]),
        "+f"(d[40]), "+f"(d[41]), "+f"(d[42]), "+f"(d[43]), "+f"(d[44]), "+f"(d[45]), "+f"(d[46]), "+f"(d[47]),
        "+f"(d[48]), "+f"(d[49]), "+f"(d[50]), "+f"(d[51]), "+f"(d[52]), "+f"(d[53]), "+f"(d[54]), "+f"(d[55]),
        "+f"(d[56]), "+f"(d[57]), "+f"(d[58]), "+f"(d[59]), "+f"(d[60]), "+f"(d[61]), "+f"(d[62]), "+f"(d[63]),
        "+f"(d[64]), "+f"(d[65]), "+f"(d[66]), "+f"(d[67]), "+f"(d[68]), "+f"(d[69]), "+f"(d[70]), "+f"(d[71]),
        "+f"(d[72]), "+f"(d[73]), "+f"(d[74]), "+f"(d[75]), "+f"(d[76]), "+f"(d[77]), "+f"(d[78]), "+f"(d[79]),
        "+f"(d[80]), "+f"(d[81]), "+f"(d[82]), "+f"(d[83]), "+f"(d[84]), "+f"(d[85]), "+f"(d[86]), "+f"(d[87]),
        "+f"(d[88]), "+f"(d[89]), "+f"(d[90]), "+f"(d[91]), "+f"(d[92]), "+f"(d[93]), "+f"(d[94]), "+f"(d[95])
      : "r"(da), "r"(db), "r"(scale_d), "n"(DESC_HI));
}
DEVI void wgmma_n64_rs(float (&d)[32], const uint4& a, uint32_t db, int scale_d) {
  asm volatile(
      "{\n.reg .pred p;\n.reg .b64 db;\nsetp.ne.b32 p, %37, 0;\nmov.b64 db, {%36, %38};\n"
      "wgmma.mma_async.sync.aligned.m64n64k16.f32.bf16.bf16 "
      "{%0,%1,%2,%3,%4,%5,%6,%7,%8,%9,%10,%11,%12,%13,%14,%15,"
      "%16,%17,%18,%19,%20,%21,%22,%23,%24,%25,%26,%27,%28,%29,%30,%31}, "
      "{%32,%33,%34,%35}, db, p, 1, 1, 1;\n}"
      : "+f"(d[0]), "+f"(d[1]), "+f"(d[2]), "+f"(d[3]), "+f"(d[4]), "+f"(d[5]), "+f"(d[6]), "+f"(d[7]),
        "+f"(d[8]), "+f"(d[9]), "+f"(d[10]), "+f"(d[11]), "+f"(d[12]), "+f"(d[13]), "+f"(d[14]), "+f"(d[15]),
        "+f"(d[16]), "+f"(d[17]), "+f"(d[18]), "+f"(d[19]), "+f"(d[20]), "+f"(d[21]), "+f"(d[22]), "+f"(d[23]),
        "+f"(d[24]), "+f"(d[25]), "+f"(d[26]), "+f"(d[27]), "+f"(d[28]), "+f"(d[29]), "+f"(d[30]), "+f"(d[31])
      : "r"(a.x), "r"(a.y), "r"(a.z), "r"(a.w), "r"(db), "r"(scale_d), "n"(DESC_HI));
}
template <int MODE>
DEVI void transpose_tile(uint32_t src, uint32_t dst, int lane) {
  const int m = lane >> 3, r = lane & 7;
#pragma unroll 2
  for (int it = 0; it < 32; ++it) {
    uint32_t v[4];
    if (MODE == 0) {
      const int tb = it >> 1, cb = (it & 1) * 4 + m;
      ldsm_x4_t(v, src + (tb * 8 + r) * 128 + ((cb ^ r) << 4));
      const int b = tb >> 3;
      stsm_x4(dst + b * 8192 + (cb * 8 + r) * 128 + (((tb & 7) ^ b ^ r) << 4), v[0], v[1], v[2], v[3]);
    } else {
      const int cb = it & 7, tb = (it >> 3) * 4 + m;
      ldsm_x4_t(v, src + (tb >> 3) * 8192 + (cb * 8 + r) * 128 + (((tb & 7) ^ r) << 4));
      stsm_x4(dst + (tb * 8 + r) * 128 + ((cb ^ r) << 4), v[0], v[1], v[2], v[3]);
    }
  }
}

struct C32 { float re, im; };
DEVI C32 csq(C32 a) { return {a.re * a.re - a.im * a.im, 2.f * a.re * a.im}; }
DEVI C32 cmul(C32 a, C32 b) { return {a.re * b.re - a.im * b.im, a.re * b.im + a.im * b.re}; }
DEVI C32 cfresh(float zl, float zi, float m) {
  float mag = ex2(zl * m), ph = zi * m;
  return {mag * __cosf(ph), mag * __sinf(ph)};
}
struct HMul { uint32_t b, bp; };
DEVI HMul mk_mul(float re, float im) { return {pack_f16(re, im), pack_f16(-im, re)}; }
DEVI uint32_t hcmul(uint32_t a, const HMul& m) {
  __half2 ah = *reinterpret_cast<__half2*>(&a);
  __half2 b = *reinterpret_cast<const __half2*>(&m.b), bp = *reinterpret_cast<const __half2*>(&m.bp);
  __half2 r = __hfma2(__high2half2(ah), bp, __hmul2(__low2half2(ah), b));
  return *reinterpret_cast<uint32_t*>(&r);
}
DEVI uint32_t badd(uint32_t a, uint32_t b) {
  __nv_bfloat162 r = __hadd2(*reinterpret_cast<__nv_bfloat162*>(&a), *reinterpret_cast<__nv_bfloat162*>(&b));
  return *reinterpret_cast<uint32_t*>(&r);
}
DEVI int kidx_l(int i) {
  const int r = i / 40, y = i - 40 * r;
  int lo;
  if (y < 16) lo = (y & 7) + ((y >> 3) << 7);
  else if (y < 24) lo = 256 + (((y - 16) >> 2) << 7) + ((y & 3) << 1);
  else if (y < 32) lo = 512 + (((y - 24) >> 1) << 7) + ((y & 1) << 2);
  else lo = 1024 + ((y - 32) << 7);
  return lo + 8 * r;
}

template <int MU0, int NMU, int DMAX>
DEVI void conv_tail(float (&acc)[16][4], uint32_t p_lane, uint32_t v_base, int back, bool edge, int lane) {
  const int hsel = (lane >> 3) & 1;
  const int row = (lane & 7) + ((lane >> 4) << 3) + PADV - 8 - (back & (hsel ^ 1));
  const uint32_t la = v_base + row * 32 + (((hsel ^ back) ^ ((row >> 2) & 1)) << 4);
  uint32_t M[3][4];
  ldsm_x4_t(M[0], la);
  ldsm_x4_t(M[1], la + 256);
  uint32_t H[2 * NMU];
#pragma unroll
  for (int i = 0; i < 2 * NMU; ++i) H[i ^ 1] = lds32(p_lane + (uint32_t)(MU0 - 1 + i) * 32);
  if (edge) {
    const uint32_t a[4] = {0u, 0u, M[0][0], M[0][1]};
#pragma unroll
    for (int k = 1; k < NMU; ++k) mma_bf16v(acc[MU0 - 2 + 2 * k], a, H[2 * k], H[2 * k + 1]);
  }
#pragma unroll
  for (int delta = -1; delta <= DMAX; ++delta) {
    if (delta + 2 <= DMAX) ldsm_x4_t(M[(delta + 3) % 3], la + (delta + 3) * 256);
#pragma unroll
    for (int k = 0; k < NMU; ++k)
      if (delta + MU0 + 2 * k < 16) mma_bf16v(acc[delta + MU0 + 2 * k], M[(delta + 1) % 3], H[2 * k], H[2 * k + 1]);
  }
}

__global__ void __cluster_dims__(2, 1, 1) __launch_bounds__(NTHREADS, 1)
fused_kernel(const __grid_constant__ Maps maps, const Ptrs p) {
  extern __shared__ __align__(1024) uint8_t smem[];
  const uint32_t sb = s2u(smem);
  const int tid = threadIdx.x, lane = tid & 31;
  const int warp = __shfl_sync(0xffffffffu, tid >> 5, 0);
  const int cta = blockIdx.x;
  const uint32_t rank = cta & 1;
  const int ti = 2 * (cta >> 4) + rank;
  const int tj = (cta >> 1) & 7;
  const uint32_t bars = sb + SM_BAR;
#define BAR(i) (bars + 8 * (i))

  const int kch = warp & 3, krd = warp >> 2;
  float zr, zi, wr, wi;
  {
    const size_t po = (size_t)(cta * 4 + kch) * 128 + krd * 32 + lane;
    const uint32_t r_ar = ldg16(p.A_re + po), r_ai = ldg16(p.A_im + po), r_br = ldg16(p.B_re + po), r_bi = ldg16(p.B_im + po);
    const uint32_t r_cr = ldg16(p.C_re + po), r_ci = ldg16(p.C_im + po), r_ldt = ldg16(p.log_dt + cta * 4 + kch);
    uint4 pt;
    if (tid < 240) pt = __ldg((const uint4*)g_ptab.v + tid);
    if (tid == 384) {
      TS(0);
#pragma unroll
      for (int i = 0; i < B_COUNT; ++i)
        mbar_init(BAR(i), i < 3 ? 1 : i < 6 ? 16 : i < B_TRDONE ? 1 : i == B_TRDONE ? 1 : 8);
      asm volatile("fence.mbarrier_init.release.cluster;" ::: "memory");
      prefetch_tmap(&maps.x); prefetch_tmap(&maps.w); prefetch_tmap(&maps.u);
    }
    __syncthreads();
    cluster_arrive();
    if (warp >= 12) {
      cluster_wait();
      if (elect_one()) {
        if (warp == 13) {
          mbar_expect_tx(BAR(B_UTILE), 16384);
          tma_load_2d(sb + SM_TIN1, &maps.u, tj * 64, ti * 128, BAR(B_UTILE));
          l2_prefetch((const char*)p.wqkv + 192 * 3072 + cta * 7680, 7680);
          l2_prefetch((const char*)p.x + (size_t)cta * 16384, 16384);
          l2_prefetch((const char*)p.wo + (size_t)cta * 4096, 4096);
        } else {
          const int ks = warp == 12 ? 0 : warp - 13;
          const uint32_t st = sb + ks * STG_BYTES, fb = BAR(B_FULL + ks);
          if (warp == 12) TS(61);
          mbar_expect_tx(fb, STG_BYTES);
          tma_load_2d(st + STG_X, &maps.x, ks * 64, ti * 128, fb);
#pragma unroll 1
          for (int nb = 0; nb < 3; ++nb)
            tma_load_2d_mc(st + STG_W + nb * 8192 + rank * 4096, &maps.w, nb * 512 + tj * 64, ks * 64 + rank * 32, fb, 3);
          if (warp == 15) { prefetch_tmap(&maps.wo); prefetch_tmap(&maps.uT); prefetch_tmap(&maps.yT); prefetch_tmap(&maps.out); }
          if (warp == 12) TS(37);
        }
      }
      __syncwarp();
    }
    if (tid < 240) sts128(sb + SM_PTAB + tid * 16, pt.x, pt.y, pt.z, pt.w);
    const float dt = round_bf16(expf(bf_lo(r_ldt)));
    zr = dt * bf_lo(r_ar); zi = dt * bf_lo(r_ai);
    const float dbr = dt * bf_lo(r_br), dbi = dt * bf_lo(r_bi), cr = bf_lo(r_cr), ci = bf_lo(r_ci);
    wr = cr * dbr - ci * dbi; wi = cr * dbi + ci * dbr;
  }
  if (tid == 0) TSD(1, wr);
  if (tid == 384) TSD(33, wr);
  {
    float mz = fmaxf(zr, 0.f), mw = fmaxf(fabsf(wr), fabsf(wi));
#pragma unroll 1
    for (int o = 16; o > 0; o >>= 1) {
      mz = fmaxf(mz, __shfl_xor_sync(0xffffffffu, mz, o));
      mw = fmaxf(mw, __shfl_xor_sync(0xffffffffu, mw, o));
    }
    const int E = min(max((__float_as_int(mw) >> 23) & 255, 1), 252);
    const float sc = __int_as_float((253 - E) << 23), inv = __int_as_float((E + 1) << 23);
    const float zl = (zr - mz) * 1.4426950408889634f, w_r = wr * sc, w_i = wi * sc;
    const uint32_t tb = sb + SM_VV + kch * VV_BYTES + krd * KG_BYTES;
    const uint32_t sta = tb + (((lane >> 2) << 4) | ((lane & 3) << 2));
    auto put = [&](int r, uint32_t v) { sts32((sta ^ ((r & 7) << 4)) + r * 128, v); };
    const uint32_t lda = tb + ((lane & 7) + (((lane >> 3) & 1) << 3)) * 128;
    const uint32_t ldb = tb + ((lane & 7) + ((lane >> 4) << 3)) * 128;
    C32 e1 = cfresh(zl, zi, 1.f), e2 = csq(e1), e4 = csq(e2), e8 = csq(e4);
    C32 e16 = cfresh(zl, zi, 16.f), e32 = csq(e16), e64 = csq(e32), e128 = csq(e64);
    C32 e256 = cfresh(zl, zi, 256.f), e512 = csq(e256), e1024 = csq(e512), e2048 = csq(e1024);
    float k2048 = w_r * e2048.re - w_i * e2048.im;
    uint32_t XA[4][4];
    {
      const HMul m16 = mk_mul(e16.re, e16.im), m32 = mk_mul(e32.re, e32.im), m64 = mk_mul(e64.re, e64.im);
      uint32_t X[8];
      X[0] = 0x00003c00u; X[1] = pack_f16(e8.re, e8.im); X[2] = m16.b; X[4] = m32.b;
      X[3] = hcmul(X[1], m16); X[5] = hcmul(X[1], m32); X[6] = hcmul(X[2], m32); X[7] = hcmul(X[3], m32);
      put(8, m64.b);
#pragma unroll
      for (int r = 0; r < 8; ++r) { put(r, X[r]); if (r) put(8 + r, hcmul(X[r], m64)); }
      __syncwarp();
#pragma unroll
      for (int k = 0; k < 4; ++k) ldsm_x4(XA[k], lda + (((2 * k + (lane >> 4)) ^ (lane & 7)) << 4));
      __syncwarp();
    }
    float D[5][4];
#pragma unroll
    for (int t = 0; t < 5; ++t) D[t][0] = D[t][1] = D[t][2] = D[t][3] = 0.f;
    auto contract = [&](int t0, int nt) {
      __syncwarp();
#pragma unroll
      for (int k = 0; k < 4; ++k) {
        uint32_t b[4];
        ldsm_x4(b, ldb + (((2 * k + ((lane >> 3) & 1)) ^ (lane & 7)) << 4));
        mma_f16(D[t0], XA[k], b[0], b[1]);
        if (nt == 2) mma_f16(D[t0 + 1], XA[k], b[2], b[3]);
      }
      __syncwarp();
    };
    const HMul c1 = mk_mul(e1.re, -e1.im), c2 = mk_mul(e2.re, -e2.im), c4 = mk_mul(e4.re, -e4.im);
    uint32_t W[8];
    W[0] = pack_f16(w_r, -w_i);
    W[1] = hcmul(W[0], c1); W[2] = hcmul(W[0], c2); W[3] = hcmul(W[1], c2);
    W[4] = hcmul(W[0], c4); W[5] = hcmul(W[1], c4); W[6] = hcmul(W[2], c4); W[7] = hcmul(W[3], c4);
    const HMul c128 = mk_mul(e128.re, -e128.im), c256 = mk_mul(e256.re, -e256.im);
#pragma unroll
    for (int i = 0; i < 8; ++i) { put(i, W[i]); put(8 + i, hcmul(W[i], c128)); }
    contract(0, 2);
    const C32 e384 = cmul(e256, e128), e640 = cmul(e512, e128), e768 = cmul(e512, e256), e896 = cmul(e768, e128);
    const HMul c384 = mk_mul(e384.re, -e384.im), c512 = mk_mul(e512.re, -e512.im), c640 = mk_mul(e640.re, -e640.im);
    const HMul c768 = mk_mul(e768.re, -e768.im), c896 = mk_mul(e896.re, -e896.im), c1024 = mk_mul(e1024.re, -e1024.im);
#pragma unroll
    for (int i = 0; i < 4; ++i) { put(i, hcmul(W[2 * i], c256)); put(4 + i, hcmul(W[2 * i], c384)); }
    put(8, hcmul(W[0], c512)); put(9, hcmul(W[4], c512)); put(10, hcmul(W[0], c640)); put(11, hcmul(W[4], c640));
    put(12, hcmul(W[0], c768)); put(13, hcmul(W[4], c768)); put(14, hcmul(W[0], c896)); put(15, hcmul(W[4], c896));
    contract(2, 2);
    const uint32_t v0 = hcmul(W[0], c1024);
    put(0, v0); put(1, hcmul(v0, c128)); put(2, hcmul(v0, c256)); put(3, hcmul(v0, c384));
    put(4, hcmul(v0, c512)); put(5, hcmul(v0, c640)); put(6, hcmul(v0, c768)); put(7, hcmul(v0, c896));
    contract(4, 1);
    {
      const int g = lane >> 2, q = lane & 3;
#pragma unroll 1
      for (int o = 16; o > 0; o >>= 1) k2048 += __shfl_xor_sync(0xffffffffu, k2048, o);
      const uint32_t a = tb + (g * 40 + 2 * q) * 4;
#pragma unroll
      for (int t = 0; t < 5; ++t) {
        sts_f32x2(a + t * 32, D[t][0] * inv, D[t][1] * inv);
        sts_f32x2(a + t * 32 + 1280, D[t][2] * inv, D[t][3] * inv);
      }
      if (lane == 0) sts_f32(tb + SL_K2048 * 4, k2048 * inv);
      if (mz > 0.f) {
        const float zt = mz * 1.4426950408889634f;
        __syncwarp();
#pragma unroll 1
        for (int i = lane; i < 641; i += 32)
          sts_f32(tb + i * 4, lds_f32(tb + i * 4) * ex2(zt * (i < 640 ? kidx_l(i) : 2048)));
      }
    }
  }
  if (tid == 0) TS(2);
  if (tid == 384) TS(34);
  if (tid == 128) TS(36);
  if (warp < 12) cluster_wait();
  __syncthreads();
  if (tid == 0) TS(32);

  if (warp < 4) {
    asm volatile("setmaxnreg.inc.sync.aligned.u32 152;");
    const unsigned epoch = __ldcg(&g_epoch);
    const int ch = warp;
    const int d = cta * 4 + ch;
    const uint32_t vv = sb + SM_VV + ch * VV_BYTES;
    const uint32_t ub = sb + SM_U + ch * U_BYTES;
    const uint32_t pb = sb + SM_P + ch * P_BYTES;
    const uint32_t kf = vv;
    const int g = lane >> 2, q = lane & 3;
    const float dskip = bf2f(p.Dskip[d]);
#pragma unroll 1
    for (int i0 = 0; i0 < 21; i0 += 3) {
      float a[3][4];
#pragma unroll
      for (int i = 0; i < 3; ++i)
#pragma unroll
        for (int r = 0; r < 4; ++r) a[i][r] = lds_f32(kf + r * KG_BYTES + ((i0 + i) * 32 + lane) * 4);
#pragma unroll
      for (int i = 0; i < 3; ++i) sts_f32(kf + ((i0 + i) * 32 + lane) * 4, (a[i][0] + a[i][1]) + (a[i][2] + a[i][3]));
    }
    __syncwarp();
    const float k1024 = lds_f32(kf + kidx_c(1024) * 4);
    if (lane == 0) {
      sts_f32(kf + SL_ZERO * 4, 0.f);
      sts_f32(kf + SL_510 * 4, lds_f32(kf + kidx_c(510) * 4) - lds_f32(kf + kidx_c(512) * 4));
      sts_f32(kf + SL_0 * 4, lds_f32(kf) + dskip);
    }
    __syncwarp();
    mbar_wait(BAR(B_TRDONE), 0);
    if (lane == 0) TS(50);
    if (lane < 16) sts128(ub + lane * 16, 0, 0, 0, 0);
#pragma unroll 1
    for (int i0 = 0; i0 < 30; i0 += 6) {
      uint32_t e[6];
      float a[6], b[6];
#pragma unroll
      for (int i = 0; i < 6; ++i) e[i] = lds32(sb + SM_PTAB + ((i0 + i) * 32 + lane) * 4);
#pragma unroll
      for (int i = 0; i < 6; ++i) { a[i] = lds_f32(kf + (e[i] & 0xffff)); b[i] = lds_f32(kf + (e[i] >> 16)); }
#pragma unroll
      for (int i = 0; i < 6; ++i) sts32(pb + ((i0 + i) * 32 + lane) * 4, pack_bf16(a[i], b[i]));
    }
    if (elect_one()) {
      TS(4);
      wait_counter(&g_cnt[(C_U + (cta >> 4)) * 32], (epoch + 1) * 16);
      mbar_expect_tx(BAR(B_UCH + ch), 4096);
      bulk_load(ub + 256, p.uT + (size_t)d * 2048, 4096, BAR(B_UCH + ch));
      TS(3);
    }
    __syncwarp();
    mbar_wait(BAR(B_UCH + ch), 0);
    if (lane == 0) TS(5);
#pragma unroll 1
    for (int it = 0; it < 8; ++it) {
      const int k = -18 + it * 32 + lane;
      const int kr = min(max(k, -2), 208);
      uint32_t E[12];
#pragma unroll
      for (int c = 0; c < 3; ++c) {
        const int kk = kr - 1 + c, r = (kk >> 1) + 8;
        const uint4 t = lds128(ub + r * 32 + (((kk & 1) ^ ((r >> 2) & 1)) << 4));
        E[4 * c] = t.x; E[4 * c + 1] = t.y; E[4 * c + 2] = t.z; E[4 * c + 3] = t.w;
      }
      uint32_t O[8];
#pragma unroll
      for (int j = 0; j < 8; ++j) O[j] = __byte_perm(E[j + 1], E[j + 2], 0x5432);
      uint32_t s3[6], s5[4], s7[4], s9[4];
#pragma unroll
      for (int j = 0; j < 6; ++j) s3[j] = badd(badd(O[j], O[j + 1]), E[j + 2]);
#pragma unroll
      for (int j = 0; j < 4; ++j) {
        s5[j] = badd(s3[j + 2], badd(E[j + 3], E[j + 5]));
        s7[j] = badd(s5[j], badd(O[j + 1], O[j + 4]));
        s9[j] = badd(s7[j], badd(E[j + 2], E[j + 6]));
      }
      const int r = (k >> 1) + PADV;
      const uint32_t a = vv + r * 32 + (((k & 1) ^ ((r >> 2) & 1)) << 4);
      if (k < 208) { sts128(a + VV_U3, s3[0], s3[1], s3[2], s3[3]); sts128(a + VV_U5, s5[0], s5[1], s5[2], s5[3]); }
      if (k < 144) { sts128(a + VV_U7, s7[0], s7[1], s7[2], s7[3]); sts128(a + VV_U9, s9[0], s9[1], s9[2], s9[3]); }
    }
    __syncwarp();
    if (lane == 0) TS(6);
    const int gq = g - 2 * q;
    uint32_t h127, h128;
    {
      const uint32_t kf2 = pack_bf16(k1024, k1024) ^ 0x80008000u;
      h127 = (gq == 4 ? 0x0000ffffu : gq == 5 ? 0xffffffffu : gq == 6 ? 0xffff0000u : 0u) & kf2;
      h128 = (gq == -4 ? 0x0000ffffu : gq == -3 ? 0xffffffffu : gq == -2 ? 0xffff0000u : 0u) & kf2;
    }
    bar_sync(4, 384);
    if (lane == 0) TS(7);
    float acc[16][4];
#pragma unroll
    for (int i = 0; i < 16; ++i) { acc[i][0] = acc[i][1] = acc[i][2] = acc[i][3] = 0.f; }
    {
      const uint32_t pd_lane = pb + (PD_OFF + 16 + gq) * 4;
      const int prow0 = 8 + (lane & 7) + ((lane >> 4) << 3), hs = (lane >> 3) & 1;
      uint32_t B[2][4][4];
      uint32_t A[4][4];
      const uint32_t la0 = ub + prow0 * 32 + ((hs ^ ((prow0 >> 2) & 1)) << 4);
#pragma unroll
      for (int m2 = 0; m2 < 4; ++m2) ldsm_x4(B[0][m2], la0 + m2 * 512);
#pragma unroll
      for (int i = 0; i < 4; ++i) {
        const uint32_t a = pd_lane + i * 512;
        A[i][0] = lds32(a); A[i][1] = lds32(a + 32); A[i][2] = lds32(a - 32); A[i][3] = A[i][0];
      }
      uint32_t la = la0;
#pragma unroll 1
      for (int rho = 0; rho < 8; ++rho) {
#pragma unroll
        for (int m2 = 0; m2 < 4; ++m2) ldsm_x4(B[1][m2], la + (4 + m2) * 512);
#pragma unroll
        for (int i = 0; i < 4; ++i)
#pragma unroll
          for (int m = 0; m < 8; ++m) mma_bf16v(acc[m + i], A[i], B[0][m >> 1][2 * (m & 1)], B[0][m >> 1][2 * (m & 1) + 1]);
        const int prow = prow0 - min(rho + 1, 7);
        la = ub + prow * 32 + ((hs ^ ((prow >> 2) & 1)) << 4);
#pragma unroll
        for (int m2 = 0; m2 < 4; ++m2) ldsm_x4(B[0][m2], la + m2 * 512);
        const uint32_t pa = pd_lane + (rho + 1) * 64;
#pragma unroll
        for (int i = 0; i < 4; ++i) {
#pragma unroll
          for (int m = 0; m < 8 - i; ++m)
            mma_bf16v(acc[8 + m + i], A[i], B[1][m >> 1][2 * (m & 1)], B[1][m >> 1][2 * (m & 1) + 1]);
          A[i][0] = lds32(pa + i * 512); A[i][1] = lds32(pa + i * 512 + 32); A[i][2] = lds32(pa + i * 512 - 32);
          A[i][3] = A[i][0];
        }
      }
      {
        uint32_t b8[4];
        ldsm_x4(b8, la + 4 * 512);
        const uint32_t h63 = lds32(pd_lane + 63 * 32), h64 = lds32(pd_lane + 64 * 32);
        const uint32_t a63[4] = {0u, h127, 0u, 0u}, a32[4] = {h64, 0u, h63, h64}, a64[4] = {h128, 0u, h127, h128};
#pragma unroll
        for (int m2 = 0; m2 < 4; ++m2) ldsm_x4(B[1][m2], la0 + m2 * 512);
#pragma unroll
        for (int m = 0; m < 8; ++m) mma_bf16v(acc[m + 7], a63, B[0][m >> 1][2 * (m & 1)], B[0][m >> 1][2 * (m & 1) + 1]);
#pragma unroll
        for (int m2 = 0; m2 < 2; ++m2) ldsm_x4(B[0][m2], la0 + (4 + m2) * 512);
#pragma unroll
        for (int m = 0; m < 8; ++m) mma_bf16v(acc[m + 4], a32, B[1][m >> 1][2 * (m & 1)], B[1][m >> 1][2 * (m & 1) + 1]);
        mma_bf16v(acc[15], a63, b8[0], b8[1]);
#pragma unroll
        for (int m = 0; m < 8; ++m) mma_bf16v(acc[m + 8], a64, B[1][m >> 1][2 * (m & 1)], B[1][m >> 1][2 * (m & 1) + 1]);
#pragma unroll
        for (int m = 0; m < 4; ++m) mma_bf16v(acc[m + 12], a32, B[0][m >> 1][2 * (m & 1)], B[0][m >> 1][2 * (m & 1) + 1]);
      }
#pragma unroll 1
      for (int v = 0; v < 4; ++v)
        conv_tail<4, 3, 11>(acc, pb + (P2_OFF + 56 * v + gq - 16) * 4, vv + ((v & 1) ? VV_U3 : VV_U5), v >> 1, v == 0, lane);
#pragma unroll 1
      for (int pi = 0; pi < 2; ++pi)
        conv_tail<8, 5, 7>(acc, pb + (P3_OFF + 88 * pi + gq - 48) * 4, vv + (pi ? VV_U7 : VV_U9), pi, pi == 0, lane);
    }
    bar_arrive(3, 384);
    if (lane == 0) TS(8);
    {
      const int mt = lane >> 3;
      const uint32_t a = vv + (128 * (mt >> 1) + 16 * (lane & 7) + 8 * (mt & 1)) * 2;
#pragma unroll
      for (int ab = 0; ab < 16; ab += 2)
        stsm_x4_t(a + ab * 256, pack_bf16(acc[ab][0], acc[ab][1]), pack_bf16(acc[ab][2], acc[ab][3]),
                  pack_bf16(acc[ab + 1][0], acc[ab + 1][1]), pack_bf16(acc[ab + 1][2], acc[ab + 1][3]));
    }
    fence_async_smem();
    __syncwarp();
    if (elect_one()) {
      bulk_store(p.yT + (size_t)d * 2048, vv, 4096);
      bulk_commit();
      bulk_wait0();
      red_relaxed_add(&g_cnt[(C_Y + (cta >> 4)) * 32], 1);
      TS(9);
    }
  } else if (warp < 12) {
    asm volatile("setmaxnreg.inc.sync.aligned.u32 160;");
    const unsigned epoch = __ldcg(&g_epoch);
    const int w8 = warp - 4;
    const int g = lane >> 2, q = lane & 3;
    {
      float acc[96];
#pragma unroll 1
      for (int ks = 0, s = 0, ph = 0; ks < 8; ++ks) {
        mbar_wait(BAR(B_FULL + s), ph);
        if (tid == 128) TS(ks == 0 ? 16 : 9 + ks + (ks > 6 ? 46 : 0));
        const uint32_t st = sb + s * STG_BYTES;
        const uint32_t da = mkdesc(st + STG_X + (w8 >> 2) * 8192, 16);
        const uint32_t db = mkdesc(st + STG_W, 8192);
        wg_fence();
#pragma unroll
        for (int k = 0; k < 4; ++k) wgmma_n192(acc, da + 2 * k, db + 128 * k, (ks | k) != 0);
        wg_commit();
        const uint32_t eprev = BAR(B_EMPTY + (s == 0 ? 2 : s - 1));
        if (++s == 3) { s = 0; ph ^= 1; }
        if (ks > 0) {
          wg_wait<1>();
          if (lane < 2) mbar_arrive_cluster(eprev, lane);
        }
      }
      wg_wait<0>();
      if (lane < 2) mbar_arrive_cluster(BAR(B_EMPTY + 1), lane);
      bar_arrive(4, 384);
      if (tid == 128) TS(17);
      bar_sync(1, 256);
      const int row = w8 * 16 + (lane & 7) + (((lane >> 3) & 1) << 3);
      const uint32_t ra = sb + SM_QS + row * 128;
#pragma unroll
      for (int i = 0; i < 24; i += 2)
        stsm_x4(ra + (i >> 3) * 16384 + ((((i & 7) + (lane >> 4)) ^ (row & 7)) << 4), pack_bf16(acc[4 * i], acc[4 * i + 1]),
                pack_bf16(acc[4 * i + 2], acc[4 * i + 3]), pack_bf16(acc[4 * i + 4], acc[4 * i + 5]),
                pack_bf16(acc[4 * i + 6], acc[4 * i + 7]));
    }
    __syncwarp();
    const unsigned par = epoch & 1;
    const int hh = w8 >> 1, dtile = w8 & 1;
    float* kvg = &g_kv[par][tj][hh][0];
#pragma unroll 1
    for (int part = 1; part >= 0; --part) {
      const uint32_t pa = sb + SM_QS + part * 16384 + w8 * 2048 + lane * 16;
#pragma unroll 1
      for (int it = 0; it < 4; ++it) {
        uint4 t = lds128(pa + it * 512);
        uint32_t* tw = &t.x;
#pragma unroll
        for (int j = 0; j < 4; ++j) {
          const uint32_t x = tw[j];
          const __nv_bfloat162 xb = *reinterpret_cast<const __nv_bfloat162*>(&x);
          const uint32_t e = pack_bf16(ex2(bf_lo(x) * 1.4426950408889634f), ex2(bf_hi(x) * 1.4426950408889634f));
          const uint32_t m = __hgt2_mask(xb, __floats2bfloat162_rn(0.f, 0.f));
          const uint32_t sel = (badd(x, 0x3f803f80u) & m) | (e & ~m);
          tw[j] = pack_bf16(bf_lo(sel) + 1e-6f, bf_hi(sel) + 1e-6f);
        }
        sts128(pa + it * 512, t.x, t.y, t.z, t.w);
      }
      if (part == 1) {
        if (tid == 128) TS(53);
        bar_sync(1, 256);
        float kv[4] = {0.f, 0.f, 0.f, 0.f}, zz[4] = {0.f, 0.f, 0.f, 0.f};
        const int m = lane >> 3;
        const uint32_t aa = sb + SM_VS + ((lane & 7) + ((m >> 1) << 3)) * 128 + (((2 * hh + (m & 1)) ^ (lane & 7)) << 4);
        const uint32_t ab = sb + SM_PK + (lane & 15) * 128 + (((2 * hh + dtile) ^ (lane & 7)) << 4);
#pragma unroll 2
        for (int ks = 0; ks < 8; ++ks) {
          uint32_t a[4], b0, b1;
          ldsm_x4_t(a, aa + ks * 2048);
          ldsm_x2_t(b0, b1, ab + ks * 2048);
          mma_bf16(kv, a[0], a[1], a[2], a[3], b0, b1);
          mma_bf16(zz, 0x3f803f80u, 0x3f803f80u, 0x3f803f80u, 0x3f803f80u, b0, b1);
        }
        asm volatile("red.global.add.v4.f32 [%0], {%1,%2,%3,%4};" ::"l"(kvg + dtile * 128 + lane * 4), "f"(kv[0]), "f"(kv[1]),
                     "f"(kv[2]), "f"(kv[3]) : "memory");
        if (g == 0)
          asm volatile("red.global.add.v2.f32 [%0], {%1,%2};" ::"l"(kvg + 256 + dtile * 8 + 2 * q), "f"(zz[0]), "f"(zz[1]) : "memory");
        if (tid == 128) TS(55);
        bar_sync(1, 256);
        if (lane == 0) mbar_arrive(BAR(B_PKVFREE));
        if (tid == 128) { red_release_add(&g_cnt[(C_KV + tj) * 32], 1); TS(18); }
        if (ti == 0) {
          float4* z = (float4*)&g_kv[par ^ 1][tj][0][0];
          for (int i = tid - 128; i < 272; i += 256) z[i] = make_float4(0.f, 0.f, 0.f, 0.f);
        }
      }
    }
    if (tid == 128) { TS(56); wait_counter(&g_cnt[(C_KV + tj) * 32], (epoch + 1) * 16); TS(19); }
    bar_sync(1, 256);
    {
      const float4 k4 = __ldcg((const float4*)(kvg + dtile * 128 + lane * 4));
      const float2 z2 = __ldcg((const float2*)(kvg + 256 + dtile * 8 + 2 * q));
      const uint32_t a = sb + SM_KVB + hh * 512 + lane * 16 + dtile * 4;
      sts32(a, pack_bf16(k4.x, k4.y));
      sts32(a + 8, pack_bf16(k4.z, k4.w));
      if (g == 0) sts32(sb + SM_KVB + 2048 + hh * 32 + q * 8 + dtile * 4, pack_bf16(z2.x, z2.y));
    }
    bar_sync(1, 256);
    {
      const int row = w8 * 16 + (lane & 7) + (((lane >> 3) & 1) << 3);
      uint4* dst = &g_ofrag[((ti * 8 + w8) * 32 + 4 * tj) * 32 + lane];
#pragma unroll 1
      for (int h = 0; h < 4; ++h) {
        uint32_t a[4];
        ldsm_x4(a, sb + SM_QS + row * 128 + (((2 * h + (lane >> 4)) ^ (row & 7)) << 4));
        const uint4 kb = lds128(sb + SM_KVB + h * 512 + lane * 16);
        const uint32_t zb0 = lds32(sb + SM_KVB + 2048 + h * 32 + q * 8), zb1 = lds32(sb + SM_KVB + 2048 + h * 32 + q * 8 + 4);
        float n0[4] = {0.f, 0.f, 0.f, 0.f}, n1[4] = {0.f, 0.f, 0.f, 0.f}, dn[4] = {0.f, 0.f, 0.f, 0.f};
        mma_bf16(n0, a[0], a[1], a[2], a[3], kb.x, kb.y);
        mma_bf16(n1, a[0], a[1], a[2], a[3], kb.z, kb.w);
        mma_bf16(dn, a[0], a[1], a[2], a[3], zb0, zb1);
        const uint32_t dd = pack_bf16(dn[0], dn[2]);
        const uint32_t d2 = pack_bf16(bf_lo(dd) + 1e-6f, bf_hi(dd) + 1e-6f);
        const float r0 = rcp(bf_lo(d2)), r1 = rcp(bf_hi(d2));
        const uint32_t x0 = pack_bf16(n0[0], n0[1]), x1 = pack_bf16(n0[2], n0[3]);
        const uint32_t x2 = pack_bf16(n1[0], n1[1]), x3 = pack_bf16(n1[2], n1[3]);
        dst[h * 32] = make_uint4(pack_bf16(bf_lo(x0) * r0, bf_hi(x0) * r0), pack_bf16(bf_lo(x1) * r1, bf_hi(x1) * r1),
                                 pack_bf16(bf_lo(x2) * r0, bf_hi(x2) * r0), pack_bf16(bf_lo(x3) * r1, bf_hi(x3) * r1));
      }
    }
    if (tid == 128) TS(57);
    bar_sync(1, 256);
    if (tid == 128) {
      red_release_add(&g_cnt[(C_O + ti) * 32], 1);
      TS(20);
      wait_counter(&g_cnt[(C_O + ti) * 32], (epoch + 1) * 8);
      if (cta == 0) g_epoch = epoch + 1;
      TS(21);
    }
    bar_sync(1, 256);
    {
      const uint4* src = &g_ofrag[((ti * 8 + w8) * 32) * 32 + lane];
      uint4 A0[8], A1[8];
#pragma unroll
      for (int h = 0; h < 8; ++h) A0[h] = __ldcg(src + h * 32);
#pragma unroll
      for (int h = 0; h < 8; ++h) A1[h] = __ldcg(src + (8 + h) * 32);
      mbar_wait(BAR(B_WO), 0);
      bar_sync(3, 384);
      if (tid == 128) TS(22);
      float o[32];
      const uint32_t db = mkdesc(sb + SM_WO, 8192);
#pragma unroll 1
      for (int it = 0; it < 2; ++it) {
        wg_fence();
#pragma unroll
        for (int h = 0; h < 8; ++h) wgmma_n64_rs(o, A0[h], db + (16 * it + h) * 128, (it | h) != 0);
        wg_commit();
        wg_wait<0>();
        if (it == 0) {
#pragma unroll
          for (int h = 0; h < 8; ++h) A0[h] = __ldcg(src + (16 + h) * 32);
        }
        wg_fence();
#pragma unroll
        for (int h = 0; h < 8; ++h) wgmma_n64_rs(o, A1[h], db + (16 * it + 8 + h) * 128, 1);
        wg_commit();
        wg_wait<0>();
        if (it == 0) {
#pragma unroll
          for (int h = 0; h < 8; ++h) A1[h] = __ldcg(src + (24 + h) * 32);
        }
      }
      const int row = w8 * 16 + (lane & 7) + (((lane >> 3) & 1) << 3);
#pragma unroll
      for (int i = 0; i < 8; i += 2)
        stsm_x4(sb + SM_BOUT + row * 128 + (((i + (lane >> 4)) ^ (row & 7)) << 4), pack_bf16(o[4 * i], o[4 * i + 1]),
                pack_bf16(o[4 * i + 2], o[4 * i + 3]), pack_bf16(o[4 * i + 4], o[4 * i + 5]), pack_bf16(o[4 * i + 6], o[4 * i + 7]));
      fence_async_smem();
      bar_sync(1, 256);
      if (warp == 4 && elect_one()) {
        tma_store_2d(&maps.out, sb + SM_BOUT, 512 + 64 * tj, 128 * ti);
        bulk_commit();
        bulk_wait_read0();
        TS(23);
      }
    }
  } else {
    asm volatile("setmaxnreg.dec.sync.aligned.u32 40;");
    if (tid == 384) TS(49);
    if (warp == 12) {
      if (elect_one()) {
#pragma unroll 1
        for (int ks = 3, s = 0, ph = 0; ks < 8; ++ks) {
          mbar_wait(BAR(B_EMPTY + s), ph);
          const uint32_t st = sb + s * STG_BYTES, fb = BAR(B_FULL + s);
          mbar_expect_tx(fb, STG_BYTES);
          tma_load_2d(st + STG_X, &maps.x, ks * 64, ti * 128, fb);
#pragma unroll 1
          for (int nb = 0; nb < 3; ++nb)
            tma_load_2d_mc(st + STG_W + nb * 8192 + rank * 4096, &maps.w, nb * 512 + tj * 64, ks * 64 + rank * 32, fb, 3);
          if (++s == 3) { s = 0; ph ^= 1; }
        }
        TS(24);
        mbar_wait(BAR(B_EMPTY + 0), 0);
        mbar_wait(BAR(B_EMPTY + 1), 0);
        mbar_expect_tx(BAR(B_WO), 65536);
        tma_load_2d_mc(sb + SM_WO + rank * 32768, &maps.wo, tj * 64, rank * 256, BAR(B_WO), 3);
      }
    } else if (warp == 13) {
      const unsigned epoch = __ldcg(&g_epoch);
      mbar_wait(BAR(B_UTILE), 0);
      if (lane == 0) TS(26);
      transpose_tile<0>(sb + SM_TIN1, sb + SM_TOUT1, lane);
      if (lane == 0) TS(58);
      fence_async_smem();
      __syncwarp();
      if (elect_one()) {
        tma_store_2d(&maps.uT, sb + SM_TOUT1, ti * 128, tj * 64);
        tma_store_2d(&maps.uT, sb + SM_TOUT1 + 8192, ti * 128 + 64, tj * 64);
        bulk_commit();
        bulk_wait0();
        TS(59);
        red_relaxed_add(&g_cnt[(C_U + tj) * 32], 1);
        mbar_arrive(BAR(B_TRDONE));
        TS(27);
        mbar_wait(BAR(B_PKVFREE), 0);
        wait_counter(&g_cnt[(C_Y + tj) * 32], (epoch + 1) * 64);
        TS(28);
        mbar_expect_tx(BAR(B_YTILE), 16384);
        tma_load_2d(sb + SM_TIN2, &maps.yT, ti * 128, tj * 64, BAR(B_YTILE));
        tma_load_2d(sb + SM_TIN2 + 8192, &maps.yT, ti * 128 + 64, tj * 64, BAR(B_YTILE));
      }
      __syncwarp();
      mbar_wait(BAR(B_YTILE), 0);
      transpose_tile<1>(sb + SM_TIN2, sb + SM_TOUT2, lane);
      fence_async_smem();
      __syncwarp();
      if (elect_one()) {
        tma_store_2d(&maps.out, sb + SM_TOUT2, 64 * tj, 128 * ti);
        bulk_commit();
        bulk_wait_read0();
        TS(29);
      }
    }
  }
  __syncwarp();
  cluster_arrive();
  cluster_wait();
  if (tid == 0) TS(31);
#undef BAR
}

typedef CUresult (*EncodeFn)(CUtensorMap*, CUtensorMapDataType, cuuint32_t, void*, const cuuint64_t*, const cuuint64_t*,
                             const cuuint32_t*, const cuuint32_t*, CUtensorMapInterleave, CUtensorMapSwizzle,
                             CUtensorMapL2promotion, CUtensorMapFloatOOBfill);

static void make_map(EncodeFn enc, CUtensorMap* m, const void* base, uint64_t inner, uint64_t outer, uint32_t box_in,
                     uint32_t box_out) {
  cuuint64_t gd[2] = {inner, outer};
  cuuint64_t gs[1] = {inner * 2};
  cuuint32_t bd[2] = {box_in, box_out};
  cuuint32_t es[2] = {1, 1};
  enc(m, CU_TENSOR_MAP_DATA_TYPE_BFLOAT16, 2, const_cast<void*>(base), gd, gs, bd, es, CU_TENSOR_MAP_INTERLEAVE_NONE,
      CU_TENSOR_MAP_SWIZZLE_128B, CU_TENSOR_MAP_L2_PROMOTION_L2_128B, CU_TENSOR_MAP_FLOAT_OOB_FILL_NONE);
}

}

extern "C" void kernel_launch(void* const* d_in, const int* in_sizes, int n_in, void* d_out, int out_size) {
  using namespace s4la;
  (void)in_sizes; (void)n_in; (void)out_size;
  static EncodeFn enc = nullptr;
  static void *uT = nullptr, *yT = nullptr;
  if (!enc) {
    void* fn = nullptr;
    cudaDriverEntryPointQueryResult qr;
    cudaGetDriverEntryPoint("cuTensorMapEncodeTiled", &fn, cudaEnableDefault, &qr);
    enc = (EncodeFn)fn;
    cudaGetSymbolAddress(&uT, g_uT);
    cudaGetSymbolAddress(&yT, g_yT);
    cudaFuncSetAttribute(fused_kernel, cudaFuncAttributeMaxDynamicSharedMemorySize, SM_TOTAL);
  }
  const __nv_bfloat16* const* in = (const __nv_bfloat16* const*)d_in;
  Maps maps;
  make_map(enc, &maps.x, in[9], 512, 2048, 64, 128);
  make_map(enc, &maps.w, in[10], 1536, 512, 64, 32);
  make_map(enc, &maps.wo, in[11], 512, 512, 64, 256);
  make_map(enc, &maps.u, in[0], 512, 2048, 64, 128);
  make_map(enc, &maps.uT, uT, 2048, 512, 64, 64);
  make_map(enc, &maps.yT, yT, 2048, 512, 64, 64);
  make_map(enc, &maps.out, d_out, 1024, 2048, 64, 128);
  Ptrs p;
  p.A_re = in[1]; p.A_im = in[2]; p.B_re = in[3]; p.B_im = in[4]; p.C_re = in[5]; p.C_im = in[6];
  p.log_dt = in[7]; p.Dskip = in[8]; p.x = in[9]; p.wqkv = in[10]; p.wo = in[11];
  p.uT = (__nv_bfloat16*)uT; p.yT = (__nv_bfloat16*)yT;
  fused_kernel<<<NCTA, NTHREADS, SM_TOTAL, cudaStreamPerThread>>>(maps, p);
}
```

```cpp
#include <cuda_runtime.h>
#include <cuda_bf16.h>
#include <cuda_fp16.h>
#include <cuda.h>
#include <stdint.h>

#define DEVI __device__ __forceinline__

namespace s4la {

constexpr int NTHREADS = 512;
constexpr int NCTA = 128;

constexpr uint32_t STG_BYTES = 40960, STG_X = 0, STG_W = 16384;
constexpr uint32_t SM_WO = 0;
constexpr uint32_t SM_BOUT = 0;
constexpr uint32_t SM_QS = 65536;
constexpr uint32_t SM_PK = SM_QS + 16384, SM_VS = SM_QS + 32768;
constexpr uint32_t SM_KV = 114688;
constexpr uint32_t SM_U = 122880, U_BYTES = 4352;
constexpr uint32_t SM_P = 140288, P_BYTES = 4096;
constexpr uint32_t SM_VV = 156672, VV_BYTES = 12800;
constexpr uint32_t VV_U5 = 0, VV_U3 = 3712, VV_U9 = 7424, VV_U7 = 10112;
constexpr uint32_t KG_BYTES = 3200;
constexpr uint32_t SM_BAR = SM_VV + 4 * VV_BYTES;
constexpr uint32_t SM_PTAB = SM_BAR + 256;
constexpr uint32_t SM_TOTAL = SM_PTAB + 3840;
constexpr int PADV = 12;

enum { B_FULL = 0, B_EMPTY = 3, B_WO = 6, B_TILE = 7, B_UCH = 8, B_KVP = 12, B_KVF = 13, B_OST = 14, B_RF = 15,
       B_RE = 18, B_COUNT = 21 };
__host__ __device__ constexpr int bar_count(int i) {
  return (i >= B_EMPTY && i < B_WO) ? 16 : (i == B_KVP || i == B_OST || i >= B_RE) ? 8 : 1;
}

constexpr int PD_OFF = 0, P2_OFF = 544, P3_OFF = 768;

constexpr int SL_K2048 = 20, SL_ZERO = 21, SL_510 = 22, SL_0 = 23;
__host__ __device__ constexpr int koff(int y) {
  return y < 8 ? y : y < 12 ? 256 + 2 * (y - 8) : y < 16 ? 512 + 256 * ((y - 12) >> 1) + 4 * (y & 1) : 1024 + 256 * (y - 16);
}
__host__ __device__ constexpr int kidx_c(int l) {
  const int y = l < 256 ? (l & 7) : l < 512 ? 8 + ((l & 7) >> 1) : l < 1024 ? 12 + (((l - 512) >> 8) << 1) + ((l >> 2) & 1)
                                                                            : 16 + ((l - 1024) >> 8);
  return ((l >> 3) & 31) * 24 + y;
}
constexpr int slot_direct(int l) {
  if (l < 0 || l > 510) return SL_ZERO;
  if (l == 510) return SL_510;
  if (l == 0) return SL_0;
  return kidx_c(l < 256 ? l : ((l + ((l >> 1) & 1)) & ~1));
}
constexpr int slot_seg2(int v, int k) { return (k >= 32 && k < 64) ? kidx_c(16 * k + 4 * v) : SL_ZERO; }
constexpr int slot_seg3(int pi, int k) {
  return (k >= 64 && k < 128) ? kidx_c(16 * k + 8 * pi) : ((k == 128 && pi == 0) ? SL_K2048 : SL_ZERO);
}
struct PTab { uint32_t v[960]; };
constexpr PTab make_ptab() {
  PTab t{};
  for (int w = 0; w < 960; ++w) t.v[w] = (SL_ZERO * 4) | ((SL_ZERO * 4) << 16);
  for (int w = 0; w < 544; ++w) t.v[w] = (slot_direct(w - 16) * 4) | ((slot_direct(w - 17) * 4) << 16);
  for (int v = 0; v < 4; ++v)
    for (int x = 16; x < 72; ++x) t.v[544 + 56 * v + x - 16] = (slot_seg2(v, x) * 4) | ((slot_seg2(v, x - 1) * 4) << 16);
  for (int pi = 0; pi < 2; ++pi)
    for (int x = 48; x < 136; ++x) t.v[768 + 88 * pi + x - 48] = (slot_seg3(pi, x) * 4) | ((slot_seg3(pi, x - 1) * 4) << 16);
  return t;
}
__device__ const PTab g_ptab = make_ptab();

__device__ __nv_bfloat16 g_uT[512 * 2048];
__device__ __nv_bfloat16 g_yT[512 * 2048];
__device__ __nv_bfloat16 g_o[2048 * 512];
__device__ float g_kv[2][8][4 * 272];
__device__ unsigned g_cnt[64 * 32];
__device__ unsigned g_epoch;
#define TS(slot) do { } while (0)
#define TSD(slot, v) do { } while (0)
enum { C_U = 0, C_KV = 8, C_O = 16, C_Y = 32 };

struct Maps {
  CUtensorMap x, w, wo, u, uT, yT, o, out;
};
struct Ptrs {
  const __nv_bfloat16 *A_re, *A_im, *B_re, *B_im, *C_re, *C_im, *log_dt, *Dskip;
  const __nv_bfloat16 *x, *wqkv, *wo;
  __nv_bfloat16 *uT, *yT;
};

DEVI uint32_t s2u(const void* p) { return (uint32_t)__cvta_generic_to_shared(p); }
DEVI void mbar_init(uint32_t b, uint32_t c) { asm volatile("mbarrier.init.shared::cta.b64 [%0], %1;" ::"r"(b), "r"(c) : "memory"); }
DEVI void mbar_expect_tx(uint32_t b, uint32_t bytes) {
  asm volatile("mbarrier.arrive.expect_tx.shared::cta.b64 _, [%0], %1;" ::"r"(b), "r"(bytes) : "memory");
}
DEVI void mbar_arrive(uint32_t b) { asm volatile("mbarrier.arrive.shared::cta.b64 _, [%0];" ::"r"(b) : "memory"); }
DEVI void mbar_arrive_cluster(uint32_t b, uint32_t cta) {
  asm volatile("{\n.reg .b32 r;\nmapa.shared::cluster.u32 r, %0, %1;\nmbarrier.arrive.shared::cluster.b64 _, [r];\n}"
               ::"r"(b), "r"(cta) : "memory");
}
DEVI void mbar_wait(uint32_t b, uint32_t parity) {
  asm volatile("{\n.reg .pred p;\nLAB_WAIT:\nmbarrier.try_wait.parity.shared::cta.b64 p, [%0], %1;\n@!p bra LAB_WAIT;\n}"
               ::"r"(b), "r"(parity) : "memory");
}
DEVI void bar_sync(int id, int n) { asm volatile("bar.sync %0, %1;" ::"r"(id), "r"(n) : "memory"); }
DEVI void bar_arrive(int id, int n) { asm volatile("bar.arrive %0, %1;" ::"r"(id), "r"(n) : "memory"); }
DEVI void fence_async_smem() { asm volatile("fence.proxy.async.shared::cta;" ::: "memory"); }
DEVI void fence_async_all() { asm volatile("fence.proxy.async;" ::: "memory"); }
DEVI void cluster_arrive() { asm volatile("barrier.cluster.arrive.relaxed.aligned;" ::: "memory"); }
DEVI void cluster_wait() { asm volatile("barrier.cluster.wait.aligned;" ::: "memory"); }

DEVI void tma_load_2d(uint32_t dst, const CUtensorMap* m, int c0, int c1, uint32_t bar) {
  asm volatile("cp.async.bulk.tensor.2d.shared::cluster.global.mbarrier::complete_tx::bytes [%0], [%1, {%3, %4}], [%2];"
               ::"r"(dst), "l"(m), "r"(bar), "r"(c0), "r"(c1) : "memory");
}
DEVI void tma_load_2d_mc(uint32_t dst, const CUtensorMap* m, int c0, int c1, uint32_t bar, uint16_t mask) {
  asm volatile("cp.async.bulk.tensor.2d.shared::cluster.global.mbarrier::complete_tx::bytes.multicast::cluster [%0], [%1, {%3, %4}], [%2], %5;"
               ::"r"(dst), "l"(m), "r"(bar), "r"(c0), "r"(c1), "h"(mask) : "memory");
}
DEVI void tma_store_2d(const CUtensorMap* m, uint32_t src, int c0, int c1) {
  asm volatile("cp.async.bulk.tensor.2d.global.shared::cta.bulk_group [%0, {%2, %3}], [%1];"
               ::"l"(m), "r"(src), "r"(c0), "r"(c1) : "memory");
}
DEVI void bulk_load(uint32_t dst, const void* src, uint32_t bytes, uint32_t bar) {
  asm volatile("cp.async.bulk.shared::cluster.global.mbarrier::complete_tx::bytes [%0], [%1], %2, [%3];"
               ::"r"(dst), "l"(src), "r"(bytes), "r"(bar) : "memory");
}
DEVI void bulk_store(void* dst, uint32_t src, uint32_t bytes) {
  asm volatile("cp.async.bulk.global.shared::cta.bulk_group [%0], [%1], %2;" ::"l"(dst), "r"(src), "r"(bytes) : "memory");
}
DEVI void bulk_reduce_add_f32(void* dst, uint32_t src, uint32_t bytes) {
  asm volatile("cp.reduce.async.bulk.global.shared::cta.bulk_group.add.f32 [%0], [%1], %2;" ::"l"(dst), "r"(src), "r"(bytes) : "memory");
}
DEVI void bulk_commit() { asm volatile("cp.async.bulk.commit_group;" ::: "memory"); }
DEVI void bulk_wait0() { asm volatile("cp.async.bulk.wait_group 0;" ::: "memory"); }
DEVI void bulk_wait_read0() { asm volatile("cp.async.bulk.wait_group.read 0;" ::: "memory"); }
DEVI void l2_prefetch(const void* p, uint32_t bytes) {
  asm volatile("cp.async.bulk.prefetch.L2.global [%0], %1;" ::"l"(p), "r"(bytes) : "memory");
}
DEVI void prefetch_tmap(const CUtensorMap* m) { asm volatile("prefetch.tensormap [%0];" ::"l"(m) : "memory"); }

DEVI void red_release_add(unsigned* p, unsigned v) {
  asm volatile("red.release.gpu.global.add.u32 [%0], %1;" ::"l"(p), "r"(v) : "memory");
}
DEVI void red_relaxed_add(unsigned* p, unsigned v) {
  asm volatile("red.relaxed.gpu.global.add.u32 [%0], %1;" ::"l"(p), "r"(v) : "memory");
}
DEVI unsigned ld_relaxed(const unsigned* p) {
  unsigned v;
  asm volatile("ld.relaxed.gpu.global.u32 %0, [%1];" : "=r"(v) : "l"(p) : "memory");
  return v;
}
DEVI void wait_counter(const unsigned* p, unsigned target) {
#pragma unroll 1
  for (int it = 0; (int)(ld_relaxed(p) - target) < 0; ++it)
    if (it > (1 << 22)) __trap();
}

DEVI void ldsm_x4(uint32_t (&r)[4], uint32_t a) {
  asm volatile("ldmatrix.sync.aligned.m8n8.x4.shared.b16 {%0,%1,%2,%3}, [%4];"
               : "=r"(r[0]), "=r"(r[1]), "=r"(r[2]), "=r"(r[3]) : "r"(a) : "memory");
}
DEVI void ldsm_x4_t(uint32_t (&r)[4], uint32_t a) {
  asm volatile("ldmatrix.sync.aligned.m8n8.x4.trans.shared.b16 {%0,%1,%2,%3}, [%4];"
               : "=r"(r[0]), "=r"(r[1]), "=r"(r[2]), "=r"(r[3]) : "r"(a) : "memory");
}
DEVI void ldsm_x2_t(uint32_t& r0, uint32_t& r1, uint32_t a) {
  asm volatile("ldmatrix.sync.aligned.m8n8.x2.trans.shared.b16 {%0,%1}, [%2];" : "=r"(r0), "=r"(r1) : "r"(a) : "memory");
}
DEVI void stsm_x4(uint32_t a, uint32_t r0, uint32_t r1, uint32_t r2, uint32_t r3) {
  asm volatile("stmatrix.sync.aligned.m8n8.x4.shared.b16 [%0], {%1,%2,%3,%4};"
               ::"r"(a), "r"(r0), "r"(r1), "r"(r2), "r"(r3) : "memory");
}
DEVI void stsm_x4_t(uint32_t a, uint32_t r0, uint32_t r1, uint32_t r2, uint32_t r3) {
  asm volatile("stmatrix.sync.aligned.m8n8.x4.trans.shared.b16 [%0], {%1,%2,%3,%4};"
               ::"r"(a), "r"(r0), "r"(r1), "r"(r2), "r"(r3) : "memory");
}
DEVI uint32_t lds32(uint32_t a) { uint32_t v; asm volatile("ld.shared.b32 %0, [%1];" : "=r"(v) : "r"(a) : "memory"); return v; }
DEVI float lds_f32(uint32_t a) { float v; asm volatile("ld.shared.f32 %0, [%1];" : "=f"(v) : "r"(a) : "memory"); return v; }
DEVI void sts32(uint32_t a, uint32_t v) { asm volatile("st.shared.b32 [%0], %1;" ::"r"(a), "r"(v) : "memory"); }
DEVI void sts_f32(uint32_t a, float v) { asm volatile("st.shared.f32 [%0], %1;" ::"r"(a), "f"(v) : "memory"); }
DEVI void sts_f32x2(uint32_t a, float x, float y) { asm volatile("st.shared.v2.f32 [%0], {%1,%2};" ::"r"(a), "f"(x), "f"(y) : "memory"); }
DEVI uint4 lds128(uint32_t a) {
  uint4 v;
  asm volatile("ld.shared.v4.b32 {%0,%1,%2,%3}, [%4];" : "=r"(v.x), "=r"(v.y), "=r"(v.z), "=r"(v.w) : "r"(a) : "memory");
  return v;
}
DEVI void sts128(uint32_t a, uint32_t x, uint32_t y, uint32_t z, uint32_t w) {
  asm volatile("st.shared.v4.b32 [%0], {%1,%2,%3,%4};" ::"r"(a), "r"(x), "r"(y), "r"(z), "r"(w) : "memory");
}

DEVI void mma_bf16(float (&d)[4], uint32_t a0, uint32_t a1, uint32_t a2, uint32_t a3, uint32_t b0, uint32_t b1) {
  asm("mma.sync.aligned.m16n8k16.row.col.f32.bf16.bf16.f32 {%0,%1,%2,%3}, {%4,%5,%6,%7}, {%8,%9}, {%0,%1,%2,%3};"
      : "+f"(d[0]), "+f"(d[1]), "+f"(d[2]), "+f"(d[3])
      : "r"(a0), "r"(a1), "r"(a2), "r"(a3), "r"(b0), "r"(b1));
}
DEVI void mma_f16(float (&d)[4], const uint32_t (&a)[4], uint32_t b0, uint32_t b1) {
  asm("mma.sync.aligned.m16n8k16.row.col.f32.f16.f16.f32 {%0,%1,%2,%3}, {%4,%5,%6,%7}, {%8,%9}, {%0,%1,%2,%3};"
      : "+f"(d[0]), "+f"(d[1]), "+f"(d[2]), "+f"(d[3])
      : "r"(a[0]), "r"(a[1]), "r"(a[2]), "r"(a[3]), "r"(b0), "r"(b1));
}
DEVI void mma_bf16v(float (&d)[4], const uint32_t (&a)[4], uint32_t b0, uint32_t b1) {
  asm volatile("mma.sync.aligned.m16n8k16.row.col.f32.bf16.bf16.f32 {%0,%1,%2,%3}, {%4,%5,%6,%7}, {%8,%9}, {%0,%1,%2,%3};"
               : "+f"(d[0]), "+f"(d[1]), "+f"(d[2]), "+f"(d[3])
               : "r"(a[0]), "r"(a[1]), "r"(a[2]), "r"(a[3]), "r"(b0), "r"(b1));
}
DEVI uint32_t pack_bf16(float lo, float hi) {
  uint32_t r;
  asm("cvt.rn.bf16x2.f32 %0, %1, %2;" : "=r"(r) : "f"(hi), "f"(lo));
  return r;
}
DEVI uint32_t pack_f16(float lo, float hi) {
  uint32_t r;
  asm("cvt.rn.f16x2.f32 %0, %1, %2;" : "=r"(r) : "f"(hi), "f"(lo));
  return r;
}
DEVI uint32_t ldg16(const __nv_bfloat16* p) {
  uint32_t v;
  asm volatile("ld.global.nc.u16 %0, [%1];" : "=r"(v) : "l"(p));
  return v;
}
DEVI bool elect_one() {
  uint32_t pred;
  asm volatile("{\n.reg .pred p;\nelect.sync _|p, 0xffffffff;\nselp.u32 %0, 1, 0, p;\n}" : "=r"(pred));
  return pred != 0;
}
DEVI float bf_lo(uint32_t v) { return __uint_as_float(v << 16); }
DEVI float bf_hi(uint32_t v) { return __uint_as_float(v & 0xffff0000u); }
DEVI float bf2f(__nv_bfloat16 v) { return __bfloat162float(v); }
DEVI float round_bf16(float v) { return __bfloat162float(__float2bfloat16_rn(v)); }
DEVI float rcp(float x) { float r; asm("rcp.approx.ftz.f32 %0, %1;" : "=f"(r) : "f"(x)); return r; }
DEVI float ex2(float x) { float r; asm("ex2.approx.ftz.f32 %0, %1;" : "=f"(r) : "f"(x)); return r; }

DEVI void wg_fence() { asm volatile("wgmma.fence.sync.aligned;" ::: "memory"); }
DEVI void wg_commit() { asm volatile("wgmma.commit_group.sync.aligned;" ::: "memory"); }
template <int N> DEVI void wg_wait() { asm volatile("wgmma.wait_group.sync.aligned %0;" ::"n"(N) : "memory"); }
constexpr uint32_t DESC_HI = (1u << 30) | (1024 >> 4);
DEVI uint32_t mkdesc(uint32_t saddr, uint32_t lbo) { return ((saddr & 0x3FFFF) >> 4) | ((lbo >> 4) << 16); }

#define R8(b) "%" #b
DEVI void wgmma_n192(float (&d)[96], uint32_t da, uint32_t db, int scale_d) {
  asm volatile(
      "{\n.reg .pred p;\n.reg .b64 da, db;\nsetp.ne.b32 p, %98, 0;\nmov.b64 da, {%96, %99};\nmov.b64 db, {%97, %99};\n"
      "wgmma.mma_async.sync.aligned.m64n192k16.f32.bf16.bf16 "
      "{%0,%1,%2,%3,%4,%5,%6,%7,%8,%9,%10,%11,%12,%13,%14,%15,"
      "%16,%17,%18,%19,%20,%21,%22,%23,%24,%25,%26,%27,%28,%29,%30,%31,"
      "%32,%33,%34,%35,%36,%37,%38,%39,%40,%41,%42,%43,%44,%45,%46,%47,"
      "%48,%49,%50,%51,%52,%53,%54,%55,%56,%57,%58,%59,%60,%61,%62,%63,"
      "%64,%65,%66,%67,%68,%69,%70,%71,%72,%73,%74,%75,%76,%77,%78,%79,"
      "%80,%81,%82,%83,%84,%85,%86,%87,%88,%89,%90,%91,%92,%93,%94,%95}, "
      "da, db, p, 1, 1, 0, 1;\n}"
      : "+f"(d[0]), "+f"(d[1]), "+f"(d[2]), "+f"(d[3]), "+f"(d[4]), "+f"(d[5]), "+f"(d[6]), "+f"(d[7]),
        "+f"(d[8]), "+f"(d[9]), "+f"(d[10]), "+f"(d[11]), "+f"(d[12]), "+f"(d[13]), "+f"(d[14]), "+f"(d[15]),
        "+f"(d[16]), "+f"(d[17]), "+f"(d[18]), "+f"(d[19]), "+f"(d[20]), "+f"(d[21]), "+f"(d[22]), "+f"(d[23]),
        "+f"(d[24]), "+f"(d[25]), "+f"(d[26]), "+f"(d[27]), "+f"(d[28]), "+f"(d[29]), "+f"(d[30]), "+f"(d[31]),
        "+f"(d[32]), "+f"(d[33]), "+f"(d[34]), "+f"(d[35]), "+f"(d[36]), "+f"(d[37]), "+f"(d[38]), "+f"(d[39]),
        "+f"(d[40]), "+f"(d[41]), "+f"(d[42]), "+f"(d[43]), "+f"(d[44]), "+f"(d[45]), "+f"(d[46]), "+f"(d[47]),
        "+f"(d[48]), "+f"(d[49]), "+f"(d[50]), "+f"(d[51]), "+f"(d[52]), "+f"(d[53]), "+f"(d[54]), "+f"(d[55]),
        "+f"(d[56]), "+f"(d[57]), "+f"(d[58]), "+f"(d[59]), "+f"(d[60]), "+f"(d[61]), "+f"(d[62]), "+f"(d[63]),
        "+f"(d[64]), "+f"(d[65]), "+f"(d[66]), "+f"(d[67]), "+f"(d[68]), "+f"(d[69]), "+f"(d[70]), "+f"(d[71]),
        "+f"(d[72]), "+f"(d[73]), "+f"(d[74]), "+f"(d[75]), "+f"(d[76]), "+f"(d[77]), "+f"(d[78]), "+f"(d[79]),
        "+f"(d[80]), "+f"(d[81]), "+f"(d[82]), "+f"(d[83]), "+f"(d[84]), "+f"(d[85]), "+f"(d[86]), "+f"(d[87]),
        "+f"(d[88]), "+f"(d[89]), "+f"(d[90]), "+f"(d[91]), "+f"(d[92]), "+f"(d[93]), "+f"(d[94]), "+f"(d[95])
      : "r"(da), "r"(db), "r"(scale_d), "n"(DESC_HI));
}
DEVI void wgmma_n64(float (&d)[32], uint32_t da, uint32_t db, int scale_d) {
  asm volatile(
      "{\n.reg .pred p;\n.reg .b64 da, db;\nsetp.ne.b32 p, %34, 0;\nmov.b64 da, {%32, %35};\nmov.b64 db, {%33, %35};\n"
      "wgmma.mma_async.sync.aligned.m64n64k16.f32.bf16.bf16 "
      "{%0,%1,%2,%3,%4,%5,%6,%7,%8,%9,%10,%11,%12,%13,%14,%15,"
      "%16,%17,%18,%19,%20,%21,%22,%23,%24,%25,%26,%27,%28,%29,%30,%31}, "
      "da, db, p, 1, 1, 0, 1;\n}"
      : "+f"(d[0]), "+f"(d[1]), "+f"(d[2]), "+f"(d[3]), "+f"(d[4]), "+f"(d[5]), "+f"(d[6]), "+f"(d[7]),
        "+f"(d[8]), "+f"(d[9]), "+f"(d[10]), "+f"(d[11]), "+f"(d[12]), "+f"(d[13]), "+f"(d[14]), "+f"(d[15]),
        "+f"(d[16]), "+f"(d[17]), "+f"(d[18]), "+f"(d[19]), "+f"(d[20]), "+f"(d[21]), "+f"(d[22]), "+f"(d[23]),
        "+f"(d[24]), "+f"(d[25]), "+f"(d[26]), "+f"(d[27]), "+f"(d[28]), "+f"(d[29]), "+f"(d[30]), "+f"(d[31])
      : "r"(da), "r"(db), "r"(scale_d), "n"(DESC_HI));
}

struct C32 { float re, im; };
DEVI C32 csq(C32 a) { return {a.re * a.re - a.im * a.im, 2.f * a.re * a.im}; }
DEVI C32 cmul(C32 a, C32 b) { return {a.re * b.re - a.im * b.im, a.re * b.im + a.im * b.re}; }
DEVI C32 cfresh(float zl, float zi, float m) {
  float mag = ex2(zl * m), ph = zi * m;
  return {mag * __cosf(ph), mag * __sinf(ph)};
}
struct HMul { uint32_t b, bp; };
DEVI HMul mk_mul(float re, float im) { return {pack_f16(re, im), pack_f16(-im, re)}; }
DEVI uint32_t hcmul(uint32_t a, const HMul& m) {
  __half2 ah = *reinterpret_cast<__half2*>(&a);
  __half2 b = *reinterpret_cast<const __half2*>(&m.b), bp = *reinterpret_cast<const __half2*>(&m.bp);
  __half2 r = __hfma2(__high2half2(ah), bp, __hmul2(__low2half2(ah), b));
  return *reinterpret_cast<uint32_t*>(&r);
}
DEVI uint32_t badd(uint32_t a, uint32_t b) {
  __nv_bfloat162 r = __hadd2(*reinterpret_cast<__nv_bfloat162*>(&a), *reinterpret_cast<__nv_bfloat162*>(&b));
  return *reinterpret_cast<uint32_t*>(&r);
}
template <int MU0, int NMU, int DMAX>
DEVI void conv_tail(float (&acc)[16][4], uint32_t p_lane, uint32_t v_base, int back, bool edge, int lane) {
  const int hsel = (lane >> 3) & 1;
  const int row = (lane & 7) + ((lane >> 4) << 3) + PADV - 8 - (back & (hsel ^ 1));
  const uint32_t la = v_base + row * 32 + (((hsel ^ back) ^ ((row >> 2) & 1)) << 4);
  uint32_t M[3][4];
  ldsm_x4_t(M[0], la);
  ldsm_x4_t(M[1], la + 256);
  uint32_t H[2 * NMU];
#pragma unroll
  for (int i = 0; i < 2 * NMU; ++i) H[i ^ 1] = lds32(p_lane + (uint32_t)(MU0 - 1 + i) * 32);
  if (edge) {
    const uint32_t a[4] = {0u, 0u, M[0][0], M[0][1]};
#pragma unroll
    for (int k = 1; k < NMU; ++k) mma_bf16v(acc[MU0 - 2 + 2 * k], a, H[2 * k], H[2 * k + 1]);
  }
#pragma unroll
  for (int delta = -1; delta <= DMAX; ++delta) {
    if (delta + 2 <= DMAX) ldsm_x4_t(M[(delta + 3) % 3], la + (delta + 3) * 256);
#pragma unroll
    for (int k = 0; k < NMU; ++k)
      if (delta + MU0 + 2 * k < 16) mma_bf16v(acc[delta + MU0 + 2 * k], M[(delta + 1) % 3], H[2 * k], H[2 * k + 1]);
  }
}

__global__ void __cluster_dims__(2, 1, 1) __launch_bounds__(NTHREADS, 1)
fused_kernel(const __grid_constant__ Maps maps, const Ptrs p) {
  extern __shared__ __align__(1024) uint8_t smem[];
  const uint32_t sb = s2u(smem);
  const int tid = threadIdx.x, lane = tid & 31;
  const int warp = __shfl_sync(0xffffffffu, tid >> 5, 0);
  const int cta = blockIdx.x;
  const uint32_t rank = cta & 1;
  const int ti = 2 * (cta >> 4) + rank;
  const int tj = (cta >> 1) & 7;
  const uint32_t bars = sb + SM_BAR;
#define BAR(i) (bars + 8 * (i))
  const int g = lane >> 2, q = lane & 3;

  const int kch = warp & 3, krd = warp >> 2;
  float zr, zi, wr, wi;
  {
    const size_t po = (size_t)(cta * 4 + kch) * 128 + krd * 32 + lane;
    const uint32_t r_ar = ldg16(p.A_re + po), r_ai = ldg16(p.A_im + po), r_br = ldg16(p.B_re + po), r_bi = ldg16(p.B_im + po);
    const uint32_t r_cr = ldg16(p.C_re + po), r_ci = ldg16(p.C_im + po), r_ldt = ldg16(p.log_dt + cta * 4 + kch);
    uint4 pt;
    if (tid < 240) pt = __ldg((const uint4*)g_ptab.v + tid);
    if (tid == 384) {
      TS(0);
#pragma unroll
      for (int i = 0; i < B_COUNT; ++i) mbar_init(BAR(i), bar_count(i));
      asm volatile("fence.mbarrier_init.release.cluster;" ::: "memory");
      prefetch_tmap(&maps.x); prefetch_tmap(&maps.w); prefetch_tmap(&maps.u);
    }
    __syncthreads();
    cluster_arrive();
    if (warp >= 12) {
      cluster_wait();
      if (elect_one()) {
        if (warp == 13) {
          mbar_expect_tx(BAR(B_TILE), 16384);
          tma_load_2d(sb + SM_U, &maps.u, tj * 64, ti * 128, BAR(B_TILE));
          l2_prefetch((const char*)p.wqkv + 192 * 3072 + cta * 7680, 7680);
          l2_prefetch((const char*)p.x + (size_t)cta * 16384, 16384);
          l2_prefetch((const char*)p.wo + (size_t)cta * 4096, 4096);
        } else {
          const int ks = warp == 12 ? 0 : warp - 13;
          const uint32_t st = sb + ks * STG_BYTES, fb = BAR(B_FULL + ks);
          if (warp == 12) TS(61);
          mbar_expect_tx(fb, STG_BYTES);
          tma_load_2d(st + STG_X, &maps.x, ks * 64, ti * 128, fb);
#pragma unroll 1
          for (int nb = 0; nb < 3; ++nb)
            tma_load_2d_mc(st + STG_W + nb * 8192 + rank * 4096, &maps.w, nb * 512 + tj * 64, ks * 64 + rank * 32, fb, 3);
        }
      }
      __syncwarp();
    }
    if (tid < 240) sts128(sb + SM_PTAB + tid * 16, pt.x, pt.y, pt.z, pt.w);
    const float dt = round_bf16(expf(bf_lo(r_ldt)));
    zr = dt * bf_lo(r_ar); zi = dt * bf_lo(r_ai);
    const float dbr = dt * bf_lo(r_br), dbi = dt * bf_lo(r_bi), cr = bf_lo(r_cr), ci = bf_lo(r_ci);
    wr = cr * dbr - ci * dbi; wi = cr * dbi + ci * dbr;
  }
  {
    const float mz = __uint_as_float(__reduce_max_sync(0xffffffffu, __float_as_uint(fmaxf(zr, 0.f))));
    const int E = min(max((int)(__reduce_max_sync(0xffffffffu, __float_as_uint(fmaxf(fabsf(wr), fabsf(wi)))) >> 23), 1), 252);
    const float sc = __int_as_float((253 - E) << 23), inv = __int_as_float((E + 1) << 23);
    const float zl = (zr - mz) * 1.4426950408889634f;
    const uint32_t tb = sb + SM_VV + kch * VV_BYTES + krd * KG_BYTES;
    const uint32_t sta = tb + (((lane >> 2) << 4) | ((lane & 3) << 2));
    auto put = [&](int r, uint32_t v) { sts32((sta ^ ((r & 7) << 4)) + r * 128, v); };
    const uint32_t lda = tb + ((lane & 7) + (((lane >> 3) & 1) << 3)) * 128;
    const uint32_t ldb = tb + ((lane & 7) + ((lane >> 4) << 3)) * 128;
    C32 e1 = cfresh(zl, zi, 1.f), e2 = csq(e1), e4 = csq(e2), e8 = csq(e4);
    C32 e16 = cfresh(zl, zi, 16.f), e32 = csq(e16), e64 = csq(e32), e128 = csq(e64);
    C32 e256 = cfresh(zl, zi, 256.f), e512 = csq(e256), e1024 = csq(e512), e768 = cmul(e512, e256);
    uint32_t XA[2][4][4];
    {
      const HMul m16 = mk_mul(e16.re, e16.im), m32 = mk_mul(e32.re, e32.im), m64 = mk_mul(e64.re, e64.im);
      const HMul m128 = mk_mul(e128.re, e128.im);
      uint32_t X[16];
      X[0] = 0x00003c00u; X[1] = pack_f16(e8.re, e8.im); X[2] = m16.b; X[4] = m32.b; X[8] = m64.b;
      X[3] = hcmul(X[1], m16); X[5] = hcmul(X[1], m32); X[6] = hcmul(X[2], m32); X[7] = hcmul(X[3], m32);
#pragma unroll
      for (int r = 1; r < 8; ++r) X[8 + r] = hcmul(X[r], m64);
#pragma unroll
      for (int h = 0; h < 2; ++h) {
#pragma unroll
        for (int r = 0; r < 16; ++r) put(r, h == 0 ? X[r] : r == 0 ? m128.b : hcmul(X[r], m128));
        __syncwarp();
#pragma unroll
        for (int k = 0; k < 4; ++k) ldsm_x4(XA[h][k], lda + (((2 * k + (lane >> 4)) ^ (lane & 7)) << 4));
        __syncwarp();
      }
    }
    float D[2][3][4];
#pragma unroll
    for (int t = 0; t < 6; ++t) D[t / 3][t % 3][0] = D[t / 3][t % 3][1] = D[t / 3][t % 3][2] = D[t / 3][t % 3][3] = 0.f;
    auto contract = [&](int t0, int nt) {
      __syncwarp();
#pragma unroll
      for (int k = 0; k < 4; ++k) {
        uint32_t b[4];
        ldsm_x4(b, ldb + (((2 * k + ((lane >> 3) & 1)) ^ (lane & 7)) << 4));
#pragma unroll
        for (int h = 0; h < 2; ++h) {
          mma_f16(D[h][t0], XA[h][k], b[0], b[1]);
          if (nt == 2) mma_f16(D[h][t0 + 1], XA[h][k], b[2], b[3]);
        }
      }
      __syncwarp();
    };
    const HMul c1 = mk_mul(e1.re, -e1.im), c2 = mk_mul(e2.re, -e2.im), c4 = mk_mul(e4.re, -e4.im);
    const HMul c256 = mk_mul(e256.re, -e256.im), c512 = mk_mul(e512.re, -e512.im), c768 = mk_mul(e768.re, -e768.im);
    const HMul c1024 = mk_mul(e1024.re, -e1024.im);
    uint32_t W[8];
    W[0] = pack_f16(wr * sc, -wi * sc);
    W[1] = hcmul(W[0], c1); W[2] = hcmul(W[0], c2); W[3] = hcmul(W[1], c2);
    W[4] = hcmul(W[0], c4); W[5] = hcmul(W[1], c4); W[6] = hcmul(W[2], c4); W[7] = hcmul(W[3], c4);
#pragma unroll
    for (int i = 0; i < 8; ++i) put(i, W[i]);
#pragma unroll
    for (int i = 0; i < 4; ++i) put(8 + i, hcmul(W[2 * i], c256));
    put(12, hcmul(W[0], c512)); put(13, hcmul(W[4], c512)); put(14, hcmul(W[0], c768)); put(15, hcmul(W[4], c768));
    contract(0, 2);
    const uint32_t v0 = hcmul(W[0], c1024);
    put(0, v0); put(1, hcmul(v0, c256)); put(2, hcmul(v0, c512)); put(3, hcmul(v0, c768)); put(4, hcmul(v0, c1024));
    contract(2, 1);
    const uint32_t a = tb + (g * 24 + 2 * q) * 4;
#pragma unroll
    for (int t = 0; t < 6; ++t) {
      const float(&d)[4] = D[t / 3][t % 3];
      sts_f32x2(a + (t / 3) * 1536 + (t % 3) * 32, d[0] * inv, d[1] * inv);
      sts_f32x2(a + (t / 3) * 1536 + (t % 3) * 32 + 768, d[2] * inv, d[3] * inv);
    }
    if (mz > 0.f) {
      __syncwarp();
#pragma unroll 1
      for (int i = lane; i < 768; i += 32) {
        const int r = i / 24, y = i - 24 * r;
        sts_f32(tb + i * 4, lds_f32(tb + i * 4) * ex2(mz * 1.4426950408889634f * (koff(y) + 8 * r)));
      }
    }
  }
  if (tid == 0) TS(2);
  if (warp < 12) cluster_wait();
  __syncthreads();

  if (warp < 4) {
    asm volatile("setmaxnreg.inc.sync.aligned.u32 152;");
    const unsigned epoch = __ldcg(&g_epoch);
    const int d = cta * 4 + warp;
    const uint32_t vv = sb + SM_VV + warp * VV_BYTES;
    const uint32_t ub = sb + SM_U + warp * U_BYTES;
    const uint32_t pb = sb + SM_P + warp * P_BYTES;
    const float dskip = bf2f(p.Dskip[d]);
#pragma unroll 1
    for (int pass = 0; pass < 2; ++pass) {
      if (pass == 1) {
        const uint32_t kf = vv;
#pragma unroll 1
        for (int i0 = 0; i0 < 24; i0 += 4) {
          float a[4][4];
#pragma unroll
          for (int i = 0; i < 4; ++i)
#pragma unroll
            for (int r = 0; r < 4; ++r) a[i][r] = lds_f32(kf + r * KG_BYTES + ((i0 + i) * 32 + lane) * 4);
#pragma unroll
          for (int i = 0; i < 4; ++i) sts_f32(kf + ((i0 + i) * 32 + lane) * 4, (a[i][0] + a[i][1]) + (a[i][2] + a[i][3]));
        }
        __syncwarp();
        const float k1024 = lds_f32(kf + kidx_c(1024) * 4);
        if (lane == 0) {
          sts_f32(kf + SL_ZERO * 4, 0.f);
          sts_f32(kf + SL_510 * 4, lds_f32(kf + kidx_c(510) * 4) - lds_f32(kf + kidx_c(512) * 4));
          sts_f32(kf + SL_0 * 4, lds_f32(kf) + dskip);
        }
        __syncwarp();
#pragma unroll 1
        for (int i0 = 0; i0 < 30; i0 += 6) {
          uint32_t e[6];
          float a[6], b[6];
#pragma unroll
          for (int i = 0; i < 6; ++i) e[i] = lds32(sb + SM_PTAB + ((i0 + i) * 32 + lane) * 4);
#pragma unroll
          for (int i = 0; i < 6; ++i) { a[i] = lds_f32(kf + (e[i] & 0xffff)); b[i] = lds_f32(kf + (e[i] >> 16)); }
#pragma unroll
          for (int i = 0; i < 6; ++i) sts32(pb + ((i0 + i) * 32 + lane) * 4, pack_bf16(a[i], b[i]));
        }
        if (lane < 16) sts128(ub + lane * 16, 0, 0, 0, 0);
        if (elect_one()) {
          TS(4);
          wait_counter(&g_cnt[(C_U + (cta >> 4)) * 32], (epoch + 1) * 16);
          mbar_expect_tx(BAR(B_UCH + warp), 4096);
          bulk_load(ub + 256, p.uT + (size_t)d * 2048, 4096, BAR(B_UCH + warp));
        }
        __syncwarp();
        mbar_wait(BAR(B_UCH + warp), 0);
        if (lane == 0) TS(5);
#pragma unroll 1
        for (int it = 0; it < 8; ++it) {
          const int k = -18 + it * 32 + lane;
          const int kr = min(max(k, -2), 208);
          uint32_t E[12];
#pragma unroll
          for (int c = 0; c < 3; ++c) {
            const int kk = kr - 1 + c, r = (kk >> 1) + 8;
            const uint4 t = lds128(ub + r * 32 + (((kk & 1) ^ ((r >> 2) & 1)) << 4));
            E[4 * c] = t.x; E[4 * c + 1] = t.y; E[4 * c + 2] = t.z; E[4 * c + 3] = t.w;
          }
          uint32_t O[8];
#pragma unroll
          for (int j = 0; j < 8; ++j) O[j] = __byte_perm(E[j + 1], E[j + 2], 0x5432);
          uint32_t s3[6], s5[4], s7[4], s9[4];
#pragma unroll
          for (int j = 0; j < 6; ++j) s3[j] = badd(badd(O[j], O[j + 1]), E[j + 2]);
#pragma unroll
          for (int j = 0; j < 4; ++j) {
            s5[j] = badd(s3[j + 2], badd(E[j + 3], E[j + 5]));
            s7[j] = badd(s5[j], badd(O[j + 1], O[j + 4]));
            s9[j] = badd(s7[j], badd(E[j + 2], E[j + 6]));
          }
          const int r = (k >> 1) + PADV;
          const uint32_t a = vv + r * 32 + (((k & 1) ^ ((r >> 2) & 1)) << 4);
          if (k < 208) { sts128(a + VV_U3, s3[0], s3[1], s3[2], s3[3]); sts128(a + VV_U5, s5[0], s5[1], s5[2], s5[3]); }
          if (k < 144) { sts128(a + VV_U7, s7[0], s7[1], s7[2], s7[3]); sts128(a + VV_U9, s9[0], s9[1], s9[2], s9[3]); }
        }
        __syncwarp();
        if (lane == 0) TS(6);
        const int gq = g - 2 * q;
        uint32_t h127, h128;
        {
          const uint32_t kf2 = pack_bf16(k1024, k1024) ^ 0x80008000u;
          h127 = (gq == 4 ? 0x0000ffffu : gq == 5 ? 0xffffffffu : gq == 6 ? 0xffff0000u : 0u) & kf2;
          h128 = (gq == -4 ? 0x0000ffffu : gq == -3 ? 0xffffffffu : gq == -2 ? 0xffff0000u : 0u) & kf2;
        }
        bar_sync(4, 384);
        if (lane == 0) TS(7);
        float acc[16][4];
#pragma unroll
        for (int i = 0; i < 16; ++i) { acc[i][0] = acc[i][1] = acc[i][2] = acc[i][3] = 0.f; }
        {
          const uint32_t pd_lane = pb + (PD_OFF + 16 + gq) * 4;
          const int prow0 = 8 + (lane & 7) + ((lane >> 4) << 3), hs = (lane >> 3) & 1;
          uint32_t B[2][4][4];
          uint32_t A[4][4];
          const uint32_t la0 = ub + prow0 * 32 + ((hs ^ ((prow0 >> 2) & 1)) << 4);
#pragma unroll
          for (int m2 = 0; m2 < 4; ++m2) ldsm_x4(B[0][m2], la0 + m2 * 512);
#pragma unroll
          for (int i = 0; i < 4; ++i) {
            const uint32_t a = pd_lane + i * 512;
            A[i][0] = lds32(a); A[i][1] = lds32(a + 32); A[i][2] = lds32(a - 32); A[i][3] = A[i][0];
          }
          uint32_t la = la0;
#pragma unroll 1
          for (int rho = 0; rho < 8; ++rho) {
#pragma unroll
            for (int m2 = 0; m2 < 4; ++m2) ldsm_x4(B[1][m2], la + (4 + m2) * 512);
#pragma unroll
            for (int i = 0; i < 4; ++i)
#pragma unroll
              for (int m = 0; m < 8; ++m) mma_bf16v(acc[m + i], A[i], B[0][m >> 1][2 * (m & 1)], B[0][m >> 1][2 * (m & 1) + 1]);
            const int prow = prow0 - min(rho + 1, 7);
            la = ub + prow * 32 + ((hs ^ ((prow >> 2) & 1)) << 4);
#pragma unroll
            for (int m2 = 0; m2 < 4; ++m2) ldsm_x4(B[0][m2], la + m2 * 512);
            const uint32_t pa = pd_lane + (rho + 1) * 64;
#pragma unroll
            for (int i = 0; i < 4; ++i) {
#pragma unroll
              for (int m = 0; m < 8 - i; ++m)
                mma_bf16v(acc[8 + m + i], A[i], B[1][m >> 1][2 * (m & 1)], B[1][m >> 1][2 * (m & 1) + 1]);
              A[i][0] = lds32(pa + i * 512); A[i][1] = lds32(pa + i * 512 + 32); A[i][2] = lds32(pa + i * 512 - 32);
              A[i][3] = A[i][0];
            }
          }
          {
            uint32_t b8[4];
            ldsm_x4(b8, la + 4 * 512);
            const uint32_t h63 = lds32(pd_lane + 63 * 32), h64 = lds32(pd_lane + 64 * 32);
            const uint32_t a63[4] = {0u, h127, 0u, 0u}, a32[4] = {h64, 0u, h63, h64}, a64[4] = {h128, 0u, h127, h128};
#pragma unroll
            for (int m2 = 0; m2 < 4; ++m2) ldsm_x4(B[1][m2], la0 + m2 * 512);
#pragma unroll
            for (int m = 0; m < 8; ++m) mma_bf16v(acc[m + 7], a63, B[0][m >> 1][2 * (m & 1)], B[0][m >> 1][2 * (m & 1) + 1]);
#pragma unroll
            for (int m2 = 0; m2 < 2; ++m2) ldsm_x4(B[0][m2], la0 + (4 + m2) * 512);
#pragma unroll
            for (int m = 0; m < 8; ++m) mma_bf16v(acc[m + 4], a32, B[1][m >> 1][2 * (m & 1)], B[1][m >> 1][2 * (m & 1) + 1]);
            mma_bf16v(acc[15], a63, b8[0], b8[1]);
#pragma unroll
            for (int m = 0; m < 8; ++m) mma_bf16v(acc[m + 8], a64, B[1][m >> 1][2 * (m & 1)], B[1][m >> 1][2 * (m & 1) + 1]);
#pragma unroll
            for (int m = 0; m < 4; ++m) mma_bf16v(acc[m + 12], a32, B[0][m >> 1][2 * (m & 1)], B[0][m >> 1][2 * (m & 1) + 1]);
          }
#pragma unroll 1
          for (int v = 0; v < 4; ++v)
            conv_tail<4, 3, 11>(acc, pb + (P2_OFF + 56 * v + gq - 16) * 4, vv + ((v & 1) ? VV_U3 : VV_U5), v >> 1, v == 0, lane);
#pragma unroll 1
          for (int pi = 0; pi < 2; ++pi)
            conv_tail<8, 5, 7>(acc, pb + (P3_OFF + 88 * pi + gq - 48) * 4, vv + (pi ? VV_U7 : VV_U9), pi, pi == 0, lane);
        }
        bar_arrive(3, 384);
        if (lane == 0) TS(8);
        {
          const int mt = lane >> 3;
          const uint32_t a = vv + (128 * (mt >> 1) + 16 * (lane & 7) + 8 * (mt & 1)) * 2;
#pragma unroll
          for (int ab = 0; ab < 16; ab += 2)
            stsm_x4_t(a + ab * 256, pack_bf16(acc[ab][0], acc[ab][1]), pack_bf16(acc[ab][2], acc[ab][3]),
                      pack_bf16(acc[ab + 1][0], acc[ab + 1][1]), pack_bf16(acc[ab + 1][2], acc[ab + 1][3]));
        }
        fence_async_smem();
        __syncwarp();
        if (elect_one()) {
          bulk_store(p.yT + (size_t)d * 2048, vv, 4096);
          bulk_commit();
          bulk_wait0();
          red_relaxed_add(&g_cnt[(C_Y + (cta >> 4)) * 32], 1);
          TS(9);
        }
        bar_sync(2, 128);
        if (warp == 0 && elect_one()) {
          wait_counter(&g_cnt[(C_Y + tj) * 32], (epoch + 1) * 64);
          TS(28);
          mbar_expect_tx(BAR(B_TILE), 16384);
          tma_load_2d(sb + SM_U, &maps.yT, ti * 128, tj * 64, BAR(B_TILE));
          tma_load_2d(sb + SM_U + 8192, &maps.yT, ti * 128 + 64, tj * 64, BAR(B_TILE));
        }
        __syncwarp();
      }
      mbar_wait(BAR(B_TILE), pass);
      if (lane == 0) TS(26 + 3 * pass);
      {
        const int m = lane >> 3, r = lane & 7;
#pragma unroll 2
        for (int it = 0; it < 8; ++it) {
          const int tb = warp * 4 + (it >> 1), cb = (it & 1) * 4 + m;
          const uint32_t at = (tb * 8 + r) * 128 + ((cb ^ r) << 4);
          const uint32_t ac = (tb >> 3) * 8192 + (cb * 8 + r) * 128 + (((tb & 7) ^ (pass ? 0 : tb >> 3) ^ r) << 4);
          uint32_t v[4];
          ldsm_x4_t(v, sb + SM_U + (pass ? ac : at));
          stsm_x4(sb + SM_P + (pass ? at : ac), v[0], v[1], v[2], v[3]);
        }
      }
      fence_async_smem();
      bar_sync(2, 128);
      if (warp == 0 && elect_one()) {
        if (pass == 0) {
          tma_store_2d(&maps.uT, sb + SM_P, ti * 128, tj * 64);
          tma_store_2d(&maps.uT, sb + SM_P + 8192, ti * 128 + 64, tj * 64);
          bulk_commit();
          bulk_wait0();
          red_relaxed_add(&g_cnt[(C_U + tj) * 32], 1);
          TS(27);
        } else {
          tma_store_2d(&maps.out, sb + SM_P, 64 * tj, 128 * ti);
          bulk_commit();
          bulk_wait_read0();
          TS(30);
        }
      }
      if (pass == 0) bar_sync(2, 128);
    }
  } else if (warp < 12) {
    asm volatile("setmaxnreg.inc.sync.aligned.u32 160;");
    const int w8 = warp - 4;
    const int row = w8 * 16 + (lane & 7) + (((lane >> 3) & 1) << 3);
    {
      float acc[96];
#pragma unroll 1
      for (int ks = 0, s = 0, ph = 0; ks < 8; ++ks) {
        mbar_wait(BAR(B_FULL + s), ph);
        if (tid == 128) TS(ks == 0 ? 16 : 9 + ks + (ks > 6 ? 46 : 0));
        const uint32_t st = sb + s * STG_BYTES;
        const uint32_t da = mkdesc(st + STG_X + (w8 >> 2) * 8192, 16);
        const uint32_t db = mkdesc(st + STG_W, 8192);
        wg_fence();
#pragma unroll
        for (int k = 0; k < 4; ++k) wgmma_n192(acc, da + 2 * k, db + 128 * k, (ks | k) != 0);
        wg_commit();
        const uint32_t eprev = BAR(B_EMPTY + (s == 0 ? 2 : s - 1));
        if (++s == 3) { s = 0; ph ^= 1; }
        if (ks > 0) {
          wg_wait<1>();
          if (lane < 2) mbar_arrive_cluster(eprev, lane);
        }
      }
      wg_wait<0>();
      if (lane < 2) mbar_arrive_cluster(BAR(B_EMPTY + 1), lane);
      bar_arrive(4, 384);
      if (tid == 128) TS(17);
      bar_sync(1, 256);
#pragma unroll
      for (int i = 0; i < 24; i += 2)
        stsm_x4(sb + SM_QS + row * 128 + (i >> 3) * 16384 + ((((i & 7) + (lane >> 4)) ^ (row & 7)) << 4),
                pack_bf16(acc[4 * i], acc[4 * i + 1]), pack_bf16(acc[4 * i + 2], acc[4 * i + 3]),
                pack_bf16(acc[4 * i + 4], acc[4 * i + 5]), pack_bf16(acc[4 * i + 6], acc[4 * i + 7]));
    }
    __syncwarp();
#pragma unroll 1
    for (int part = 1; part >= 0; --part) {
      const uint32_t pa = sb + SM_QS + part * 16384 + w8 * 2048 + lane * 16;
#pragma unroll 1
      for (int it = 0; it < 4; ++it) {
        uint4 t = lds128(pa + it * 512);
        uint32_t* tw = &t.x;
#pragma unroll
        for (int j = 0; j < 4; ++j) {
          const uint32_t x = tw[j];
          const __nv_bfloat162 xb = *reinterpret_cast<const __nv_bfloat162*>(&x);
          const uint32_t e = pack_bf16(ex2(bf_lo(x) * 1.4426950408889634f), ex2(bf_hi(x) * 1.4426950408889634f));
          const uint32_t m = __hgt2_mask(xb, __floats2bfloat162_rn(0.f, 0.f));
          const uint32_t sel = (badd(x, 0x3f803f80u) & m) | (e & ~m);
          tw[j] = pack_bf16(bf_lo(sel) + 1e-6f, bf_hi(sel) + 1e-6f);
        }
        sts128(pa + it * 512, t.x, t.y, t.z, t.w);
      }
      if (part == 1) {
        if (tid == 128) TS(53);
        bar_sync(1, 256);
        const int hh = w8 >> 1, dtile = w8 & 1;
        float kv[4] = {0.f, 0.f, 0.f, 0.f}, zz[4] = {0.f, 0.f, 0.f, 0.f};
        const int m = lane >> 3;
        const uint32_t aa = sb + SM_VS + ((lane & 7) + ((m >> 1) << 3)) * 128 + (((2 * hh + (m & 1)) ^ (lane & 7)) << 4);
        const uint32_t ab = sb + SM_PK + (lane & 15) * 128 + (((2 * hh + dtile) ^ (lane & 7)) << 4);
#pragma unroll 2
        for (int ks = 0; ks < 8; ++ks) {
          uint32_t a[4], b0, b1;
          ldsm_x4_t(a, aa + ks * 2048);
          ldsm_x2_t(b0, b1, ab + ks * 2048);
          mma_bf16(kv, a[0], a[1], a[2], a[3], b0, b1);
          mma_bf16(zz, 0x3f803f80u, 0x3f803f80u, 0x3f803f80u, 0x3f803f80u, b0, b1);
        }
        const uint32_t kp = sb + SM_KV + hh * 1088;
        sts128(kp + dtile * 512 + lane * 16, __float_as_uint(kv[0]), __float_as_uint(kv[1]), __float_as_uint(kv[2]),
               __float_as_uint(kv[3]));
        if (g == 0) sts_f32x2(kp + 1024 + dtile * 32 + q * 8, zz[0], zz[1]);
        fence_async_smem();
        __syncwarp();
        if (lane == 0) mbar_arrive(BAR(B_KVP));
        if (tid == 128) TS(55);
      }
    }
    __syncwarp();
    if (tid == 128) TS(56);
    mbar_wait(BAR(B_KVF), 0);
    if (tid == 128) TS(19);
#pragma unroll 1
    for (int h = 0; h < 4; ++h) {
      uint32_t a[4];
      const uint32_t qa = sb + SM_QS + row * 128 + (((2 * h + (lane >> 4)) ^ (row & 7)) << 4);
      ldsm_x4(a, qa);
      const uint32_t kp = sb + SM_KV + h * 1088;
      const uint4 k0 = lds128(kp + lane * 16), k1 = lds128(kp + 512 + lane * 16);
      const uint32_t za = kp + 1024 + q * 8;
      auto pk2 = [](uint32_t x, uint32_t y) { return pack_bf16(__uint_as_float(x), __uint_as_float(y)); };
      float n0[4] = {0.f, 0.f, 0.f, 0.f}, n1[4] = {0.f, 0.f, 0.f, 0.f}, dn[4] = {0.f, 0.f, 0.f, 0.f};
      mma_bf16(n0, a[0], a[1], a[2], a[3], pk2(k0.x, k0.y), pk2(k1.x, k1.y));
      mma_bf16(n1, a[0], a[1], a[2], a[3], pk2(k0.z, k0.w), pk2(k1.z, k1.w));
      mma_bf16(dn, a[0], a[1], a[2], a[3], pack_bf16(lds_f32(za), lds_f32(za + 4)), pack_bf16(lds_f32(za + 32), lds_f32(za + 36)));
      const uint32_t dd = pack_bf16(dn[0], dn[2]);
      const uint32_t d2 = pack_bf16(bf_lo(dd) + 1e-6f, bf_hi(dd) + 1e-6f);
      const float r0 = rcp(bf_lo(d2)), r1 = rcp(bf_hi(d2));
      const uint32_t x0 = pack_bf16(n0[0], n0[1]), x1 = pack_bf16(n0[2], n0[3]);
      const uint32_t x2 = pack_bf16(n1[0], n1[1]), x3 = pack_bf16(n1[2], n1[3]);
      stsm_x4(qa, pack_bf16(bf_lo(x0) * r0, bf_hi(x0) * r0), pack_bf16(bf_lo(x1) * r1, bf_hi(x1) * r1),
              pack_bf16(bf_lo(x2) * r0, bf_hi(x2) * r0), pack_bf16(bf_lo(x3) * r1, bf_hi(x3) * r1));
    }
    fence_async_smem();
    __syncwarp();
    if (lane == 0) mbar_arrive(BAR(B_OST));
    if (tid == 128) TS(57);
    mbar_wait(BAR(B_WO), 0);
    bar_sync(3, 384);
    {
      float o[32];
#pragma unroll 1
      for (int c = 0, s = 0, ph = 0; c < 8; ++c) {
        mbar_wait(BAR(B_RF + s), ph);
        if (c == 0 && tid == 128) TS(22);
        const uint32_t da = mkdesc(sb + SM_QS + s * 16384 + (w8 >> 2) * 8192, 16);
        const uint32_t db = mkdesc(sb + SM_WO + c * 8192, 8192);
        wg_fence();
#pragma unroll
        for (int k = 0; k < 4; ++k) wgmma_n64(o, da + 2 * k, db + 128 * k, (c | k) != 0);
        wg_commit();
        const uint32_t eprev = BAR(B_RE + (s == 0 ? 2 : s - 1));
        if (++s == 3) { s = 0; ph ^= 1; }
        if (c > 0) {
          wg_wait<1>();
          if (lane == 0) mbar_arrive(eprev);
        }
      }
      wg_wait<0>();
#pragma unroll
      for (int i = 0; i < 8; i += 2)
        stsm_x4(sb + SM_BOUT + row * 128 + (((i + (lane >> 4)) ^ (row & 7)) << 4), pack_bf16(o[4 * i], o[4 * i + 1]),
                pack_bf16(o[4 * i + 2], o[4 * i + 3]), pack_bf16(o[4 * i + 4], o[4 * i + 5]), pack_bf16(o[4 * i + 6], o[4 * i + 7]));
      fence_async_smem();
      bar_sync(1, 256);
      if (warp == 4 && elect_one()) {
        tma_store_2d(&maps.out, sb + SM_BOUT, 512 + 64 * tj, 128 * ti);
        bulk_commit();
        bulk_wait_read0();
        TS(23);
      }
    }
  } else {
    asm volatile("setmaxnreg.dec.sync.aligned.u32 40;");
    if (warp == 12) {
      if (elect_one()) {
        const unsigned epoch = __ldcg(&g_epoch);
#pragma unroll 1
        for (int ks = 3, s = 0, ph = 0; ks < 8; ++ks) {
          mbar_wait(BAR(B_EMPTY + s), ph);
          const uint32_t st = sb + s * STG_BYTES, fb = BAR(B_FULL + s);
          mbar_expect_tx(fb, STG_BYTES);
          tma_load_2d(st + STG_X, &maps.x, ks * 64, ti * 128, fb);
#pragma unroll 1
          for (int nb = 0; nb < 3; ++nb)
            tma_load_2d_mc(st + STG_W + nb * 8192 + rank * 4096, &maps.w, nb * 512 + tj * 64, ks * 64 + rank * 32, fb, 3);
          if (++s == 3) { s = 0; ph ^= 1; }
        }
        prefetch_tmap(&maps.wo); prefetch_tmap(&maps.o); prefetch_tmap(&maps.out);
        mbar_wait(BAR(B_EMPTY + 0), 0);
        mbar_wait(BAR(B_EMPTY + 1), 0);
        mbar_expect_tx(BAR(B_WO), 65536);
        tma_load_2d_mc(sb + SM_WO + rank * 32768, &maps.wo, tj * 64, rank * 256, BAR(B_WO), 3);
        float* kvg = &g_kv[epoch & 1][tj][0];
        mbar_wait(BAR(B_KVP), 0);
        bulk_reduce_add_f32(kvg, sb + SM_KV, 4352);
        bulk_commit();
        bulk_wait0();
        red_relaxed_add(&g_cnt[(C_KV + tj) * 32], 1);
        TS(18);
        wait_counter(&g_cnt[(C_KV + tj) * 32], (epoch + 1) * 16);
        mbar_expect_tx(BAR(B_KVF), 4352);
        bulk_load(sb + SM_KV, kvg, 4352, BAR(B_KVF));
        mbar_wait(BAR(B_OST), 0);
        tma_store_2d(&maps.o, sb + SM_QS, tj * 64, ti * 128);
        bulk_commit();
        bulk_wait0();
        red_relaxed_add(&g_cnt[(C_O + ti) * 32], 1);
        TS(20);
        wait_counter(&g_cnt[(C_O + ti) * 32], (epoch + 1) * 8);
        if (cta == 0) g_epoch = epoch + 1;
        TS(21);
#pragma unroll 1
        for (int c = 0, s = 0, ph = 1; c < 8; ++c) {
          if (c >= 3) mbar_wait(BAR(B_RE + s), ph);
          mbar_expect_tx(BAR(B_RF + s), 16384);
          tma_load_2d(sb + SM_QS + s * 16384, &maps.o, c * 64, ti * 128, BAR(B_RF + s));
          if (++s == 3) { s = 0; ph ^= 1; }
        }
      }
    } else if (warp == 13 && ti == 0) {
      float4* z = (float4*)&g_kv[(__ldcg(&g_epoch) & 1) ^ 1][tj][0];
#pragma unroll 1
      for (int i = lane; i < 272; i += 32) z[i] = make_float4(0.f, 0.f, 0.f, 0.f);
    }
  }
  __syncwarp();
  cluster_arrive();
  cluster_wait();
  if (tid == 0) TS(31);
#undef BAR
}

typedef CUresult (*EncodeFn)(CUtensorMap*, CUtensorMapDataType, cuuint32_t, void*, const cuuint64_t*, const cuuint64_t*,
                             const cuuint32_t*, const cuuint32_t*, CUtensorMapInterleave, CUtensorMapSwizzle,
                             CUtensorMapL2promotion, CUtensorMapFloatOOBfill);

static void make_map(EncodeFn enc, CUtensorMap* m, const void* base, uint64_t inner, uint64_t outer, uint32_t box_in,
                     uint32_t box_out) {
  cuuint64_t gd[2] = {inner, outer};
  cuuint64_t gs[1] = {inner * 2};
  cuuint32_t bd[2] = {box_in, box_out};
  cuuint32_t es[2] = {1, 1};
  enc(m, CU_TENSOR_MAP_DATA_TYPE_BFLOAT16, 2, const_cast<void*>(base), gd, gs, bd, es, CU_TENSOR_MAP_INTERLEAVE_NONE,
      CU_TENSOR_MAP_SWIZZLE_128B, CU_TENSOR_MAP_L2_PROMOTION_L2_128B, CU_TENSOR_MAP_FLOAT_OOB_FILL_NONE);
}

}

extern "C" void kernel_launch(void* const* d_in, const int* in_sizes, int n_in, void* d_out, int out_size) {
  using namespace s4la;
  (void)in_sizes; (void)n_in; (void)out_size;
  static EncodeFn enc = nullptr;
  static void *uT = nullptr, *yT = nullptr, *oS = nullptr;
  if (!enc) {
    void* fn = nullptr;
    cudaDriverEntryPointQueryResult qr;
    cudaGetDriverEntryPoint("cuTensorMapEncodeTiled", &fn, cudaEnableDefault, &qr);
    enc = (EncodeFn)fn;
    cudaGetSymbolAddress(&uT, g_uT);
    cudaGetSymbolAddress(&yT, g_yT);
    cudaGetSymbolAddress(&oS, g_o);
    cudaFuncSetAttribute(fused_kernel, cudaFuncAttributeMaxDynamicSharedMemorySize, SM_TOTAL);
  }
  const __nv_bfloat16* const* in = (const __nv_bfloat16* const*)d_in;
  Maps maps;
  make_map(enc, &maps.x, in[9], 512, 2048, 64, 128);
  make_map(enc, &maps.w, in[10], 1536, 512, 64, 32);
  make_map(enc, &maps.wo, in[11], 512, 512, 64, 256);
  make_map(enc, &maps.u, in[0], 512, 2048, 64, 128);
  make_map(enc, &maps.uT, uT, 2048, 512, 64, 64);
  make_map(enc, &maps.yT, yT, 2048, 512, 64, 64);
  make_map(enc, &maps.o, oS, 512, 2048, 64, 128);
  make_map(enc, &maps.out, d_out, 1024, 2048, 64, 128);
  Ptrs p;
  p.A_re = in[1]; p.A_im = in[2]; p.B_re = in[3]; p.B_im = in[4]; p.C_re = in[5]; p.C_im = in[6];
  p.log_dt = in[7]; p.Dskip = in[8]; p.x = in[9]; p.wqkv = in[10]; p.wo = in[11];
  p.uT = (__nv_bfloat16*)uT; p.yT = (__nv_bfloat16*)yT;
  fused_kernel<<<NCTA, NTHREADS, SM_TOTAL, cudaStreamPerThread>>>(maps, p);
}
```

```cpp
#include <cuda_runtime.h>
#include <cuda_bf16.h>
#include <cuda_fp16.h>
#include <cuda.h>
#include <stdint.h>

#define DEVI __device__ __forceinline__

namespace s4la {

constexpr int NTHREADS = 512;
constexpr int NCTA = 128;

constexpr int NSTG = 7;
constexpr uint32_t STG_BYTES = 20480, STG_X = 0, STG_W = 8192;
constexpr int NRING = 5;
constexpr uint32_t SM_QS = 0;
constexpr uint32_t SM_PK = SM_QS + 16384, SM_VS = SM_QS + 32768;
constexpr uint32_t SM_WO = 81920;
constexpr uint32_t SM_KV = 122880;
constexpr uint32_t SM_BOUT = 126976;
constexpr uint32_t SM_U = 143360, U_BYTES = 4352;
constexpr uint32_t SM_P = 160768, P_BYTES = 4096;
constexpr uint32_t SM_VV = 177152, VV_BYTES = 12800;
constexpr uint32_t VV_U5 = 0, VV_U3 = 3712, VV_U9 = 7424, VV_U7 = 10112;
constexpr uint32_t KG_BYTES = 3200;
constexpr uint32_t SM_BAR = SM_VV + 4 * VV_BYTES;
constexpr uint32_t SM_PTAB = SM_BAR + 256;
constexpr uint32_t SM_TOTAL = SM_PTAB + 3840;
static_assert(SM_TOTAL <= 232448, "shared memory");
constexpr int PADV = 12;

enum { B_FULL = 0, B_EMPTY = 7, B_TILE = 14, B_UCH = 15, B_KVP = 19, B_KVF = 20, B_OST = 21, B_RF = 22, B_RE = 27, B_COUNT = 32 };
__host__ __device__ constexpr int bar_count(int i) {
  return (i >= B_EMPTY && i < B_TILE) ? 16 : (i == B_KVP || i == B_OST || i >= B_RE) ? 8 : 1;
}

constexpr int PD_OFF = 0, P2_OFF = 544, P3_OFF = 768;

constexpr int SL_K2048 = 20, SL_ZERO = 21, SL_510 = 22, SL_0 = 23;
__host__ __device__ constexpr int koff(int y) {
  return y < 8 ? y : y < 12 ? 256 + 2 * (y - 8) : y < 16 ? 512 + 256 * ((y - 12) >> 1) + 4 * (y & 1) : 1024 + 256 * (y - 16);
}
__host__ __device__ constexpr int kidx_c(int l) {
  const int y = l < 256 ? (l & 7) : l < 512 ? 8 + ((l & 7) >> 1) : l < 1024 ? 12 + (((l - 512) >> 8) << 1) + ((l >> 2) & 1)
                                                                            : 16 + ((l - 1024) >> 8);
  return ((l >> 3) & 31) * 24 + y;
}
constexpr int slot_direct(int l) {
  if (l < 0 || l > 510) return SL_ZERO;
  if (l == 510) return SL_510;
  if (l == 0) return SL_0;
  return kidx_c(l < 256 ? l : ((l + ((l >> 1) & 1)) & ~1));
}
constexpr int slot_seg2(int v, int k) { return (k >= 32 && k < 64) ? kidx_c(16 * k + 4 * v) : SL_ZERO; }
constexpr int slot_seg3(int pi, int k) {
  return (k >= 64 && k < 128) ? kidx_c(16 * k + 8 * pi) : ((k == 128 && pi == 0) ? SL_K2048 : SL_ZERO);
}
struct PTab { uint32_t v[960]; };
constexpr PTab make_ptab() {
  PTab t{};
  for (int w = 0; w < 960; ++w) t.v[w] = (SL_ZERO * 4) | ((SL_ZERO * 4) << 16);
  for (int w = 0; w < 544; ++w) t.v[w] = (slot_direct(w - 16) * 4) | ((slot_direct(w - 17) * 4) << 16);
  for (int v = 0; v < 4; ++v)
    for (int x = 16; x < 72; ++x) t.v[544 + 56 * v + x - 16] = (slot_seg2(v, x) * 4) | ((slot_seg2(v, x - 1) * 4) << 16);
  for (int pi = 0; pi < 2; ++pi)
    for (int x = 48; x < 136; ++x) t.v[768 + 88 * pi + x - 48] = (slot_seg3(pi, x) * 4) | ((slot_seg3(pi, x - 1) * 4) << 16);
  return t;
}
__device__ const PTab g_ptab = make_ptab();

__device__ __nv_bfloat16 g_uT[512 * 2048];
__device__ __nv_bfloat16 g_yT[512 * 2048];
__device__ __nv_bfloat16 g_o[2048 * 512];
__device__ float g_kv[2][8][4 * 272];
__device__ unsigned g_cnt[64 * 32];
__device__ unsigned g_epoch;
#define TS(slot) do { } while (0)
#define TSR(on, slot) do { } while (0)
enum { C_U = 0, C_KV = 8, C_O = 16, C_Y = 32 };

struct Maps {
  CUtensorMap x, w, wo, u, uT, yT, o, out;
};
struct Ptrs {
  const __nv_bfloat16 *A_re, *A_im, *B_re, *B_im, *C_re, *C_im, *log_dt, *Dskip;
  const __nv_bfloat16 *x, *wqkv, *wo;
  __nv_bfloat16 *uT, *yT;
};

DEVI uint32_t s2u(const void* p) { return (uint32_t)__cvta_generic_to_shared(p); }
DEVI void mbar_init(uint32_t b, uint32_t c) { asm volatile("mbarrier.init.shared::cta.b64 [%0], %1;" ::"r"(b), "r"(c) : "memory"); }
DEVI void mbar_expect_tx(uint32_t b, uint32_t bytes) {
  asm volatile("mbarrier.arrive.expect_tx.shared::cta.b64 _, [%0], %1;" ::"r"(b), "r"(bytes) : "memory");
}
DEVI void mbar_arrive(uint32_t b) { asm volatile("mbarrier.arrive.shared::cta.b64 _, [%0];" ::"r"(b) : "memory"); }
DEVI void mbar_arrive_cluster(uint32_t b, uint32_t cta) {
  asm volatile("{\n.reg .b32 r;\nmapa.shared::cluster.u32 r, %0, %1;\nmbarrier.arrive.shared::cluster.b64 _, [r];\n}"
               ::"r"(b), "r"(cta) : "memory");
}
DEVI void mbar_wait(uint32_t b, uint32_t parity) {
  asm volatile("{\n.reg .pred p;\nLAB_WAIT:\nmbarrier.try_wait.parity.shared::cta.b64 p, [%0], %1;\n@!p bra LAB_WAIT;\n}"
               ::"r"(b), "r"(parity) : "memory");
}
DEVI void bar_sync(int id, int n) { asm volatile("bar.sync %0, %1;" ::"r"(id), "r"(n) : "memory"); }
DEVI void bar_arrive(int id, int n) { asm volatile("bar.arrive %0, %1;" ::"r"(id), "r"(n) : "memory"); }
DEVI void fence_async_smem() { asm volatile("fence.proxy.async.shared::cta;" ::: "memory"); }
DEVI void fence_async_all() { asm volatile("fence.proxy.async;" ::: "memory"); }
DEVI void cluster_arrive() { asm volatile("barrier.cluster.arrive.relaxed.aligned;" ::: "memory"); }
DEVI void cluster_wait() { asm volatile("barrier.cluster.wait.aligned;" ::: "memory"); }

DEVI void tma_load_2d(uint32_t dst, const CUtensorMap* m, int c0, int c1, uint32_t bar) {
  asm volatile("cp.async.bulk.tensor.2d.shared::cluster.global.mbarrier::complete_tx::bytes [%0], [%1, {%3, %4}], [%2];"
               ::"r"(dst), "l"(m), "r"(bar), "r"(c0), "r"(c1) : "memory");
}
DEVI void tma_load_3d_mc(uint32_t dst, const CUtensorMap* m, int c0, int c1, int c2, uint32_t bar, uint16_t mask) {
  asm volatile("cp.async.bulk.tensor.3d.shared::cluster.global.mbarrier::complete_tx::bytes.multicast::cluster [%0], [%1, {%3, %4, %5}], [%2], %6;"
               ::"r"(dst), "l"(m), "r"(bar), "r"(c0), "r"(c1), "r"(c2), "h"(mask) : "memory");
}
DEVI void tma_store_2d(const CUtensorMap* m, uint32_t src, int c0, int c1) {
  asm volatile("cp.async.bulk.tensor.2d.global.shared::cta.bulk_group [%0, {%2, %3}], [%1];"
               ::"l"(m), "r"(src), "r"(c0), "r"(c1) : "memory");
}
DEVI void bulk_load(uint32_t dst, const void* src, uint32_t bytes, uint32_t bar) {
  asm volatile("cp.async.bulk.shared::cluster.global.mbarrier::complete_tx::bytes [%0], [%1], %2, [%3];"
               ::"r"(dst), "l"(src), "r"(bytes), "r"(bar) : "memory");
}
DEVI void bulk_store(void* dst, uint32_t src, uint32_t bytes) {
  asm volatile("cp.async.bulk.global.shared::cta.bulk_group [%0], [%1], %2;" ::"l"(dst), "r"(src), "r"(bytes) : "memory");
}
DEVI void bulk_reduce_add_f32(void* dst, uint32_t src, uint32_t bytes) {
  asm volatile("cp.reduce.async.bulk.global.shared::cta.bulk_group.add.f32 [%0], [%1], %2;" ::"l"(dst), "r"(src), "r"(bytes) : "memory");
}
DEVI void bulk_commit() { asm volatile("cp.async.bulk.commit_group;" ::: "memory"); }
DEVI void bulk_wait0() { asm volatile("cp.async.bulk.wait_group 0;" ::: "memory"); }
DEVI void bulk_wait_read0() { asm volatile("cp.async.bulk.wait_group.read 0;" ::: "memory"); }
DEVI void l2_prefetch(const void* p, uint32_t bytes) {
  asm volatile("cp.async.bulk.prefetch.L2.global [%0], %1;" ::"l"(p), "r"(bytes) : "memory");
}
DEVI void prefetch_tmap(const CUtensorMap* m) { asm volatile("prefetch.tensormap [%0];" ::"l"(m) : "memory"); }

DEVI void red_release_add(unsigned* p, unsigned v) {
  asm volatile("red.release.gpu.global.add.u32 [%0], %1;" ::"l"(p), "r"(v) : "memory");
}
DEVI void red_relaxed_add(unsigned* p, unsigned v) {
  asm volatile("red.relaxed.gpu.global.add.u32 [%0], %1;" ::"l"(p), "r"(v) : "memory");
}
DEVI unsigned ld_relaxed(const unsigned* p) {
  unsigned v;
  asm volatile("ld.relaxed.gpu.global.u32 %0, [%1];" : "=r"(v) : "l"(p) : "memory");
  return v;
}
DEVI void wait_counter(const unsigned* p, unsigned target) {
#pragma unroll 1
  for (int it = 0; (int)(ld_relaxed(p) - target) < 0; ++it)
    if (it > (1 << 22)) __trap();
}

DEVI void ldsm_x4(uint32_t (&r)[4], uint32_t a) {
  asm volatile("ldmatrix.sync.aligned.m8n8.x4.shared.b16 {%0,%1,%2,%3}, [%4];"
               : "=r"(r[0]), "=r"(r[1]), "=r"(r[2]), "=r"(r[3]) : "r"(a) : "memory");
}
DEVI void ldsm_x4_t(uint32_t (&r)[4], uint32_t a) {
  asm volatile("ldmatrix.sync.aligned.m8n8.x4.trans.shared.b16 {%0,%1,%2,%3}, [%4];"
               : "=r"(r[0]), "=r"(r[1]), "=r"(r[2]), "=r"(r[3]) : "r"(a) : "memory");
}
DEVI void ldsm_x2_t(uint32_t& r0, uint32_t& r1, uint32_t a) {
  asm volatile("ldmatrix.sync.aligned.m8n8.x2.trans.shared.b16 {%0,%1}, [%2];" : "=r"(r0), "=r"(r1) : "r"(a) : "memory");
}
DEVI void stsm_x4(uint32_t a, uint32_t r0, uint32_t r1, uint32_t r2, uint32_t r3) {
  asm volatile("stmatrix.sync.aligned.m8n8.x4.shared.b16 [%0], {%1,%2,%3,%4};"
               ::"r"(a), "r"(r0), "r"(r1), "r"(r2), "r"(r3) : "memory");
}
DEVI void stsm_x4_t(uint32_t a, uint32_t r0, uint32_t r1, uint32_t r2, uint32_t r3) {
  asm volatile("stmatrix.sync.aligned.m8n8.x4.trans.shared.b16 [%0], {%1,%2,%3,%4};"
               ::"r"(a), "r"(r0), "r"(r1), "r"(r2), "r"(r3) : "memory");
}
DEVI uint32_t lds32(uint32_t a) { uint32_t v; asm volatile("ld.shared.b32 %0, [%1];" : "=r"(v) : "r"(a) : "memory"); return v; }
DEVI float lds_f32(uint32_t a) { float v; asm volatile("ld.shared.f32 %0, [%1];" : "=f"(v) : "r"(a) : "memory"); return v; }
DEVI void sts32(uint32_t a, uint32_t v) { asm volatile("st.shared.b32 [%0], %1;" ::"r"(a), "r"(v) : "memory"); }
DEVI void sts_f32(uint32_t a, float v) { asm volatile("st.shared.f32 [%0], %1;" ::"r"(a), "f"(v) : "memory"); }
DEVI void sts_f32x2(uint32_t a, float x, float y) { asm volatile("st.shared.v2.f32 [%0], {%1,%2};" ::"r"(a), "f"(x), "f"(y) : "memory"); }
DEVI uint4 lds128(uint32_t a) {
  uint4 v;
  asm volatile("ld.shared.v4.b32 {%0,%1,%2,%3}, [%4];" : "=r"(v.x), "=r"(v.y), "=r"(v.z), "=r"(v.w) : "r"(a) : "memory");
  return v;
}
DEVI void sts128(uint32_t a, uint32_t x, uint32_t y, uint32_t z, uint32_t w) {
  asm volatile("st.shared.v4.b32 [%0], {%1,%2,%3,%4};" ::"r"(a), "r"(x), "r"(y), "r"(z), "r"(w) : "memory");
}

DEVI void mma_bf16(float (&d)[4], uint32_t a0, uint32_t a1, uint32_t a2, uint32_t a3, uint32_t b0, uint32_t b1) {
  asm("mma.sync.aligned.m16n8k16.row.col.f32.bf16.bf16.f32 {%0,%1,%2,%3}, {%4,%5,%6,%7}, {%8,%9}, {%0,%1,%2,%3};"
      : "+f"(d[0]), "+f"(d[1]), "+f"(d[2]), "+f"(d[3])
      : "r"(a0), "r"(a1), "r"(a2), "r"(a3), "r"(b0), "r"(b1));
}
DEVI void mma_f16(float (&d)[4], const uint32_t (&a)[4], uint32_t b0, uint32_t b1) {
  asm("mma.sync.aligned.m16n8k16.row.col.f32.f16.f16.f32 {%0,%1,%2,%3}, {%4,%5,%6,%7}, {%8,%9}, {%0,%1,%2,%3};"
      : "+f"(d[0]), "+f"(d[1]), "+f"(d[2]), "+f"(d[3])
      : "r"(a[0]), "r"(a[1]), "r"(a[2]), "r"(a[3]), "r"(b0), "r"(b1));
}
DEVI void mma_bf16v(float (&d)[4], const uint32_t (&a)[4], uint32_t b0, uint32_t b1) {
  asm volatile("mma.sync.aligned.m16n8k16.row.col.f32.bf16.bf16.f32 {%0,%1,%2,%3}, {%4,%5,%6,%7}, {%8,%9}, {%0,%1,%2,%3};"
               : "+f"(d[0]), "+f"(d[1]), "+f"(d[2]), "+f"(d[3])
               : "r"(a[0]), "r"(a[1]), "r"(a[2]), "r"(a[3]), "r"(b0), "r"(b1));
}
DEVI uint32_t pack_bf16(float lo, float hi) {
  uint32_t r;
  asm("cvt.rn.bf16x2.f32 %0, %1, %2;" : "=r"(r) : "f"(hi), "f"(lo));
  return r;
}
DEVI uint32_t pack_f16(float lo, float hi) {
  uint32_t r;
  asm("cvt.rn.f16x2.f32 %0, %1, %2;" : "=r"(r) : "f"(hi), "f"(lo));
  return r;
}
DEVI uint32_t ldg16(const __nv_bfloat16* p) {
  uint32_t v;
  asm volatile("ld.global.nc.u16 %0, [%1];" : "=r"(v) : "l"(p));
  return v;
}
DEVI bool elect_one() {
  uint32_t pred;
  asm volatile("{\n.reg .pred p;\nelect.sync _|p, 0xffffffff;\nselp.u32 %0, 1, 0, p;\n}" : "=r"(pred));
  return pred != 0;
}
DEVI float bf_lo(uint32_t v) { return __uint_as_float(v << 16); }
DEVI float bf_hi(uint32_t v) { return __uint_as_float(v & 0xffff0000u); }
DEVI float bf2f(__nv_bfloat16 v) { return __bfloat162float(v); }
DEVI float round_bf16(float v) { return __bfloat162float(__float2bfloat16_rn(v)); }
DEVI float rcp(float x) { float r; asm("rcp.approx.ftz.f32 %0, %1;" : "=f"(r) : "f"(x)); return r; }
DEVI float ex2(float x) { float r; asm("ex2.approx.ftz.f32 %0, %1;" : "=f"(r) : "f"(x)); return r; }

DEVI void wg_fence() { asm volatile("wgmma.fence.sync.aligned;" ::: "memory"); }
DEVI void wg_commit() { asm volatile("wgmma.commit_group.sync.aligned;" ::: "memory"); }
template <int N> DEVI void wg_wait() { asm volatile("wgmma.wait_group.sync.aligned %0;" ::"n"(N) : "memory"); }
constexpr uint32_t DESC_HI = (1u << 30) | (1024 >> 4);
constexpr uint32_t DESC_HI64 = (2u << 30) | (512 >> 4);
DEVI uint32_t mkdesc(uint32_t saddr, uint32_t lbo) { return ((saddr & 0x3FFFF) >> 4) | ((lbo >> 4) << 16); }

#define R8(b) "%" #b
DEVI void wgmma_n192(float (&d)[96], uint32_t da, uint32_t db, int scale_d) {
  asm volatile(
      "{\n.reg .pred p;\n.reg .b64 da, db;\nsetp.ne.b32 p, %98, 0;\nmov.b64 da, {%96, %100};\nmov.b64 db, {%97, %99};\n"
      "wgmma.mma_async.sync.aligned.m64n192k16.f32.bf16.bf16 "
      "{%0,%1,%2,%3,%4,%5,%6,%7,%8,%9,%10,%11,%12,%13,%14,%15,"
      "%16,%17,%18,%19,%20,%21,%22,%23,%24,%25,%26,%27,%28,%29,%30,%31,"
      "%32,%33,%34,%35,%36,%37,%38,%39,%40,%41,%42,%43,%44,%45,%46,%47,"
      "%48,%49,%50,%51,%52,%53,%54,%55,%56,%57,%58,%59,%60,%61,%62,%63,"
      "%64,%65,%66,%67,%68,%69,%70,%71,%72,%73,%74,%75,%76,%77,%78,%79,"
      "%80,%81,%82,%83,%84,%85,%86,%87,%88,%89,%90,%91,%92,%93,%94,%95}, "
      "da, db, p, 1, 1, 0, 1;\n}"
      : "+f"(d[0]), "+f"(d[1]), "+f"(d[2]), "+f"(d[3]), "+f"(d[4]), "+f"(d[5]), "+f"(d[6]), "+f"(d[7]),
        "+f"(d[8]), "+f"(d[9]), "+f"(d[10]), "+f"(d[11]), "+f"(d[12]), "+f"(d[13]), "+f"(d[14]), "+f"(d[15]),
        "+f"(d[16]), "+f"(d[17]), "+f"(d[18]), "+f"(d[19]), "+f"(d[20]), "+f"(d[21]), "+f"(d[22]), "+f"(d[23]),
        "+f"(d[24]), "+f"(d[25]), "+f"(d[26]), "+f"(d[27]), "+f"(d[28]), "+f"(d[29]), "+f"(d[30]), "+f"(d[31]),
        "+f"(d[32]), "+f"(d[33]), "+f"(d[34]), "+f"(d[35]), "+f"(d[36]), "+f"(d[37]), "+f"(d[38]), "+f"(d[39]),
        "+f"(d[40]), "+f"(d[41]), "+f"(d[42]), "+f"(d[43]), "+f"(d[44]), "+f"(d[45]), "+f"(d[46]), "+f"(d[47]),
        "+f"(d[48]), "+f"(d[49]), "+f"(d[50]), "+f"(d[51]), "+f"(d[52]), "+f"(d[53]), "+f"(d[54]), "+f"(d[55]),
        "+f"(d[56]), "+f"(d[57]), "+f"(d[58]), "+f"(d[59]), "+f"(d[60]), "+f"(d[61]), "+f"(d[62]), "+f"(d[63]),
        "+f"(d[64]), "+f"(d[65]), "+f"(d[66]), "+f"(d[67]), "+f"(d[68]), "+f"(d[69]), "+f"(d[70]), "+f"(d[71]),
        "+f"(d[72]), "+f"(d[73]), "+f"(d[74]), "+f"(d[75]), "+f"(d[76]), "+f"(d[77]), "+f"(d[78]), "+f"(d[79]),
        "+f"(d[80]), "+f"(d[81]), "+f"(d[82]), "+f"(d[83]), "+f"(d[84]), "+f"(d[85]), "+f"(d[86]), "+f"(d[87]),
        "+f"(d[88]), "+f"(d[89]), "+f"(d[90]), "+f"(d[91]), "+f"(d[92]), "+f"(d[93]), "+f"(d[94]), "+f"(d[95])
      : "r"(da), "r"(db), "r"(scale_d), "n"(DESC_HI), "n"(DESC_HI64));
}
DEVI void wgmma_n64(float (&d)[32], uint32_t da, uint32_t db, int scale_d) {
  asm volatile(
      "{\n.reg .pred p;\n.reg .b64 da, db;\nsetp.ne.b32 p, %34, 0;\nmov.b64 da, {%32, %35};\nmov.b64 db, {%33, %35};\n"
      "wgmma.mma_async.sync.aligned.m64n64k16.f32.bf16.bf16 "
      "{%0,%1,%2,%3,%4,%5,%6,%7,%8,%9,%10,%11,%12,%13,%14,%15,"
      "%16,%17,%18,%19,%20,%21,%22,%23,%24,%25,%26,%27,%28,%29,%30,%31}, "
      "da, db, p, 1, 1, 0, 1;\n}"
      : "+f"(d[0]), "+f"(d[1]), "+f"(d[2]), "+f"(d[3]), "+f"(d[4]), "+f"(d[5]), "+f"(d[6]), "+f"(d[7]),
        "+f"(d[8]), "+f"(d[9]), "+f"(d[10]), "+f"(d[11]), "+f"(d[12]), "+f"(d[13]), "+f"(d[14]), "+f"(d[15]),
        "+f"(d[16]), "+f"(d[17]), "+f"(d[18]), "+f"(d[19]), "+f"(d[20]), "+f"(d[21]), "+f"(d[22]), "+f"(d[23]),
        "+f"(d[24]), "+f"(d[25]), "+f"(d[26]), "+f"(d[27]), "+f"(d[28]), "+f"(d[29]), "+f"(d[30]), "+f"(d[31])
      : "r"(da), "r"(db), "r"(scale_d), "n"(DESC_HI));
}

struct C32 { float re, im; };
DEVI C32 csq(C32 a) { return {a.re * a.re - a.im * a.im, 2.f * a.re * a.im}; }
DEVI C32 cmul(C32 a, C32 b) { return {a.re * b.re - a.im * b.im, a.re * b.im + a.im * b.re}; }
DEVI C32 cfresh(float zl, float zi, float m) {
  float mag = ex2(zl * m), ph = zi * m;
  return {mag * __cosf(ph), mag * __sinf(ph)};
}
struct HMul { uint32_t b, bp; };
DEVI HMul mk_mul(float re, float im) { return {pack_f16(re, im), pack_f16(-im, re)}; }
DEVI uint32_t hcmul(uint32_t a, const HMul& m) {
  __half2 ah = *reinterpret_cast<__half2*>(&a);
  __half2 b = *reinterpret_cast<const __half2*>(&m.b), bp = *reinterpret_cast<const __half2*>(&m.bp);
  __half2 r = __hfma2(__high2half2(ah), bp, __hmul2(__low2half2(ah), b));
  return *reinterpret_cast<uint32_t*>(&r);
}
DEVI uint32_t badd(uint32_t a, uint32_t b) {
  __nv_bfloat162 r = __hadd2(*reinterpret_cast<__nv_bfloat162*>(&a), *reinterpret_cast<__nv_bfloat162*>(&b));
  return *reinterpret_cast<uint32_t*>(&r);
}
template <int MU0, int NMU, int DMAX>
DEVI void conv_tail(float (&acc)[16][4], uint32_t p_lane, uint32_t v_base, int back, bool edge, int lane) {
  const int hsel = (lane >> 3) & 1;
  const int row = (lane & 7) + ((lane >> 4) << 3) + PADV - 8 - (back & (hsel ^ 1));
  const uint32_t la = v_base + row * 32 + (((hsel ^ back) ^ ((row >> 2) & 1)) << 4);
  uint32_t M[3][4];
  ldsm_x4_t(M[0], la);
  ldsm_x4_t(M[1], la + 256);
  uint32_t H[2 * NMU];
#pragma unroll
  for (int i = 0; i < 2 * NMU; ++i) H[i ^ 1] = lds32(p_lane + (uint32_t)(MU0 - 1 + i) * 32);
  if (edge) {
    const uint32_t a[4] = {0u, 0u, M[0][0], M[0][1]};
#pragma unroll
    for (int k = 1; k < NMU; ++k) mma_bf16v(acc[MU0 - 2 + 2 * k], a, H[2 * k], H[2 * k + 1]);
  }
#pragma unroll
  for (int delta = -1; delta <= DMAX; ++delta) {
    if (delta + 2 <= DMAX) ldsm_x4_t(M[(delta + 3) % 3], la + (delta + 3) * 256);
#pragma unroll
    for (int k = 0; k < NMU; ++k)
      if (delta + MU0 + 2 * k < 16) mma_bf16v(acc[delta + MU0 + 2 * k], M[(delta + 1) % 3], H[2 * k], H[2 * k + 1]);
  }
}

__global__ void __cluster_dims__(2, 1, 1) __launch_bounds__(NTHREADS, 1)
fused_kernel(const __grid_constant__ Maps maps, const Ptrs p) {
  extern __shared__ __align__(1024) uint8_t smem[];
  const uint32_t sb = s2u(smem);
  const int tid = threadIdx.x, lane = tid & 31;
  const int warp = __shfl_sync(0xffffffffu, tid >> 5, 0);
  const int cta = blockIdx.x;
  const uint32_t rank = cta & 1;
  const int ti = 2 * (cta >> 4) + rank;
  const int tj = (cta >> 1) & 7;
  const uint32_t bars = sb + SM_BAR;
#define BAR(i) (bars + 8 * (i))
  const int g = lane >> 2, q = lane & 3;

  const int kch = warp & 3, krd = warp >> 2;
  float zr, zi, wr, wi;
  {
    const size_t po = (size_t)(cta * 4 + kch) * 128 + krd * 32 + lane;
    const uint32_t r_ar = ldg16(p.A_re + po), r_ai = ldg16(p.A_im + po), r_br = ldg16(p.B_re + po), r_bi = ldg16(p.B_im + po);
    const uint32_t r_cr = ldg16(p.C_re + po), r_ci = ldg16(p.C_im + po), r_ldt = ldg16(p.log_dt + cta * 4 + kch);
    uint4 pt;
    if (tid < 240) pt = __ldg((const uint4*)g_ptab.v + tid);
    if (tid == 384) {
      TS(0);
#pragma unroll
      for (int i = 0; i < B_COUNT; ++i) mbar_init(BAR(i), bar_count(i));
      asm volatile("fence.mbarrier_init.release.cluster;" ::: "memory");
      prefetch_tmap(&maps.x); prefetch_tmap(&maps.w); prefetch_tmap(&maps.u);
    }
    __syncthreads();
    cluster_arrive();
    if (warp >= 12) {
      cluster_wait();
      if (elect_one()) {
        if (warp == 13) {
          mbar_expect_tx(BAR(B_TILE), 16384);
          tma_load_2d(sb + SM_U, &maps.u, tj * 64, ti * 128, BAR(B_TILE));
          l2_prefetch((const char*)p.wqkv + 224 * 3072 + cta * 6912, 6912);
          l2_prefetch((const char*)p.x + (size_t)cta * 16384, 16384);
          l2_prefetch((const char*)p.wo + (size_t)cta * 4096, 4096);
        } else {
          if (warp == 12) TS(61);
#pragma unroll 1
          for (int ks = warp == 12 ? 0 : warp - 13; ks < NSTG; ks += 3) {
            const uint32_t st = sb + ks * STG_BYTES, fb = BAR(B_FULL + ks);
            mbar_expect_tx(fb, STG_BYTES);
            tma_load_2d(st + STG_X, &maps.x, ks * 32, ti * 128, fb);
            tma_load_3d_mc(st + STG_W + rank * 6144, &maps.w, tj * 64, ks * 32 + rank * 16, 0, fb, 3);
          }
        }
      }
      __syncwarp();
    }
    if (tid < 240) sts128(sb + SM_PTAB + tid * 16, pt.x, pt.y, pt.z, pt.w);
    const float dt = round_bf16(expf(bf_lo(r_ldt)));
    zr = dt * bf_lo(r_ar); zi = dt * bf_lo(r_ai);
    const float dbr = dt * bf_lo(r_br), dbi = dt * bf_lo(r_bi), cr = bf_lo(r_cr), ci = bf_lo(r_ci);
    wr = cr * dbr - ci * dbi; wi = cr * dbi + ci * dbr;
  }
  {
    const float mz = __uint_as_float(__reduce_max_sync(0xffffffffu, __float_as_uint(fmaxf(zr, 0.f))));
    const int E = min(max((int)(__reduce_max_sync(0xffffffffu, __float_as_uint(fmaxf(fabsf(wr), fabsf(wi)))) >> 23), 1), 252);
    const float sc = __int_as_float((253 - E) << 23), inv = __int_as_float((E + 1) << 23);
    const float zl = (zr - mz) * 1.4426950408889634f;
    const uint32_t tb = sb + SM_VV + kch * VV_BYTES + krd * KG_BYTES;
    const uint32_t sta = tb + (((lane >> 2) << 4) | ((lane & 3) << 2));
    auto put = [&](int r, uint32_t v) { sts32((sta ^ ((r & 7) << 4)) + r * 128, v); };
    const uint32_t lda = tb + ((lane & 7) + (((lane >> 3) & 1) << 3)) * 128;
    const uint32_t ldb = tb + ((lane & 7) + ((lane >> 4) << 3)) * 128;
    C32 e1 = cfresh(zl, zi, 1.f), e2 = csq(e1), e4 = csq(e2), e8 = csq(e4);
    C32 e16 = cfresh(zl, zi, 16.f), e32 = csq(e16), e64 = csq(e32), e128 = csq(e64);
    C32 e256 = cfresh(zl, zi, 256.f), e512 = csq(e256), e1024 = csq(e512), e768 = cmul(e512, e256);
    uint32_t XA[2][4][4];
    {
      const HMul m16 = mk_mul(e16.re, e16.im), m32 = mk_mul(e32.re, e32.im), m64 = mk_mul(e64.re, e64.im);
      const HMul m128 = mk_mul(e128.re, e128.im);
      uint32_t X[16];
      X[0] = 0x00003c00u; X[1] = pack_f16(e8.re, e8.im); X[2] = m16.b; X[4] = m32.b; X[8] = m64.b;
      X[3] = hcmul(X[1], m16); X[5] = hcmul(X[1], m32); X[6] = hcmul(X[2], m32); X[7] = hcmul(X[3], m32);
#pragma unroll
      for (int r = 1; r < 8; ++r) X[8 + r] = hcmul(X[r], m64);
#pragma unroll
      for (int h = 0; h < 2; ++h) {
#pragma unroll
        for (int r = 0; r < 16; ++r) put(r, h == 0 ? X[r] : r == 0 ? m128.b : hcmul(X[r], m128));
        __syncwarp();
#pragma unroll
        for (int k = 0; k < 4; ++k) ldsm_x4(XA[h][k], lda + (((2 * k + (lane >> 4)) ^ (lane & 7)) << 4));
        __syncwarp();
      }
    }
    float D[2][3][4];
#pragma unroll
    for (int t = 0; t < 6; ++t) D[t / 3][t % 3][0] = D[t / 3][t % 3][1] = D[t / 3][t % 3][2] = D[t / 3][t % 3][3] = 0.f;
    auto contract = [&](int t0, int nt) {
      __syncwarp();
#pragma unroll
      for (int k = 0; k < 4; ++k) {
        uint32_t b[4];
        ldsm_x4(b, ldb + (((2 * k + ((lane >> 3) & 1)) ^ (lane & 7)) << 4));
#pragma unroll
        for (int h = 0; h < 2; ++h) {
          mma_f16(D[h][t0], XA[h][k], b[0], b[1]);
          if (nt == 2) mma_f16(D[h][t0 + 1], XA[h][k], b[2], b[3]);
        }
      }
      __syncwarp();
    };
    const HMul c1 = mk_mul(e1.re, -e1.im), c2 = mk_mul(e2.re, -e2.im), c4 = mk_mul(e4.re, -e4.im);
    const HMul c256 = mk_mul(e256.re, -e256.im), c512 = mk_mul(e512.re, -e512.im), c768 = mk_mul(e768.re, -e768.im);
    const HMul c1024 = mk_mul(e1024.re, -e1024.im);
    uint32_t W[8];
    W[0] = pack_f16(wr * sc, -wi * sc);
    W[1] = hcmul(W[0], c1); W[2] = hcmul(W[0], c2); W[3] = hcmul(W[1], c2);
    W[4] = hcmul(W[0], c4); W[5] = hcmul(W[1], c4); W[6] = hcmul(W[2], c4); W[7] = hcmul(W[3], c4);
#pragma unroll
    for (int i = 0; i < 8; ++i) put(i, W[i]);
#pragma unroll
    for (int i = 0; i < 4; ++i) put(8 + i, hcmul(W[2 * i], c256));
    put(12, hcmul(W[0], c512)); put(13, hcmul(W[4], c512)); put(14, hcmul(W[0], c768)); put(15, hcmul(W[4], c768));
    contract(0, 2);
    const uint32_t v0 = hcmul(W[0], c1024);
    put(0, v0); put(1, hcmul(v0, c256)); put(2, hcmul(v0, c512)); put(3, hcmul(v0, c768)); put(4, hcmul(v0, c1024));
    contract(2, 1);
    const uint32_t a = tb + (g * 24 + 2 * q) * 4;
#pragma unroll
    for (int t = 0; t < 6; ++t) {
      const float(&d)[4] = D[t / 3][t % 3];
      sts_f32x2(a + (t / 3) * 1536 + (t % 3) * 32, d[0] * inv, d[1] * inv);
      sts_f32x2(a + (t / 3) * 1536 + (t % 3) * 32 + 768, d[2] * inv, d[3] * inv);
    }
    if (mz > 0.f) {
      __syncwarp();
#pragma unroll 1
      for (int i = lane; i < 768; i += 32) {
        const int r = i / 24, y = i - 24 * r;
        sts_f32(tb + i * 4, lds_f32(tb + i * 4) * ex2(mz * 1.4426950408889634f * (koff(y) + 8 * r)));
      }
    }
  }
  if (tid == 0) TS(2);
  if (warp < 12) cluster_wait();
  __syncthreads();

  if (warp < 4) {
    asm volatile("setmaxnreg.inc.sync.aligned.u32 152;");
    const unsigned epoch = __ldcg(&g_epoch);
    const int d = cta * 4 + warp;
    const uint32_t vv = sb + SM_VV + warp * VV_BYTES;
    const uint32_t ub = sb + SM_U + warp * U_BYTES;
    const uint32_t pb = sb + SM_P + warp * P_BYTES;
    const float dskip = bf2f(p.Dskip[d]);
#pragma unroll 1
    for (int pass = 0; pass < 2; ++pass) {
      if (pass == 1) {
        const uint32_t kf = vv;
#pragma unroll 1
        for (int i0 = 0; i0 < 24; i0 += 4) {
          float a[4][4];
#pragma unroll
          for (int i = 0; i < 4; ++i)
#pragma unroll
            for (int r = 0; r < 4; ++r) a[i][r] = lds_f32(kf + r * KG_BYTES + ((i0 + i) * 32 + lane) * 4);
#pragma unroll
          for (int i = 0; i < 4; ++i) sts_f32(kf + ((i0 + i) * 32 + lane) * 4, (a[i][0] + a[i][1]) + (a[i][2] + a[i][3]));
        }
        __syncwarp();
        const float k1024 = lds_f32(kf + kidx_c(1024) * 4);
        if (lane == 0) {
          sts_f32(kf + SL_ZERO * 4, 0.f);
          sts_f32(kf + SL_510 * 4, lds_f32(kf + kidx_c(510) * 4) - lds_f32(kf + kidx_c(512) * 4));
          sts_f32(kf + SL_0 * 4, lds_f32(kf) + dskip);
        }
        __syncwarp();
#pragma unroll 1
        for (int i0 = 0; i0 < 30; i0 += 6) {
          uint32_t e[6];
          float a[6], b[6];
#pragma unroll
          for (int i = 0; i < 6; ++i) e[i] = lds32(sb + SM_PTAB + ((i0 + i) * 32 + lane) * 4);
#pragma unroll
          for (int i = 0; i < 6; ++i) { a[i] = lds_f32(kf + (e[i] & 0xffff)); b[i] = lds_f32(kf + (e[i] >> 16)); }
#pragma unroll
          for (int i = 0; i < 6; ++i) sts32(pb + ((i0 + i) * 32 + lane) * 4, pack_bf16(a[i], b[i]));
        }
        if (lane < 16) sts128(ub + lane * 16, 0, 0, 0, 0);
        if (elect_one()) {
          TS(4);
          wait_counter(&g_cnt[(C_U + (cta >> 4)) * 32], (epoch + 1) * 16);
          mbar_expect_tx(BAR(B_UCH + warp), 4096);
          bulk_load(ub + 256, p.uT + (size_t)d * 2048, 4096, BAR(B_UCH + warp));
        }
        __syncwarp();
        const int gq = g - 2 * q;
        uint32_t h127, h128;
        {
          const uint32_t kf2 = pack_bf16(k1024, k1024) ^ 0x80008000u;
          h127 = (gq == 4 ? 0x0000ffffu : gq == 5 ? 0xffffffffu : gq == 6 ? 0xffff0000u : 0u) & kf2;
          h128 = (gq == -4 ? 0x0000ffffu : gq == -3 ? 0xffffffffu : gq == -2 ? 0xffff0000u : 0u) & kf2;
        }
        bar_sync(4, 480);
        mbar_wait(BAR(B_UCH + warp), 0);
        if (lane == 0) TS(7);
        float acc[16][4];
#pragma unroll
        for (int i = 0; i < 16; ++i) { acc[i][0] = acc[i][1] = acc[i][2] = acc[i][3] = 0.f; }
        {
          const uint32_t pd_lane = pb + (PD_OFF + 16 + gq) * 4;
          const int prow0 = 8 + (lane & 7) + ((lane >> 4) << 3), hs = (lane >> 3) & 1;
          uint32_t B[2][4][4];
          uint32_t A[4][4];
          const uint32_t la0 = ub + prow0 * 32 + ((hs ^ ((prow0 >> 2) & 1)) << 4);
#pragma unroll
          for (int m2 = 0; m2 < 4; ++m2) ldsm_x4(B[0][m2], la0 + m2 * 512);
#pragma unroll
          for (int i = 0; i < 4; ++i) {
            const uint32_t a = pd_lane + i * 512;
            A[i][0] = lds32(a); A[i][1] = lds32(a + 32); A[i][2] = lds32(a - 32); A[i][3] = A[i][0];
          }
          uint32_t la = la0;
#pragma unroll 1
          for (int rho = 0; rho < 8; ++rho) {
#pragma unroll
            for (int m2 = 0; m2 < 4; ++m2) ldsm_x4(B[1][m2], la + (4 + m2) * 512);
#pragma unroll
            for (int i = 0; i < 4; ++i)
#pragma unroll
              for (int m = 0; m < 8; ++m) mma_bf16v(acc[m + i], A[i], B[0][m >> 1][2 * (m & 1)], B[0][m >> 1][2 * (m & 1) + 1]);
            const int prow = prow0 - min(rho + 1, 7);
            la = ub + prow * 32 + ((hs ^ ((prow >> 2) & 1)) << 4);
#pragma unroll
            for (int m2 = 0; m2 < 4; ++m2) ldsm_x4(B[0][m2], la + m2 * 512);
            const uint32_t pa = pd_lane + (rho + 1) * 64;
#pragma unroll
            for (int i = 0; i < 4; ++i) {
#pragma unroll
              for (int m = 0; m < 8 - i; ++m)
                mma_bf16v(acc[8 + m + i], A[i], B[1][m >> 1][2 * (m & 1)], B[1][m >> 1][2 * (m & 1) + 1]);
              A[i][0] = lds32(pa + i * 512); A[i][1] = lds32(pa + i * 512 + 32); A[i][2] = lds32(pa + i * 512 - 32);
              A[i][3] = A[i][0];
            }
          }
          {
            uint32_t b8[4];
            ldsm_x4(b8, la + 4 * 512);
            const uint32_t h63 = lds32(pd_lane + 63 * 32), h64 = lds32(pd_lane + 64 * 32);
            const uint32_t a63[4] = {0u, h127, 0u, 0u}, a32[4] = {h64, 0u, h63, h64}, a64[4] = {h128, 0u, h127, h128};
#pragma unroll
            for (int m2 = 0; m2 < 4; ++m2) ldsm_x4(B[1][m2], la0 + m2 * 512);
#pragma unroll
            for (int m = 0; m < 8; ++m) mma_bf16v(acc[m + 7], a63, B[0][m >> 1][2 * (m & 1)], B[0][m >> 1][2 * (m & 1) + 1]);
#pragma unroll
            for (int m2 = 0; m2 < 2; ++m2) ldsm_x4(B[0][m2], la0 + (4 + m2) * 512);
#pragma unroll
            for (int m = 0; m < 8; ++m) mma_bf16v(acc[m + 4], a32, B[1][m >> 1][2 * (m & 1)], B[1][m >> 1][2 * (m & 1) + 1]);
            mma_bf16v(acc[15], a63, b8[0], b8[1]);
#pragma unroll
            for (int m = 0; m < 8; ++m) mma_bf16v(acc[m + 8], a64, B[1][m >> 1][2 * (m & 1)], B[1][m >> 1][2 * (m & 1) + 1]);
#pragma unroll
            for (int m = 0; m < 4; ++m) mma_bf16v(acc[m + 12], a32, B[0][m >> 1][2 * (m & 1)], B[0][m >> 1][2 * (m & 1) + 1]);
          }
          bar_sync(5, 224);
#pragma unroll 1
          for (int v = 0; v < 4; ++v)
            conv_tail<4, 3, 11>(acc, pb + (P2_OFF + 56 * v + gq - 16) * 4, vv + ((v & 1) ? VV_U3 : VV_U5), v >> 1, v == 0, lane);
#pragma unroll 1
          for (int pi = 0; pi < 2; ++pi)
            conv_tail<8, 5, 7>(acc, pb + (P3_OFF + 88 * pi + gq - 48) * 4, vv + (pi ? VV_U7 : VV_U9), pi, pi == 0, lane);
        }
        bar_arrive(3, 384);
        if (lane == 0) TS(8);
        {
          const int mt = lane >> 3;
          const uint32_t a = vv + (128 * (mt >> 1) + 16 * (lane & 7) + 8 * (mt & 1)) * 2;
#pragma unroll
          for (int ab = 0; ab < 16; ab += 2)
            stsm_x4_t(a + ab * 256, pack_bf16(acc[ab][0], acc[ab][1]), pack_bf16(acc[ab][2], acc[ab][3]),
                      pack_bf16(acc[ab + 1][0], acc[ab + 1][1]), pack_bf16(acc[ab + 1][2], acc[ab + 1][3]));
        }
        fence_async_smem();
        __syncwarp();
        if (elect_one()) {
          bulk_store(p.yT + (size_t)d * 2048, vv, 4096);
          bulk_commit();
          bulk_wait0();
          red_relaxed_add(&g_cnt[(C_Y + (cta >> 4)) * 32], 1);
          TS(9);
        }
        bar_sync(2, 128);
        if (warp == 0 && elect_one()) {
          wait_counter(&g_cnt[(C_Y + tj) * 32], (epoch + 1) * 64);
          TS(28);
          mbar_expect_tx(BAR(B_TILE), 16384);
          tma_load_2d(sb + SM_U, &maps.yT, ti * 128, tj * 64, BAR(B_TILE));
          tma_load_2d(sb + SM_U + 8192, &maps.yT, ti * 128 + 64, tj * 64, BAR(B_TILE));
        }
        __syncwarp();
      }
      mbar_wait(BAR(B_TILE), pass);
      if (lane == 0) TS(26 + 3 * pass);
      {
        const int m = lane >> 3, r = lane & 7;
#pragma unroll 2
        for (int it = 0; it < 8; ++it) {
          const int tb = warp * 4 + (it >> 1), cb = (it & 1) * 4 + m;
          const uint32_t at = (tb * 8 + r) * 128 + ((cb ^ r) << 4);
          const uint32_t ac = (tb >> 3) * 8192 + (cb * 8 + r) * 128 + (((tb & 7) ^ (pass ? 0 : tb >> 3) ^ r) << 4);
          uint32_t v[4];
          ldsm_x4_t(v, sb + SM_U + (pass ? ac : at));
          stsm_x4(sb + SM_P + (pass ? at : ac), v[0], v[1], v[2], v[3]);
        }
      }
      fence_async_smem();
      bar_sync(2, 128);
      if (warp == 0 && elect_one()) {
        if (pass == 0) {
          tma_store_2d(&maps.uT, sb + SM_P, ti * 128, tj * 64);
          tma_store_2d(&maps.uT, sb + SM_P + 8192, ti * 128 + 64, tj * 64);
          bulk_commit();
          bulk_wait0();
          red_relaxed_add(&g_cnt[(C_U + tj) * 32], 1);
          TS(27);
        } else {
          tma_store_2d(&maps.out, sb + SM_P, 64 * tj, 128 * ti);
          bulk_commit();
          bulk_wait_read0();
          TS(30);
        }
      }
      if (pass == 0) bar_sync(2, 128);
    }
  } else if (warp < 12) {
    asm volatile("setmaxnreg.inc.sync.aligned.u32 160;");
    const int w8 = warp - 4;
    const int row = w8 * 16 + (lane & 7) + (((lane >> 3) & 1) << 3);
    {
      float acc[96];
#pragma unroll 1
      for (int ks = 0, s = 0, ph = 0; ks < 16; ++ks) {
        mbar_wait(BAR(B_FULL + s), ph);
        if (tid == 128 && !(ks & 1)) TSR(16, ks == 0 ? 16 : 9 + (ks >> 1) + (ks > 12 ? 46 : 0));
        const uint32_t st = sb + s * STG_BYTES;
        const uint32_t da = mkdesc(st + STG_X + (w8 >> 2) * 4096, 16);
        const uint32_t db = mkdesc(st + STG_W, 2048);
        wg_fence();
        wgmma_n192(acc, da, db, ks != 0);
        wgmma_n192(acc, da + 2, db + 384, 1);
        wg_commit();
        const uint32_t eprev = BAR(B_EMPTY + (s == 0 ? NSTG - 1 : s - 1));
        if (++s == NSTG) { s = 0; ph ^= 1; }
        if (ks > 0) {
          wg_wait<1>();
          if (lane < 2) mbar_arrive_cluster(eprev, lane);
        }
      }
      wg_wait<0>();
      bar_arrive(4, 480);
      if (tid == 128) TS(17);
      bar_sync(1, 256);
#pragma unroll
      for (int i = 0; i < 24; i += 2)
        stsm_x4(sb + SM_QS + row * 128 + (i >> 3) * 16384 + ((((i & 7) + (lane >> 4)) ^ (row & 7)) << 4),
                pack_bf16(acc[4 * i], acc[4 * i + 1]), pack_bf16(acc[4 * i + 2], acc[4 * i + 3]),
                pack_bf16(acc[4 * i + 4], acc[4 * i + 5]), pack_bf16(acc[4 * i + 6], acc[4 * i + 7]));
    }
    __syncwarp();
#pragma unroll 1
    for (int part = 1; part >= 0; --part) {
      const uint32_t pa = sb + SM_QS + part * 16384 + w8 * 2048 + lane * 16;
#pragma unroll 1
      for (int it = 0; it < 4; ++it) {
        uint4 t = lds128(pa + it * 512);
        uint32_t* tw = &t.x;
#pragma unroll
        for (int j = 0; j < 4; ++j) {
          const uint32_t x = tw[j];
          const __nv_bfloat162 xb = *reinterpret_cast<const __nv_bfloat162*>(&x);
          const uint32_t e = pack_bf16(ex2(bf_lo(x) * 1.4426950408889634f), ex2(bf_hi(x) * 1.4426950408889634f));
          const uint32_t m = __hgt2_mask(xb, __floats2bfloat162_rn(0.f, 0.f));
          const uint32_t sel = (badd(x, 0x3f803f80u) & m) | (e & ~m);
          tw[j] = pack_bf16(bf_lo(sel) + 1e-6f, bf_hi(sel) + 1e-6f);
        }
        sts128(pa + it * 512, t.x, t.y, t.z, t.w);
      }
      if (part == 1) {
        if (tid == 128) TS(53);
        bar_sync(1, 256);
        const int hh = w8 >> 1, dtile = w8 & 1;
        float kv[4] = {0.f, 0.f, 0.f, 0.f}, zz[4] = {0.f, 0.f, 0.f, 0.f};
        const int m = lane >> 3;
        const uint32_t aa = sb + SM_VS + ((lane & 7) + ((m >> 1) << 3)) * 128 + (((2 * hh + (m & 1)) ^ (lane & 7)) << 4);
        const uint32_t ab = sb + SM_PK + (lane & 15) * 128 + (((2 * hh + dtile) ^ (lane & 7)) << 4);
#pragma unroll 2
        for (int ks = 0; ks < 8; ++ks) {
          uint32_t a[4], b0, b1;
          ldsm_x4_t(a, aa + ks * 2048);
          ldsm_x2_t(b0, b1, ab + ks * 2048);
          mma_bf16(kv, a[0], a[1], a[2], a[3], b0, b1);
          mma_bf16(zz, 0x3f803f80u, 0x3f803f80u, 0x3f803f80u, 0x3f803f80u, b0, b1);
        }
        const uint32_t kp = sb + SM_KV + hh * 1088;
        sts128(kp + dtile * 512 + lane * 16, __float_as_uint(kv[0]), __float_as_uint(kv[1]), __float_as_uint(kv[2]),
               __float_as_uint(kv[3]));
        if (g == 0) sts_f32x2(kp + 1024 + dtile * 32 + q * 8, zz[0], zz[1]);
        fence_async_smem();
        __syncwarp();
        if (lane == 0) mbar_arrive(BAR(B_KVP));
        if (tid == 128) TS(55);
      }
    }
    __syncwarp();
    if (tid == 128) TS(56);
    mbar_wait(BAR(B_KVF), 0);
    if (tid == 128) TS(19);
#pragma unroll 1
    for (int h = 0; h < 4; ++h) {
      uint32_t a[4];
      const uint32_t qa = sb + SM_QS + row * 128 + (((2 * h + (lane >> 4)) ^ (row & 7)) << 4);
      ldsm_x4(a, qa);
      const uint32_t kp = sb + SM_KV + h * 1088;
      const uint4 k0 = lds128(kp + lane * 16), k1 = lds128(kp + 512 + lane * 16);
      const uint32_t za = kp + 1024 + q * 8;
      auto pk2 = [](uint32_t x, uint32_t y) { return pack_bf16(__uint_as_float(x), __uint_as_float(y)); };
      float n0[4] = {0.f, 0.f, 0.f, 0.f}, n1[4] = {0.f, 0.f, 0.f, 0.f}, dn[4] = {0.f, 0.f, 0.f, 0.f};
      mma_bf16(n0, a[0], a[1], a[2], a[3], pk2(k0.x, k0.y), pk2(k1.x, k1.y));
      mma_bf16(n1, a[0], a[1], a[2], a[3], pk2(k0.z, k0.w), pk2(k1.z, k1.w));
      mma_bf16(dn, a[0], a[1], a[2], a[3], pack_bf16(lds_f32(za), lds_f32(za + 4)), pack_bf16(lds_f32(za + 32), lds_f32(za + 36)));
      const uint32_t dd = pack_bf16(dn[0], dn[2]);
      const uint32_t d2 = pack_bf16(bf_lo(dd) + 1e-6f, bf_hi(dd) + 1e-6f);
      const float r0 = rcp(bf_lo(d2)), r1 = rcp(bf_hi(d2));
      const uint32_t x0 = pack_bf16(n0[0], n0[1]), x1 = pack_bf16(n0[2], n0[3]);
      const uint32_t x2 = pack_bf16(n1[0], n1[1]), x3 = pack_bf16(n1[2], n1[3]);
      stsm_x4(qa, pack_bf16(bf_lo(x0) * r0, bf_hi(x0) * r0), pack_bf16(bf_lo(x1) * r1, bf_hi(x1) * r1),
              pack_bf16(bf_lo(x2) * r0, bf_hi(x2) * r0), pack_bf16(bf_lo(x3) * r1, bf_hi(x3) * r1));
    }
    fence_async_smem();
    __syncwarp();
    if (lane == 0) mbar_arrive(BAR(B_OST));
    if (tid == 128) TS(57);
    bar_sync(3, 384);
    {
      float o[32];
#pragma unroll 1
      for (int c = 0, s = 0, ph = 0; c < 8; ++c) {
        mbar_wait(BAR(B_RF + s), ph);
        if (c == 0 && tid == 128) TS(22);
        const uint32_t da = mkdesc(sb + SM_QS + s * 16384 + (w8 >> 2) * 8192, 16);
        const uint32_t db = mkdesc(sb + SM_WO + s * 8192, 8192);
        wg_fence();
#pragma unroll
        for (int k = 0; k < 4; ++k) wgmma_n64(o, da + 2 * k, db + 128 * k, (c | k) != 0);
        wg_commit();
        const uint32_t eprev = BAR(B_RE + (s == 0 ? NRING - 1 : s - 1));
        if (++s == NRING) { s = 0; ph ^= 1; }
        if (c > 0) {
          wg_wait<1>();
          if (lane == 0) mbar_arrive(eprev);
        }
      }
      wg_wait<0>();
#pragma unroll
      for (int i = 0; i < 8; i += 2)
        stsm_x4(sb + SM_BOUT + row * 128 + (((i + (lane >> 4)) ^ (row & 7)) << 4), pack_bf16(o[4 * i], o[4 * i + 1]),
                pack_bf16(o[4 * i + 2], o[4 * i + 3]), pack_bf16(o[4 * i + 4], o[4 * i + 5]), pack_bf16(o[4 * i + 6], o[4 * i + 7]));
      fence_async_smem();
      bar_sync(1, 256);
      if (warp == 4 && elect_one()) {
        tma_store_2d(&maps.out, sb + SM_BOUT, 512 + 64 * tj, 128 * ti);
        bulk_commit();
        bulk_wait_read0();
        TS(23);
      }
    }
  } else {
    asm volatile("setmaxnreg.dec.sync.aligned.u32 40;");
    if (warp == 12) {
      if (elect_one()) {
        const unsigned epoch = __ldcg(&g_epoch);
#pragma unroll 1
        for (int ks = NSTG, s = 0, ph = 0; ks < 16; ++ks) {
          mbar_wait(BAR(B_EMPTY + s), ph);
          TSR(38, 31 + ks);
          const uint32_t st = sb + s * STG_BYTES, fb = BAR(B_FULL + s);
          mbar_expect_tx(fb, STG_BYTES);
          tma_load_2d(st + STG_X, &maps.x, ks * 32, ti * 128, fb);
          tma_load_3d_mc(st + STG_W + rank * 6144, &maps.w, tj * 64, ks * 32 + rank * 16, 0, fb, 3);
          if (++s == NSTG) { s = 0; ph ^= 1; }
        }
        prefetch_tmap(&maps.wo); prefetch_tmap(&maps.o); prefetch_tmap(&maps.out);
        mbar_wait(BAR(B_EMPTY + 4), 1);
        mbar_wait(BAR(B_EMPTY + 5), 1);
#pragma unroll 1
        for (int c = 0; c < NRING; ++c) {
          mbar_expect_tx(BAR(B_RF + c), 24576);
          tma_load_2d(sb + SM_WO + c * 8192, &maps.wo, tj * 64, c * 64, BAR(B_RF + c));
        }
        float* kvg = &g_kv[epoch & 1][tj][0];
        mbar_wait(BAR(B_KVP), 0);
        bulk_reduce_add_f32(kvg, sb + SM_KV, 4352);
        bulk_commit();
        bulk_wait0();
        red_relaxed_add(&g_cnt[(C_KV + tj) * 32], 1);
        TS(18);
        wait_counter(&g_cnt[(C_KV + tj) * 32], (epoch + 1) * 16);
        mbar_expect_tx(BAR(B_KVF), 4352);
        bulk_load(sb + SM_KV, kvg, 4352, BAR(B_KVF));
        mbar_wait(BAR(B_OST), 0);
        tma_store_2d(&maps.o, sb + SM_QS, tj * 64, ti * 128);
        bulk_commit();
        bulk_wait0();
        red_relaxed_add(&g_cnt[(C_O + ti) * 32], 1);
        TS(20);
        wait_counter(&g_cnt[(C_O + ti) * 32], (epoch + 1) * 8);
        if (cta == 0) g_epoch = epoch + 1;
        TS(21);
#pragma unroll 1
        for (int c = 0, s = 0; c < 8; ++c) {
          if (c >= NRING) {
            mbar_wait(BAR(B_RE + s), 0);
            mbar_expect_tx(BAR(B_RF + s), 24576);
            tma_load_2d(sb + SM_WO + s * 8192, &maps.wo, tj * 64, c * 64, BAR(B_RF + s));
          }
          tma_load_2d(sb + SM_QS + s * 16384, &maps.o, c * 64, ti * 128, BAR(B_RF + s));
          if (++s == NRING) s = 0;
        }
      }
    } else {
      if (warp == 13 && ti == 0) {
        float4* z = (float4*)&g_kv[(__ldcg(&g_epoch) & 1) ^ 1][tj][0];
#pragma unroll 1
        for (int i = lane; i < 272; i += 32) z[i] = make_float4(0.f, 0.f, 0.f, 0.f);
      }
      bar_sync(4, 480);
#pragma unroll 1
      for (int item = warp - 13; item < 32; item += 3) {
        const int ch = item >> 3, it = item & 7;
        mbar_wait(BAR(B_UCH + ch), 0);
          const int k = -18 + it * 32 + lane;
          const int kr = min(max(k, -2), 208);
          uint32_t E[12];
#pragma unroll
          for (int c = 0; c < 3; ++c) {
            const int kk = kr - 1 + c, r = (kk >> 1) + 8;
            const uint4 t = lds128(sb + SM_U + ch * U_BYTES + r * 32 + (((kk & 1) ^ ((r >> 2) & 1)) << 4));
            E[4 * c] = t.x; E[4 * c + 1] = t.y; E[4 * c + 2] = t.z; E[4 * c + 3] = t.w;
          }
          uint32_t O[8];
#pragma unroll
          for (int j = 0; j < 8; ++j) O[j] = __byte_perm(E[j + 1], E[j + 2], 0x5432);
          uint32_t s3[6], s5[4], s7[4], s9[4];
#pragma unroll
          for (int j = 0; j < 6; ++j) s3[j] = badd(badd(O[j], O[j + 1]), E[j + 2]);
#pragma unroll
          for (int j = 0; j < 4; ++j) {
            s5[j] = badd(s3[j + 2], badd(E[j + 3], E[j + 5]));
            s7[j] = badd(s5[j], badd(O[j + 1], O[j + 4]));
            s9[j] = badd(s7[j], badd(E[j + 2], E[j + 6]));
          }
          const int r = (k >> 1) + PADV;
          const uint32_t a = sb + SM_VV + ch * VV_BYTES + r * 32 + (((k & 1) ^ ((r >> 2) & 1)) << 4);
          if (k < 208) { sts128(a + VV_U3, s3[0], s3[1], s3[2], s3[3]); sts128(a + VV_U5, s5[0], s5[1], s5[2], s5[3]); }
          if (k < 144) { sts128(a + VV_U7, s7[0], s7[1], s7[2], s7[3]); sts128(a + VV_U9, s9[0], s9[1], s9[2], s9[3]); }
      }
      if (lane == 0 && warp == 13) TS(6);
      bar_arrive(5, 224);
    }
  }
  __syncwarp();
  cluster_arrive();
  cluster_wait();
  if (tid == 0) TS(31);
#undef BAR
}

typedef CUresult (*EncodeFn)(CUtensorMap*, CUtensorMapDataType, cuuint32_t, void*, const cuuint64_t*, const cuuint64_t*,
                             const cuuint32_t*, const cuuint32_t*, CUtensorMapInterleave, CUtensorMapSwizzle,
                             CUtensorMapL2promotion, CUtensorMapFloatOOBfill);

static void make_map(EncodeFn enc, CUtensorMap* m, const void* base, uint64_t inner, uint64_t outer, uint32_t box_in,
                     uint32_t box_out, CUtensorMapSwizzle swz = CU_TENSOR_MAP_SWIZZLE_128B) {
  cuuint64_t gd[2] = {inner, outer};
  cuuint64_t gs[1] = {inner * 2};
  cuuint32_t bd[2] = {box_in, box_out};
  cuuint32_t es[2] = {1, 1};
  enc(m, CU_TENSOR_MAP_DATA_TYPE_BFLOAT16, 2, const_cast<void*>(base), gd, gs, bd, es, CU_TENSOR_MAP_INTERLEAVE_NONE,
      swz, CU_TENSOR_MAP_L2_PROMOTION_L2_128B, CU_TENSOR_MAP_FLOAT_OOB_FILL_NONE);
}

}

extern "C" void kernel_launch(void* const* d_in, const int* in_sizes, int n_in, void* d_out, int out_size) {
  using namespace s4la;
  (void)in_sizes; (void)n_in; (void)out_size;
  static EncodeFn enc = nullptr;
  static void *uT = nullptr, *yT = nullptr, *oS = nullptr;
  if (!enc) {
    void* fn = nullptr;
    cudaDriverEntryPointQueryResult qr;
    cudaGetDriverEntryPoint("cuTensorMapEncodeTiled", &fn, cudaEnableDefault, &qr);
    enc = (EncodeFn)fn;
    cudaGetSymbolAddress(&uT, g_uT);
    cudaGetSymbolAddress(&yT, g_yT);
    cudaGetSymbolAddress(&oS, g_o);
    cudaFuncSetAttribute(fused_kernel, cudaFuncAttributeMaxDynamicSharedMemorySize, SM_TOTAL);
  }
  const __nv_bfloat16* const* in = (const __nv_bfloat16* const*)d_in;
  Maps maps;
  make_map(enc, &maps.x, in[9], 512, 2048, 32, 128, CU_TENSOR_MAP_SWIZZLE_64B);
  {
    cuuint64_t gd[3] = {512, 512, 3};
    cuuint64_t gs[2] = {3072, 1024};
    cuuint32_t bd[3] = {64, 16, 3};
    cuuint32_t es[3] = {1, 1, 1};
    enc(&maps.w, CU_TENSOR_MAP_DATA_TYPE_BFLOAT16, 3, const_cast<__nv_bfloat16*>(in[10]), gd, gs, bd, es,
        CU_TENSOR_MAP_INTERLEAVE_NONE, CU_TENSOR_MAP_SWIZZLE_128B, CU_TENSOR_MAP_L2_PROMOTION_L2_128B,
        CU_TENSOR_MAP_FLOAT_OOB_FILL_NONE);
  }
  make_map(enc, &maps.wo, in[11], 512, 512, 64, 64);
  make_map(enc, &maps.u, in[0], 512, 2048, 64, 128);
  make_map(enc, &maps.uT, uT, 2048, 512, 64, 64);
  make_map(enc, &maps.yT, yT, 2048, 512, 64, 64);
  make_map(enc, &maps.o, oS, 512, 2048, 64, 128);
  make_map(enc, &maps.out, d_out, 1024, 2048, 64, 128);
  Ptrs p;
  p.A_re = in[1]; p.A_im = in[2]; p.B_re = in[3]; p.B_im = in[4]; p.C_re = in[5]; p.C_im = in[6];
  p.log_dt = in[7]; p.Dskip = in[8]; p.x = in[9]; p.wqkv = in[10]; p.wo = in[11];
  p.uT = (__nv_bfloat16*)uT; p.yT = (__nv_bfloat16*)yT;
  fused_kernel<<<NCTA, NTHREADS, SM_TOTAL, cudaStreamPerThread>>>(maps, p);
}
```

```cpp
#include <cuda_runtime.h>
#include <cuda_bf16.h>
#include <cuda_fp16.h>
#include <cuda.h>
#include <stdint.h>

#define DEVI __device__ __forceinline__

namespace s4la {

constexpr int NTHREADS = 512;
constexpr int NCTA = 128;

constexpr int NSTG = 7;
constexpr uint32_t STG_BYTES = 20480, STG_X = 0, STG_W = 8192;
constexpr int NRING = 5;
constexpr uint32_t SM_QS = 0;
constexpr uint32_t SM_PK = SM_QS + 16384, SM_VS = SM_QS + 32768;
constexpr uint32_t SM_WO = 81920;
constexpr uint32_t SM_KV = 122880;
constexpr uint32_t SM_BOUT = 126976;
constexpr uint32_t SM_U = 143360, U_BYTES = 4352;
constexpr uint32_t SM_P = 160768, P_BYTES = 4096;
constexpr uint32_t SM_VV = 177152, VV_BYTES = 12800;
constexpr uint32_t VV_U5 = 0, VV_U3 = 3712, VV_U9 = 7424, VV_U7 = 10112;
constexpr uint32_t KG_BYTES = 3200;
constexpr uint32_t SM_BAR = SM_VV + 4 * VV_BYTES;
constexpr uint32_t SM_PTAB = SM_BAR + 320;
constexpr uint32_t SM_TOTAL = SM_PTAB + 2048;
static_assert(SM_TOTAL <= 232448, "shared memory");
constexpr int PADV = 12;

enum { B_FULL = 0, B_EMPTY = 7, B_TILE = 14, B_UCH = 15, B_KVP = 19, B_KVF = 20, B_OST = 21, B_RF = 22, B_RE = 27, B_PFREE = 32, B_COUNT = 33 };
__host__ __device__ constexpr int bar_count(int i) {
  return (i >= B_EMPTY && i < B_TILE) ? 16 : (i == B_KVP || i == B_OST || (i >= B_RE && i < B_PFREE)) ? 8 : 1;
}

constexpr int PD_OFF = 0, P2_OFF = 544, P3_OFF = 768;

constexpr int SL_K2048 = 20, SL_ZERO = 21, SL_510 = 22, SL_0 = 23;
__host__ __device__ constexpr int koff(int y) {
  return y < 8 ? y : y < 12 ? 256 + 2 * (y - 8) : y < 16 ? 512 + 256 * ((y - 12) >> 1) + 4 * (y & 1) : 1024 + 256 * (y - 16);
}
__host__ __device__ constexpr int kidx_c(int l) {
  const int y = l < 256 ? (l & 7) : l < 512 ? 8 + ((l & 7) >> 1) : l < 1024 ? 12 + (((l - 512) >> 8) << 1) + ((l >> 2) & 1)
                                                                            : 16 + ((l - 1024) >> 8);
  return ((l >> 3) & 31) * 24 + y;
}
constexpr int slot_direct(int l) {
  if (l < 0 || l > 510) return SL_ZERO;
  if (l == 510) return SL_510;
  if (l == 0) return SL_0;
  return kidx_c(l < 256 ? l : ((l + ((l >> 1) & 1)) & ~1));
}
constexpr int slot_seg2(int v, int k) { return (k >= 32 && k < 64) ? kidx_c(16 * k + 4 * v) : SL_ZERO; }
constexpr int slot_seg3(int pi, int k) {
  return (k >= 64 && k < 128) ? kidx_c(16 * k + 8 * pi) : ((k == 128 && pi == 0) ? SL_K2048 : SL_ZERO);
}
constexpr int slot_word(int w) {
  return w < 0 ? SL_ZERO : w < 544 ? slot_direct(w - 16) : w < 768 ? slot_seg2((w - 544) / 56, 16 + (w - 544) % 56)
       : w < 944 ? slot_seg3((w - 768) / 88, 48 + (w - 768) % 88) : SL_ZERO;
}
struct PTab { uint32_t v[512]; };
constexpr PTab make_ptab() {
  PTab t{};
  for (int lane = 0; lane < 32; ++lane)
    for (int i = 0; i < 16; ++i)
      t.v[i * 32 + lane] = (slot_word(30 * lane - 1 + 2 * i) * 4) | ((slot_word(30 * lane + 2 * i) * 4) << 16);
  return t;
}
__device__ const PTab g_ptab = make_ptab();

__device__ __nv_bfloat16 g_uT[512 * 2048];
__device__ __nv_bfloat16 g_yT[512 * 2048];
__device__ __nv_bfloat16 g_o[2048 * 512];
__device__ float g_kv[2][8][4 * 272];
__device__ unsigned g_cnt[64 * 32];
__device__ unsigned g_epoch;
#define TS(slot) do { } while (0)
#define TSR(on, slot) do { } while (0)
enum { C_U = 0, C_KV = 8, C_O = 16, C_Y = 32 };

struct Maps {
  CUtensorMap x, w, wo, u, uT, yT, o, out;
};
struct Ptrs {
  const __nv_bfloat16 *A_re, *A_im, *B_re, *B_im, *C_re, *C_im, *log_dt, *Dskip;
  const __nv_bfloat16 *x, *wqkv, *wo;
  __nv_bfloat16 *uT, *yT;
};

DEVI uint32_t s2u(const void* p) { return (uint32_t)__cvta_generic_to_shared(p); }
DEVI void mbar_init(uint32_t b, uint32_t c) { asm volatile("mbarrier.init.shared::cta.b64 [%0], %1;" ::"r"(b), "r"(c) : "memory"); }
DEVI void mbar_expect_tx(uint32_t b, uint32_t bytes) {
  asm volatile("mbarrier.arrive.expect_tx.shared::cta.b64 _, [%0], %1;" ::"r"(b), "r"(bytes) : "memory");
}
DEVI void mbar_arrive(uint32_t b) { asm volatile("mbarrier.arrive.shared::cta.b64 _, [%0];" ::"r"(b) : "memory"); }
DEVI void mbar_arrive_cluster(uint32_t b, uint32_t cta) {
  asm volatile("{\n.reg .b32 r;\nmapa.shared::cluster.u32 r, %0, %1;\nmbarrier.arrive.shared::cluster.b64 _, [r];\n}"
               ::"r"(b), "r"(cta) : "memory");
}
DEVI void mbar_wait(uint32_t b, uint32_t parity) {
  asm volatile("{\n.reg .pred p;\nLAB_WAIT:\nmbarrier.try_wait.parity.shared::cta.b64 p, [%0], %1;\n@!p bra LAB_WAIT;\n}"
               ::"r"(b), "r"(parity) : "memory");
}
DEVI void bar_sync(int id, int n) { asm volatile("bar.sync %0, %1;" ::"r"(id), "r"(n) : "memory"); }
DEVI void bar_arrive(int id, int n) { asm volatile("bar.arrive %0, %1;" ::"r"(id), "r"(n) : "memory"); }
DEVI void fence_async_smem() { asm volatile("fence.proxy.async.shared::cta;" ::: "memory"); }
DEVI void fence_async_all() { asm volatile("fence.proxy.async;" ::: "memory"); }
DEVI void cluster_arrive() { asm volatile("barrier.cluster.arrive.relaxed.aligned;" ::: "memory"); }
DEVI void cluster_wait() { asm volatile("barrier.cluster.wait.aligned;" ::: "memory"); }

DEVI void tma_load_2d(uint32_t dst, const CUtensorMap* m, int c0, int c1, uint32_t bar) {
  asm volatile("cp.async.bulk.tensor.2d.shared::cluster.global.mbarrier::complete_tx::bytes [%0], [%1, {%3, %4}], [%2];"
               ::"r"(dst), "l"(m), "r"(bar), "r"(c0), "r"(c1) : "memory");
}
DEVI void tma_load_3d_mc(uint32_t dst, const CUtensorMap* m, int c0, int c1, int c2, uint32_t bar, uint16_t mask) {
  asm volatile("cp.async.bulk.tensor.3d.shared::cluster.global.mbarrier::complete_tx::bytes.multicast::cluster [%0], [%1, {%3, %4, %5}], [%2], %6;"
               ::"r"(dst), "l"(m), "r"(bar), "r"(c0), "r"(c1), "r"(c2), "h"(mask) : "memory");
}
DEVI void tma_store_2d(const CUtensorMap* m, uint32_t src, int c0, int c1) {
  asm volatile("cp.async.bulk.tensor.2d.global.shared::cta.bulk_group [%0, {%2, %3}], [%1];"
               ::"l"(m), "r"(src), "r"(c0), "r"(c1) : "memory");
}
DEVI void bulk_load(uint32_t dst, const void* src, uint32_t bytes, uint32_t bar) {
  asm volatile("cp.async.bulk.shared::cluster.global.mbarrier::complete_tx::bytes [%0], [%1], %2, [%3];"
               ::"r"(dst), "l"(src), "r"(bytes), "r"(bar) : "memory");
}
DEVI void bulk_store(void* dst, uint32_t src, uint32_t bytes) {
  asm volatile("cp.async.bulk.global.shared::cta.bulk_group [%0], [%1], %2;" ::"l"(dst), "r"(src), "r"(bytes) : "memory");
}
DEVI void bulk_reduce_add_f32(void* dst, uint32_t src, uint32_t bytes) {
  asm volatile("cp.reduce.async.bulk.global.shared::cta.bulk_group.add.f32 [%0], [%1], %2;" ::"l"(dst), "r"(src), "r"(bytes) : "memory");
}
DEVI void bulk_commit() { asm volatile("cp.async.bulk.commit_group;" ::: "memory"); }
DEVI void bulk_wait0() { asm volatile("cp.async.bulk.wait_group 0;" ::: "memory"); }
DEVI void bulk_wait_read0() { asm volatile("cp.async.bulk.wait_group.read 0;" ::: "memory"); }
DEVI void l2_prefetch(const void* p, uint32_t bytes) {
  asm volatile("cp.async.bulk.prefetch.L2.global [%0], %1;" ::"l"(p), "r"(bytes) : "memory");
}
DEVI void prefetch_tmap(const CUtensorMap* m) { asm volatile("prefetch.tensormap [%0];" ::"l"(m) : "memory"); }

DEVI void red_release_add(unsigned* p, unsigned v) {
  asm volatile("red.release.gpu.global.add.u32 [%0], %1;" ::"l"(p), "r"(v) : "memory");
}
DEVI void red_relaxed_add(unsigned* p, unsigned v) {
  asm volatile("red.relaxed.gpu.global.add.u32 [%0], %1;" ::"l"(p), "r"(v) : "memory");
}
DEVI unsigned ld_relaxed(const unsigned* p) {
  unsigned v;
  asm volatile("ld.relaxed.gpu.global.u32 %0, [%1];" : "=r"(v) : "l"(p) : "memory");
  return v;
}
DEVI void wait_counter(const unsigned* p, unsigned target) {
#pragma unroll 1
  for (int it = 0; (int)(ld_relaxed(p) - target) < 0; ++it)
    if (it > (1 << 22)) __trap();
}

DEVI void ldsm_x4(uint32_t (&r)[4], uint32_t a) {
  asm volatile("ldmatrix.sync.aligned.m8n8.x4.shared.b16 {%0,%1,%2,%3}, [%4];"
               : "=r"(r[0]), "=r"(r[1]), "=r"(r[2]), "=r"(r[3]) : "r"(a) : "memory");
}
DEVI void ldsm_x4_t(uint32_t (&r)[4], uint32_t a) {
  asm volatile("ldmatrix.sync.aligned.m8n8.x4.trans.shared.b16 {%0,%1,%2,%3}, [%4];"
               : "=r"(r[0]), "=r"(r[1]), "=r"(r[2]), "=r"(r[3]) : "r"(a) : "memory");
}
DEVI void ldsm_x2_t(uint32_t& r0, uint32_t& r1, uint32_t a) {
  asm volatile("ldmatrix.sync.aligned.m8n8.x2.trans.shared.b16 {%0,%1}, [%2];" : "=r"(r0), "=r"(r1) : "r"(a) : "memory");
}
DEVI void stsm_x4(uint32_t a, uint32_t r0, uint32_t r1, uint32_t r2, uint32_t r3) {
  asm volatile("stmatrix.sync.aligned.m8n8.x4.shared.b16 [%0], {%1,%2,%3,%4};"
               ::"r"(a), "r"(r0), "r"(r1), "r"(r2), "r"(r3) : "memory");
}
DEVI void stsm_x4_t(uint32_t a, uint32_t r0, uint32_t r1, uint32_t r2, uint32_t r3) {
  asm volatile("stmatrix.sync.aligned.m8n8.x4.trans.shared.b16 [%0], {%1,%2,%3,%4};"
               ::"r"(a), "r"(r0), "r"(r1), "r"(r2), "r"(r3) : "memory");
}
DEVI uint32_t lds32(uint32_t a) { uint32_t v; asm volatile("ld.shared.b32 %0, [%1];" : "=r"(v) : "r"(a) : "memory"); return v; }
DEVI float lds_f32(uint32_t a) { float v; asm volatile("ld.shared.f32 %0, [%1];" : "=f"(v) : "r"(a) : "memory"); return v; }
DEVI void sts32(uint32_t a, uint32_t v) { asm volatile("st.shared.b32 [%0], %1;" ::"r"(a), "r"(v) : "memory"); }
DEVI void sts_f32(uint32_t a, float v) { asm volatile("st.shared.f32 [%0], %1;" ::"r"(a), "f"(v) : "memory"); }
DEVI void sts_f32x2(uint32_t a, float x, float y) { asm volatile("st.shared.v2.f32 [%0], {%1,%2};" ::"r"(a), "f"(x), "f"(y) : "memory"); }
DEVI uint4 lds128(uint32_t a) {
  uint4 v;
  asm volatile("ld.shared.v4.b32 {%0,%1,%2,%3}, [%4];" : "=r"(v.x), "=r"(v.y), "=r"(v.z), "=r"(v.w) : "r"(a) : "memory");
  return v;
}
DEVI void sts128(uint32_t a, uint32_t x, uint32_t y, uint32_t z, uint32_t w) {
  asm volatile("st.shared.v4.b32 [%0], {%1,%2,%3,%4};" ::"r"(a), "r"(x), "r"(y), "r"(z), "r"(w) : "memory");
}

DEVI void mma_bf16(float (&d)[4], uint32_t a0, uint32_t a1, uint32_t a2, uint32_t a3, uint32_t b0, uint32_t b1) {
  asm("mma.sync.aligned.m16n8k16.row.col.f32.bf16.bf16.f32 {%0,%1,%2,%3}, {%4,%5,%6,%7}, {%8,%9}, {%0,%1,%2,%3};"
      : "+f"(d[0]), "+f"(d[1]), "+f"(d[2]), "+f"(d[3])
      : "r"(a0), "r"(a1), "r"(a2), "r"(a3), "r"(b0), "r"(b1));
}
DEVI void mma_f16(float (&d)[4], const uint32_t (&a)[4], uint32_t b0, uint32_t b1) {
  asm("mma.sync.aligned.m16n8k16.row.col.f32.f16.f16.f32 {%0,%1,%2,%3}, {%4,%5,%6,%7}, {%8,%9}, {%0,%1,%2,%3};"
      : "+f"(d[0]), "+f"(d[1]), "+f"(d[2]), "+f"(d[3])
      : "r"(a[0]), "r"(a[1]), "r"(a[2]), "r"(a[3]), "r"(b0), "r"(b1));
}
DEVI void mma_bf16v(float (&d)[4], const uint32_t (&a)[4], uint32_t b0, uint32_t b1) {
  asm volatile("mma.sync.aligned.m16n8k16.row.col.f32.bf16.bf16.f32 {%0,%1,%2,%3}, {%4,%5,%6,%7}, {%8,%9}, {%0,%1,%2,%3};"
               : "+f"(d[0]), "+f"(d[1]), "+f"(d[2]), "+f"(d[3])
               : "r"(a[0]), "r"(a[1]), "r"(a[2]), "r"(a[3]), "r"(b0), "r"(b1));
}
DEVI uint32_t pack_bf16(float lo, float hi) {
  uint32_t r;
  asm("cvt.rn.bf16x2.f32 %0, %1, %2;" : "=r"(r) : "f"(hi), "f"(lo));
  return r;
}
DEVI uint32_t pack_f16(float lo, float hi) {
  uint32_t r;
  asm("cvt.rn.f16x2.f32 %0, %1, %2;" : "=r"(r) : "f"(hi), "f"(lo));
  return r;
}
DEVI uint32_t ldg16(const __nv_bfloat16* p) {
  uint32_t v;
  asm volatile("ld.global.nc.u16 %0, [%1];" : "=r"(v) : "l"(p));
  return v;
}
DEVI bool elect_one() {
  uint32_t pred;
  asm volatile("{\n.reg .pred p;\nelect.sync _|p, 0xffffffff;\nselp.u32 %0, 1, 0, p;\n}" : "=r"(pred));
  return pred != 0;
}
DEVI float bf_lo(uint32_t v) { return __uint_as_float(v << 16); }
DEVI float bf_hi(uint32_t v) { return __uint_as_float(v & 0xffff0000u); }
DEVI float bf2f(__nv_bfloat16 v) { return __bfloat162float(v); }
DEVI float round_bf16(float v) { return __bfloat162float(__float2bfloat16_rn(v)); }
DEVI float rcp(float x) { float r; asm("rcp.approx.ftz.f32 %0, %1;" : "=f"(r) : "f"(x)); return r; }
DEVI float ex2(float x) { float r; asm("ex2.approx.ftz.f32 %0, %1;" : "=f"(r) : "f"(x)); return r; }

DEVI void wg_fence() { asm volatile("wgmma.fence.sync.aligned;" ::: "memory"); }
DEVI void wg_commit() { asm volatile("wgmma.commit_group.sync.aligned;" ::: "memory"); }
template <int N> DEVI void wg_wait() { asm volatile("wgmma.wait_group.sync.aligned %0;" ::"n"(N) : "memory"); }
constexpr uint32_t DESC_HI = (1u << 30) | (1024 >> 4);
constexpr uint32_t DESC_HI64 = (2u << 30) | (512 >> 4);
DEVI uint32_t mkdesc(uint32_t saddr, uint32_t lbo) { return ((saddr & 0x3FFFF) >> 4) | ((lbo >> 4) << 16); }

#define R8(b) "%" #b
DEVI void wgmma_n192(float (&d)[96], uint32_t da, uint32_t db, int scale_d) {
  asm volatile(
      "{\n.reg .pred p;\n.reg .b64 da, db;\nsetp.ne.b32 p, %98, 0;\nmov.b64 da, {%96, %100};\nmov.b64 db, {%97, %99};\n"
      "wgmma.mma_async.sync.aligned.m64n192k16.f32.bf16.bf16 "
      "{%0,%1,%2,%3,%4,%5,%6,%7,%8,%9,%10,%11,%12,%13,%14,%15,"
      "%16,%17,%18,%19,%20,%21,%22,%23,%24,%25,%26,%27,%28,%29,%30,%31,"
      "%32,%33,%34,%35,%36,%37,%38,%39,%40,%41,%42,%43,%44,%45,%46,%47,"
      "%48,%49,%50,%51,%52,%53,%54,%55,%56,%57,%58,%59,%60,%61,%62,%63,"
      "%64,%65,%66,%67,%68,%69,%70,%71,%72,%73,%74,%75,%76,%77,%78,%79,"
      "%80,%81,%82,%83,%84,%85,%86,%87,%88,%89,%90,%91,%92,%93,%94,%95}, "
      "da, db, p, 1, 1, 0, 1;\n}"
      : "+f"(d[0]), "+f"(d[1]), "+f"(d[2]), "+f"(d[3]), "+f"(d[4]), "+f"(d[5]), "+f"(d[6]), "+f"(d[7]),
        "+f"(d[8]), "+f"(d[9]), "+f"(d[10]), "+f"(d[11]), "+f"(d[12]), "+f"(d[13]), "+f"(d[14]), "+f"(d[15]),
        "+f"(d[16]), "+f"(d[17]), "+f"(d[18]), "+f"(d[19]), "+f"(d[20]), "+f"(d[21]), "+f"(d[22]), "+f"(d[23]),
        "+f"(d[24]), "+f"(d[25]), "+f"(d[26]), "+f"(d[27]), "+f"(d[28]), "+f"(d[29]), "+f"(d[30]), "+f"(d[31]),
        "+f"(d[32]), "+f"(d[33]), "+f"(d[34]), "+f"(d[35]), "+f"(d[36]), "+f"(d[37]), "+f"(d[38]), "+f"(d[39]),
        "+f"(d[40]), "+f"(d[41]), "+f"(d[42]), "+f"(d[43]), "+f"(d[44]), "+f"(d[45]), "+f"(d[46]), "+f"(d[47]),
        "+f"(d[48]), "+f"(d[49]), "+f"(d[50]), "+f"(d[51]), "+f"(d[52]), "+f"(d[53]), "+f"(d[54]), "+f"(d[55]),
        "+f"(d[56]), "+f"(d[57]), "+f"(d[58]), "+f"(d[59]), "+f"(d[60]), "+f"(d[61]), "+f"(d[62]), "+f"(d[63]),
        "+f"(d[64]), "+f"(d[65]), "+f"(d[66]), "+f"(d[67]), "+f"(d[68]), "+f"(d[69]), "+f"(d[70]), "+f"(d[71]),
        "+f"(d[72]), "+f"(d[73]), "+f"(d[74]), "+f"(d[75]), "+f"(d[76]), "+f"(d[77]), "+f"(d[78]), "+f"(d[79]),
        "+f"(d[80]), "+f"(d[81]), "+f"(d[82]), "+f"(d[83]), "+f"(d[84]), "+f"(d[85]), "+f"(d[86]), "+f"(d[87]),
        "+f"(d[88]), "+f"(d[89]), "+f"(d[90]), "+f"(d[91]), "+f"(d[92]), "+f"(d[93]), "+f"(d[94]), "+f"(d[95])
      : "r"(da), "r"(db), "r"(scale_d), "n"(DESC_HI), "n"(DESC_HI64));
}
DEVI void wgmma_n64(float (&d)[32], uint32_t da, uint32_t db, int scale_d) {
  asm volatile(
      "{\n.reg .pred p;\n.reg .b64 da, db;\nsetp.ne.b32 p, %34, 0;\nmov.b64 da, {%32, %35};\nmov.b64 db, {%33, %35};\n"
      "wgmma.mma_async.sync.aligned.m64n64k16.f32.bf16.bf16 "
      "{%0,%1,%2,%3,%4,%5,%6,%7,%8,%9,%10,%11,%12,%13,%14,%15,"
      "%16,%17,%18,%19,%20,%21,%22,%23,%24,%25,%26,%27,%28,%29,%30,%31}, "
      "da, db, p, 1, 1, 0, 1;\n}"
      : "+f"(d[0]), "+f"(d[1]), "+f"(d[2]), "+f"(d[3]), "+f"(d[4]), "+f"(d[5]), "+f"(d[6]), "+f"(d[7]),
        "+f"(d[8]), "+f"(d[9]), "+f"(d[10]), "+f"(d[11]), "+f"(d[12]), "+f"(d[13]), "+f"(d[14]), "+f"(d[15]),
        "+f"(d[16]), "+f"(d[17]), "+f"(d[18]), "+f"(d[19]), "+f"(d[20]), "+f"(d[21]), "+f"(d[22]), "+f"(d[23]),
        "+f"(d[24]), "+f"(d[25]), "+f"(d[26]), "+f"(d[27]), "+f"(d[28]), "+f"(d[29]), "+f"(d[30]), "+f"(d[31])
      : "r"(da), "r"(db), "r"(scale_d), "n"(DESC_HI));
}

struct C32 { float re, im; };
DEVI C32 csq(C32 a) { return {a.re * a.re - a.im * a.im, 2.f * a.re * a.im}; }
DEVI C32 cmul(C32 a, C32 b) { return {a.re * b.re - a.im * b.im, a.re * b.im + a.im * b.re}; }
DEVI C32 cfresh(float zl, float zi, float m) {
  float mag = ex2(zl * m), ph = zi * m;
  return {mag * __cosf(ph), mag * __sinf(ph)};
}
struct HMul { uint32_t b, bp; };
DEVI HMul mk_mul(float re, float im) { return {pack_f16(re, im), pack_f16(-im, re)}; }
DEVI uint32_t hcmul(uint32_t a, const HMul& m) {
  __half2 ah = *reinterpret_cast<__half2*>(&a);
  __half2 b = *reinterpret_cast<const __half2*>(&m.b), bp = *reinterpret_cast<const __half2*>(&m.bp);
  __half2 r = __hfma2(__high2half2(ah), bp, __hmul2(__low2half2(ah), b));
  return *reinterpret_cast<uint32_t*>(&r);
}
DEVI uint32_t badd(uint32_t a, uint32_t b) {
  __nv_bfloat162 r = __hadd2(*reinterpret_cast<__nv_bfloat162*>(&a), *reinterpret_cast<__nv_bfloat162*>(&b));
  return *reinterpret_cast<uint32_t*>(&r);
}
template <int MU0, int NMU, int DMAX>
DEVI void conv_tail(float (&acc)[16][4], uint32_t p_lane, uint32_t v_base, int back, bool edge, int lane) {
  const int hsel = (lane >> 3) & 1;
  const int row = (lane & 7) + ((lane >> 4) << 3) + PADV - 8 - (back & (hsel ^ 1));
  const uint32_t la = v_base + row * 32 + (((hsel ^ back) ^ ((row >> 2) & 1)) << 4);
  uint32_t M[3][4];
  ldsm_x4_t(M[0], la);
  ldsm_x4_t(M[1], la + 256);
  uint32_t H[2 * NMU];
#pragma unroll
  for (int i = 0; i < 2 * NMU; ++i) H[i ^ 1] = lds32(p_lane + (uint32_t)(MU0 - 1 + i) * 32);
  if (edge) {
    const uint32_t a[4] = {0u, 0u, M[0][0], M[0][1]};
#pragma unroll
    for (int k = 1; k < NMU; ++k) mma_bf16v(acc[MU0 - 2 + 2 * k], a, H[2 * k], H[2 * k + 1]);
  }
#pragma unroll
  for (int delta = -1; delta <= DMAX; ++delta) {
    if (delta + 2 <= DMAX) ldsm_x4_t(M[(delta + 3) % 3], la + (delta + 3) * 256);
#pragma unroll
    for (int k = 0; k < NMU; ++k)
      if (delta + MU0 + 2 * k < 16) mma_bf16v(acc[delta + MU0 + 2 * k], M[(delta + 1) % 3], H[2 * k], H[2 * k + 1]);
  }
}

__global__ void __cluster_dims__(2, 1, 1) __launch_bounds__(NTHREADS, 1)
fused_kernel(const __grid_constant__ Maps maps, const Ptrs p) {
  extern __shared__ __align__(1024) uint8_t smem[];
  const uint32_t sb = s2u(smem);
  const int tid = threadIdx.x, lane = tid & 31;
  const int warp = __shfl_sync(0xffffffffu, tid >> 5, 0);
  const int cta = blockIdx.x;
  const uint32_t rank = cta & 1;
  const int ti = 2 * (cta >> 4) + rank;
  const int tj = (cta >> 1) & 7;
  const uint32_t bars = sb + SM_BAR;
#define BAR(i) (bars + 8 * (i))
  const int g = lane >> 2, q = lane & 3;

  const int kch = warp & 3, krd = warp >> 2;
  float zr, zi, wr, wi;
  {
    const size_t po = (size_t)(cta * 4 + kch) * 128 + krd * 32 + lane;
    const uint32_t r_ar = ldg16(p.A_re + po), r_ai = ldg16(p.A_im + po), r_br = ldg16(p.B_re + po), r_bi = ldg16(p.B_im + po);
    const uint32_t r_cr = ldg16(p.C_re + po), r_ci = ldg16(p.C_im + po), r_ldt = ldg16(p.log_dt + cta * 4 + kch);
    uint4 pt;
    if (tid < 128) pt = __ldg((const uint4*)g_ptab.v + tid);
    if (tid == 384) {
      TS(0);
#pragma unroll
      for (int i = 0; i < B_COUNT; ++i) mbar_init(BAR(i), bar_count(i));
      asm volatile("fence.mbarrier_init.release.cluster;" ::: "memory");
      prefetch_tmap(&maps.x); prefetch_tmap(&maps.w); prefetch_tmap(&maps.u);
    }
    __syncthreads();
    cluster_arrive();
    if (warp >= 12) {
      cluster_wait();
      if (elect_one()) {
        if (warp == 13) {
          mbar_expect_tx(BAR(B_TILE), 16384);
          tma_load_2d(sb + SM_U, &maps.u, tj * 64, ti * 128, BAR(B_TILE));
          l2_prefetch((const char*)p.wqkv + 224 * 3072 + cta * 6912, 6912);
          l2_prefetch((const char*)p.x + (size_t)cta * 16384, 16384);
          l2_prefetch((const char*)p.wo + (size_t)cta * 4096, 4096);
        } else {
          if (warp == 12) TS(61);
#pragma unroll 1
          for (int ks = warp == 12 ? 0 : warp - 13; ks < NSTG; ks += 3) {
            const uint32_t st = sb + ks * STG_BYTES, fb = BAR(B_FULL + ks);
            mbar_expect_tx(fb, STG_BYTES);
            tma_load_2d(st + STG_X, &maps.x, ks * 32, ti * 128, fb);
            tma_load_3d_mc(st + STG_W + rank * 6144, &maps.w, tj * 64, ks * 32 + rank * 16, 0, fb, 3);
          }
        }
      }
      __syncwarp();
    }
    if (tid < 128) sts128(sb + SM_PTAB + tid * 16, pt.x, pt.y, pt.z, pt.w);
    const float dt = round_bf16(expf(bf_lo(r_ldt)));
    zr = dt * bf_lo(r_ar); zi = dt * bf_lo(r_ai);
    const float dbr = dt * bf_lo(r_br), dbi = dt * bf_lo(r_bi), cr = bf_lo(r_cr), ci = bf_lo(r_ci);
    wr = cr * dbr - ci * dbi; wi = cr * dbi + ci * dbr;
  }
  {
    const float mz = __uint_as_float(__reduce_max_sync(0xffffffffu, __float_as_uint(fmaxf(zr, 0.f))));
    const int E = min(max((int)(__reduce_max_sync(0xffffffffu, __float_as_uint(fmaxf(fabsf(wr), fabsf(wi)))) >> 23), 1), 252);
    const float sc = __int_as_float((253 - E) << 23), inv = __int_as_float((E + 1) << 23);
    const float zl = (zr - mz) * 1.4426950408889634f;
    const uint32_t tb = sb + SM_VV + kch * VV_BYTES + krd * KG_BYTES;
    const uint32_t sta = tb + (((lane >> 2) << 4) | ((lane & 3) << 2));
    auto put = [&](int r, uint32_t v) { sts32((sta ^ ((r & 7) << 4)) + r * 128, v); };
    const uint32_t lda = tb + ((lane & 7) + (((lane >> 3) & 1) << 3)) * 128;
    const uint32_t ldb = tb + ((lane & 7) + ((lane >> 4) << 3)) * 128;
    C32 e1 = cfresh(zl, zi, 1.f), e2 = csq(e1), e4 = csq(e2), e8 = csq(e4);
    C32 e16 = cfresh(zl, zi, 16.f), e32 = csq(e16), e64 = csq(e32), e128 = csq(e64);
    C32 e256 = cfresh(zl, zi, 256.f), e512 = csq(e256), e1024 = csq(e512), e768 = cmul(e512, e256);
    uint32_t XA[2][4][4];
    {
      const HMul m16 = mk_mul(e16.re, e16.im), m32 = mk_mul(e32.re, e32.im), m64 = mk_mul(e64.re, e64.im);
      const HMul m128 = mk_mul(e128.re, e128.im);
      uint32_t X[16];
      X[0] = 0x00003c00u; X[1] = pack_f16(e8.re, e8.im); X[2] = m16.b; X[4] = m32.b; X[8] = m64.b;
      X[3] = hcmul(X[1], m16); X[5] = hcmul(X[1], m32); X[6] = hcmul(X[2], m32); X[7] = hcmul(X[3], m32);
#pragma unroll
      for (int r = 1; r < 8; ++r) X[8 + r] = hcmul(X[r], m64);
#pragma unroll
      for (int h = 0; h < 2; ++h) {
#pragma unroll
        for (int r = 0; r < 16; ++r) put(r, h == 0 ? X[r] : r == 0 ? m128.b : hcmul(X[r], m128));
        __syncwarp();
#pragma unroll
        for (int k = 0; k < 4; ++k) ldsm_x4(XA[h][k], lda + (((2 * k + (lane >> 4)) ^ (lane & 7)) << 4));
        __syncwarp();
      }
    }
    float D[2][3][4];
#pragma unroll
    for (int t = 0; t < 6; ++t) D[t / 3][t % 3][0] = D[t / 3][t % 3][1] = D[t / 3][t % 3][2] = D[t / 3][t % 3][3] = 0.f;
    auto contract = [&](int t0, int nt) {
      __syncwarp();
#pragma unroll
      for (int k = 0; k < 4; ++k) {
        uint32_t b[4];
        ldsm_x4(b, ldb + (((2 * k + ((lane >> 3) & 1)) ^ (lane & 7)) << 4));
#pragma unroll
        for (int h = 0; h < 2; ++h) {
          mma_f16(D[h][t0], XA[h][k], b[0], b[1]);
          if (nt == 2) mma_f16(D[h][t0 + 1], XA[h][k], b[2], b[3]);
        }
      }
      __syncwarp();
    };
    const HMul c1 = mk_mul(e1.re, -e1.im), c2 = mk_mul(e2.re, -e2.im), c4 = mk_mul(e4.re, -e4.im);
    const HMul c256 = mk_mul(e256.re, -e256.im), c512 = mk_mul(e512.re, -e512.im), c768 = mk_mul(e768.re, -e768.im);
    const HMul c1024 = mk_mul(e1024.re, -e1024.im);
    uint32_t W[8];
    W[0] = pack_f16(wr * sc, -wi * sc);
    W[1] = hcmul(W[0], c1); W[2] = hcmul(W[0], c2); W[3] = hcmul(W[1], c2);
    W[4] = hcmul(W[0], c4); W[5] = hcmul(W[1], c4); W[6] = hcmul(W[2], c4); W[7] = hcmul(W[3], c4);
#pragma unroll
    for (int i = 0; i < 8; ++i) put(i, W[i]);
#pragma unroll
    for (int i = 0; i < 4; ++i) put(8 + i, hcmul(W[2 * i], c256));
    put(12, hcmul(W[0], c512)); put(13, hcmul(W[4], c512)); put(14, hcmul(W[0], c768)); put(15, hcmul(W[4], c768));
    contract(0, 2);
    const uint32_t v0 = hcmul(W[0], c1024);
    put(0, v0); put(1, hcmul(v0, c256)); put(2, hcmul(v0, c512)); put(3, hcmul(v0, c768)); put(4, hcmul(v0, c1024));
    contract(2, 1);
    const uint32_t a = tb + (g * 24 + 2 * q) * 4;
#pragma unroll
    for (int t = 0; t < 6; ++t) {
      const float(&d)[4] = D[t / 3][t % 3];
      sts_f32x2(a + (t / 3) * 1536 + (t % 3) * 32, d[0] * inv, d[1] * inv);
      sts_f32x2(a + (t / 3) * 1536 + (t % 3) * 32 + 768, d[2] * inv, d[3] * inv);
    }
    if (mz > 0.f) {
      __syncwarp();
#pragma unroll 1
      for (int i = lane; i < 768; i += 32) {
        const int r = i / 24, y = i - 24 * r;
        sts_f32(tb + i * 4, lds_f32(tb + i * 4) * ex2(mz * 1.4426950408889634f * (koff(y) + 8 * r)));
      }
    }
  }
  if (tid == 0) TS(2);
  if (warp < 12) cluster_wait();
  __syncthreads();

  if (warp < 4) {
    asm volatile("setmaxnreg.inc.sync.aligned.u32 152;");
    const unsigned epoch = __ldcg(&g_epoch);
    const int d = cta * 4 + warp;
    const uint32_t vv = sb + SM_VV + warp * VV_BYTES;
    const uint32_t ub = sb + SM_U + warp * U_BYTES;
    const uint32_t pb = sb + SM_P + warp * P_BYTES;
    const float dskip = bf2f(p.Dskip[d]);
#pragma unroll 1
    for (int pass = 0; pass < 2; ++pass) {
      if (pass == 1) {
        const uint32_t kf = vv;
#pragma unroll 2
        for (int i = 0; i < 6; ++i) {
          const uint32_t a = kf + (i * 32 + lane) * 16;
          const uint4 x0 = lds128(a), x1 = lds128(a + KG_BYTES), x2 = lds128(a + 2 * KG_BYTES), x3 = lds128(a + 3 * KG_BYTES);
          auto s4 = [](uint32_t a0, uint32_t a1, uint32_t a2, uint32_t a3) {
            return __float_as_uint((__uint_as_float(a0) + __uint_as_float(a1)) + (__uint_as_float(a2) + __uint_as_float(a3)));
          };
          sts128(a, s4(x0.x, x1.x, x2.x, x3.x), s4(x0.y, x1.y, x2.y, x3.y), s4(x0.z, x1.z, x2.z, x3.z), s4(x0.w, x1.w, x2.w, x3.w));
        }
        __syncwarp();
        const float k1024 = lds_f32(kf + kidx_c(1024) * 4);
        if (lane == 0) {
          sts_f32(kf + SL_ZERO * 4, 0.f);
          sts_f32(kf + SL_510 * 4, lds_f32(kf + kidx_c(510) * 4) - lds_f32(kf + kidx_c(512) * 4));
          sts_f32(kf + SL_0 * 4, lds_f32(kf) + dskip);
        }
        __syncwarp();
        mbar_wait(BAR(B_PFREE), 0);
        {
          float prev = 0.f;
#pragma unroll 1
          for (int i0 = 0; i0 < 16; i0 += 4) {
            uint32_t e[4];
            float a[4], b[4];
#pragma unroll
            for (int i = 0; i < 4; ++i) e[i] = lds32(sb + SM_PTAB + ((i0 + i) * 32 + lane) * 4);
#pragma unroll
            for (int i = 0; i < 4; ++i) { a[i] = lds_f32(kf + (e[i] & 0xffff)); b[i] = lds_f32(kf + (e[i] >> 16)); }
#pragma unroll
            for (int i = 0; i < 4; ++i) {
              const uint32_t w = pb + (30 * lane + 2 * (i0 + i)) * 4;
              if (i0 + i > 0) sts32(w - 4, pack_bf16(a[i], prev));
              if (i0 + i < 15) sts32(w, pack_bf16(b[i], a[i]));
              prev = b[i];
            }
          }
        }
        if (lane < 16) sts128(ub + lane * 16, 0, 0, 0, 0);
        __syncwarp();
        if (elect_one()) {
          TS(4);
          wait_counter(&g_cnt[(C_U + (cta >> 4)) * 32], (epoch + 1) * 16);
          mbar_expect_tx(BAR(B_UCH + warp), 4096);
          bulk_load(ub + 256, p.uT + (size_t)d * 2048, 4096, BAR(B_UCH + warp));
        }
        __syncwarp();
        const int gq = g - 2 * q;
        uint32_t h127, h128;
        {
          const uint32_t kf2 = pack_bf16(k1024, k1024) ^ 0x80008000u;
          h127 = (gq == 4 ? 0x0000ffffu : gq == 5 ? 0xffffffffu : gq == 6 ? 0xffff0000u : 0u) & kf2;
          h128 = (gq == -4 ? 0x0000ffffu : gq == -3 ? 0xffffffffu : gq == -2 ? 0xffff0000u : 0u) & kf2;
        }
        bar_sync(4, 384);
        mbar_wait(BAR(B_UCH + warp), 0);
        if (lane == 0) TS(7);
        float acc[16][4];
#pragma unroll
        for (int i = 0; i < 16; ++i) { acc[i][0] = acc[i][1] = acc[i][2] = acc[i][3] = 0.f; }
        {
          const uint32_t pd_lane = pb + (PD_OFF + 16 + gq) * 4;
          const int prow0 = 8 + (lane & 7) + ((lane >> 4) << 3), hs = (lane >> 3) & 1;
          uint32_t B[2][4][4];
          uint32_t A[4][4];
          const uint32_t la0 = ub + prow0 * 32 + ((hs ^ ((prow0 >> 2) & 1)) << 4);
#pragma unroll
          for (int m2 = 0; m2 < 4; ++m2) ldsm_x4(B[0][m2], la0 + m2 * 512);
#pragma unroll
          for (int i = 0; i < 4; ++i) {
            const uint32_t a = pd_lane + i * 512;
            A[i][0] = lds32(a); A[i][1] = lds32(a + 32); A[i][2] = lds32(a - 32); A[i][3] = A[i][0];
          }
          uint32_t la = la0;
#pragma unroll 1
          for (int rho = 0; rho < 8; ++rho) {
#pragma unroll
            for (int m2 = 0; m2 < 4; ++m2) ldsm_x4(B[1][m2], la + (4 + m2) * 512);
#pragma unroll
            for (int i = 0; i < 4; ++i)
#pragma unroll
              for (int m = 0; m < 8; ++m) mma_bf16v(acc[m + i], A[i], B[0][m >> 1][2 * (m & 1)], B[0][m >> 1][2 * (m & 1) + 1]);
            const int prow = prow0 - min(rho + 1, 7);
            la = ub + prow * 32 + ((hs ^ ((prow >> 2) & 1)) << 4);
#pragma unroll
            for (int m2 = 0; m2 < 4; ++m2) ldsm_x4(B[0][m2], la + m2 * 512);
            const uint32_t pa = pd_lane + (rho + 1) * 64;
#pragma unroll
            for (int i = 0; i < 4; ++i) {
#pragma unroll
              for (int m = 0; m < 8 - i; ++m)
                mma_bf16v(acc[8 + m + i], A[i], B[1][m >> 1][2 * (m & 1)], B[1][m >> 1][2 * (m & 1) + 1]);
              A[i][0] = lds32(pa + i * 512); A[i][1] = lds32(pa + i * 512 + 32); A[i][2] = lds32(pa + i * 512 - 32);
              A[i][3] = A[i][0];
            }
          }
          {
            uint32_t b8[4];
            ldsm_x4(b8, la + 4 * 512);
            const uint32_t h63 = lds32(pd_lane + 63 * 32), h64 = lds32(pd_lane + 64 * 32);
            const uint32_t a63[4] = {0u, h127, 0u, 0u}, a32[4] = {h64, 0u, h63, h64}, a64[4] = {h128, 0u, h127, h128};
#pragma unroll
            for (int m2 = 0; m2 < 4; ++m2) ldsm_x4(B[1][m2], la0 + m2 * 512);
#pragma unroll
            for (int m = 0; m < 8; ++m) mma_bf16v(acc[m + 7], a63, B[0][m >> 1][2 * (m & 1)], B[0][m >> 1][2 * (m & 1) + 1]);
#pragma unroll
            for (int m2 = 0; m2 < 2; ++m2) ldsm_x4(B[0][m2], la0 + (4 + m2) * 512);
#pragma unroll
            for (int m = 0; m < 8; ++m) mma_bf16v(acc[m + 4], a32, B[1][m >> 1][2 * (m & 1)], B[1][m >> 1][2 * (m & 1) + 1]);
            mma_bf16v(acc[15], a63, b8[0], b8[1]);
#pragma unroll
            for (int m = 0; m < 8; ++m) mma_bf16v(acc[m + 8], a64, B[1][m >> 1][2 * (m & 1)], B[1][m >> 1][2 * (m & 1) + 1]);
#pragma unroll
            for (int m = 0; m < 4; ++m) mma_bf16v(acc[m + 12], a32, B[0][m >> 1][2 * (m & 1)], B[0][m >> 1][2 * (m & 1) + 1]);
          }
          bar_sync(5, 384);
#pragma unroll 1
          for (int v = 0; v < 4; ++v)
            conv_tail<4, 3, 11>(acc, pb + (P2_OFF + 56 * v + gq - 16) * 4, vv + ((v & 1) ? VV_U3 : VV_U5), v >> 1, v == 0, lane);
#pragma unroll 1
          for (int pi = 0; pi < 2; ++pi)
            conv_tail<8, 5, 7>(acc, pb + (P3_OFF + 88 * pi + gq - 48) * 4, vv + (pi ? VV_U7 : VV_U9), pi, pi == 0, lane);
        }
        if (lane == 0) TS(8);
        {
          const int mt = lane >> 3;
          const uint32_t a = vv + (128 * (mt >> 1) + 16 * (lane & 7) + 8 * (mt & 1)) * 2;
#pragma unroll
          for (int ab = 0; ab < 16; ab += 2)
            stsm_x4_t(a + ab * 256, pack_bf16(acc[ab][0], acc[ab][1]), pack_bf16(acc[ab][2], acc[ab][3]),
                      pack_bf16(acc[ab + 1][0], acc[ab + 1][1]), pack_bf16(acc[ab + 1][2], acc[ab + 1][3]));
        }
        bar_arrive(3, 384);
        fence_async_smem();
        __syncwarp();
        if (elect_one()) {
          bulk_store(p.yT + (size_t)d * 2048, vv, 4096);
          bulk_commit();
          bulk_wait0();
          red_relaxed_add(&g_cnt[(C_Y + (cta >> 4)) * 32], 1);
          TS(9);
        }
        bar_sync(2, 128);
        if (warp == 0 && elect_one()) {
          wait_counter(&g_cnt[(C_Y + tj) * 32], (epoch + 1) * 64);
          TS(28);
          mbar_expect_tx(BAR(B_TILE), 16384);
          tma_load_2d(sb + SM_U, &maps.yT, ti * 128, tj * 64, BAR(B_TILE));
          tma_load_2d(sb + SM_U + 8192, &maps.yT, ti * 128 + 64, tj * 64, BAR(B_TILE));
        }
        __syncwarp();
      }
      mbar_wait(BAR(B_TILE), pass);
      if (lane == 0) TS(26 + 3 * pass);
      {
        const int m = lane >> 3, r = lane & 7;
#pragma unroll 2
        for (int it = 0; it < 8; ++it) {
          const int tb = warp * 4 + (it >> 1), cb = (it & 1) * 4 + m;
          const uint32_t at = (tb * 8 + r) * 128 + ((cb ^ r) << 4);
          const uint32_t ac = (tb >> 3) * 8192 + (cb * 8 + r) * 128 + (((tb & 7) ^ (pass ? 0 : tb >> 3) ^ r) << 4);
          uint32_t v[4];
          ldsm_x4_t(v, sb + SM_U + (pass ? ac : at));
          stsm_x4(sb + SM_P + (pass ? at : ac), v[0], v[1], v[2], v[3]);
        }
      }
      fence_async_smem();
      if (pass == 0) {
        bar_arrive(6, 160);
      } else {
        bar_sync(2, 128);
        if (warp == 0 && elect_one()) {
          tma_store_2d(&maps.out, sb + SM_P, 64 * tj, 128 * ti);
          bulk_commit();
          bulk_wait_read0();
          TS(30);
        }
      }
    }
  } else if (warp < 12) {
    asm volatile("setmaxnreg.inc.sync.aligned.u32 160;");
    const int w8 = warp - 4;
    const int row = w8 * 16 + (lane & 7) + (((lane >> 3) & 1) << 3);
    {
      float acc[96];
#pragma unroll 1
      for (int ks = 0, s = 0, ph = 0; ks < 16; ++ks) {
        mbar_wait(BAR(B_FULL + s), ph);
        if (tid == 128 && !(ks & 1)) TSR(16, ks == 0 ? 16 : 9 + (ks >> 1) + (ks > 12 ? 46 : 0));
        const uint32_t st = sb + s * STG_BYTES;
        const uint32_t da = mkdesc(st + STG_X + (w8 >> 2) * 4096, 16);
        const uint32_t db = mkdesc(st + STG_W, 2048);
        wg_fence();
        wgmma_n192(acc, da, db, ks != 0);
        wgmma_n192(acc, da + 2, db + 384, 1);
        wg_commit();
        const uint32_t eprev = BAR(B_EMPTY + (s == 0 ? NSTG - 1 : s - 1));
        if (++s == NSTG) { s = 0; ph ^= 1; }
        if (ks > 0) {
          wg_wait<1>();
          if (lane < 2) mbar_arrive_cluster(eprev, lane);
        }
      }
      wg_wait<0>();
      bar_arrive(4, 384);
      if (tid == 128) TS(17);
      bar_sync(1, 256);
#pragma unroll
      for (int i = 0; i < 24; i += 2)
        stsm_x4(sb + SM_QS + row * 128 + (i >> 3) * 16384 + ((((i & 7) + (lane >> 4)) ^ (row & 7)) << 4),
                pack_bf16(acc[4 * i], acc[4 * i + 1]), pack_bf16(acc[4 * i + 2], acc[4 * i + 3]),
                pack_bf16(acc[4 * i + 4], acc[4 * i + 5]), pack_bf16(acc[4 * i + 6], acc[4 * i + 7]));
    }
    __syncwarp();
#pragma unroll 1
    for (int part = 1; part >= 0; --part) {
      const uint32_t pa = sb + SM_QS + part * 16384 + w8 * 2048 + lane * 16;
#pragma unroll 1
      for (int it = 0; it < 4; ++it) {
        uint4 t = lds128(pa + it * 512);
        uint32_t* tw = &t.x;
#pragma unroll
        for (int j = 0; j < 4; ++j) {
          const uint32_t x = tw[j];
          const __nv_bfloat162 xb = *reinterpret_cast<const __nv_bfloat162*>(&x);
          const uint32_t e = pack_bf16(ex2(bf_lo(x) * 1.4426950408889634f), ex2(bf_hi(x) * 1.4426950408889634f));
          const uint32_t m = __hgt2_mask(xb, __floats2bfloat162_rn(0.f, 0.f));
          const uint32_t sel = (badd(x, 0x3f803f80u) & m) | (e & ~m);
          tw[j] = pack_bf16(bf_lo(sel) + 1e-6f, bf_hi(sel) + 1e-6f);
        }
        sts128(pa + it * 512, t.x, t.y, t.z, t.w);
      }
      if (part == 1) {
        if (tid == 128) TS(53);
        bar_sync(1, 256);
        const int hh = w8 >> 1, dtile = w8 & 1;
        float kv[4] = {0.f, 0.f, 0.f, 0.f}, zz[4] = {0.f, 0.f, 0.f, 0.f};
        const int m = lane >> 3;
        const uint32_t aa = sb + SM_VS + ((lane & 7) + ((m >> 1) << 3)) * 128 + (((2 * hh + (m & 1)) ^ (lane & 7)) << 4);
        const uint32_t ab = sb + SM_PK + (lane & 15) * 128 + (((2 * hh + dtile) ^ (lane & 7)) << 4);
#pragma unroll 2
        for (int ks = 0; ks < 8; ++ks) {
          uint32_t a[4], b0, b1;
          ldsm_x4_t(a, aa + ks * 2048);
          ldsm_x2_t(b0, b1, ab + ks * 2048);
          mma_bf16(kv, a[0], a[1], a[2], a[3], b0, b1);
          mma_bf16(zz, 0x3f803f80u, 0x3f803f80u, 0x3f803f80u, 0x3f803f80u, b0, b1);
        }
        const uint32_t kp = sb + SM_KV + hh * 1088;
        sts128(kp + dtile * 512 + lane * 16, __float_as_uint(kv[0]), __float_as_uint(kv[1]), __float_as_uint(kv[2]),
               __float_as_uint(kv[3]));
        if (g == 0) sts_f32x2(kp + 1024 + dtile * 32 + q * 8, zz[0], zz[1]);
        fence_async_smem();
        __syncwarp();
        if (lane == 0) mbar_arrive(BAR(B_KVP));
        if (tid == 128) TS(55);
      }
    }
    if (tid == 128) TS(56);
    {
      const int ch = w8 >> 1;
      mbar_wait(BAR(B_UCH + ch), 0);
#pragma unroll 1
      for (int it = w8 & 1; it < 8; it += 2) {
          const int k = -18 + it * 32 + lane;
          const int kr = min(max(k, -2), 208);
          uint32_t E[12];
#pragma unroll
          for (int c = 0; c < 3; ++c) {
            const int kk = kr - 1 + c, r = (kk >> 1) + 8;
            const uint4 t = lds128(sb + SM_U + ch * U_BYTES + r * 32 + (((kk & 1) ^ ((r >> 2) & 1)) << 4));
            E[4 * c] = t.x; E[4 * c + 1] = t.y; E[4 * c + 2] = t.z; E[4 * c + 3] = t.w;
          }
          uint32_t O[8];
#pragma unroll
          for (int j = 0; j < 8; ++j) O[j] = __byte_perm(E[j + 1], E[j + 2], 0x5432);
          uint32_t s3[6], s5[4], s7[4], s9[4];
#pragma unroll
          for (int j = 0; j < 6; ++j) s3[j] = badd(badd(O[j], O[j + 1]), E[j + 2]);
#pragma unroll
          for (int j = 0; j < 4; ++j) {
            s5[j] = badd(s3[j + 2], badd(E[j + 3], E[j + 5]));
            s7[j] = badd(s5[j], badd(O[j + 1], O[j + 4]));
            s9[j] = badd(s7[j], badd(E[j + 2], E[j + 6]));
          }
          const int r = (k >> 1) + PADV;
          const uint32_t a = sb + SM_VV + ch * VV_BYTES + r * 32 + (((k & 1) ^ ((r >> 2) & 1)) << 4);
          if (k < 208) { sts128(a + VV_U3, s3[0], s3[1], s3[2], s3[3]); sts128(a + VV_U5, s5[0], s5[1], s5[2], s5[3]); }
          if (k < 144) { sts128(a + VV_U7, s7[0], s7[1], s7[2], s7[3]); sts128(a + VV_U9, s9[0], s9[1], s9[2], s9[3]); }
      }
      bar_arrive(5, 384);
    }
    if (tid == 128) TS(6);
    mbar_wait(BAR(B_KVF), 0);
    if (tid == 128) TS(19);
#pragma unroll 1
    for (int h = 0; h < 4; ++h) {
      uint32_t a[4];
      const uint32_t qa = sb + SM_QS + row * 128 + (((2 * h + (lane >> 4)) ^ (row & 7)) << 4);
      ldsm_x4(a, qa);
      const uint32_t kp = sb + SM_KV + h * 1088;
      const uint4 k0 = lds128(kp + lane * 16), k1 = lds128(kp + 512 + lane * 16);
      const uint32_t za = kp + 1024 + q * 8;
      auto pk2 = [](uint32_t x, uint32_t y) { return pack_bf16(__uint_as_float(x), __uint_as_float(y)); };
      float n0[4] = {0.f, 0.f, 0.f, 0.f}, n1[4] = {0.f, 0.f, 0.f, 0.f}, dn[4] = {0.f, 0.f, 0.f, 0.f};
      mma_bf16(n0, a[0], a[1], a[2], a[3], pk2(k0.x, k0.y), pk2(k1.x, k1.y));
      mma_bf16(n1, a[0], a[1], a[2], a[3], pk2(k0.z, k0.w), pk2(k1.z, k1.w));
      mma_bf16(dn, a[0], a[1], a[2], a[3], pack_bf16(lds_f32(za), lds_f32(za + 4)), pack_bf16(lds_f32(za + 32), lds_f32(za + 36)));
      const uint32_t dd = pack_bf16(dn[0], dn[2]);
      const uint32_t d2 = pack_bf16(bf_lo(dd) + 1e-6f, bf_hi(dd) + 1e-6f);
      const float r0 = rcp(bf_lo(d2)), r1 = rcp(bf_hi(d2));
      const uint32_t x0 = pack_bf16(n0[0], n0[1]), x1 = pack_bf16(n0[2], n0[3]);
      const uint32_t x2 = pack_bf16(n1[0], n1[1]), x3 = pack_bf16(n1[2], n1[3]);
      stsm_x4(qa, pack_bf16(bf_lo(x0) * r0, bf_hi(x0) * r0), pack_bf16(bf_lo(x1) * r1, bf_hi(x1) * r1),
              pack_bf16(bf_lo(x2) * r0, bf_hi(x2) * r0), pack_bf16(bf_lo(x3) * r1, bf_hi(x3) * r1));
    }
    fence_async_smem();
    __syncwarp();
    if (lane == 0) mbar_arrive(BAR(B_OST));
    if (tid == 128) TS(57);
    bar_sync(3, 384);
    {
      float o[32];
#pragma unroll 1
      for (int c = 0, s = 0, ph = 0; c < 8; ++c) {
        mbar_wait(BAR(B_RF + s), ph);
        if (c == 0 && tid == 128) TS(22);
        const uint32_t da = mkdesc(sb + SM_QS + s * 16384 + (w8 >> 2) * 8192, 16);
        const uint32_t db = mkdesc(sb + SM_WO + s * 8192, 8192);
        wg_fence();
#pragma unroll
        for (int k = 0; k < 4; ++k) wgmma_n64(o, da + 2 * k, db + 128 * k, (c | k) != 0);
        wg_commit();
        const uint32_t eprev = BAR(B_RE + (s == 0 ? NRING - 1 : s - 1));
        if (++s == NRING) { s = 0; ph ^= 1; }
        if (c > 0) {
          wg_wait<1>();
          if (lane == 0) mbar_arrive(eprev);
        }
      }
      wg_wait<0>();
#pragma unroll
      for (int i = 0; i < 8; i += 2)
        stsm_x4(sb + SM_BOUT + row * 128 + (((i + (lane >> 4)) ^ (row & 7)) << 4), pack_bf16(o[4 * i], o[4 * i + 1]),
                pack_bf16(o[4 * i + 2], o[4 * i + 3]), pack_bf16(o[4 * i + 4], o[4 * i + 5]), pack_bf16(o[4 * i + 6], o[4 * i + 7]));
      fence_async_smem();
      bar_sync(1, 256);
      if (warp == 4 && elect_one()) {
        tma_store_2d(&maps.out, sb + SM_BOUT, 512 + 64 * tj, 128 * ti);
        bulk_commit();
        bulk_wait_read0();
        TS(23);
      }
    }
  } else {
    asm volatile("setmaxnreg.dec.sync.aligned.u32 40;");
    if (warp == 12) {
      if (elect_one()) {
        const unsigned epoch = __ldcg(&g_epoch);
#pragma unroll 1
        for (int ks = NSTG, s = 0, ph = 0; ks < 16; ++ks) {
          mbar_wait(BAR(B_EMPTY + s), ph);
          TSR(38, 31 + ks);
          const uint32_t st = sb + s * STG_BYTES, fb = BAR(B_FULL + s);
          mbar_expect_tx(fb, STG_BYTES);
          tma_load_2d(st + STG_X, &maps.x, ks * 32, ti * 128, fb);
          tma_load_3d_mc(st + STG_W + rank * 6144, &maps.w, tj * 64, ks * 32 + rank * 16, 0, fb, 3);
          if (++s == NSTG) { s = 0; ph ^= 1; }
        }
        prefetch_tmap(&maps.wo); prefetch_tmap(&maps.o); prefetch_tmap(&maps.out);
        mbar_wait(BAR(B_EMPTY + 4), 1);
        mbar_wait(BAR(B_EMPTY + 5), 1);
#pragma unroll 1
        for (int c = 0; c < NRING; ++c) {
          mbar_expect_tx(BAR(B_RF + c), 24576);
          tma_load_2d(sb + SM_WO + c * 8192, &maps.wo, tj * 64, c * 64, BAR(B_RF + c));
        }
        float* kvg = &g_kv[epoch & 1][tj][0];
        mbar_wait(BAR(B_KVP), 0);
        bulk_reduce_add_f32(kvg, sb + SM_KV, 4352);
        bulk_commit();
        bulk_wait0();
        red_relaxed_add(&g_cnt[(C_KV + tj) * 32], 1);
        TS(18);
        wait_counter(&g_cnt[(C_KV + tj) * 32], (epoch + 1) * 16);
        mbar_expect_tx(BAR(B_KVF), 4352);
        bulk_load(sb + SM_KV, kvg, 4352, BAR(B_KVF));
        mbar_wait(BAR(B_OST), 0);
        tma_store_2d(&maps.o, sb + SM_QS, tj * 64, ti * 128);
        bulk_commit();
        bulk_wait0();
        red_relaxed_add(&g_cnt[(C_O + ti) * 32], 1);
        TS(20);
        wait_counter(&g_cnt[(C_O + ti) * 32], (epoch + 1) * 8);
        if (cta == 0) g_epoch = epoch + 1;
        TS(21);
#pragma unroll 1
        for (int c = 0, s = 0; c < 8; ++c) {
          if (c >= NRING) {
            mbar_wait(BAR(B_RE + s), 0);
            mbar_expect_tx(BAR(B_RF + s), 24576);
            tma_load_2d(sb + SM_WO + s * 8192, &maps.wo, tj * 64, c * 64, BAR(B_RF + s));
          }
          tma_load_2d(sb + SM_QS + s * 16384, &maps.o, c * 64, ti * 128, BAR(B_RF + s));
          if (++s == NRING) s = 0;
        }
      }
    } else if (warp == 13) {
      bar_sync(6, 160);
      if (elect_one()) {
        tma_store_2d(&maps.uT, sb + SM_P, ti * 128, tj * 64);
        tma_store_2d(&maps.uT, sb + SM_P + 8192, ti * 128 + 64, tj * 64);
        bulk_commit();
        bulk_wait_read0();
        mbar_arrive(BAR(B_PFREE));
        bulk_wait0();
        red_relaxed_add(&g_cnt[(C_U + tj) * 32], 1);
        TS(27);
      }
      __syncwarp();
      if (ti == 0) {
        float4* z = (float4*)&g_kv[(__ldcg(&g_epoch) & 1) ^ 1][tj][0];
#pragma unroll 1
        for (int i = lane; i < 272; i += 32) z[i] = make_float4(0.f, 0.f, 0.f, 0.f);
      }
    }
  }
  __syncwarp();
  cluster_arrive();
  cluster_wait();
  if (tid == 0) TS(31);
#undef BAR
}

typedef CUresult (*EncodeFn)(CUtensorMap*, CUtensorMapDataType, cuuint32_t, void*, const cuuint64_t*, const cuuint64_t*,
                             const cuuint32_t*, const cuuint32_t*, CUtensorMapInterleave, CUtensorMapSwizzle,
                             CUtensorMapL2promotion, CUtensorMapFloatOOBfill);

static void make_map(EncodeFn enc, CUtensorMap* m, const void* base, uint64_t inner, uint64_t outer, uint32_t box_in,
                     uint32_t box_out, CUtensorMapSwizzle swz = CU_TENSOR_MAP_SWIZZLE_128B) {
  cuuint64_t gd[2] = {inner, outer};
  cuuint64_t gs[1] = {inner * 2};
  cuuint32_t bd[2] = {box_in, box_out};
  cuuint32_t es[2] = {1, 1};
  enc(m, CU_TENSOR_MAP_DATA_TYPE_BFLOAT16, 2, const_cast<void*>(base), gd, gs, bd, es, CU_TENSOR_MAP_INTERLEAVE_NONE,
      swz, CU_TENSOR_MAP_L2_PROMOTION_L2_128B, CU_TENSOR_MAP_FLOAT_OOB_FILL_NONE);
}

}

extern "C" void kernel_launch(void* const* d_in, const int* in_sizes, int n_in, void* d_out, int out_size) {
  using namespace s4la;
  (void)in_sizes; (void)n_in; (void)out_size;
  static EncodeFn enc = nullptr;
  static void *uT = nullptr, *yT = nullptr, *oS = nullptr;
  if (!enc) {
    void* fn = nullptr;
    cudaDriverEntryPointQueryResult qr;
    cudaGetDriverEntryPoint("cuTensorMapEncodeTiled", &fn, cudaEnableDefault, &qr);
    enc = (EncodeFn)fn;
    cudaGetSymbolAddress(&uT, g_uT);
    cudaGetSymbolAddress(&yT, g_yT);
    cudaGetSymbolAddress(&oS, g_o);
    cudaFuncSetAttribute(fused_kernel, cudaFuncAttributeMaxDynamicSharedMemorySize, SM_TOTAL);
  }
  const __nv_bfloat16* const* in = (const __nv_bfloat16* const*)d_in;
  Maps maps;
  make_map(enc, &maps.x, in[9], 512, 2048, 32, 128, CU_TENSOR_MAP_SWIZZLE_64B);
  {
    cuuint64_t gd[3] = {512, 512, 3};
    cuuint64_t gs[2] = {3072, 1024};
    cuuint32_t bd[3] = {64, 16, 3};
    cuuint32_t es[3] = {1, 1, 1};
    enc(&maps.w, CU_TENSOR_MAP_DATA_TYPE_BFLOAT16, 3, const_cast<__nv_bfloat16*>(in[10]), gd, gs, bd, es,
        CU_TENSOR_MAP_INTERLEAVE_NONE, CU_TENSOR_MAP_SWIZZLE_128B, CU_TENSOR_MAP_L2_PROMOTION_L2_128B,
        CU_TENSOR_MAP_FLOAT_OOB_FILL_NONE);
  }
  make_map(enc, &maps.wo, in[11], 512, 512, 64, 64);
  make_map(enc, &maps.u, in[0], 512, 2048, 64, 128);
  make_map(enc, &maps.uT, uT, 2048, 512, 64, 64);
  make_map(enc, &maps.yT, yT, 2048, 512, 64, 64);
  make_map(enc, &maps.o, oS, 512, 2048, 64, 128);
  make_map(enc, &maps.out, d_out, 1024, 2048, 64, 128);
  Ptrs p;
  p.A_re = in[1]; p.A_im = in[2]; p.B_re = in[3]; p.B_im = in[4]; p.C_re = in[5]; p.C_im = in[6];
  p.log_dt = in[7]; p.Dskip = in[8]; p.x = in[9]; p.wqkv = in[10]; p.wo = in[11];
  p.uT = (__nv_bfloat16*)uT; p.yT = (__nv_bfloat16*)yT;
  fused_kernel<<<NCTA, NTHREADS, SM_TOTAL, cudaStreamPerThread>>>(maps, p);
}
```

```cpp
#include <cuda_runtime.h>
#include <cuda_bf16.h>
#include <cuda_fp16.h>
#include <cuda.h>
#include <stdint.h>

#define DEVI __device__ __forceinline__

namespace s4la {

constexpr int NTHREADS = 512;
constexpr int NCTA = 128;

constexpr int NSTG = 7;
constexpr uint32_t STG_BYTES = 20480, STG_X = 0, STG_W = 8192;
constexpr uint32_t SM_QS = 0;
constexpr uint32_t SM_PK = SM_QS + 16384, SM_VS = SM_QS + 32768;
constexpr uint32_t SM_WO = 65536;
constexpr uint32_t SM_KV = 131072;
constexpr uint32_t SM_BOUT = 16384;
constexpr uint32_t SM_U = 143360, U_BYTES = 4352;
constexpr uint32_t SM_P = 160768, P_BYTES = 4096;
constexpr uint32_t SM_VV = 177152, VV_BYTES = 12800;
constexpr uint32_t VV_U5 = 0, VV_U3 = 3712, VV_U9 = 7424, VV_U7 = 10112;
constexpr uint32_t KG_BYTES = 3200;
constexpr uint32_t SM_BAR = SM_VV + 4 * VV_BYTES;
constexpr uint32_t SM_PTAB = SM_BAR + 320;
constexpr uint32_t SM_TOTAL = SM_PTAB + 2048;
static_assert(SM_TOTAL <= 232448, "shared memory");
constexpr int PADV = 12;

enum { B_FULL = 0, B_EMPTY = 7, B_TILE = 14, B_UCH = 15, B_KVP = 19, B_KVF = 20, B_OST = 21, B_RF = 22, B_WO = 30, B_RE = 31, B_PFREE = 32, B_CONVD = 33, B_COUNT = 34 };
__host__ __device__ constexpr int bar_count(int i) {
  return (i >= B_EMPTY && i < B_TILE) ? 16 : (i == B_KVP || i == B_OST || i == B_RE) ? 8 : i == B_CONVD ? 4 : 1;
}

constexpr int PD_OFF = 0, P2_OFF = 544, P3_OFF = 768;

constexpr int SL_K2048 = 20, SL_ZERO = 21, SL_510 = 22, SL_0 = 23;
__host__ __device__ constexpr int koff(int y) {
  return y < 8 ? y : y < 12 ? 256 + 2 * (y - 8) : y < 16 ? 512 + 256 * ((y - 12) >> 1) + 4 * (y & 1) : 1024 + 256 * (y - 16);
}
__host__ __device__ constexpr int kidx_c(int l) {
  const int y = l < 256 ? (l & 7) : l < 512 ? 8 + ((l & 7) >> 1) : l < 1024 ? 12 + (((l - 512) >> 8) << 1) + ((l >> 2) & 1)
                                                                            : 16 + ((l - 1024) >> 8);
  return ((l >> 3) & 31) * 24 + y;
}
constexpr int slot_direct(int l) {
  if (l < 0 || l > 510) return SL_ZERO;
  if (l == 510) return SL_510;
  if (l == 0) return SL_0;
  return kidx_c(l < 256 ? l : ((l + ((l >> 1) & 1)) & ~1));
}
constexpr int slot_seg2(int v, int k) { return (k >= 32 && k < 64) ? kidx_c(16 * k + 4 * v) : SL_ZERO; }
constexpr int slot_seg3(int pi, int k) {
  return (k >= 64 && k < 128) ? kidx_c(16 * k + 8 * pi) : ((k == 128 && pi == 0) ? SL_K2048 : SL_ZERO);
}
constexpr int slot_word(int w) {
  return w < 0 ? SL_ZERO : w < 544 ? slot_direct(w - 16) : w < 768 ? slot_seg2((w - 544) / 56, 16 + (w - 544) % 56)
       : w < 944 ? slot_seg3((w - 768) / 88, 48 + (w - 768) % 88) : SL_ZERO;
}
struct PTab { uint32_t v[512]; };
constexpr PTab make_ptab() {
  PTab t{};
  for (int lane = 0; lane < 32; ++lane)
    for (int i = 0; i < 16; ++i)
      t.v[i * 32 + lane] = (slot_word(31 * lane - 1 + 2 * i) * 4) | ((slot_word(31 * lane + 2 * i) * 4) << 16);
  return t;
}
__device__ const PTab g_ptab = make_ptab();

__device__ __nv_bfloat16 g_uT[512 * 2048];
__device__ __nv_bfloat16 g_yT[512 * 2048];
__device__ __nv_bfloat16 g_o[2048 * 512];
__device__ float g_kv[2][8][4 * 272];
__device__ unsigned g_cnt[64 * 32];
__device__ unsigned g_epoch;
#define TS(slot) do { } while (0)
#define TSR(on, slot) do { } while (0)
enum { C_U = 0, C_KV = 8, C_O = 16, C_Y = 32 };

struct Maps {
  CUtensorMap x, w, wo, u, uT, yT, o, out;
};
struct Ptrs {
  const __nv_bfloat16 *A_re, *A_im, *B_re, *B_im, *C_re, *C_im, *log_dt, *Dskip;
  const __nv_bfloat16 *x, *wqkv, *wo;
  __nv_bfloat16 *uT, *yT;
};

DEVI uint32_t s2u(const void* p) { return (uint32_t)__cvta_generic_to_shared(p); }
DEVI void mbar_init(uint32_t b, uint32_t c) { asm volatile("mbarrier.init.shared::cta.b64 [%0], %1;" ::"r"(b), "r"(c) : "memory"); }
DEVI void mbar_expect_tx(uint32_t b, uint32_t bytes) {
  asm volatile("mbarrier.arrive.expect_tx.shared::cta.b64 _, [%0], %1;" ::"r"(b), "r"(bytes) : "memory");
}
DEVI void mbar_arrive(uint32_t b) { asm volatile("mbarrier.arrive.shared::cta.b64 _, [%0];" ::"r"(b) : "memory"); }
DEVI void mbar_arrive_cluster(uint32_t b, uint32_t cta) {
  asm volatile("{\n.reg .b32 r;\nmapa.shared::cluster.u32 r, %0, %1;\nmbarrier.arrive.shared::cluster.b64 _, [r];\n}"
               ::"r"(b), "r"(cta) : "memory");
}
DEVI void mbar_wait(uint32_t b, uint32_t parity) {
  asm volatile("{\n.reg .pred p;\nLAB_WAIT:\nmbarrier.try_wait.parity.shared::cta.b64 p, [%0], %1;\n@!p bra LAB_WAIT;\n}"
               ::"r"(b), "r"(parity) : "memory");
}
DEVI void bar_sync(int id, int n) { asm volatile("bar.sync %0, %1;" ::"r"(id), "r"(n) : "memory"); }
DEVI void bar_arrive(int id, int n) { asm volatile("bar.arrive %0, %1;" ::"r"(id), "r"(n) : "memory"); }
DEVI void fence_async_smem() { asm volatile("fence.proxy.async.shared::cta;" ::: "memory"); }
DEVI void fence_async_all() { asm volatile("fence.proxy.async;" ::: "memory"); }
DEVI void cluster_arrive() { asm volatile("barrier.cluster.arrive.relaxed.aligned;" ::: "memory"); }
DEVI void cluster_wait() { asm volatile("barrier.cluster.wait.aligned;" ::: "memory"); }

DEVI void tma_load_2d(uint32_t dst, const CUtensorMap* m, int c0, int c1, uint32_t bar) {
  asm volatile("cp.async.bulk.tensor.2d.shared::cluster.global.mbarrier::complete_tx::bytes [%0], [%1, {%3, %4}], [%2];"
               ::"r"(dst), "l"(m), "r"(bar), "r"(c0), "r"(c1) : "memory");
}
DEVI void tma_load_2d_mc(uint32_t dst, const CUtensorMap* m, int c0, int c1, uint32_t bar, uint16_t mask) {
  asm volatile("cp.async.bulk.tensor.2d.shared::cluster.global.mbarrier::complete_tx::bytes.multicast::cluster [%0], [%1, {%3, %4}], [%2], %5;"
               ::"r"(dst), "l"(m), "r"(bar), "r"(c0), "r"(c1), "h"(mask) : "memory");
}
DEVI void tma_load_3d_mc(uint32_t dst, const CUtensorMap* m, int c0, int c1, int c2, uint32_t bar, uint16_t mask) {
  asm volatile("cp.async.bulk.tensor.3d.shared::cluster.global.mbarrier::complete_tx::bytes.multicast::cluster [%0], [%1, {%3, %4, %5}], [%2], %6;"
               ::"r"(dst), "l"(m), "r"(bar), "r"(c0), "r"(c1), "r"(c2), "h"(mask) : "memory");
}
DEVI void tma_store_2d(const CUtensorMap* m, uint32_t src, int c0, int c1) {
  asm volatile("cp.async.bulk.tensor.2d.global.shared::cta.bulk_group [%0, {%2, %3}], [%1];"
               ::"l"(m), "r"(src), "r"(c0), "r"(c1) : "memory");
}
DEVI void bulk_load(uint32_t dst, const void* src, uint32_t bytes, uint32_t bar) {
  asm volatile("cp.async.bulk.shared::cluster.global.mbarrier::complete_tx::bytes [%0], [%1], %2, [%3];"
               ::"r"(dst), "l"(src), "r"(bytes), "r"(bar) : "memory");
}
DEVI void bulk_store(void* dst, uint32_t src, uint32_t bytes) {
  asm volatile("cp.async.bulk.global.shared::cta.bulk_group [%0], [%1], %2;" ::"l"(dst), "r"(src), "r"(bytes) : "memory");
}
DEVI void bulk_reduce_add_f32(void* dst, uint32_t src, uint32_t bytes) {
  asm volatile("cp.reduce.async.bulk.global.shared::cta.bulk_group.add.f32 [%0], [%1], %2;" ::"l"(dst), "r"(src), "r"(bytes) : "memory");
}
DEVI void bulk_commit() { asm volatile("cp.async.bulk.commit_group;" ::: "memory"); }
DEVI void bulk_wait0() { asm volatile("cp.async.bulk.wait_group 0;" ::: "memory"); }
DEVI void bulk_wait_read0() { asm volatile("cp.async.bulk.wait_group.read 0;" ::: "memory"); }
DEVI void l2_prefetch(const void* p, uint32_t bytes) {
  asm volatile("cp.async.bulk.prefetch.L2.global [%0], %1;" ::"l"(p), "r"(bytes) : "memory");
}
DEVI void prefetch_tmap(const CUtensorMap* m) { asm volatile("prefetch.tensormap [%0];" ::"l"(m) : "memory"); }

DEVI void red_release_add(unsigned* p, unsigned v) {
  asm volatile("red.release.gpu.global.add.u32 [%0], %1;" ::"l"(p), "r"(v) : "memory");
}
DEVI void red_relaxed_add(unsigned* p, unsigned v) {
  asm volatile("red.relaxed.gpu.global.add.u32 [%0], %1;" ::"l"(p), "r"(v) : "memory");
}
DEVI unsigned ld_relaxed(const unsigned* p) {
  unsigned v;
  asm volatile("ld.relaxed.gpu.global.u32 %0, [%1];" : "=r"(v) : "l"(p) : "memory");
  return v;
}
DEVI void wait_counter(const unsigned* p, unsigned target) {
#pragma unroll 1
  for (int it = 0; (int)(ld_relaxed(p) - target) < 0; ++it)
    if (it > (1 << 22)) __trap();
}

DEVI void ldsm_x4(uint32_t (&r)[4], uint32_t a) {
  asm volatile("ldmatrix.sync.aligned.m8n8.x4.shared.b16 {%0,%1,%2,%3}, [%4];"
               : "=r"(r[0]), "=r"(r[1]), "=r"(r[2]), "=r"(r[3]) : "r"(a) : "memory");
}
DEVI void ldsm_x4_t(uint32_t (&r)[4], uint32_t a) {
  asm volatile("ldmatrix.sync.aligned.m8n8.x4.trans.shared.b16 {%0,%1,%2,%3}, [%4];"
               : "=r"(r[0]), "=r"(r[1]), "=r"(r[2]), "=r"(r[3]) : "r"(a) : "memory");
}
DEVI void ldsm_x2_t(uint32_t& r0, uint32_t& r1, uint32_t a) {
  asm volatile("ldmatrix.sync.aligned.m8n8.x2.trans.shared.b16 {%0,%1}, [%2];" : "=r"(r0), "=r"(r1) : "r"(a) : "memory");
}
DEVI void stsm_x4(uint32_t a, uint32_t r0, uint32_t r1, uint32_t r2, uint32_t r3) {
  asm volatile("stmatrix.sync.aligned.m8n8.x4.shared.b16 [%0], {%1,%2,%3,%4};"
               ::"r"(a), "r"(r0), "r"(r1), "r"(r2), "r"(r3) : "memory");
}
DEVI void stsm_x4_t(uint32_t a, uint32_t r0, uint32_t r1, uint32_t r2, uint32_t r3) {
  asm volatile("stmatrix.sync.aligned.m8n8.x4.trans.shared.b16 [%0], {%1,%2,%3,%4};"
               ::"r"(a), "r"(r0), "r"(r1), "r"(r2), "r"(r3) : "memory");
}
DEVI uint32_t lds32(uint32_t a) { uint32_t v; asm volatile("ld.shared.b32 %0, [%1];" : "=r"(v) : "r"(a) : "memory"); return v; }
DEVI float lds_f32(uint32_t a) { float v; asm volatile("ld.shared.f32 %0, [%1];" : "=f"(v) : "r"(a) : "memory"); return v; }
DEVI void sts32(uint32_t a, uint32_t v) { asm volatile("st.shared.b32 [%0], %1;" ::"r"(a), "r"(v) : "memory"); }
DEVI void sts_f32(uint32_t a, float v) { asm volatile("st.shared.f32 [%0], %1;" ::"r"(a), "f"(v) : "memory"); }
DEVI void sts_f32x2(uint32_t a, float x, float y) { asm volatile("st.shared.v2.f32 [%0], {%1,%2};" ::"r"(a), "f"(x), "f"(y) : "memory"); }
DEVI uint4 lds128(uint32_t a) {
  uint4 v;
  asm volatile("ld.shared.v4.b32 {%0,%1,%2,%3}, [%4];" : "=r"(v.x), "=r"(v.y), "=r"(v.z), "=r"(v.w) : "r"(a) : "memory");
  return v;
}
DEVI void sts128(uint32_t a, uint32_t x, uint32_t y, uint32_t z, uint32_t w) {
  asm volatile("st.shared.v4.b32 [%0], {%1,%2,%3,%4};" ::"r"(a), "r"(x), "r"(y), "r"(z), "r"(w) : "memory");
}

DEVI void mma_bf16(float (&d)[4], uint32_t a0, uint32_t a1, uint32_t a2, uint32_t a3, uint32_t b0, uint32_t b1) {
  asm("mma.sync.aligned.m16n8k16.row.col.f32.bf16.bf16.f32 {%0,%1,%2,%3}, {%4,%5,%6,%7}, {%8,%9}, {%0,%1,%2,%3};"
      : "+f"(d[0]), "+f"(d[1]), "+f"(d[2]), "+f"(d[3])
      : "r"(a0), "r"(a1), "r"(a2), "r"(a3), "r"(b0), "r"(b1));
}
DEVI void mma_f16(float (&d)[4], const uint32_t (&a)[4], uint32_t b0, uint32_t b1) {
  asm("mma.sync.aligned.m16n8k16.row.col.f32.f16.f16.f32 {%0,%1,%2,%3}, {%4,%5,%6,%7}, {%8,%9}, {%0,%1,%2,%3};"
      : "+f"(d[0]), "+f"(d[1]), "+f"(d[2]), "+f"(d[3])
      : "r"(a[0]), "r"(a[1]), "r"(a[2]), "r"(a[3]), "r"(b0), "r"(b1));
}
DEVI void mma_bf16v(float (&d)[4], const uint32_t (&a)[4], uint32_t b0, uint32_t b1) {
  asm volatile("mma.sync.aligned.m16n8k16.row.col.f32.bf16.bf16.f32 {%0,%1,%2,%3}, {%4,%5,%6,%7}, {%8,%9}, {%0,%1,%2,%3};"
               : "+f"(d[0]), "+f"(d[1]), "+f"(d[2]), "+f"(d[3])
               : "r"(a[0]), "r"(a[1]), "r"(a[2]), "r"(a[3]), "r"(b0), "r"(b1));
}
DEVI uint32_t pack_bf16(float lo, float hi) {
  uint32_t r;
  asm("cvt.rn.bf16x2.f32 %0, %1, %2;" : "=r"(r) : "f"(hi), "f"(lo));
  return r;
}
DEVI uint32_t pack_f16(float lo, float hi) {
  uint32_t r;
  asm("cvt.rn.f16x2.f32 %0, %1, %2;" : "=r"(r) : "f"(hi), "f"(lo));
  return r;
}
DEVI uint32_t ldg16(const __nv_bfloat16* p) {
  uint32_t v;
  asm volatile("ld.global.nc.u16 %0, [%1];" : "=r"(v) : "l"(p));
  return v;
}
DEVI bool elect_one() {
  uint32_t pred;
  asm volatile("{\n.reg .pred p;\nelect.sync _|p, 0xffffffff;\nselp.u32 %0, 1, 0, p;\n}" : "=r"(pred));
  return pred != 0;
}
DEVI float bf_lo(uint32_t v) { return __uint_as_float(v << 16); }
DEVI float bf_hi(uint32_t v) { return __uint_as_float(v & 0xffff0000u); }
DEVI float bf2f(__nv_bfloat16 v) { return __bfloat162float(v); }
DEVI float round_bf16(float v) { return __bfloat162float(__float2bfloat16_rn(v)); }
DEVI float rcp(float x) { float r; asm("rcp.approx.ftz.f32 %0, %1;" : "=f"(r) : "f"(x)); return r; }
DEVI float ex2(float x) { float r; asm("ex2.approx.ftz.f32 %0, %1;" : "=f"(r) : "f"(x)); return r; }

DEVI void wg_fence() { asm volatile("wgmma.fence.sync.aligned;" ::: "memory"); }
DEVI void wg_commit() { asm volatile("wgmma.commit_group.sync.aligned;" ::: "memory"); }
template <int N> DEVI void wg_wait() { asm volatile("wgmma.wait_group.sync.aligned %0;" ::"n"(N) : "memory"); }
constexpr uint32_t DESC_HI = (1u << 30) | (1024 >> 4);
constexpr uint32_t DESC_HI64 = (2u << 30) | (512 >> 4);
DEVI uint32_t mkdesc(uint32_t saddr, uint32_t lbo) { return ((saddr & 0x3FFFF) >> 4) | ((lbo >> 4) << 16); }

#define R8(b) "%" #b
DEVI void wgmma_n192(float (&d)[96], uint32_t da, uint32_t db, int scale_d) {
  asm volatile(
      "{\n.reg .pred p;\n.reg .b64 da, db;\nsetp.ne.b32 p, %98, 0;\nmov.b64 da, {%96, %100};\nmov.b64 db, {%97, %99};\n"
      "wgmma.mma_async.sync.aligned.m64n192k16.f32.bf16.bf16 "
      "{%0,%1,%2,%3,%4,%5,%6,%7,%8,%9,%10,%11,%12,%13,%14,%15,"
      "%16,%17,%18,%19,%20,%21,%22,%23,%24,%25,%26,%27,%28,%29,%30,%31,"
      "%32,%33,%34,%35,%36,%37,%38,%39,%40,%41,%42,%43,%44,%45,%46,%47,"
      "%48,%49,%50,%51,%52,%53,%54,%55,%56,%57,%58,%59,%60,%61,%62,%63,"
      "%64,%65,%66,%67,%68,%69,%70,%71,%72,%73,%74,%75,%76,%77,%78,%79,"
      "%80,%81,%82,%83,%84,%85,%86,%87,%88,%89,%90,%91,%92,%93,%94,%95}, "
      "da, db, p, 1, 1, 0, 1;\n}"
      : "+f"(d[0]), "+f"(d[1]), "+f"(d[2]), "+f"(d[3]), "+f"(d[4]), "+f"(d[5]), "+f"(d[6]), "+f"(d[7]),
        "+f"(d[8]), "+f"(d[9]), "+f"(d[10]), "+f"(d[11]), "+f"(d[12]), "+f"(d[13]), "+f"(d[14]), "+f"(d[15]),
        "+f"(d[16]), "+f"(d[17]), "+f"(d[18]), "+f"(d[19]), "+f"(d[20]), "+f"(d[21]), "+f"(d[22]), "+f"(d[23]),
        "+f"(d[24]), "+f"(d[25]), "+f"(d[26]), "+f"(d[27]), "+f"(d[28]), "+f"(d[29]), "+f"(d[30]), "+f"(d[31]),
        "+f"(d[32]), "+f"(d[33]), "+f"(d[34]), "+f"(d[35]), "+f"(d[36]), "+f"(d[37]), "+f"(d[38]), "+f"(d[39]),
        "+f"(d[40]), "+f"(d[41]), "+f"(d[42]), "+f"(d[43]), "+f"(d[44]), "+f"(d[45]), "+f"(d[46]), "+f"(d[47]),
        "+f"(d[48]), "+f"(d[49]), "+f"(d[50]), "+f"(d[51]), "+f"(d[52]), "+f"(d[53]), "+f"(d[54]), "+f"(d[55]),
        "+f"(d[56]), "+f"(d[57]), "+f"(d[58]), "+f"(d[59]), "+f"(d[60]), "+f"(d[61]), "+f"(d[62]), "+f"(d[63]),
        "+f"(d[64]), "+f"(d[65]), "+f"(d[66]), "+f"(d[67]), "+f"(d[68]), "+f"(d[69]), "+f"(d[70]), "+f"(d[71]),
        "+f"(d[72]), "+f"(d[73]), "+f"(d[74]), "+f"(d[75]), "+f"(d[76]), "+f"(d[77]), "+f"(d[78]), "+f"(d[79]),
        "+f"(d[80]), "+f"(d[81]), "+f"(d[82]), "+f"(d[83]), "+f"(d[84]), "+f"(d[85]), "+f"(d[86]), "+f"(d[87]),
        "+f"(d[88]), "+f"(d[89]), "+f"(d[90]), "+f"(d[91]), "+f"(d[92]), "+f"(d[93]), "+f"(d[94]), "+f"(d[95])
      : "r"(da), "r"(db), "r"(scale_d), "n"(DESC_HI), "n"(DESC_HI64));
}
DEVI void wgmma_n64(float (&d)[32], uint32_t da, uint32_t db, int scale_d) {
  asm volatile(
      "{\n.reg .pred p;\n.reg .b64 da, db;\nsetp.ne.b32 p, %34, 0;\nmov.b64 da, {%32, %35};\nmov.b64 db, {%33, %35};\n"
      "wgmma.mma_async.sync.aligned.m64n64k16.f32.bf16.bf16 "
      "{%0,%1,%2,%3,%4,%5,%6,%7,%8,%9,%10,%11,%12,%13,%14,%15,"
      "%16,%17,%18,%19,%20,%21,%22,%23,%24,%25,%26,%27,%28,%29,%30,%31}, "
      "da, db, p, 1, 1, 0, 1;\n}"
      : "+f"(d[0]), "+f"(d[1]), "+f"(d[2]), "+f"(d[3]), "+f"(d[4]), "+f"(d[5]), "+f"(d[6]), "+f"(d[7]),
        "+f"(d[8]), "+f"(d[9]), "+f"(d[10]), "+f"(d[11]), "+f"(d[12]), "+f"(d[13]), "+f"(d[14]), "+f"(d[15]),
        "+f"(d[16]), "+f"(d[17]), "+f"(d[18]), "+f"(d[19]), "+f"(d[20]), "+f"(d[21]), "+f"(d[22]), "+f"(d[23]),
        "+f"(d[24]), "+f"(d[25]), "+f"(d[26]), "+f"(d[27]), "+f"(d[28]), "+f"(d[29]), "+f"(d[30]), "+f"(d[31])
      : "r"(da), "r"(db), "r"(scale_d), "n"(DESC_HI));
}

struct C32 { float re, im; };
DEVI C32 csq(C32 a) { return {a.re * a.re - a.im * a.im, 2.f * a.re * a.im}; }
DEVI C32 cmul(C32 a, C32 b) { return {a.re * b.re - a.im * b.im, a.re * b.im + a.im * b.re}; }
DEVI C32 cfresh(float zl, float zi, float m) {
  float mag = ex2(zl * m), ph = zi * m;
  return {mag * __cosf(ph), mag * __sinf(ph)};
}
struct HMul { uint32_t b, bp; };
DEVI HMul mk_mul(float re, float im) { return {pack_f16(re, im), pack_f16(-im, re)}; }
DEVI uint32_t hcmul(uint32_t a, const HMul& m) {
  __half2 ah = *reinterpret_cast<__half2*>(&a);
  __half2 b = *reinterpret_cast<const __half2*>(&m.b), bp = *reinterpret_cast<const __half2*>(&m.bp);
  __half2 r = __hfma2(__high2half2(ah), bp, __hmul2(__low2half2(ah), b));
  return *reinterpret_cast<uint32_t*>(&r);
}
DEVI uint32_t badd(uint32_t a, uint32_t b) {
  __nv_bfloat162 r = __hadd2(*reinterpret_cast<__nv_bfloat162*>(&a), *reinterpret_cast<__nv_bfloat162*>(&b));
  return *reinterpret_cast<uint32_t*>(&r);
}
template <int MU0, int NMU, int DMAX>
DEVI void conv_tail(float (&acc)[16][4], uint32_t p_lane, uint32_t v_base, int back, bool edge, int lane) {
  const int hsel = (lane >> 3) & 1;
  const int row = (lane & 7) + ((lane >> 4) << 3) + PADV - 8 - (back & (hsel ^ 1));
  const uint32_t la = v_base + row * 32 + (((hsel ^ back) ^ ((row >> 2) & 1)) << 4);
  uint32_t M[3][4];
  ldsm_x4_t(M[0], la);
  ldsm_x4_t(M[1], la + 256);
  uint32_t H[2 * NMU];
#pragma unroll
  for (int i = 0; i < 2 * NMU; ++i) H[i ^ 1] = lds32(p_lane + (uint32_t)(MU0 - 1 + i) * 32);
  if (edge) {
    const uint32_t a[4] = {0u, 0u, M[0][0], M[0][1]};
#pragma unroll
    for (int k = 1; k < NMU; ++k) mma_bf16v(acc[MU0 - 2 + 2 * k], a, H[2 * k], H[2 * k + 1]);
  }
#pragma unroll
  for (int delta = -1; delta <= DMAX; ++delta) {
    if (delta + 2 <= DMAX) ldsm_x4_t(M[(delta + 3) % 3], la + (delta + 3) * 256);
#pragma unroll
    for (int k = 0; k < NMU; ++k)
      if (delta + MU0 + 2 * k < 16) mma_bf16v(acc[delta + MU0 + 2 * k], M[(delta + 1) % 3], H[2 * k], H[2 * k + 1]);
  }
}

__global__ void __cluster_dims__(2, 1, 1) __launch_bounds__(NTHREADS, 1)
fused_kernel(const __grid_constant__ Maps maps, const Ptrs p) {
  extern __shared__ __align__(1024) uint8_t smem[];
  const uint32_t sb = s2u(smem);
  const int tid = threadIdx.x, lane = tid & 31;
  const int warp = __shfl_sync(0xffffffffu, tid >> 5, 0);
  const int cta = blockIdx.x;
  const uint32_t rank = cta & 1;
  const int ti = 2 * (cta >> 4) + rank;
  const int tj = (cta >> 1) & 7;
  const uint32_t bars = sb + SM_BAR;
#define BAR(i) (bars + 8 * (i))
  const int g = lane >> 2, q = lane & 3;

  const int kch = warp & 3, krd = warp >> 2;
  float zr, zi, wr, wi;
  {
    const size_t po = (size_t)(cta * 4 + kch) * 128 + krd * 32 + lane;
    const uint32_t r_ar = ldg16(p.A_re + po), r_ai = ldg16(p.A_im + po), r_br = ldg16(p.B_re + po), r_bi = ldg16(p.B_im + po);
    const uint32_t r_cr = ldg16(p.C_re + po), r_ci = ldg16(p.C_im + po), r_ldt = ldg16(p.log_dt + cta * 4 + kch);
    uint4 pt;
    if (tid < 128) pt = __ldg((const uint4*)g_ptab.v + tid);
    if (tid == 384) {
      TS(0);
#pragma unroll
      for (int i = 0; i < B_COUNT; ++i) mbar_init(BAR(i), bar_count(i));
      asm volatile("fence.mbarrier_init.release.cluster;" ::: "memory");
      prefetch_tmap(&maps.x); prefetch_tmap(&maps.w); prefetch_tmap(&maps.u);
    }
    __syncthreads();
    cluster_arrive();
    if (warp >= 12) {
      cluster_wait();
      if (elect_one()) {
        if (warp == 13) {
          mbar_expect_tx(BAR(B_TILE), 16384);
          tma_load_2d(sb + SM_U, &maps.u, tj * 64, ti * 128, BAR(B_TILE));
          l2_prefetch((const char*)p.wqkv + 224 * 3072 + cta * 6912, 6912);
          l2_prefetch((const char*)p.x + (size_t)cta * 16384, 16384);
          l2_prefetch((const char*)p.wo + (size_t)cta * 4096, 4096);
        } else {
          if (warp == 12) TS(61);
#pragma unroll 1
          for (int ks = warp == 12 ? 0 : warp - 13; ks < NSTG; ks += 3) {
            const uint32_t st = sb + ks * STG_BYTES, fb = BAR(B_FULL + ks);
            mbar_expect_tx(fb, STG_BYTES);
            tma_load_2d(st + STG_X, &maps.x, ks * 32, ti * 128, fb);
            tma_load_3d_mc(st + STG_W + rank * 6144, &maps.w, tj * 64, ks * 32 + rank * 16, 0, fb, 3);
          }
        }
      }
      __syncwarp();
    }
    if (tid < 128) sts128(sb + SM_PTAB + tid * 16, pt.x, pt.y, pt.z, pt.w);
    const float dt = round_bf16(expf(bf_lo(r_ldt)));
    zr = dt * bf_lo(r_ar); zi = dt * bf_lo(r_ai);
    const float dbr = dt * bf_lo(r_br), dbi = dt * bf_lo(r_bi), cr = bf_lo(r_cr), ci = bf_lo(r_ci);
    wr = cr * dbr - ci * dbi; wi = cr * dbi + ci * dbr;
  }
  {
    const float mz = __uint_as_float(__reduce_max_sync(0xffffffffu, __float_as_uint(fmaxf(zr, 0.f))));
    const int E = min(max((int)(__reduce_max_sync(0xffffffffu, __float_as_uint(fmaxf(fabsf(wr), fabsf(wi)))) >> 23), 1), 252);
    const float sc = __int_as_float((253 - E) << 23), inv = __int_as_float((E + 1) << 23);
    const float zl = (zr - mz) * 1.4426950408889634f;
    const uint32_t tb = sb + SM_VV + kch * VV_BYTES + krd * KG_BYTES;
    const uint32_t sta = tb + (((lane >> 2) << 4) | ((lane & 3) << 2));
    auto put = [&](int r, uint32_t v) { sts32((sta ^ ((r & 7) << 4)) + r * 128, v); };
    const uint32_t lda = tb + ((lane & 7) + (((lane >> 3) & 1) << 3)) * 128;
    const uint32_t ldb = tb + ((lane & 7) + ((lane >> 4) << 3)) * 128;
    C32 e1 = cfresh(zl, zi, 1.f), e2 = csq(e1), e4 = csq(e2), e8 = csq(e4);
    C32 e16 = cfresh(zl, zi, 16.f), e32 = csq(e16), e64 = csq(e32), e128 = csq(e64);
    C32 e256 = cfresh(zl, zi, 256.f), e512 = csq(e256), e1024 = csq(e512), e768 = cmul(e512, e256);
    uint32_t XA[2][4][4];
    {
      const HMul m16 = mk_mul(e16.re, e16.im), m32 = mk_mul(e32.re, e32.im), m64 = mk_mul(e64.re, e64.im);
      const HMul m128 = mk_mul(e128.re, e128.im);
      uint32_t X[16];
      X[0] = 0x00003c00u; X[1] = pack_f16(e8.re, e8.im); X[2] = m16.b; X[4] = m32.b; X[8] = m64.b;
      X[3] = hcmul(X[1], m16); X[5] = hcmul(X[1], m32); X[6] = hcmul(X[2], m32); X[7] = hcmul(X[3], m32);
#pragma unroll
      for (int r = 1; r < 8; ++r) X[8 + r] = hcmul(X[r], m64);
#pragma unroll
      for (int h = 0; h < 2; ++h) {
#pragma unroll
        for (int r = 0; r < 16; ++r) put(r, h == 0 ? X[r] : r == 0 ? m128.b : hcmul(X[r], m128));
        __syncwarp();
#pragma unroll
        for (int k = 0; k < 4; ++k) ldsm_x4(XA[h][k], lda + (((2 * k + (lane >> 4)) ^ (lane & 7)) << 4));
        __syncwarp();
      }
    }
    float D[2][3][4];
#pragma unroll
    for (int t = 0; t < 6; ++t) D[t / 3][t % 3][0] = D[t / 3][t % 3][1] = D[t / 3][t % 3][2] = D[t / 3][t % 3][3] = 0.f;
    auto contract = [&](int t0, int nt) {
      __syncwarp();
#pragma unroll
      for (int k = 0; k < 4; ++k) {
        uint32_t b[4];
        ldsm_x4(b, ldb + (((2 * k + ((lane >> 3) & 1)) ^ (lane & 7)) << 4));
#pragma unroll
        for (int h = 0; h < 2; ++h) {
          mma_f16(D[h][t0], XA[h][k], b[0], b[1]);
          if (nt == 2) mma_f16(D[h][t0 + 1], XA[h][k], b[2], b[3]);
        }
      }
      __syncwarp();
    };
    const HMul c1 = mk_mul(e1.re, -e1.im), c2 = mk_mul(e2.re, -e2.im), c4 = mk_mul(e4.re, -e4.im);
    const HMul c256 = mk_mul(e256.re, -e256.im), c512 = mk_mul(e512.re, -e512.im), c768 = mk_mul(e768.re, -e768.im);
    const HMul c1024 = mk_mul(e1024.re, -e1024.im);
    uint32_t W[8];
    W[0] = pack_f16(wr * sc, -wi * sc);
    W[1] = hcmul(W[0], c1); W[2] = hcmul(W[0], c2); W[3] = hcmul(W[1], c2);
    W[4] = hcmul(W[0], c4); W[5] = hcmul(W[1], c4); W[6] = hcmul(W[2], c4); W[7] = hcmul(W[3], c4);
#pragma unroll
    for (int i = 0; i < 8; ++i) put(i, W[i]);
#pragma unroll
    for (int i = 0; i < 4; ++i) put(8 + i, hcmul(W[2 * i], c256));
    put(12, hcmul(W[0], c512)); put(13, hcmul(W[4], c512)); put(14, hcmul(W[0], c768)); put(15, hcmul(W[4], c768));
    contract(0, 2);
    const uint32_t v0 = hcmul(W[0], c1024);
    put(0, v0); put(1, hcmul(v0, c256)); put(2, hcmul(v0, c512)); put(3, hcmul(v0, c768)); put(4, hcmul(v0, c1024));
    contract(2, 1);
    const uint32_t a = tb + (g * 24 + 2 * q) * 4;
#pragma unroll
    for (int t = 0; t < 6; ++t) {
      const float(&d)[4] = D[t / 3][t % 3];
      sts_f32x2(a + (t / 3) * 1536 + (t % 3) * 32, d[0] * inv, d[1] * inv);
      sts_f32x2(a + (t / 3) * 1536 + (t % 3) * 32 + 768, d[2] * inv, d[3] * inv);
    }
    if (mz > 0.f) {
      __syncwarp();
#pragma unroll 1
      for (int i = lane; i < 768; i += 32) {
        const int r = i / 24, y = i - 24 * r;
        sts_f32(tb + i * 4, lds_f32(tb + i * 4) * ex2(mz * 1.4426950408889634f * (koff(y) + 8 * r)));
      }
    }
  }
  if (tid == 0) TS(2);
  if (warp < 12) cluster_wait();
  __syncthreads();

  if (warp < 4) {
    asm volatile("setmaxnreg.inc.sync.aligned.u32 152;");
    const unsigned epoch = __ldcg(&g_epoch);
    const int d = cta * 4 + warp;
    const uint32_t vv = sb + SM_VV + warp * VV_BYTES;
    const uint32_t ub = sb + SM_U + warp * U_BYTES;
    const uint32_t pb = sb + SM_P + warp * P_BYTES;
    const float dskip = bf2f(p.Dskip[d]);
#pragma unroll 1
    for (int pass = 0; pass < 2; ++pass) {
      if (pass == 1) {
        const uint32_t kf = vv;
#pragma unroll 2
        for (int i = 0; i < 6; ++i) {
          const uint32_t a = kf + (i * 32 + lane) * 16;
          const uint4 x0 = lds128(a), x1 = lds128(a + KG_BYTES), x2 = lds128(a + 2 * KG_BYTES), x3 = lds128(a + 3 * KG_BYTES);
          auto s4 = [](uint32_t a0, uint32_t a1, uint32_t a2, uint32_t a3) {
            return __float_as_uint((__uint_as_float(a0) + __uint_as_float(a1)) + (__uint_as_float(a2) + __uint_as_float(a3)));
          };
          sts128(a, s4(x0.x, x1.x, x2.x, x3.x), s4(x0.y, x1.y, x2.y, x3.y), s4(x0.z, x1.z, x2.z, x3.z), s4(x0.w, x1.w, x2.w, x3.w));
        }
        __syncwarp();
        const float k1024 = lds_f32(kf + kidx_c(1024) * 4);
        if (lane == 0) {
          sts_f32(kf + SL_ZERO * 4, 0.f);
          sts_f32(kf + SL_510 * 4, lds_f32(kf + kidx_c(510) * 4) - lds_f32(kf + kidx_c(512) * 4));
          sts_f32(kf + SL_0 * 4, lds_f32(kf) + dskip);
        }
        __syncwarp();
        mbar_wait(BAR(B_PFREE), 0);
        if (lane < 16) sts128(ub + lane * 16, 0, 0, 0, 0);
        __syncwarp();
        if (elect_one()) {
          wait_counter(&g_cnt[(C_U + (cta >> 4)) * 32], (epoch + 1) * 16);
          mbar_expect_tx(BAR(B_UCH + warp), 4096);
          bulk_load(ub + 256, p.uT + (size_t)d * 2048, 4096, BAR(B_UCH + warp));
        }
        __syncwarp();
        {
          float prev = 0.f;
#pragma unroll 1
          for (int i0 = 0; i0 < 16; i0 += 4) {
            uint32_t e[4];
            float a[4], b[4];
#pragma unroll
            for (int i = 0; i < 4; ++i) e[i] = lds32(sb + SM_PTAB + ((i0 + i) * 32 + lane) * 4);
#pragma unroll
            for (int i = 0; i < 4; ++i) { a[i] = lds_f32(kf + (e[i] & 0xffff)); b[i] = lds_f32(kf + (e[i] >> 16)); }
#pragma unroll
            for (int i = 0; i < 4; ++i) {
              const uint32_t w = pb + (31 * lane + 2 * (i0 + i)) * 4;
              if (i0 + i > 0) sts32(w - 4, pack_bf16(a[i], prev));
              sts32(w, pack_bf16(b[i], a[i]));
              prev = b[i];
            }
          }
        }
        __syncwarp();
        bar_arrive(7, 384);
        if (lane == 0) TS(4);
        const int gq = g - 2 * q;
        uint32_t h127, h128;
        {
          const uint32_t kf2 = pack_bf16(k1024, k1024) ^ 0x80008000u;
          h127 = (gq == 4 ? 0x0000ffffu : gq == 5 ? 0xffffffffu : gq == 6 ? 0xffff0000u : 0u) & kf2;
          h128 = (gq == -4 ? 0x0000ffffu : gq == -3 ? 0xffffffffu : gq == -2 ? 0xffff0000u : 0u) & kf2;
        }
        bar_sync(4, 384);
        mbar_wait(BAR(B_UCH + warp), 0);
        if (lane == 0) TS(7);
        float acc[16][4];
#pragma unroll
        for (int i = 0; i < 16; ++i) { acc[i][0] = acc[i][1] = acc[i][2] = acc[i][3] = 0.f; }
        {
          const uint32_t pd_lane = pb + (PD_OFF + 16 + gq) * 4;
          const int prow0 = 8 + (lane & 7) + ((lane >> 4) << 3), hs = (lane >> 3) & 1;
          uint32_t B[2][4][4];
          uint32_t A[4][4];
          const uint32_t la0 = ub + prow0 * 32 + ((hs ^ ((prow0 >> 2) & 1)) << 4);
#pragma unroll
          for (int m2 = 0; m2 < 4; ++m2) ldsm_x4(B[0][m2], la0 + m2 * 512);
#pragma unroll
          for (int i = 0; i < 4; ++i) {
            const uint32_t a = pd_lane + i * 512;
            A[i][0] = lds32(a); A[i][1] = lds32(a + 32); A[i][2] = lds32(a - 32); A[i][3] = A[i][0];
          }
          uint32_t la = la0;
#pragma unroll 1
          for (int rho = 0; rho < 8; ++rho) {
#pragma unroll
            for (int m2 = 0; m2 < 4; ++m2) ldsm_x4(B[1][m2], la + (4 + m2) * 512);
#pragma unroll
            for (int i = 0; i < 4; ++i)
#pragma unroll
              for (int m = 0; m < 8; ++m) mma_bf16v(acc[m + i], A[i], B[0][m >> 1][2 * (m & 1)], B[0][m >> 1][2 * (m & 1) + 1]);
            const int prow = prow0 - min(rho + 1, 7);
            la = ub + prow * 32 + ((hs ^ ((prow >> 2) & 1)) << 4);
#pragma unroll
            for (int m2 = 0; m2 < 4; ++m2) ldsm_x4(B[0][m2], la + m2 * 512);
            const uint32_t pa = pd_lane + (rho + 1) * 64;
#pragma unroll
            for (int i = 0; i < 4; ++i) {
#pragma unroll
              for (int m = 0; m < 8 - i; ++m)
                mma_bf16v(acc[8 + m + i], A[i], B[1][m >> 1][2 * (m & 1)], B[1][m >> 1][2 * (m & 1) + 1]);
              A[i][0] = lds32(pa + i * 512); A[i][1] = lds32(pa + i * 512 + 32); A[i][2] = lds32(pa + i * 512 - 32);
              A[i][3] = A[i][0];
            }
          }
          {
            uint32_t b8[4];
            ldsm_x4(b8, la + 4 * 512);
            const uint32_t h63 = lds32(pd_lane + 63 * 32), h64 = lds32(pd_lane + 64 * 32);
            const uint32_t a63[4] = {0u, h127, 0u, 0u}, a32[4] = {h64, 0u, h63, h64}, a64[4] = {h128, 0u, h127, h128};
#pragma unroll
            for (int m2 = 0; m2 < 4; ++m2) ldsm_x4(B[1][m2], la0 + m2 * 512);
#pragma unroll
            for (int m = 0; m < 8; ++m) mma_bf16v(acc[m + 7], a63, B[0][m >> 1][2 * (m & 1)], B[0][m >> 1][2 * (m & 1) + 1]);
#pragma unroll
            for (int m2 = 0; m2 < 2; ++m2) ldsm_x4(B[0][m2], la0 + (4 + m2) * 512);
#pragma unroll
            for (int m = 0; m < 8; ++m) mma_bf16v(acc[m + 4], a32, B[1][m >> 1][2 * (m & 1)], B[1][m >> 1][2 * (m & 1) + 1]);
            mma_bf16v(acc[15], a63, b8[0], b8[1]);
#pragma unroll
            for (int m = 0; m < 8; ++m) mma_bf16v(acc[m + 8], a64, B[1][m >> 1][2 * (m & 1)], B[1][m >> 1][2 * (m & 1) + 1]);
#pragma unroll
            for (int m = 0; m < 4; ++m) mma_bf16v(acc[m + 12], a32, B[0][m >> 1][2 * (m & 1)], B[0][m >> 1][2 * (m & 1) + 1]);
          }
          bar_sync(5, 384);
#pragma unroll 1
          for (int v = 0; v < 4; ++v)
            conv_tail<4, 3, 11>(acc, pb + (P2_OFF + 56 * v + gq - 16) * 4, vv + ((v & 1) ? VV_U3 : VV_U5), v >> 1, v == 0, lane);
#pragma unroll 1
          for (int pi = 0; pi < 2; ++pi)
            conv_tail<8, 5, 7>(acc, pb + (P3_OFF + 88 * pi + gq - 48) * 4, vv + (pi ? VV_U7 : VV_U9), pi, pi == 0, lane);
        }
        if (lane == 0) TS(8);
        __syncwarp();
        {
          const int mt = lane >> 3;
          const uint32_t a = pb + (128 * (mt >> 1) + 16 * (lane & 7) + 8 * (mt & 1)) * 2;
#pragma unroll
          for (int ab = 0; ab < 16; ab += 2)
            stsm_x4_t(a + ab * 256, pack_bf16(acc[ab][0], acc[ab][1]), pack_bf16(acc[ab][2], acc[ab][3]),
                      pack_bf16(acc[ab + 1][0], acc[ab + 1][1]), pack_bf16(acc[ab + 1][2], acc[ab + 1][3]));
        }
        fence_async_smem();
        __syncwarp();
        if (lane == 0) mbar_arrive(BAR(B_CONVD));
        bar_arrive(3, 384);
        if (elect_one()) {
          bulk_store(p.yT + (size_t)d * 2048, pb, 4096);
          bulk_commit();
          bulk_wait0();
          red_relaxed_add(&g_cnt[(C_Y + (cta >> 4)) * 32], 1);
          TS(9);
        }
        bar_sync(2, 128);
        if (warp == 0 && elect_one()) {
          wait_counter(&g_cnt[(C_Y + tj) * 32], (epoch + 1) * 64);
          TS(28);
          mbar_expect_tx(BAR(B_TILE), 16384);
          tma_load_2d(sb + SM_U, &maps.yT, ti * 128, tj * 64, BAR(B_TILE));
          tma_load_2d(sb + SM_U + 8192, &maps.yT, ti * 128 + 64, tj * 64, BAR(B_TILE));
        }
        __syncwarp();
      }
      mbar_wait(BAR(B_TILE), pass);
      if (lane == 0) TS(26 + 3 * pass);
      {
        const int m = lane >> 3, r = lane & 7;
#pragma unroll 2
        for (int it = 0; it < 8; ++it) {
          const int tb = warp * 4 + (it >> 1), cb = (it & 1) * 4 + m;
          const uint32_t at = (tb * 8 + r) * 128 + ((cb ^ r) << 4);
          const uint32_t ac = (tb >> 3) * 8192 + (cb * 8 + r) * 128 + (((tb & 7) ^ (pass ? 0 : tb >> 3) ^ r) << 4);
          uint32_t v[4];
          ldsm_x4_t(v, sb + SM_U + (pass ? ac : at));
          stsm_x4(sb + SM_P + (pass ? at : ac), v[0], v[1], v[2], v[3]);
        }
      }
      fence_async_smem();
      if (pass == 0) {
        bar_arrive(6, 160);
      } else {
        bar_sync(2, 128);
        if (warp == 0 && elect_one()) {
          tma_store_2d(&maps.out, sb + SM_P, 64 * tj, 128 * ti);
          bulk_commit();
          bulk_wait_read0();
          TS(30);
        }
      }
    }
  } else if (warp < 12) {
    asm volatile("setmaxnreg.inc.sync.aligned.u32 160;");
    const int w8 = warp - 4;
    const int row = w8 * 16 + (lane & 7) + (((lane >> 3) & 1) << 3);
    {
      float acc[96];
#pragma unroll 1
      for (int ks = 0, s = 0, ph = 0; ks < 16; ++ks) {
        mbar_wait(BAR(B_FULL + s), ph);
        if (tid == 128 && !(ks & 1)) TSR(16, ks == 0 ? 16 : 9 + (ks >> 1) + (ks > 12 ? 46 : 0));
        const uint32_t st = sb + s * STG_BYTES;
        const uint32_t da = mkdesc(st + STG_X + (w8 >> 2) * 4096, 16);
        const uint32_t db = mkdesc(st + STG_W, 2048);
        wg_fence();
        wgmma_n192(acc, da, db, ks != 0);
        wgmma_n192(acc, da + 2, db + 384, 1);
        wg_commit();
        const uint32_t eprev = BAR(B_EMPTY + (s == 0 ? NSTG - 1 : s - 1));
        if (++s == NSTG) { s = 0; ph ^= 1; }
        if (ks > 0) {
          wg_wait<1>();
          if (lane < 2) mbar_arrive_cluster(eprev, lane);
        }
      }
      wg_wait<0>();
      bar_arrive(4, 384);
      if (tid == 128) TS(17);
      bar_sync(1, 256);
#pragma unroll
      for (int i = 0; i < 24; i += 2)
        stsm_x4(sb + SM_QS + row * 128 + (i >> 3) * 16384 + ((((i & 7) + (lane >> 4)) ^ (row & 7)) << 4),
                pack_bf16(acc[4 * i], acc[4 * i + 1]), pack_bf16(acc[4 * i + 2], acc[4 * i + 3]),
                pack_bf16(acc[4 * i + 4], acc[4 * i + 5]), pack_bf16(acc[4 * i + 6], acc[4 * i + 7]));
    }
    __syncwarp();
#pragma unroll 1
    for (int part = 1; part >= 0; --part) {
      const uint32_t pa = sb + SM_QS + part * 16384 + w8 * 2048 + lane * 16;
#pragma unroll 1
      for (int it = 0; it < 4; ++it) {
        uint4 t = lds128(pa + it * 512);
        uint32_t* tw = &t.x;
#pragma unroll
        for (int j = 0; j < 4; ++j) {
          const uint32_t x = tw[j];
          const __nv_bfloat162 xb = *reinterpret_cast<const __nv_bfloat162*>(&x);
          const uint32_t e = pack_bf16(ex2(bf_lo(x) * 1.4426950408889634f), ex2(bf_hi(x) * 1.4426950408889634f));
          const uint32_t m = __hgt2_mask(xb, __floats2bfloat162_rn(0.f, 0.f));
          const uint32_t sel = (badd(x, 0x3f803f80u) & m) | (e & ~m);
          tw[j] = pack_bf16(bf_lo(sel) + 1e-6f, bf_hi(sel) + 1e-6f);
        }
        sts128(pa + it * 512, t.x, t.y, t.z, t.w);
      }
      if (part == 1) {
        if (tid == 128) TS(53);
        bar_sync(1, 256);
        const int hh = w8 >> 1, dtile = w8 & 1;
        float kv[4] = {0.f, 0.f, 0.f, 0.f}, zz[4] = {0.f, 0.f, 0.f, 0.f};
        const int m = lane >> 3;
        const uint32_t aa = sb + SM_VS + ((lane & 7) + ((m >> 1) << 3)) * 128 + (((2 * hh + (m & 1)) ^ (lane & 7)) << 4);
        const uint32_t ab = sb + SM_PK + (lane & 15) * 128 + (((2 * hh + dtile) ^ (lane & 7)) << 4);
#pragma unroll 2
        for (int ks = 0; ks < 8; ++ks) {
          uint32_t a[4], b0, b1;
          ldsm_x4_t(a, aa + ks * 2048);
          ldsm_x2_t(b0, b1, ab + ks * 2048);
          mma_bf16(kv, a[0], a[1], a[2], a[3], b0, b1);
          mma_bf16(zz, 0x3f803f80u, 0x3f803f80u, 0x3f803f80u, 0x3f803f80u, b0, b1);
        }
        const uint32_t kp = sb + SM_KV + hh * 1088;
        sts128(kp + dtile * 512 + lane * 16, __float_as_uint(kv[0]), __float_as_uint(kv[1]), __float_as_uint(kv[2]),
               __float_as_uint(kv[3]));
        if (g == 0) sts_f32x2(kp + 1024 + dtile * 32 + q * 8, zz[0], zz[1]);
        fence_async_smem();
        __syncwarp();
        if (lane == 0) mbar_arrive(BAR(B_KVP));
        if (tid == 128) TS(55);
      }
    }
    if (tid == 128) TS(56);
    {
      const int ch = w8 >> 1;
      bar_sync(7, 384);
      mbar_wait(BAR(B_UCH + ch), 0);
#pragma unroll 1
      for (int it = w8 & 1; it < 8; it += 2) {
          const int k = -18 + it * 32 + lane;
          const int kr = min(max(k, -2), 208);
          uint32_t E[12];
#pragma unroll
          for (int c = 0; c < 3; ++c) {
            const int kk = kr - 1 + c, r = (kk >> 1) + 8;
            const uint4 t = lds128(sb + SM_U + ch * U_BYTES + r * 32 + (((kk & 1) ^ ((r >> 2) & 1)) << 4));
            E[4 * c] = t.x; E[4 * c + 1] = t.y; E[4 * c + 2] = t.z; E[4 * c + 3] = t.w;
          }
          uint32_t O[8];
#pragma unroll
          for (int j = 0; j < 8; ++j) O[j] = __byte_perm(E[j + 1], E[j + 2], 0x5432);
          uint32_t s3[6], s5[4], s7[4], s9[4];
#pragma unroll
          for (int j = 0; j < 6; ++j) s3[j] = badd(badd(O[j], O[j + 1]), E[j + 2]);
#pragma unroll
          for (int j = 0; j < 4; ++j) {
            s5[j] = badd(s3[j + 2], badd(E[j + 3], E[j + 5]));
            s7[j] = badd(s5[j], badd(O[j + 1], O[j + 4]));
            s9[j] = badd(s7[j], badd(E[j + 2], E[j + 6]));
          }
          const int r = (k >> 1) + PADV;
          const uint32_t a = sb + SM_VV + ch * VV_BYTES + r * 32 + (((k & 1) ^ ((r >> 2) & 1)) << 4);
          if (k < 208) { sts128(a + VV_U3, s3[0], s3[1], s3[2], s3[3]); sts128(a + VV_U5, s5[0], s5[1], s5[2], s5[3]); }
          if (k < 144) { sts128(a + VV_U7, s7[0], s7[1], s7[2], s7[3]); sts128(a + VV_U9, s9[0], s9[1], s9[2], s9[3]); }
      }
      bar_arrive(5, 384);
    }
    if (tid == 128) TS(6);
    mbar_wait(BAR(B_KVF), 0);
    if (tid == 128) TS(19);
#pragma unroll 1
    for (int h = 0; h < 4; ++h) {
      uint32_t a[4];
      const uint32_t qa = sb + SM_QS + row * 128 + (((2 * h + (lane >> 4)) ^ (row & 7)) << 4);
      ldsm_x4(a, qa);
      const uint32_t kp = sb + SM_KV + h * 1088;
      const uint4 k0 = lds128(kp + lane * 16), k1 = lds128(kp + 512 + lane * 16);
      const uint32_t za = kp + 1024 + q * 8;
      auto pk2 = [](uint32_t x, uint32_t y) { return pack_bf16(__uint_as_float(x), __uint_as_float(y)); };
      float n0[4] = {0.f, 0.f, 0.f, 0.f}, n1[4] = {0.f, 0.f, 0.f, 0.f}, dn[4] = {0.f, 0.f, 0.f, 0.f};
      mma_bf16(n0, a[0], a[1], a[2], a[3], pk2(k0.x, k0.y), pk2(k1.x, k1.y));
      mma_bf16(n1, a[0], a[1], a[2], a[3], pk2(k0.z, k0.w), pk2(k1.z, k1.w));
      mma_bf16(dn, a[0], a[1], a[2], a[3], pack_bf16(lds_f32(za), lds_f32(za + 4)), pack_bf16(lds_f32(za + 32), lds_f32(za + 36)));
      const uint32_t dd = pack_bf16(dn[0], dn[2]);
      const uint32_t d2 = pack_bf16(bf_lo(dd) + 1e-6f, bf_hi(dd) + 1e-6f);
      const float r0 = rcp(bf_lo(d2)), r1 = rcp(bf_hi(d2));
      const uint32_t x0 = pack_bf16(n0[0], n0[1]), x1 = pack_bf16(n0[2], n0[3]);
      const uint32_t x2 = pack_bf16(n1[0], n1[1]), x3 = pack_bf16(n1[2], n1[3]);
      stsm_x4(qa, pack_bf16(bf_lo(x0) * r0, bf_hi(x0) * r0), pack_bf16(bf_lo(x1) * r1, bf_hi(x1) * r1),
              pack_bf16(bf_lo(x2) * r0, bf_hi(x2) * r0), pack_bf16(bf_lo(x3) * r1, bf_hi(x3) * r1));
    }
    fence_async_smem();
    __syncwarp();
    if (lane == 0) mbar_arrive(BAR(B_OST));
    if (tid == 128) TS(57);
    mbar_wait(BAR(B_WO), 0);
    bar_sync(3, 384);
    {
      float o[32];
#pragma unroll 1
      for (int c = 0; c < 8; ++c) {
        mbar_wait(BAR(B_RF + c), 0);
        if (c == 0 && tid == 128) TS(22);
        const uint32_t slot = c < 4 ? SM_QS + c * 16384 : c < 7 ? SM_VV + (c - 4) * 16384 : SM_QS;
        const uint32_t da = mkdesc(sb + slot + (w8 >> 2) * 8192, 16);
        const uint32_t db = mkdesc(sb + SM_WO + c * 8192, 8192);
        wg_fence();
#pragma unroll
        for (int k = 0; k < 4; ++k) wgmma_n64(o, da + 2 * k, db + 128 * k, (c | k) != 0);
        wg_commit();
        if (c == 1) {
          wg_wait<1>();
          if (lane == 0) mbar_arrive(BAR(B_RE));
        }
      }
      wg_wait<0>();
      bar_sync(1, 256);
#pragma unroll
      for (int i = 0; i < 8; i += 2)
        stsm_x4(sb + SM_BOUT + row * 128 + (((i + (lane >> 4)) ^ (row & 7)) << 4), pack_bf16(o[4 * i], o[4 * i + 1]),
                pack_bf16(o[4 * i + 2], o[4 * i + 3]), pack_bf16(o[4 * i + 4], o[4 * i + 5]), pack_bf16(o[4 * i + 6], o[4 * i + 7]));
      fence_async_smem();
      bar_sync(1, 256);
      if (warp == 4 && elect_one()) {
        tma_store_2d(&maps.out, sb + SM_BOUT, 512 + 64 * tj, 128 * ti);
        bulk_commit();
        bulk_wait_read0();
        TS(23);
      }
    }
  } else {
    asm volatile("setmaxnreg.dec.sync.aligned.u32 40;");
    if (warp == 12) {
      if (elect_one()) {
        const unsigned epoch = __ldcg(&g_epoch);
#pragma unroll 1
        for (int ks = NSTG, s = 0, ph = 0; ks < 16; ++ks) {
          mbar_wait(BAR(B_EMPTY + s), ph);
          TSR(38, 31 + ks);
          const uint32_t st = sb + s * STG_BYTES, fb = BAR(B_FULL + s);
          mbar_expect_tx(fb, STG_BYTES);
          tma_load_2d(st + STG_X, &maps.x, ks * 32, ti * 128, fb);
          tma_load_3d_mc(st + STG_W + rank * 6144, &maps.w, tj * 64, ks * 32 + rank * 16, 0, fb, 3);
          if (++s == NSTG) { s = 0; ph ^= 1; }
        }
        prefetch_tmap(&maps.wo); prefetch_tmap(&maps.o); prefetch_tmap(&maps.out);
        mbar_wait(BAR(B_EMPTY + 3), 1);
        mbar_wait(BAR(B_EMPTY + 6), 1);
        mbar_expect_tx(BAR(B_WO), 65536);
        tma_load_2d_mc(sb + SM_WO + rank * 32768, &maps.wo, tj * 64, rank * 256, BAR(B_WO), 3);
        float* kvg = &g_kv[epoch & 1][tj][0];
        mbar_wait(BAR(B_KVP), 0);
        bulk_reduce_add_f32(kvg, sb + SM_KV, 4352);
        bulk_commit();
        bulk_wait0();
        red_relaxed_add(&g_cnt[(C_KV + tj) * 32], 1);
        TS(18);
        wait_counter(&g_cnt[(C_KV + tj) * 32], (epoch + 1) * 16);
        mbar_expect_tx(BAR(B_KVF), 4352);
        bulk_load(sb + SM_KV, kvg, 4352, BAR(B_KVF));
        mbar_wait(BAR(B_OST), 0);
        tma_store_2d(&maps.o, sb + SM_QS, tj * 64, ti * 128);
        bulk_commit();
        bulk_wait0();
        red_relaxed_add(&g_cnt[(C_O + ti) * 32], 1);
        TS(20);
        wait_counter(&g_cnt[(C_O + ti) * 32], (epoch + 1) * 8);
        if (cta == 0) g_epoch = epoch + 1;
        TS(21);
#pragma unroll 1
        for (int c = 0; c < 8; ++c) {
          if (c == 4) mbar_wait(BAR(B_CONVD), 0);
          if (c == 7) mbar_wait(BAR(B_RE), 0);
          const uint32_t slot = c < 4 ? SM_QS + c * 16384 : c < 7 ? SM_VV + (c - 4) * 16384 : SM_QS;
          mbar_expect_tx(BAR(B_RF + c), 16384);
          tma_load_2d(sb + slot, &maps.o, c * 64, ti * 128, BAR(B_RF + c));
        }
      }
    } else if (warp == 13) {
      bar_sync(6, 160);
      if (elect_one()) {
        tma_store_2d(&maps.uT, sb + SM_P, ti * 128, tj * 64);
        tma_store_2d(&maps.uT, sb + SM_P + 8192, ti * 128 + 64, tj * 64);
        bulk_commit();
        bulk_wait_read0();
        mbar_arrive(BAR(B_PFREE));
        bulk_wait0();
        red_relaxed_add(&g_cnt[(C_U + tj) * 32], 1);
        TS(27);
      }
      __syncwarp();
      if (ti == 0) {
        float4* z = (float4*)&g_kv[(__ldcg(&g_epoch) & 1) ^ 1][tj][0];
#pragma unroll 1
        for (int i = lane; i < 272; i += 32) z[i] = make_float4(0.f, 0.f, 0.f, 0.f);
      }
    }
  }
  __syncwarp();
  cluster_arrive();
  cluster_wait();
  if (tid == 0) TS(31);
#undef BAR
}

typedef CUresult (*EncodeFn)(CUtensorMap*, CUtensorMapDataType, cuuint32_t, void*, const cuuint64_t*, const cuuint64_t*,
                             const cuuint32_t*, const cuuint32_t*, CUtensorMapInterleave, CUtensorMapSwizzle,
                             CUtensorMapL2promotion, CUtensorMapFloatOOBfill);

static void make_map(EncodeFn enc, CUtensorMap* m, const void* base, uint64_t inner, uint64_t outer, uint32_t box_in,
                     uint32_t box_out, CUtensorMapSwizzle swz = CU_TENSOR_MAP_SWIZZLE_128B) {
  cuuint64_t gd[2] = {inner, outer};
  cuuint64_t gs[1] = {inner * 2};
  cuuint32_t bd[2] = {box_in, box_out};
  cuuint32_t es[2] = {1, 1};
  enc(m, CU_TENSOR_MAP_DATA_TYPE_BFLOAT16, 2, const_cast<void*>(base), gd, gs, bd, es, CU_TENSOR_MAP_INTERLEAVE_NONE,
      swz, CU_TENSOR_MAP_L2_PROMOTION_L2_128B, CU_TENSOR_MAP_FLOAT_OOB_FILL_NONE);
}

}

extern "C" void kernel_launch(void* const* d_in, const int* in_sizes, int n_in, void* d_out, int out_size) {
  using namespace s4la;
  (void)in_sizes; (void)n_in; (void)out_size;
  static EncodeFn enc = nullptr;
  static void *uT = nullptr, *yT = nullptr, *oS = nullptr;
  if (!enc) {
    void* fn = nullptr;
    cudaDriverEntryPointQueryResult qr;
    cudaGetDriverEntryPoint("cuTensorMapEncodeTiled", &fn, cudaEnableDefault, &qr);
    enc = (EncodeFn)fn;
    cudaGetSymbolAddress(&uT, g_uT);
    cudaGetSymbolAddress(&yT, g_yT);
    cudaGetSymbolAddress(&oS, g_o);
    cudaFuncSetAttribute(fused_kernel, cudaFuncAttributeMaxDynamicSharedMemorySize, SM_TOTAL);
  }
  const __nv_bfloat16* const* in = (const __nv_bfloat16* const*)d_in;
  Maps maps;
  make_map(enc, &maps.x, in[9], 512, 2048, 32, 128, CU_TENSOR_MAP_SWIZZLE_64B);
  {
    cuuint64_t gd[3] = {512, 512, 3};
    cuuint64_t gs[2] = {3072, 1024};
    cuuint32_t bd[3] = {64, 16, 3};
    cuuint32_t es[3] = {1, 1, 1};
    enc(&maps.w, CU_TENSOR_MAP_DATA_TYPE_BFLOAT16, 3, const_cast<__nv_bfloat16*>(in[10]), gd, gs, bd, es,
        CU_TENSOR_MAP_INTERLEAVE_NONE, CU_TENSOR_MAP_SWIZZLE_128B, CU_TENSOR_MAP_L2_PROMOTION_L2_128B,
        CU_TENSOR_MAP_FLOAT_OOB_FILL_NONE);
  }
  make_map(enc, &maps.wo, in[11], 512, 512, 64, 256);
  make_map(enc, &maps.u, in[0], 512, 2048, 64, 128);
  make_map(enc, &maps.uT, uT, 2048, 512, 64, 64);
  make_map(enc, &maps.yT, yT, 2048, 512, 64, 64);
  make_map(enc, &maps.o, oS, 512, 2048, 64, 128);
  make_map(enc, &maps.out, d_out, 1024, 2048, 64, 128);
  Ptrs p;
  p.A_re = in[1]; p.A_im = in[2]; p.B_re = in[3]; p.B_im = in[4]; p.C_re = in[5]; p.C_im = in[6];
  p.log_dt = in[7]; p.Dskip = in[8]; p.x = in[9]; p.wqkv = in[10]; p.wo = in[11];
  p.uT = (__nv_bfloat16*)uT; p.yT = (__nv_bfloat16*)yT;
  fused_kernel<<<NCTA, NTHREADS, SM_TOTAL, cudaStreamPerThread>>>(maps, p);
}
```

```cpp
#include <cuda_runtime.h>
#include <cuda_bf16.h>
#include <cuda_fp16.h>
#include <cuda.h>
#include <stdint.h>

#define DEVI __device__ __forceinline__

namespace s4la {

constexpr int NTHREADS = 512;
constexpr int NCTA = 128;

constexpr int NSTG = 7;
constexpr uint32_t STG_BYTES = 20480, STG_X = 0, STG_W = 8192;
constexpr uint32_t SM_QS = 0;
constexpr uint32_t SM_PK = SM_QS + 16384, SM_VS = SM_QS + 32768;
constexpr uint32_t SM_WO = 65536;
constexpr uint32_t SM_KV = 131072;
constexpr uint32_t SM_BOUT = 16384;
constexpr uint32_t SM_U = 143360, U_BYTES = 4352;
constexpr uint32_t SM_P = 160768, P_BYTES = 4096;
constexpr uint32_t SM_VV = 177152, VV_BYTES = 12800;
constexpr uint32_t VV_U5 = 0, VV_U3 = 3712, VV_U9 = 7424, VV_U7 = 10112;
constexpr uint32_t KG_BYTES = 3200;
constexpr uint32_t SM_BAR = SM_VV + 4 * VV_BYTES;
constexpr uint32_t SM_PTAB = SM_BAR + 320;
constexpr uint32_t SM_TOTAL = SM_PTAB + 2048;
static_assert(SM_TOTAL <= 232448, "shared memory");
constexpr int PADV = 12;

enum { B_FULL = 0, B_EMPTY = 7, B_TILE = 14, B_UCH = 15, B_KVP = 19, B_KVF = 20, B_OST = 21, B_RF = 22, B_WO = 30, B_RE = 31, B_PFREE = 32, B_CONVD = 33, B_COUNT = 34 };
__host__ __device__ constexpr int bar_count(int i) {
  return (i >= B_EMPTY && i < B_TILE) ? 16 : (i == B_KVP || i == B_OST || i == B_RE) ? 8 : i == B_CONVD ? 4 : 1;
}

constexpr int PD_OFF = 0, P2_OFF = 544, P3_OFF = 768;

constexpr int SL_K2048 = 20, SL_ZERO = 21, SL_510 = 22, SL_0 = 23;
__host__ __device__ constexpr int koff(int y) {
  return y < 8 ? y : y < 12 ? 256 + 2 * (y - 8) : y < 16 ? 512 + 256 * ((y - 12) >> 1) + 4 * (y & 1) : 1024 + 256 * (y - 16);
}
__host__ __device__ constexpr int kidx_c(int l) {
  const int y = l < 256 ? (l & 7) : l < 512 ? 8 + ((l & 7) >> 1) : l < 1024 ? 12 + (((l - 512) >> 8) << 1) + ((l >> 2) & 1)
                                                                            : 16 + ((l - 1024) >> 8);
  return ((l >> 3) & 31) * 24 + y;
}
constexpr int slot_direct(int l) {
  if (l < 0 || l > 510) return SL_ZERO;
  if (l == 510) return SL_510;
  if (l == 0) return SL_0;
  return kidx_c(l < 256 ? l : ((l + ((l >> 1) & 1)) & ~1));
}
constexpr int slot_seg2(int v, int k) { return (k >= 32 && k < 64) ? kidx_c(16 * k + 4 * v) : SL_ZERO; }
constexpr int slot_seg3(int pi, int k) {
  return (k >= 64 && k < 128) ? kidx_c(16 * k + 8 * pi) : ((k == 128 && pi == 0) ? SL_K2048 : SL_ZERO);
}
constexpr int slot_word(int w) {
  return w < 0 ? SL_ZERO : w < 544 ? slot_direct(w - 16) : w < 768 ? slot_seg2((w - 544) / 56, 16 + (w - 544) % 56)
       : w < 944 ? slot_seg3((w - 768) / 88, 48 + (w - 768) % 88) : SL_ZERO;
}
struct PTab { uint32_t v[512]; };
constexpr PTab make_ptab() {
  PTab t{};
  for (int lane = 0; lane < 32; ++lane)
    for (int i = 0; i < 16; ++i)
      t.v[i * 32 + lane] = (slot_word(31 * lane - 1 + 2 * i) * 4) | ((slot_word(31 * lane + 2 * i) * 4) << 16);
  return t;
}
__device__ const PTab g_ptab = make_ptab();

__device__ __nv_bfloat16 g_uT[512 * 2048];
__device__ __nv_bfloat16 g_yT[512 * 2048];
__device__ __nv_bfloat16 g_o[2048 * 512];
__device__ float g_kv[2][8][4 * 272];
__device__ unsigned g_cnt[64 * 32];
__device__ unsigned g_epoch;
#define TS(slot) do { } while (0)
#define TSR(on, slot) do { } while (0)
enum { C_U = 0, C_KV = 8, C_O = 16, C_Y = 32 };

struct Maps {
  CUtensorMap x, w, wo, u, uT, yT, o, out;
};
struct Ptrs {
  const __nv_bfloat16 *A_re, *A_im, *B_re, *B_im, *C_re, *C_im, *log_dt, *Dskip;
  const __nv_bfloat16 *x, *wqkv, *wo;
  __nv_bfloat16 *uT, *yT;
};

DEVI uint32_t s2u(const void* p) { return (uint32_t)__cvta_generic_to_shared(p); }
DEVI void mbar_init(uint32_t b, uint32_t c) { asm volatile("mbarrier.init.shared::cta.b64 [%0], %1;" ::"r"(b), "r"(c) : "memory"); }
DEVI void mbar_expect_tx(uint32_t b, uint32_t bytes) {
  asm volatile("mbarrier.arrive.expect_tx.shared::cta.b64 _, [%0], %1;" ::"r"(b), "r"(bytes) : "memory");
}
DEVI void mbar_arrive(uint32_t b) { asm volatile("mbarrier.arrive.shared::cta.b64 _, [%0];" ::"r"(b) : "memory"); }
DEVI void mbar_arrive_cluster(uint32_t b, uint32_t cta) {
  asm volatile("{\n.reg .b32 r;\nmapa.shared::cluster.u32 r, %0, %1;\nmbarrier.arrive.shared::cluster.b64 _, [r];\n}"
               ::"r"(b), "r"(cta) : "memory");
}
DEVI void mbar_wait(uint32_t b, uint32_t parity) {
  asm volatile("{\n.reg .pred p;\nLAB_WAIT:\nmbarrier.try_wait.parity.shared::cta.b64 p, [%0], %1;\n@!p bra LAB_WAIT;\n}"
               ::"r"(b), "r"(parity) : "memory");
}
DEVI void bar_sync(int id, int n) { asm volatile("bar.sync %0, %1;" ::"r"(id), "r"(n) : "memory"); }
DEVI void bar_arrive(int id, int n) { asm volatile("bar.arrive %0, %1;" ::"r"(id), "r"(n) : "memory"); }
DEVI void fence_async_smem() { asm volatile("fence.proxy.async.shared::cta;" ::: "memory"); }
DEVI void fence_async_all() { asm volatile("fence.proxy.async;" ::: "memory"); }
DEVI void cluster_arrive() { asm volatile("barrier.cluster.arrive.relaxed.aligned;" ::: "memory"); }
DEVI void cluster_wait() { asm volatile("barrier.cluster.wait.aligned;" ::: "memory"); }

DEVI void tma_load_2d(uint32_t dst, const CUtensorMap* m, int c0, int c1, uint32_t bar) {
  asm volatile("cp.async.bulk.tensor.2d.shared::cluster.global.mbarrier::complete_tx::bytes [%0], [%1, {%3, %4}], [%2];"
               ::"r"(dst), "l"(m), "r"(bar), "r"(c0), "r"(c1) : "memory");
}
DEVI void tma_load_2d_mc(uint32_t dst, const CUtensorMap* m, int c0, int c1, uint32_t bar, uint16_t mask) {
  asm volatile("cp.async.bulk.tensor.2d.shared::cluster.global.mbarrier::complete_tx::bytes.multicast::cluster [%0], [%1, {%3, %4}], [%2], %5;"
               ::"r"(dst), "l"(m), "r"(bar), "r"(c0), "r"(c1), "h"(mask) : "memory");
}
DEVI void tma_load_3d_mc(uint32_t dst, const CUtensorMap* m, int c0, int c1, int c2, uint32_t bar, uint16_t mask) {
  asm volatile("cp.async.bulk.tensor.3d.shared::cluster.global.mbarrier::complete_tx::bytes.multicast::cluster [%0], [%1, {%3, %4, %5}], [%2], %6;"
               ::"r"(dst), "l"(m), "r"(bar), "r"(c0), "r"(c1), "r"(c2), "h"(mask) : "memory");
}
DEVI void tma_store_2d(const CUtensorMap* m, uint32_t src, int c0, int c1) {
  asm volatile("cp.async.bulk.tensor.2d.global.shared::cta.bulk_group [%0, {%2, %3}], [%1];"
               ::"l"(m), "r"(src), "r"(c0), "r"(c1) : "memory");
}
DEVI void bulk_load(uint32_t dst, const void* src, uint32_t bytes, uint32_t bar) {
  asm volatile("cp.async.bulk.shared::cluster.global.mbarrier::complete_tx::bytes [%0], [%1], %2, [%3];"
               ::"r"(dst), "l"(src), "r"(bytes), "r"(bar) : "memory");
}
DEVI void bulk_store(void* dst, uint32_t src, uint32_t bytes) {
  asm volatile("cp.async.bulk.global.shared::cta.bulk_group [%0], [%1], %2;" ::"l"(dst), "r"(src), "r"(bytes) : "memory");
}
DEVI void bulk_reduce_add_f32(void* dst, uint32_t src, uint32_t bytes) {
  asm volatile("cp.reduce.async.bulk.global.shared::cta.bulk_group.add.f32 [%0], [%1], %2;" ::"l"(dst), "r"(src), "r"(bytes) : "memory");
}
DEVI void bulk_commit() { asm volatile("cp.async.bulk.commit_group;" ::: "memory"); }
DEVI void bulk_wait0() { asm volatile("cp.async.bulk.wait_group 0;" ::: "memory"); }
DEVI void bulk_wait_read0() { asm volatile("cp.async.bulk.wait_group.read 0;" ::: "memory"); }
DEVI void l2_prefetch(const void* p, uint32_t bytes) {
  asm volatile("cp.async.bulk.prefetch.L2.global [%0], %1;" ::"l"(p), "r"(bytes) : "memory");
}
DEVI void prefetch_tmap(const CUtensorMap* m) { asm volatile("prefetch.tensormap [%0];" ::"l"(m) : "memory"); }

DEVI void red_release_add(unsigned* p, unsigned v) {
  asm volatile("red.release.gpu.global.add.u32 [%0], %1;" ::"l"(p), "r"(v) : "memory");
}
DEVI void red_relaxed_add(unsigned* p, unsigned v) {
  asm volatile("red.relaxed.gpu.global.add.u32 [%0], %1;" ::"l"(p), "r"(v) : "memory");
}
DEVI unsigned ld_relaxed(const unsigned* p) {
  unsigned v;
  asm volatile("ld.relaxed.gpu.global.u32 %0, [%1];" : "=r"(v) : "l"(p) : "memory");
  return v;
}
DEVI void wait_counter(const unsigned* p, unsigned target) {
#pragma unroll 1
  for (int it = 0; (int)(ld_relaxed(p) - target) < 0; ++it)
    if (it > (1 << 22)) __trap();
}

DEVI void ldsm_x4(uint32_t (&r)[4], uint32_t a) {
  asm volatile("ldmatrix.sync.aligned.m8n8.x4.shared.b16 {%0,%1,%2,%3}, [%4];"
               : "=r"(r[0]), "=r"(r[1]), "=r"(r[2]), "=r"(r[3]) : "r"(a) : "memory");
}
DEVI void ldsm_x4_t(uint32_t (&r)[4], uint32_t a) {
  asm volatile("ldmatrix.sync.aligned.m8n8.x4.trans.shared.b16 {%0,%1,%2,%3}, [%4];"
               : "=r"(r[0]), "=r"(r[1]), "=r"(r[2]), "=r"(r[3]) : "r"(a) : "memory");
}
DEVI void ldsm_x2_t(uint32_t& r0, uint32_t& r1, uint32_t a) {
  asm volatile("ldmatrix.sync.aligned.m8n8.x2.trans.shared.b16 {%0,%1}, [%2];" : "=r"(r0), "=r"(r1) : "r"(a) : "memory");
}
DEVI void stsm_x4(uint32_t a, uint32_t r0, uint32_t r1, uint32_t r2, uint32_t r3) {
  asm volatile("stmatrix.sync.aligned.m8n8.x4.shared.b16 [%0], {%1,%2,%3,%4};"
               ::"r"(a), "r"(r0), "r"(r1), "r"(r2), "r"(r3) : "memory");
}
DEVI void stsm_x4_t(uint32_t a, uint32_t r0, uint32_t r1, uint32_t r2, uint32_t r3) {
  asm volatile("stmatrix.sync.aligned.m8n8.x4.trans.shared.b16 [%0], {%1,%2,%3,%4};"
               ::"r"(a), "r"(r0), "r"(r1), "r"(r2), "r"(r3) : "memory");
}
DEVI uint32_t lds32(uint32_t a) { uint32_t v; asm volatile("ld.shared.b32 %0, [%1];" : "=r"(v) : "r"(a) : "memory"); return v; }
DEVI float lds_f32(uint32_t a) { float v; asm volatile("ld.shared.f32 %0, [%1];" : "=f"(v) : "r"(a) : "memory"); return v; }
DEVI void sts32(uint32_t a, uint32_t v) { asm volatile("st.shared.b32 [%0], %1;" ::"r"(a), "r"(v) : "memory"); }
DEVI void sts_f32(uint32_t a, float v) { asm volatile("st.shared.f32 [%0], %1;" ::"r"(a), "f"(v) : "memory"); }
DEVI void sts_f32x2(uint32_t a, float x, float y) { asm volatile("st.shared.v2.f32 [%0], {%1,%2};" ::"r"(a), "f"(x), "f"(y) : "memory"); }
DEVI uint4 lds128(uint32_t a) {
  uint4 v;
  asm volatile("ld.shared.v4.b32 {%0,%1,%2,%3}, [%4];" : "=r"(v.x), "=r"(v.y), "=r"(v.z), "=r"(v.w) : "r"(a) : "memory");
  return v;
}
DEVI void sts128(uint32_t a, uint32_t x, uint32_t y, uint32_t z, uint32_t w) {
  asm volatile("st.shared.v4.b32 [%0], {%1,%2,%3,%4};" ::"r"(a), "r"(x), "r"(y), "r"(z), "r"(w) : "memory");
}

DEVI void mma_bf16(float (&d)[4], uint32_t a0, uint32_t a1, uint32_t a2, uint32_t a3, uint32_t b0, uint32_t b1) {
  asm("mma.sync.aligned.m16n8k16.row.col.f32.bf16.bf16.f32 {%0,%1,%2,%3}, {%4,%5,%6,%7}, {%8,%9}, {%0,%1,%2,%3};"
      : "+f"(d[0]), "+f"(d[1]), "+f"(d[2]), "+f"(d[3])
      : "r"(a0), "r"(a1), "r"(a2), "r"(a3), "r"(b0), "r"(b1));
}
DEVI void mma_f16(float (&d)[4], const uint32_t (&a)[4], uint32_t b0, uint32_t b1) {
  asm("mma.sync.aligned.m16n8k16.row.col.f32.f16.f16.f32 {%0,%1,%2,%3}, {%4,%5,%6,%7}, {%8,%9}, {%0,%1,%2,%3};"
      : "+f"(d[0]), "+f"(d[1]), "+f"(d[2]), "+f"(d[3])
      : "r"(a[0]), "r"(a[1]), "r"(a[2]), "r"(a[3]), "r"(b0), "r"(b1));
}
DEVI void mma_bf16v(float (&d)[4], const uint32_t (&a)[4], uint32_t b0, uint32_t b1) {
  asm volatile("mma.sync.aligned.m16n8k16.row.col.f32.bf16.bf16.f32 {%0,%1,%2,%3}, {%4,%5,%6,%7}, {%8,%9}, {%0,%1,%2,%3};"
               : "+f"(d[0]), "+f"(d[1]), "+f"(d[2]), "+f"(d[3])
               : "r"(a[0]), "r"(a[1]), "r"(a[2]), "r"(a[3]), "r"(b0), "r"(b1));
}
DEVI uint32_t pack_bf16(float lo, float hi) {
  uint32_t r;
  asm("cvt.rn.bf16x2.f32 %0, %1, %2;" : "=r"(r) : "f"(hi), "f"(lo));
  return r;
}
DEVI uint32_t pack_f16(float lo, float hi) {
  uint32_t r;
  asm("cvt.rn.f16x2.f32 %0, %1, %2;" : "=r"(r) : "f"(hi), "f"(lo));
  return r;
}
DEVI uint32_t ldg16(const __nv_bfloat16* p) {
  uint32_t v;
  asm volatile("ld.global.nc.u16 %0, [%1];" : "=r"(v) : "l"(p));
  return v;
}
DEVI bool elect_one() {
  uint32_t pred;
  asm volatile("{\n.reg .pred p;\nelect.sync _|p, 0xffffffff;\nselp.u32 %0, 1, 0, p;\n}" : "=r"(pred));
  return pred != 0;
}
DEVI float bf_lo(uint32_t v) { return __uint_as_float(v << 16); }
DEVI float bf_hi(uint32_t v) { return __uint_as_float(v & 0xffff0000u); }
DEVI float bf2f(__nv_bfloat16 v) { return __bfloat162float(v); }
DEVI float round_bf16(float v) { return __bfloat162float(__float2bfloat16_rn(v)); }
DEVI float rcp(float x) { float r; asm("rcp.approx.ftz.f32 %0, %1;" : "=f"(r) : "f"(x)); return r; }
DEVI float ex2(float x) { float r; asm("ex2.approx.ftz.f32 %0, %1;" : "=f"(r) : "f"(x)); return r; }

DEVI void wg_fence() { asm volatile("wgmma.fence.sync.aligned;" ::: "memory"); }
DEVI void wg_commit() { asm volatile("wgmma.commit_group.sync.aligned;" ::: "memory"); }
template <int N> DEVI void wg_wait() { asm volatile("wgmma.wait_group.sync.aligned %0;" ::"n"(N) : "memory"); }
constexpr uint32_t DESC_HI = (1u << 30) | (1024 >> 4);
constexpr uint32_t DESC_HI64 = (2u << 30) | (512 >> 4);
DEVI uint32_t mkdesc(uint32_t saddr, uint32_t lbo) { return ((saddr & 0x3FFFF) >> 4) | ((lbo >> 4) << 16); }

#define R8(b) "%" #b
DEVI void wgmma_n192(float (&d)[96], uint32_t da, uint32_t db, int scale_d) {
  asm volatile(
      "{\n.reg .pred p;\n.reg .b64 da, db;\nsetp.ne.b32 p, %98, 0;\nmov.b64 da, {%96, %100};\nmov.b64 db, {%97, %99};\n"
      "wgmma.mma_async.sync.aligned.m64n192k16.f32.bf16.bf16 "
      "{%0,%1,%2,%3,%4,%5,%6,%7,%8,%9,%10,%11,%12,%13,%14,%15,"
      "%16,%17,%18,%19,%20,%21,%22,%23,%24,%25,%26,%27,%28,%29,%30,%31,"
      "%32,%33,%34,%35,%36,%37,%38,%39,%40,%41,%42,%43,%44,%45,%46,%47,"
      "%48,%49,%50,%51,%52,%53,%54,%55,%56,%57,%58,%59,%60,%61,%62,%63,"
      "%64,%65,%66,%67,%68,%69,%70,%71,%72,%73,%74,%75,%76,%77,%78,%79,"
      "%80,%81,%82,%83,%84,%85,%86,%87,%88,%89,%90,%91,%92,%93,%94,%95}, "
      "da, db, p, 1, 1, 0, 1;\n}"
      : "+f"(d[0]), "+f"(d[1]), "+f"(d[2]), "+f"(d[3]), "+f"(d[4]), "+f"(d[5]), "+f"(d[6]), "+f"(d[7]),
        "+f"(d[8]), "+f"(d[9]), "+f"(d[10]), "+f"(d[11]), "+f"(d[12]), "+f"(d[13]), "+f"(d[14]), "+f"(d[15]),
        "+f"(d[16]), "+f"(d[17]), "+f"(d[18]), "+f"(d[19]), "+f"(d[20]), "+f"(d[21]), "+f"(d[22]), "+f"(d[23]),
        "+f"(d[24]), "+f"(d[25]), "+f"(d[26]), "+f"(d[27]), "+f"(d[28]), "+f"(d[29]), "+f"(d[30]), "+f"(d[31]),
        "+f"(d[32]), "+f"(d[33]), "+f"(d[34]), "+f"(d[35]), "+f"(d[36]), "+f"(d[37]), "+f"(d[38]), "+f"(d[39]),
        "+f"(d[40]), "+f"(d[41]), "+f"(d[42]), "+f"(d[43]), "+f"(d[44]), "+f"(d[45]), "+f"(d[46]), "+f"(d[47]),
        "+f"(d[48]), "+f"(d[49]), "+f"(d[50]), "+f"(d[51]), "+f"(d[52]), "+f"(d[53]), "+f"(d[54]), "+f"(d[55]),
        "+f"(d[56]), "+f"(d[57]), "+f"(d[58]), "+f"(d[59]), "+f"(d[60]), "+f"(d[61]), "+f"(d[62]), "+f"(d[63]),
        "+f"(d[64]), "+f"(d[65]), "+f"(d[66]), "+f"(d[67]), "+f"(d[68]), "+f"(d[69]), "+f"(d[70]), "+f"(d[71]),
        "+f"(d[72]), "+f"(d[73]), "+f"(d[74]), "+f"(d[75]), "+f"(d[76]), "+f"(d[77]), "+f"(d[78]), "+f"(d[79]),
        "+f"(d[80]), "+f"(d[81]), "+f"(d[82]), "+f"(d[83]), "+f"(d[84]), "+f"(d[85]), "+f"(d[86]), "+f"(d[87]),
        "+f"(d[88]), "+f"(d[89]), "+f"(d[90]), "+f"(d[91]), "+f"(d[92]), "+f"(d[93]), "+f"(d[94]), "+f"(d[95])
      : "r"(da), "r"(db), "r"(scale_d), "n"(DESC_HI), "n"(DESC_HI64));
}
DEVI void wgmma_n64(float (&d)[32], uint32_t da, uint32_t db, int scale_d) {
  asm volatile(
      "{\n.reg .pred p;\n.reg .b64 da, db;\nsetp.ne.b32 p, %34, 0;\nmov.b64 da, {%32, %35};\nmov.b64 db, {%33, %35};\n"
      "wgmma.mma_async.sync.aligned.m64n64k16.f32.bf16.bf16 "
      "{%0,%1,%2,%3,%4,%5,%6,%7,%8,%9,%10,%11,%12,%13,%14,%15,"
      "%16,%17,%18,%19,%20,%21,%22,%23,%24,%25,%26,%27,%28,%29,%30,%31}, "
      "da, db, p, 1, 1, 0, 1;\n}"
      : "+f"(d[0]), "+f"(d[1]), "+f"(d[2]), "+f"(d[3]), "+f"(d[4]), "+f"(d[5]), "+f"(d[6]), "+f"(d[7]),
        "+f"(d[8]), "+f"(d[9]), "+f"(d[10]), "+f"(d[11]), "+f"(d[12]), "+f"(d[13]), "+f"(d[14]), "+f"(d[15]),
        "+f"(d[16]), "+f"(d[17]), "+f"(d[18]), "+f"(d[19]), "+f"(d[20]), "+f"(d[21]), "+f"(d[22]), "+f"(d[23]),
        "+f"(d[24]), "+f"(d[25]), "+f"(d[26]), "+f"(d[27]), "+f"(d[28]), "+f"(d[29]), "+f"(d[30]), "+f"(d[31])
      : "r"(da), "r"(db), "r"(scale_d), "n"(DESC_HI));
}

struct C32 { float re, im; };
DEVI C32 csq(C32 a) { return {a.re * a.re - a.im * a.im, 2.f * a.re * a.im}; }
DEVI C32 cmul(C32 a, C32 b) { return {a.re * b.re - a.im * b.im, a.re * b.im + a.im * b.re}; }
DEVI C32 cfresh(float zl, float zi, float m) {
  float mag = ex2(zl * m), ph = zi * m;
  return {mag * __cosf(ph), mag * __sinf(ph)};
}
struct HMul { uint32_t b, bp; };
DEVI HMul mk_mul(float re, float im) { return {pack_f16(re, im), pack_f16(-im, re)}; }
DEVI uint32_t hcmul(uint32_t a, const HMul& m) {
  __half2 ah = *reinterpret_cast<__half2*>(&a);
  __half2 b = *reinterpret_cast<const __half2*>(&m.b), bp = *reinterpret_cast<const __half2*>(&m.bp);
  __half2 r = __hfma2(__high2half2(ah), bp, __hmul2(__low2half2(ah), b));
  return *reinterpret_cast<uint32_t*>(&r);
}
DEVI uint32_t badd(uint32_t a, uint32_t b) {
  __nv_bfloat162 r = __hadd2(*reinterpret_cast<__nv_bfloat162*>(&a), *reinterpret_cast<__nv_bfloat162*>(&b));
  return *reinterpret_cast<uint32_t*>(&r);
}
template <int MU0, int NMU, int DMAX>
DEVI void conv_tail(float (&acc)[16][4], uint32_t p_lane, uint32_t v_base, int back, bool edge, int lane) {
  const int hsel = (lane >> 3) & 1;
  const int row = (lane & 7) + ((lane >> 4) << 3) + PADV - 8 - (back & (hsel ^ 1));
  const uint32_t la = v_base + row * 32 + (((hsel ^ back) ^ ((row >> 2) & 1)) << 4);
  uint32_t M[3][4];
  ldsm_x4_t(M[0], la);
  ldsm_x4_t(M[1], la + 256);
  uint32_t H[2 * NMU];
#pragma unroll
  for (int i = 0; i < 2 * NMU; ++i) H[i ^ 1] = lds32(p_lane + (uint32_t)(MU0 - 1 + i) * 32);
  if (edge) {
    const uint32_t a[4] = {0u, 0u, M[0][0], M[0][1]};
#pragma unroll
    for (int k = 1; k < NMU; ++k) mma_bf16v(acc[MU0 - 2 + 2 * k], a, H[2 * k], H[2 * k + 1]);
  }
#pragma unroll
  for (int delta = -1; delta <= DMAX; ++delta) {
    if (delta + 2 <= DMAX) ldsm_x4_t(M[(delta + 3) % 3], la + (delta + 3) * 256);
#pragma unroll
    for (int k = 0; k < NMU; ++k)
      if (delta + MU0 + 2 * k < 16) mma_bf16v(acc[delta + MU0 + 2 * k], M[(delta + 1) % 3], H[2 * k], H[2 * k + 1]);
  }
}

__global__ void __cluster_dims__(2, 1, 1) __launch_bounds__(NTHREADS, 1)
fused_kernel(const __grid_constant__ Maps maps, const Ptrs p) {
  extern __shared__ __align__(1024) uint8_t smem[];
  const uint32_t sb = s2u(smem);
  const int tid = threadIdx.x, lane = tid & 31;
  const int warp = __shfl_sync(0xffffffffu, tid >> 5, 0);
  const int cta = blockIdx.x;
  const uint32_t rank = cta & 1;
  const int ti = 2 * (cta >> 4) + rank;
  const int tj = (cta >> 1) & 7;
  const uint32_t bars = sb + SM_BAR;
#define BAR(i) (bars + 8 * (i))
  const int g = lane >> 2, q = lane & 3;

  const int kch = warp & 3, krd = warp >> 2;
  float zr, zi, wr, wi;
  {
    const size_t po = (size_t)(cta * 4 + kch) * 128 + krd * 32 + lane;
    const uint32_t r_ar = ldg16(p.A_re + po), r_ai = ldg16(p.A_im + po), r_br = ldg16(p.B_re + po), r_bi = ldg16(p.B_im + po);
    const uint32_t r_cr = ldg16(p.C_re + po), r_ci = ldg16(p.C_im + po), r_ldt = ldg16(p.log_dt + cta * 4 + kch);
    uint4 pt;
    if (tid < 128) pt = __ldg((const uint4*)g_ptab.v + tid);
    if (tid == 384) {
      TS(0);
#pragma unroll
      for (int i = 0; i < B_COUNT; ++i) mbar_init(BAR(i), bar_count(i));
      asm volatile("fence.mbarrier_init.release.cluster;" ::: "memory");
      prefetch_tmap(&maps.x); prefetch_tmap(&maps.w); prefetch_tmap(&maps.u);
    }
    __syncthreads();
    cluster_arrive();
    if (warp >= 12) {
      cluster_wait();
      if (elect_one()) {
        if (warp == 13) {
          mbar_expect_tx(BAR(B_TILE), 16384);
          tma_load_2d(sb + SM_U, &maps.u, tj * 64, ti * 128, BAR(B_TILE));
          l2_prefetch((const char*)p.wqkv + 224 * 3072 + cta * 6912, 6912);
          l2_prefetch((const char*)p.x + (size_t)cta * 16384, 16384);
          l2_prefetch((const char*)p.wo + (size_t)cta * 4096, 4096);
        } else {
          if (warp == 12) TS(61);
#pragma unroll 1
          for (int ks = warp == 12 ? 0 : warp - 13; ks < NSTG; ks += 3) {
            const uint32_t st = sb + ks * STG_BYTES, fb = BAR(B_FULL + ks);
            mbar_expect_tx(fb, STG_BYTES);
            tma_load_2d(st + STG_X, &maps.x, ks * 32, ti * 128, fb);
            tma_load_3d_mc(st + STG_W + rank * 6144, &maps.w, tj * 64, ks * 32 + rank * 16, 0, fb, 3);
          }
        }
      }
      __syncwarp();
    }
    if (tid < 128) sts128(sb + SM_PTAB + tid * 16, pt.x, pt.y, pt.z, pt.w);
    const float dt = round_bf16(expf(bf_lo(r_ldt)));
    zr = dt * bf_lo(r_ar); zi = dt * bf_lo(r_ai);
    const float dbr = dt * bf_lo(r_br), dbi = dt * bf_lo(r_bi), cr = bf_lo(r_cr), ci = bf_lo(r_ci);
    wr = cr * dbr - ci * dbi; wi = cr * dbi + ci * dbr;
  }
  {
    const float mz = __uint_as_float(__reduce_max_sync(0xffffffffu, __float_as_uint(fmaxf(zr, 0.f))));
    const int E = min(max((int)(__reduce_max_sync(0xffffffffu, __float_as_uint(fmaxf(fabsf(wr), fabsf(wi)))) >> 23), 1), 252);
    const float sc = __int_as_float((253 - E) << 23), inv = __int_as_float((E + 1) << 23);
    const float zl = (zr - mz) * 1.4426950408889634f;
    const uint32_t tb = sb + SM_VV + kch * VV_BYTES + krd * KG_BYTES;
    const uint32_t sta = tb + (((lane >> 2) << 4) | ((lane & 3) << 2));
    auto put = [&](int r, uint32_t v) { sts32((sta ^ ((r & 7) << 4)) + r * 128, v); };
    const uint32_t lda = tb + ((lane & 7) + (((lane >> 3) & 1) << 3)) * 128;
    const uint32_t ldb = tb + ((lane & 7) + ((lane >> 4) << 3)) * 128;
    C32 e1 = cfresh(zl, zi, 1.f), e2 = csq(e1), e4 = csq(e2), e8 = csq(e4);
    C32 e16 = cfresh(zl, zi, 16.f), e32 = csq(e16), e64 = csq(e32), e128 = csq(e64);
    C32 e256 = cfresh(zl, zi, 256.f), e512 = csq(e256), e1024 = csq(e512), e768 = cmul(e512, e256);
    uint32_t XA[2][4][4];
    {
      const HMul m16 = mk_mul(e16.re, e16.im), m32 = mk_mul(e32.re, e32.im), m64 = mk_mul(e64.re, e64.im);
      const HMul m128 = mk_mul(e128.re, e128.im);
      uint32_t X[16];
      X[0] = 0x00003c00u; X[1] = pack_f16(e8.re, e8.im); X[2] = m16.b; X[4] = m32.b; X[8] = m64.b;
      X[3] = hcmul(X[1], m16); X[5] = hcmul(X[1], m32); X[6] = hcmul(X[2], m32); X[7] = hcmul(X[3], m32);
#pragma unroll
      for (int r = 1; r < 8; ++r) X[8 + r] = hcmul(X[r], m64);
#pragma unroll
      for (int h = 0; h < 2; ++h) {
#pragma unroll
        for (int r = 0; r < 16; ++r) put(r, h == 0 ? X[r] : r == 0 ? m128.b : hcmul(X[r], m128));
        __syncwarp();
#pragma unroll
        for (int k = 0; k < 4; ++k) ldsm_x4(XA[h][k], lda + (((2 * k + (lane >> 4)) ^ (lane & 7)) << 4));
        __syncwarp();
      }
    }
    float D[2][3][4];
#pragma unroll
    for (int t = 0; t < 6; ++t) D[t / 3][t % 3][0] = D[t / 3][t % 3][1] = D[t / 3][t % 3][2] = D[t / 3][t % 3][3] = 0.f;
    auto contract = [&](int t0, int nt) {
      __syncwarp();
#pragma unroll
      for (int k = 0; k < 4; ++k) {
        uint32_t b[4];
        ldsm_x4(b, ldb + (((2 * k + ((lane >> 3) & 1)) ^ (lane & 7)) << 4));
#pragma unroll
        for (int h = 0; h < 2; ++h) {
          mma_f16(D[h][t0], XA[h][k], b[0], b[1]);
          if (nt == 2) mma_f16(D[h][t0 + 1], XA[h][k], b[2], b[3]);
        }
      }
      __syncwarp();
    };
    const HMul c1 = mk_mul(e1.re, -e1.im), c2 = mk_mul(e2.re, -e2.im), c4 = mk_mul(e4.re, -e4.im);
    const HMul c256 = mk_mul(e256.re, -e256.im), c512 = mk_mul(e512.re, -e512.im), c768 = mk_mul(e768.re, -e768.im);
    const HMul c1024 = mk_mul(e1024.re, -e1024.im);
    uint32_t W[8];
    W[0] = pack_f16(wr * sc, -wi * sc);
    W[1] = hcmul(W[0], c1); W[2] = hcmul(W[0], c2); W[3] = hcmul(W[1], c2);
    W[4] = hcmul(W[0], c4); W[5] = hcmul(W[1], c4); W[6] = hcmul(W[2], c4); W[7] = hcmul(W[3], c4);
#pragma unroll
    for (int i = 0; i < 8; ++i) put(i, W[i]);
#pragma unroll
    for (int i = 0; i < 4; ++i) put(8 + i, hcmul(W[2 * i], c256));
    put(12, hcmul(W[0], c512)); put(13, hcmul(W[4], c512)); put(14, hcmul(W[0], c768)); put(15, hcmul(W[4], c768));
    contract(0, 2);
    const uint32_t v0 = hcmul(W[0], c1024);
    put(0, v0); put(1, hcmul(v0, c256)); put(2, hcmul(v0, c512)); put(3, hcmul(v0, c768)); put(4, hcmul(v0, c1024));
    contract(2, 1);
    const uint32_t a = tb + (g * 24 + 2 * q) * 4;
#pragma unroll
    for (int t = 0; t < 6; ++t) {
      const float(&d)[4] = D[t / 3][t % 3];
      sts_f32x2(a + (t / 3) * 1536 + (t % 3) * 32, d[0] * inv, d[1] * inv);
      sts_f32x2(a + (t / 3) * 1536 + (t % 3) * 32 + 768, d[2] * inv, d[3] * inv);
    }
    if (mz > 0.f) {
      __syncwarp();
#pragma unroll 1
      for (int i = lane; i < 768; i += 32) {
        const int r = i / 24, y = i - 24 * r;
        sts_f32(tb + i * 4, lds_f32(tb + i * 4) * ex2(mz * 1.4426950408889634f * (koff(y) + 8 * r)));
      }
    }
  }
  if (tid == 0) TS(2);
  if (warp < 12) cluster_wait();
  __syncthreads();

  if (warp < 4) {
    asm volatile("setmaxnreg.inc.sync.aligned.u32 152;");
    const unsigned epoch = __ldcg(&g_epoch);
    const int d = cta * 4 + warp;
    const uint32_t vv = sb + SM_VV + warp * VV_BYTES;
    const uint32_t ub = sb + SM_U + warp * U_BYTES;
    const uint32_t pb = sb + SM_P + warp * P_BYTES;
    const float dskip = bf2f(p.Dskip[d]);
#pragma unroll 1
    for (int pass = 0; pass < 2; ++pass) {
      if (pass == 1) {
        const uint32_t kf = vv;
#pragma unroll 2
        for (int i = 0; i < 6; ++i) {
          const uint32_t a = kf + (i * 32 + lane) * 16;
          const uint4 x0 = lds128(a), x1 = lds128(a + KG_BYTES), x2 = lds128(a + 2 * KG_BYTES), x3 = lds128(a + 3 * KG_BYTES);
          auto s4 = [](uint32_t a0, uint32_t a1, uint32_t a2, uint32_t a3) {
            return __float_as_uint((__uint_as_float(a0) + __uint_as_float(a1)) + (__uint_as_float(a2) + __uint_as_float(a3)));
          };
          sts128(a, s4(x0.x, x1.x, x2.x, x3.x), s4(x0.y, x1.y, x2.y, x3.y), s4(x0.z, x1.z, x2.z, x3.z), s4(x0.w, x1.w, x2.w, x3.w));
        }
        __syncwarp();
        const float k1024 = lds_f32(kf + kidx_c(1024) * 4);
        if (lane == 0) {
          sts_f32(kf + SL_ZERO * 4, 0.f);
          sts_f32(kf + SL_510 * 4, lds_f32(kf + kidx_c(510) * 4) - lds_f32(kf + kidx_c(512) * 4));
          sts_f32(kf + SL_0 * 4, lds_f32(kf) + dskip);
        }
        __syncwarp();
        mbar_wait(BAR(B_PFREE), 0);
        {
          float prev = 0.f;
#pragma unroll 1
          for (int i0 = 0; i0 < 16; i0 += 4) {
            uint32_t e[4];
            float a[4], b[4];
#pragma unroll
            for (int i = 0; i < 4; ++i) e[i] = lds32(sb + SM_PTAB + ((i0 + i) * 32 + lane) * 4);
#pragma unroll
            for (int i = 0; i < 4; ++i) { a[i] = lds_f32(kf + (e[i] & 0xffff)); b[i] = lds_f32(kf + (e[i] >> 16)); }
#pragma unroll
            for (int i = 0; i < 4; ++i) {
              const uint32_t w = pb + (31 * lane + 2 * (i0 + i)) * 4;
              if (i0 + i > 0) sts32(w - 4, pack_bf16(a[i], prev));
              sts32(w, pack_bf16(b[i], a[i]));
              prev = b[i];
            }
          }
        }
        __syncwarp();
        bar_arrive(7, 384);
        if (lane == 0) TS(4);
        const int gq = g - 2 * q;
        uint32_t h127, h128;
        {
          const uint32_t kf2 = pack_bf16(k1024, k1024) ^ 0x80008000u;
          h127 = (gq == 4 ? 0x0000ffffu : gq == 5 ? 0xffffffffu : gq == 6 ? 0xffff0000u : 0u) & kf2;
          h128 = (gq == -4 ? 0x0000ffffu : gq == -3 ? 0xffffffffu : gq == -2 ? 0xffff0000u : 0u) & kf2;
        }
        bar_sync(4, 384);
        mbar_wait(BAR(B_UCH + warp), 0);
        if (lane == 0) TS(7);
        float acc[16][4];
#pragma unroll
        for (int i = 0; i < 16; ++i) { acc[i][0] = acc[i][1] = acc[i][2] = acc[i][3] = 0.f; }
        {
          const uint32_t pd_lane = pb + (PD_OFF + 16 + gq) * 4;
          const int prow0 = 8 + (lane & 7) + ((lane >> 4) << 3), hs = (lane >> 3) & 1;
          uint32_t B[2][4][4];
          uint32_t A[4][4];
          const uint32_t la0 = ub + prow0 * 32 + ((hs ^ ((prow0 >> 2) & 1)) << 4);
#pragma unroll
          for (int m2 = 0; m2 < 4; ++m2) ldsm_x4(B[0][m2], la0 + m2 * 512);
#pragma unroll
          for (int i = 0; i < 4; ++i) {
            const uint32_t a = pd_lane + i * 512;
            A[i][0] = lds32(a); A[i][1] = lds32(a + 32); A[i][2] = lds32(a - 32); A[i][3] = A[i][0];
          }
          uint32_t la = la0;
#pragma unroll 1
          for (int rho = 0; rho < 8; ++rho) {
#pragma unroll
            for (int m2 = 0; m2 < 4; ++m2) ldsm_x4(B[1][m2], la + (4 + m2) * 512);
#pragma unroll
            for (int i = 0; i < 4; ++i)
#pragma unroll
              for (int m = 0; m < 8; ++m) mma_bf16v(acc[m + i], A[i], B[0][m >> 1][2 * (m & 1)], B[0][m >> 1][2 * (m & 1) + 1]);
            const int prow = prow0 - min(rho + 1, 7);
            la = ub + prow * 32 + ((hs ^ ((prow >> 2) & 1)) << 4);
#pragma unroll
            for (int m2 = 0; m2 < 4; ++m2) ldsm_x4(B[0][m2], la + m2 * 512);
            const uint32_t pa = pd_lane + (rho + 1) * 64;
#pragma unroll
            for (int i = 0; i < 4; ++i) {
#pragma unroll
              for (int m = 0; m < 8 - i; ++m)
                mma_bf16v(acc[8 + m + i], A[i], B[1][m >> 1][2 * (m & 1)], B[1][m >> 1][2 * (m & 1) + 1]);
              A[i][0] = lds32(pa + i * 512); A[i][1] = lds32(pa + i * 512 + 32); A[i][2] = lds32(pa + i * 512 - 32);
              A[i][3] = A[i][0];
            }
          }
          {
            uint32_t b8[4];
            ldsm_x4(b8, la + 4 * 512);
            const uint32_t h63 = lds32(pd_lane + 63 * 32), h64 = lds32(pd_lane + 64 * 32);
            const uint32_t a63[4] = {0u, h127, 0u, 0u}, a32[4] = {h64, 0u, h63, h64}, a64[4] = {h128, 0u, h127, h128};
#pragma unroll
            for (int m2 = 0; m2 < 4; ++m2) ldsm_x4(B[1][m2], la0 + m2 * 512);
#pragma unroll
            for (int m = 0; m < 8; ++m) mma_bf16v(acc[m + 7], a63, B[0][m >> 1][2 * (m & 1)], B[0][m >> 1][2 * (m & 1) + 1]);
#pragma unroll
            for (int m2 = 0; m2 < 2; ++m2) ldsm_x4(B[0][m2], la0 + (4 + m2) * 512);
#pragma unroll
            for (int m = 0; m < 8; ++m) mma_bf16v(acc[m + 4], a32, B[1][m >> 1][2 * (m & 1)], B[1][m >> 1][2 * (m & 1) + 1]);
            mma_bf16v(acc[15], a63, b8[0], b8[1]);
#pragma unroll
            for (int m = 0; m < 8; ++m) mma_bf16v(acc[m + 8], a64, B[1][m >> 1][2 * (m & 1)], B[1][m >> 1][2 * (m & 1) + 1]);
#pragma unroll
            for (int m = 0; m < 4; ++m) mma_bf16v(acc[m + 12], a32, B[0][m >> 1][2 * (m & 1)], B[0][m >> 1][2 * (m & 1) + 1]);
          }
          bar_sync(5, 384);
#pragma unroll 1
          for (int v = 0; v < 4; ++v)
            conv_tail<4, 3, 11>(acc, pb + (P2_OFF + 56 * v + gq - 16) * 4, vv + ((v & 1) ? VV_U3 : VV_U5), v >> 1, v == 0, lane);
#pragma unroll 1
          for (int pi = 0; pi < 2; ++pi)
            conv_tail<8, 5, 7>(acc, pb + (P3_OFF + 88 * pi + gq - 48) * 4, vv + (pi ? VV_U7 : VV_U9), pi, pi == 0, lane);
        }
        if (lane == 0) TS(8);
        __syncwarp();
        {
          const int mt = lane >> 3;
          const uint32_t a = pb + (128 * (mt >> 1) + 16 * (lane & 7) + 8 * (mt & 1)) * 2;
#pragma unroll
          for (int ab = 0; ab < 16; ab += 2)
            stsm_x4_t(a + ab * 256, pack_bf16(acc[ab][0], acc[ab][1]), pack_bf16(acc[ab][2], acc[ab][3]),
                      pack_bf16(acc[ab + 1][0], acc[ab + 1][1]), pack_bf16(acc[ab + 1][2], acc[ab + 1][3]));
        }
        fence_async_smem();
        __syncwarp();
        if (lane == 0) mbar_arrive(BAR(B_CONVD));
        bar_arrive(3, 384);
        if (elect_one()) {
          bulk_store(p.yT + (size_t)d * 2048, pb, 4096);
          bulk_commit();
          bulk_wait0();
          red_relaxed_add(&g_cnt[(C_Y + (cta >> 4)) * 32], 1);
          TS(9);
        }
        bar_sync(2, 128);
        if (warp == 0 && elect_one()) {
          wait_counter(&g_cnt[(C_Y + tj) * 32], (epoch + 1) * 64);
          TS(28);
          mbar_expect_tx(BAR(B_TILE), 16384);
          tma_load_2d(sb + SM_U, &maps.yT, ti * 128, tj * 64, BAR(B_TILE));
          tma_load_2d(sb + SM_U + 8192, &maps.yT, ti * 128 + 64, tj * 64, BAR(B_TILE));
        }
        __syncwarp();
      }
      mbar_wait(BAR(B_TILE), pass);
      if (lane == 0) TS(26 + 3 * pass);
      {
        const int m = lane >> 3, r = lane & 7;
#pragma unroll 2
        for (int it = 0; it < 8; ++it) {
          const int tb = warp * 4 + (it >> 1), cb = (it & 1) * 4 + m;
          const uint32_t at = (tb * 8 + r) * 128 + ((cb ^ r) << 4);
          const uint32_t ac = (tb >> 3) * 8192 + (cb * 8 + r) * 128 + (((tb & 7) ^ (pass ? 0 : tb >> 3) ^ r) << 4);
          uint32_t v[4];
          ldsm_x4_t(v, sb + SM_U + (pass ? ac : at));
          stsm_x4(sb + SM_P + (pass ? at : ac), v[0], v[1], v[2], v[3]);
        }
      }
      fence_async_smem();
      if (pass == 0) {
        bar_arrive(6, 160);
      } else {
        bar_sync(2, 128);
        if (warp == 0 && elect_one()) {
          tma_store_2d(&maps.out, sb + SM_P, 64 * tj, 128 * ti);
          bulk_commit();
          bulk_wait_read0();
          TS(30);
        }
      }
    }
  } else if (warp < 12) {
    asm volatile("setmaxnreg.inc.sync.aligned.u32 160;");
    const int w8 = warp - 4;
    const int row = w8 * 16 + (lane & 7) + (((lane >> 3) & 1) << 3);
    {
      float acc[96];
#pragma unroll 1
      for (int ks = 0, s = 0, ph = 0; ks < 16; ++ks) {
        mbar_wait(BAR(B_FULL + s), ph);
        if (tid == 128 && !(ks & 1)) TSR(16, ks == 0 ? 16 : 9 + (ks >> 1) + (ks > 12 ? 46 : 0));
        const uint32_t st = sb + s * STG_BYTES;
        const uint32_t da = mkdesc(st + STG_X + (w8 >> 2) * 4096, 16);
        const uint32_t db = mkdesc(st + STG_W, 2048);
        wg_fence();
        wgmma_n192(acc, da, db, ks != 0);
        wgmma_n192(acc, da + 2, db + 384, 1);
        wg_commit();
        const uint32_t eprev = BAR(B_EMPTY + (s == 0 ? NSTG - 1 : s - 1));
        if (++s == NSTG) { s = 0; ph ^= 1; }
        if (ks > 0) {
          wg_wait<1>();
          if (lane < 2) mbar_arrive_cluster(eprev, lane);
        }
      }
      wg_wait<0>();
      bar_arrive(4, 384);
      if (tid == 128) TS(17);
      bar_sync(1, 256);
#pragma unroll
      for (int i = 0; i < 24; i += 2)
        stsm_x4(sb + SM_QS + row * 128 + (i >> 3) * 16384 + ((((i & 7) + (lane >> 4)) ^ (row & 7)) << 4),
                pack_bf16(acc[4 * i], acc[4 * i + 1]), pack_bf16(acc[4 * i + 2], acc[4 * i + 3]),
                pack_bf16(acc[4 * i + 4], acc[4 * i + 5]), pack_bf16(acc[4 * i + 6], acc[4 * i + 7]));
    }
    __syncwarp();
#pragma unroll 1
    for (int part = 1; part >= 0; --part) {
      const uint32_t pa = sb + SM_QS + part * 16384 + w8 * 2048 + lane * 16;
#pragma unroll 1
      for (int it = 0; it < 4; ++it) {
        uint4 t = lds128(pa + it * 512);
        uint32_t* tw = &t.x;
#pragma unroll
        for (int j = 0; j < 4; ++j) {
          const uint32_t x = tw[j];
          const __nv_bfloat162 xb = *reinterpret_cast<const __nv_bfloat162*>(&x);
          const uint32_t e = pack_bf16(ex2(bf_lo(x) * 1.4426950408889634f), ex2(bf_hi(x) * 1.4426950408889634f));
          const uint32_t m = __hgt2_mask(xb, __floats2bfloat162_rn(0.f, 0.f));
          const uint32_t sel = (badd(x, 0x3f803f80u) & m) | (e & ~m);
          tw[j] = pack_bf16(bf_lo(sel) + 1e-6f, bf_hi(sel) + 1e-6f);
        }
        sts128(pa + it * 512, t.x, t.y, t.z, t.w);
      }
      if (part == 1) {
        if (tid == 128) TS(53);
        bar_sync(1, 256);
        const int hh = w8 >> 1, dtile = w8 & 1;
        float kv[4] = {0.f, 0.f, 0.f, 0.f}, zz[4] = {0.f, 0.f, 0.f, 0.f};
        const int m = lane >> 3;
        const uint32_t aa = sb + SM_VS + ((lane & 7) + ((m >> 1) << 3)) * 128 + (((2 * hh + (m & 1)) ^ (lane & 7)) << 4);
        const uint32_t ab = sb + SM_PK + (lane & 15) * 128 + (((2 * hh + dtile) ^ (lane & 7)) << 4);
#pragma unroll 2
        for (int ks = 0; ks < 8; ++ks) {
          uint32_t a[4], b0, b1;
          ldsm_x4_t(a, aa + ks * 2048);
          ldsm_x2_t(b0, b1, ab + ks * 2048);
          mma_bf16(kv, a[0], a[1], a[2], a[3], b0, b1);
          mma_bf16(zz, 0x3f803f80u, 0x3f803f80u, 0x3f803f80u, 0x3f803f80u, b0, b1);
        }
        const uint32_t kp = sb + SM_KV + hh * 1088;
        sts128(kp + dtile * 512 + lane * 16, __float_as_uint(kv[0]), __float_as_uint(kv[1]), __float_as_uint(kv[2]),
               __float_as_uint(kv[3]));
        if (g == 0) sts_f32x2(kp + 1024 + dtile * 32 + q * 8, zz[0], zz[1]);
        fence_async_smem();
        __syncwarp();
        if (lane == 0) mbar_arrive(BAR(B_KVP));
        if (tid == 128) TS(55);
      }
    }
    if (tid == 128) TS(56);
    {
      const int ch = w8 >> 1;
      bar_sync(7, 384);
      mbar_wait(BAR(B_UCH + ch), 0);
#pragma unroll 1
      for (int it = w8 & 1; it < 8; it += 2) {
          const int k = -18 + it * 32 + lane;
          const int kr = min(max(k, -2), 208);
          uint32_t E[12];
#pragma unroll
          for (int c = 0; c < 3; ++c) {
            const int kk = kr - 1 + c, r = (kk >> 1) + 8;
            const uint4 t = lds128(sb + SM_U + ch * U_BYTES + r * 32 + (((kk & 1) ^ ((r >> 2) & 1)) << 4));
            E[4 * c] = t.x; E[4 * c + 1] = t.y; E[4 * c + 2] = t.z; E[4 * c + 3] = t.w;
          }
          uint32_t O[8];
#pragma unroll
          for (int j = 0; j < 8; ++j) O[j] = __byte_perm(E[j + 1], E[j + 2], 0x5432);
          uint32_t s3[6], s5[4], s7[4], s9[4];
#pragma unroll
          for (int j = 0; j < 6; ++j) s3[j] = badd(badd(O[j], O[j + 1]), E[j + 2]);
#pragma unroll
          for (int j = 0; j < 4; ++j) {
            s5[j] = badd(s3[j + 2], badd(E[j + 3], E[j + 5]));
            s7[j] = badd(s5[j], badd(O[j + 1], O[j + 4]));
            s9[j] = badd(s7[j], badd(E[j + 2], E[j + 6]));
          }
          const int r = (k >> 1) + PADV;
          const uint32_t a = sb + SM_VV + ch * VV_BYTES + r * 32 + (((k & 1) ^ ((r >> 2) & 1)) << 4);
          if (k < 208) { sts128(a + VV_U3, s3[0], s3[1], s3[2], s3[3]); sts128(a + VV_U5, s5[0], s5[1], s5[2], s5[3]); }
          if (k < 144) { sts128(a + VV_U7, s7[0], s7[1], s7[2], s7[3]); sts128(a + VV_U9, s9[0], s9[1], s9[2], s9[3]); }
      }
      bar_arrive(5, 384);
    }
    if (tid == 128) TS(6);
    mbar_wait(BAR(B_KVF), 0);
    if (tid == 128) TS(19);
#pragma unroll 1
    for (int h = 0; h < 4; ++h) {
      uint32_t a[4];
      const uint32_t qa = sb + SM_QS + row * 128 + (((2 * h + (lane >> 4)) ^ (row & 7)) << 4);
      ldsm_x4(a, qa);
      const uint32_t kp = sb + SM_KV + h * 1088;
      const uint4 k0 = lds128(kp + lane * 16), k1 = lds128(kp + 512 + lane * 16);
      const uint32_t za = kp + 1024 + q * 8;
      auto pk2 = [](uint32_t x, uint32_t y) { return pack_bf16(__uint_as_float(x), __uint_as_float(y)); };
      float n0[4] = {0.f, 0.f, 0.f, 0.f}, n1[4] = {0.f, 0.f, 0.f, 0.f}, dn[4] = {0.f, 0.f, 0.f, 0.f};
      mma_bf16(n0, a[0], a[1], a[2], a[3], pk2(k0.x, k0.y), pk2(k1.x, k1.y));
      mma_bf16(n1, a[0], a[1], a[2], a[3], pk2(k0.z, k0.w), pk2(k1.z, k1.w));
      mma_bf16(dn, a[0], a[1], a[2], a[3], pack_bf16(lds_f32(za), lds_f32(za + 4)), pack_bf16(lds_f32(za + 32), lds_f32(za + 36)));
      const uint32_t dd = pack_bf16(dn[0], dn[2]);
      const uint32_t d2 = pack_bf16(bf_lo(dd) + 1e-6f, bf_hi(dd) + 1e-6f);
      const float r0 = rcp(bf_lo(d2)), r1 = rcp(bf_hi(d2));
      const uint32_t x0 = pack_bf16(n0[0], n0[1]), x1 = pack_bf16(n0[2], n0[3]);
      const uint32_t x2 = pack_bf16(n1[0], n1[1]), x3 = pack_bf16(n1[2], n1[3]);
      stsm_x4(qa, pack_bf16(bf_lo(x0) * r0, bf_hi(x0) * r0), pack_bf16(bf_lo(x1) * r1, bf_hi(x1) * r1),
              pack_bf16(bf_lo(x2) * r0, bf_hi(x2) * r0), pack_bf16(bf_lo(x3) * r1, bf_hi(x3) * r1));
    }
    fence_async_smem();
    __syncwarp();
    if (lane == 0) mbar_arrive(BAR(B_OST));
    if (tid == 128) TS(57);
    mbar_wait(BAR(B_WO), 0);
    bar_sync(3, 384);
    {
      float o[32];
#pragma unroll 1
      for (int c = 0; c < 8; ++c) {
        mbar_wait(BAR(B_RF + c), 0);
        if (tid == 128) TSR(22, c == 0 ? 22 : 43 + c);
        const uint32_t slot = c < 4 ? SM_QS + c * 16384 : c < 7 ? SM_VV + (c - 4) * 16384 : SM_QS;
        const uint32_t da = mkdesc(sb + slot + (w8 >> 2) * 8192, 16);
        const uint32_t db = mkdesc(sb + SM_WO + c * 8192, 8192);
        wg_fence();
#pragma unroll
        for (int k = 0; k < 4; ++k) wgmma_n64(o, da + 2 * k, db + 128 * k, (c | k) != 0);
        wg_commit();
        if (c == 1) {
          wg_wait<1>();
          if (lane == 0) mbar_arrive(BAR(B_RE));
        }
      }
      wg_wait<0>();
      if (tid == 128) TS(51);
      bar_sync(1, 256);
#pragma unroll
      for (int i = 0; i < 8; i += 2)
        stsm_x4(sb + SM_BOUT + row * 128 + (((i + (lane >> 4)) ^ (row & 7)) << 4), pack_bf16(o[4 * i], o[4 * i + 1]),
                pack_bf16(o[4 * i + 2], o[4 * i + 3]), pack_bf16(o[4 * i + 4], o[4 * i + 5]), pack_bf16(o[4 * i + 6], o[4 * i + 7]));
      fence_async_smem();
      bar_sync(1, 256);
      if (tid == 128) TS(52);
      if (warp == 4 && elect_one()) {
        tma_store_2d(&maps.out, sb + SM_BOUT, 512 + 64 * tj, 128 * ti);
        bulk_commit();
        bulk_wait_read0();
        TS(23);
      }
    }
  } else {
    asm volatile("setmaxnreg.dec.sync.aligned.u32 40;");
    if (warp == 12) {
      if (elect_one()) {
        const unsigned epoch = __ldcg(&g_epoch);
#pragma unroll 1
        for (int ks = NSTG, s = 0, ph = 0; ks < 16; ++ks) {
          mbar_wait(BAR(B_EMPTY + s), ph);
          TSR(38, 31 + ks);
          const uint32_t st = sb + s * STG_BYTES, fb = BAR(B_FULL + s);
          mbar_expect_tx(fb, STG_BYTES);
          tma_load_2d(st + STG_X, &maps.x, ks * 32, ti * 128, fb);
          tma_load_3d_mc(st + STG_W + rank * 6144, &maps.w, tj * 64, ks * 32 + rank * 16, 0, fb, 3);
          if (++s == NSTG) { s = 0; ph ^= 1; }
        }
        prefetch_tmap(&maps.wo); prefetch_tmap(&maps.o); prefetch_tmap(&maps.out);
        mbar_wait(BAR(B_EMPTY + 3), 1);
        mbar_wait(BAR(B_EMPTY + 6), 1);
        mbar_expect_tx(BAR(B_WO), 65536);
        tma_load_2d_mc(sb + SM_WO + rank * 32768, &maps.wo, tj * 64, rank * 256, BAR(B_WO), 3);
        float* kvg = &g_kv[epoch & 1][tj][0];
        mbar_wait(BAR(B_KVP), 0);
        bulk_reduce_add_f32(kvg, sb + SM_KV, 4352);
        bulk_commit();
        bulk_wait0();
        red_relaxed_add(&g_cnt[(C_KV + tj) * 32], 1);
        TS(18);
        wait_counter(&g_cnt[(C_KV + tj) * 32], (epoch + 1) * 16);
        mbar_expect_tx(BAR(B_KVF), 4352);
        bulk_load(sb + SM_KV, kvg, 4352, BAR(B_KVF));
        mbar_wait(BAR(B_OST), 0);
        tma_store_2d(&maps.o, sb + SM_QS, tj * 64, ti * 128);
        bulk_commit();
        bulk_wait0();
        red_relaxed_add(&g_cnt[(C_O + ti) * 32], 1);
        TS(20);
        wait_counter(&g_cnt[(C_O + ti) * 32], (epoch + 1) * 8);
        if (cta == 0) g_epoch = epoch + 1;
        TS(21);
#pragma unroll 1
        for (int c = 0; c < 8; ++c) {
          if (c == 4) mbar_wait(BAR(B_CONVD), 0);
          if (c == 7) mbar_wait(BAR(B_RE), 0);
          const uint32_t slot = c < 4 ? SM_QS + c * 16384 : c < 7 ? SM_VV + (c - 4) * 16384 : SM_QS;
          mbar_expect_tx(BAR(B_RF + c), 16384);
          tma_load_2d(sb + slot, &maps.o, c * 64, ti * 128, BAR(B_RF + c));
        }
      }
    } else if (warp == 13) {
      bar_sync(6, 160);
      sts128(sb + SM_U + (lane >> 4) * U_BYTES + (lane & 15) * 16, 0, 0, 0, 0);
      sts128(sb + SM_U + (2 + (lane >> 4)) * U_BYTES + (lane & 15) * 16, 0, 0, 0, 0);
      __syncwarp();
      if (elect_one()) {
        const unsigned epoch = __ldcg(&g_epoch);
        tma_store_2d(&maps.uT, sb + SM_P, ti * 128, tj * 64);
        tma_store_2d(&maps.uT, sb + SM_P + 8192, ti * 128 + 64, tj * 64);
        bulk_commit();
        bulk_wait_read0();
        mbar_arrive(BAR(B_PFREE));
        bulk_wait0();
        red_relaxed_add(&g_cnt[(C_U + tj) * 32], 1);
        TS(27);
        wait_counter(&g_cnt[(C_U + (cta >> 4)) * 32], (epoch + 1) * 16);
#pragma unroll 1
        for (int c = 0; c < 4; ++c) {
          mbar_expect_tx(BAR(B_UCH + c), 4096);
          bulk_load(sb + SM_U + c * U_BYTES + 256, p.uT + (size_t)(cta * 4 + c) * 2048, 4096, BAR(B_UCH + c));
        }
        TS(3);
      }
      __syncwarp();
      if (ti == 0) {
        float4* z = (float4*)&g_kv[(__ldcg(&g_epoch) & 1) ^ 1][tj][0];
#pragma unroll 1
        for (int i = lane; i < 272; i += 32) z[i] = make_float4(0.f, 0.f, 0.f, 0.f);
      }
    }
  }
  __syncwarp();
  cluster_arrive();
  cluster_wait();
  if (tid == 0) TS(31);
#undef BAR
}

typedef CUresult (*EncodeFn)(CUtensorMap*, CUtensorMapDataType, cuuint32_t, void*, const cuuint64_t*, const cuuint64_t*,
                             const cuuint32_t*, const cuuint32_t*, CUtensorMapInterleave, CUtensorMapSwizzle,
                             CUtensorMapL2promotion, CUtensorMapFloatOOBfill);

static void make_map(EncodeFn enc, CUtensorMap* m, const void* base, uint64_t inner, uint64_t outer, uint32_t box_in,
                     uint32_t box_out, CUtensorMapSwizzle swz = CU_TENSOR_MAP_SWIZZLE_128B) {
  cuuint64_t gd[2] = {inner, outer};
  cuuint64_t gs[1] = {inner * 2};
  cuuint32_t bd[2] = {box_in, box_out};
  cuuint32_t es[2] = {1, 1};
  enc(m, CU_TENSOR_MAP_DATA_TYPE_BFLOAT16, 2, const_cast<void*>(base), gd, gs, bd, es, CU_TENSOR_MAP_INTERLEAVE_NONE,
      swz, CU_TENSOR_MAP_L2_PROMOTION_L2_128B, CU_TENSOR_MAP_FLOAT_OOB_FILL_NONE);
}

}

extern "C" void kernel_launch(void* const* d_in, const int* in_sizes, int n_in, void* d_out, int out_size) {
  using namespace s4la;
  (void)in_sizes; (void)n_in; (void)out_size;
  static EncodeFn enc = nullptr;
  static void *uT = nullptr, *yT = nullptr, *oS = nullptr;
  if (!enc) {
    void* fn = nullptr;
    cudaDriverEntryPointQueryResult qr;
    cudaGetDriverEntryPoint("cuTensorMapEncodeTiled", &fn, cudaEnableDefault, &qr);
    enc = (EncodeFn)fn;
    cudaGetSymbolAddress(&uT, g_uT);
    cudaGetSymbolAddress(&yT, g_yT);
    cudaGetSymbolAddress(&oS, g_o);
    cudaFuncSetAttribute(fused_kernel, cudaFuncAttributeMaxDynamicSharedMemorySize, SM_TOTAL);
  }
  const __nv_bfloat16* const* in = (const __nv_bfloat16* const*)d_in;
  Maps maps;
  make_map(enc, &maps.x, in[9], 512, 2048, 32, 128, CU_TENSOR_MAP_SWIZZLE_64B);
  {
    cuuint64_t gd[3] = {512, 512, 3};
    cuuint64_t gs[2] = {3072, 1024};
    cuuint32_t bd[3] = {64, 16, 3};
    cuuint32_t es[3] = {1, 1, 1};
    enc(&maps.w, CU_TENSOR_MAP_DATA_TYPE_BFLOAT16, 3, const_cast<__nv_bfloat16*>(in[10]), gd, gs, bd, es,
        CU_TENSOR_MAP_INTERLEAVE_NONE, CU_TENSOR_MAP_SWIZZLE_128B, CU_TENSOR_MAP_L2_PROMOTION_L2_128B,
        CU_TENSOR_MAP_FLOAT_OOB_FILL_NONE);
  }
  make_map(enc, &maps.wo, in[11], 512, 512, 64, 256);
  make_map(enc, &maps.u, in[0], 512, 2048, 64, 128);
  make_map(enc, &maps.uT, uT, 2048, 512, 64, 64);
  make_map(enc, &maps.yT, yT, 2048, 512, 64, 64);
  make_map(enc, &maps.o, oS, 512, 2048, 64, 128);
  make_map(enc, &maps.out, d_out, 1024, 2048, 64, 128);
  Ptrs p;
  p.A_re = in[1]; p.A_im = in[2]; p.B_re = in[3]; p.B_im = in[4]; p.C_re = in[5]; p.C_im = in[6];
  p.log_dt = in[7]; p.Dskip = in[8]; p.x = in[9]; p.wqkv = in[10]; p.wo = in[11];
  p.uT = (__nv_bfloat16*)uT; p.yT = (__nv_bfloat16*)yT;
  fused_kernel<<<NCTA, NTHREADS, SM_TOTAL, cudaStreamPerThread>>>(maps, p);
}
```

```cpp
#include <cuda_runtime.h>
#include <cuda_bf16.h>
#include <cuda_fp16.h>
#include <cuda.h>
#include <stdint.h>

#define DEVI __device__ __forceinline__

namespace s4la {

constexpr int NTHREADS = 512;
constexpr int NCTA = 128;

constexpr int NSTG = 7;
constexpr uint32_t STG_BYTES = 20480, STG_X = 0, STG_W = 8192;
constexpr uint32_t SM_QS = 0;
constexpr uint32_t SM_PK = SM_QS + 16384, SM_VS = SM_QS + 32768;
constexpr uint32_t SM_WO = 65536;
constexpr uint32_t SM_KV = 131072;
constexpr uint32_t SM_BOUT = 16384;
constexpr uint32_t SM_U = 143360, U_BYTES = 4352;
constexpr uint32_t SM_P = 160768, P_BYTES = 4096;
constexpr uint32_t SM_VV = 177152, VV_BYTES = 12800;
constexpr uint32_t VV_U5 = 0, VV_U3 = 3712, VV_U9 = 7424, VV_U7 = 10112;
constexpr uint32_t KG_BYTES = 3200;
constexpr uint32_t SM_BAR = SM_VV + 4 * VV_BYTES;
constexpr uint32_t SM_PTAB = SM_BAR + 320;
constexpr uint32_t SM_TOTAL = SM_PTAB + 2048;
static_assert(SM_TOTAL <= 232448, "shared memory");
constexpr int PADV = 12;

enum { B_FULL = 0, B_EMPTY = 7, B_TILE = 14, B_UCH = 15, B_KVP = 19, B_KVF = 20, B_OST = 21, B_RF = 22, B_WO = 30, B_RE = 31, B_PFREE = 32, B_CONVD = 33, B_COUNT = 34 };
__host__ __device__ constexpr int bar_count(int i) {
  return (i >= B_EMPTY && i < B_TILE) ? 16 : (i == B_KVP || i == B_OST || i == B_RE) ? 8 : i == B_CONVD ? 4 : 1;
}

constexpr int PD_OFF = 0, P2_OFF = 544, P3_OFF = 768;

constexpr int SL_K2048 = 20, SL_ZERO = 21, SL_510 = 22, SL_0 = 23;
__host__ __device__ constexpr int koff(int y) {
  return y < 8 ? y : y < 12 ? 256 + 2 * (y - 8) : y < 16 ? 512 + 256 * ((y - 12) >> 1) + 4 * (y & 1) : 1024 + 256 * (y - 16);
}
__host__ __device__ constexpr int kidx_c(int l) {
  const int y = l < 256 ? (l & 7) : l < 512 ? 8 + ((l & 7) >> 1) : l < 1024 ? 12 + (((l - 512) >> 8) << 1) + ((l >> 2) & 1)
                                                                            : 16 + ((l - 1024) >> 8);
  return ((l >> 3) & 31) * 24 + y;
}
constexpr int slot_direct(int l) {
  if (l < 0 || l > 510) return SL_ZERO;
  if (l == 510) return SL_510;
  if (l == 0) return SL_0;
  return kidx_c(l < 256 ? l : ((l + ((l >> 1) & 1)) & ~1));
}
constexpr int slot_seg2(int v, int k) { return (k >= 32 && k < 64) ? kidx_c(16 * k + 4 * v) : SL_ZERO; }
constexpr int slot_seg3(int pi, int k) {
  return (k >= 64 && k < 128) ? kidx_c(16 * k + 8 * pi) : ((k == 128 && pi == 0) ? SL_K2048 : SL_ZERO);
}
constexpr int slot_word(int w) {
  return w < 0 ? SL_ZERO : w < 544 ? slot_direct(w - 16) : w < 768 ? slot_seg2((w - 544) / 56, 16 + (w - 544) % 56)
       : w < 944 ? slot_seg3((w - 768) / 88, 48 + (w - 768) % 88) : SL_ZERO;
}
struct PTab { uint32_t v[512]; };
constexpr PTab make_ptab() {
  PTab t{};
  for (int lane = 0; lane < 32; ++lane)
    for (int i = 0; i < 16; ++i)
      t.v[i * 32 + lane] = (slot_word(31 * lane - 1 + 2 * i) * 4) | ((slot_word(31 * lane + 2 * i) * 4) << 16);
  return t;
}
__device__ const PTab g_ptab = make_ptab();

__device__ __nv_bfloat16 g_uT[512 * 2048];
__device__ __nv_bfloat16 g_yT[512 * 2048];
__device__ __nv_bfloat16 g_o[2048 * 512];
__device__ float g_kv[2][8][4 * 272];
__device__ unsigned g_cnt[64 * 32];
__device__ unsigned g_epoch;
#define TS(slot) do { } while (0)
#define TSR(on, slot) do { } while (0)
enum { C_U = 0, C_KV = 8, C_O = 16, C_Y = 32 };

struct Maps {
  CUtensorMap x, w, wo, u, uT, yT, o, out;
};
struct Ptrs {
  const __nv_bfloat16 *A_re, *A_im, *B_re, *B_im, *C_re, *C_im, *log_dt, *Dskip;
  const __nv_bfloat16 *x, *wqkv, *wo;
  __nv_bfloat16 *uT, *yT;
};

DEVI uint32_t s2u(const void* p) { return (uint32_t)__cvta_generic_to_shared(p); }
DEVI void mbar_init(uint32_t b, uint32_t c) { asm volatile("mbarrier.init.shared::cta.b64 [%0], %1;" ::"r"(b), "r"(c) : "memory"); }
DEVI void mbar_expect_tx(uint32_t b, uint32_t bytes) {
  asm volatile("mbarrier.arrive.expect_tx.shared::cta.b64 _, [%0], %1;" ::"r"(b), "r"(bytes) : "memory");
}
DEVI void mbar_arrive(uint32_t b) { asm volatile("mbarrier.arrive.shared::cta.b64 _, [%0];" ::"r"(b) : "memory"); }
DEVI void mbar_arrive_cluster(uint32_t b, uint32_t cta) {
  asm volatile("{\n.reg .b32 r;\nmapa.shared::cluster.u32 r, %0, %1;\nmbarrier.arrive.shared::cluster.b64 _, [r];\n}"
               ::"r"(b), "r"(cta) : "memory");
}
DEVI void mbar_wait(uint32_t b, uint32_t parity) {
  asm volatile("{\n.reg .pred p;\nLAB_WAIT:\nmbarrier.try_wait.parity.shared::cta.b64 p, [%0], %1;\n@!p bra LAB_WAIT;\n}"
               ::"r"(b), "r"(parity) : "memory");
}
DEVI void mbar_wait_long(uint32_t b, uint32_t parity) {
  asm volatile("{\n.reg .pred p;\nLAB_WAIT:\nmbarrier.try_wait.parity.shared::cta.b64 p, [%0], %1, 0x989680;\n@!p bra LAB_WAIT;\n}"
               ::"r"(b), "r"(parity) : "memory");
}
DEVI void bar_sync(int id, int n) { asm volatile("bar.sync %0, %1;" ::"r"(id), "r"(n) : "memory"); }
DEVI void bar_arrive(int id, int n) { asm volatile("bar.arrive %0, %1;" ::"r"(id), "r"(n) : "memory"); }
DEVI void fence_async_smem() { asm volatile("fence.proxy.async.shared::cta;" ::: "memory"); }
DEVI void fence_async_all() { asm volatile("fence.proxy.async;" ::: "memory"); }
DEVI void cluster_arrive() { asm volatile("barrier.cluster.arrive.relaxed.aligned;" ::: "memory"); }
DEVI void cluster_wait() { asm volatile("barrier.cluster.wait.aligned;" ::: "memory"); }

DEVI void tma_load_2d(uint32_t dst, const CUtensorMap* m, int c0, int c1, uint32_t bar) {
  asm volatile("cp.async.bulk.tensor.2d.shared::cluster.global.mbarrier::complete_tx::bytes [%0], [%1, {%3, %4}], [%2];"
               ::"r"(dst), "l"(m), "r"(bar), "r"(c0), "r"(c1) : "memory");
}
DEVI void tma_load_2d_mc(uint32_t dst, const CUtensorMap* m, int c0, int c1, uint32_t bar, uint16_t mask) {
  asm volatile("cp.async.bulk.tensor.2d.shared::cluster.global.mbarrier::complete_tx::bytes.multicast::cluster [%0], [%1, {%3, %4}], [%2], %5;"
               ::"r"(dst), "l"(m), "r"(bar), "r"(c0), "r"(c1), "h"(mask) : "memory");
}
DEVI void tma_load_3d_mc(uint32_t dst, const CUtensorMap* m, int c0, int c1, int c2, uint32_t bar, uint16_t mask) {
  asm volatile("cp.async.bulk.tensor.3d.shared::cluster.global.mbarrier::complete_tx::bytes.multicast::cluster [%0], [%1, {%3, %4, %5}], [%2], %6;"
               ::"r"(dst), "l"(m), "r"(bar), "r"(c0), "r"(c1), "r"(c2), "h"(mask) : "memory");
}
DEVI void tma_store_2d(const CUtensorMap* m, uint32_t src, int c0, int c1) {
  asm volatile("cp.async.bulk.tensor.2d.global.shared::cta.bulk_group [%0, {%2, %3}], [%1];"
               ::"l"(m), "r"(src), "r"(c0), "r"(c1) : "memory");
}
DEVI void bulk_load(uint32_t dst, const void* src, uint32_t bytes, uint32_t bar) {
  asm volatile("cp.async.bulk.shared::cluster.global.mbarrier::complete_tx::bytes [%0], [%1], %2, [%3];"
               ::"r"(dst), "l"(src), "r"(bytes), "r"(bar) : "memory");
}
DEVI void bulk_store(void* dst, uint32_t src, uint32_t bytes) {
  asm volatile("cp.async.bulk.global.shared::cta.bulk_group [%0], [%1], %2;" ::"l"(dst), "r"(src), "r"(bytes) : "memory");
}
DEVI void bulk_reduce_add_f32(void* dst, uint32_t src, uint32_t bytes) {
  asm volatile("cp.reduce.async.bulk.global.shared::cta.bulk_group.add.f32 [%0], [%1], %2;" ::"l"(dst), "r"(src), "r"(bytes) : "memory");
}
DEVI void bulk_commit() { asm volatile("cp.async.bulk.commit_group;" ::: "memory"); }
DEVI void bulk_wait0() { asm volatile("cp.async.bulk.wait_group 0;" ::: "memory"); }
DEVI void bulk_wait_read0() { asm volatile("cp.async.bulk.wait_group.read 0;" ::: "memory"); }
DEVI void l2_prefetch(const void* p, uint32_t bytes) {
  asm volatile("cp.async.bulk.prefetch.L2.global [%0], %1;" ::"l"(p), "r"(bytes) : "memory");
}
DEVI void prefetch_tmap(const CUtensorMap* m) { asm volatile("prefetch.tensormap [%0];" ::"l"(m) : "memory"); }

DEVI void red_release_add(unsigned* p, unsigned v) {
  asm volatile("red.release.gpu.global.add.u32 [%0], %1;" ::"l"(p), "r"(v) : "memory");
}
DEVI void red_relaxed_add(unsigned* p, unsigned v) {
  asm volatile("red.relaxed.gpu.global.add.u32 [%0], %1;" ::"l"(p), "r"(v) : "memory");
}
DEVI unsigned ld_relaxed(const unsigned* p) {
  unsigned v;
  asm volatile("ld.relaxed.gpu.global.u32 %0, [%1];" : "=r"(v) : "l"(p) : "memory");
  return v;
}
DEVI void wait_counter(const unsigned* p, unsigned target) {
#pragma unroll 1
  for (int it = 0; (int)(ld_relaxed(p) - target) < 0; ++it)
    if (it > (1 << 22)) __trap();
}

DEVI void ldsm_x4(uint32_t (&r)[4], uint32_t a) {
  asm volatile("ldmatrix.sync.aligned.m8n8.x4.shared.b16 {%0,%1,%2,%3}, [%4];"
               : "=r"(r[0]), "=r"(r[1]), "=r"(r[2]), "=r"(r[3]) : "r"(a) : "memory");
}
DEVI void ldsm_x4_t(uint32_t (&r)[4], uint32_t a) {
  asm volatile("ldmatrix.sync.aligned.m8n8.x4.trans.shared.b16 {%0,%1,%2,%3}, [%4];"
               : "=r"(r[0]), "=r"(r[1]), "=r"(r[2]), "=r"(r[3]) : "r"(a) : "memory");
}
DEVI void ldsm_x2_t(uint32_t& r0, uint32_t& r1, uint32_t a) {
  asm volatile("ldmatrix.sync.aligned.m8n8.x2.trans.shared.b16 {%0,%1}, [%2];" : "=r"(r0), "=r"(r1) : "r"(a) : "memory");
}
DEVI void stsm_x4(uint32_t a, uint32_t r0, uint32_t r1, uint32_t r2, uint32_t r3) {
  asm volatile("stmatrix.sync.aligned.m8n8.x4.shared.b16 [%0], {%1,%2,%3,%4};"
               ::"r"(a), "r"(r0), "r"(r1), "r"(r2), "r"(r3) : "memory");
}
DEVI void stsm_x4_t(uint32_t a, uint32_t r0, uint32_t r1, uint32_t r2, uint32_t r3) {
  asm volatile("stmatrix.sync.aligned.m8n8.x4.trans.shared.b16 [%0], {%1,%2,%3,%4};"
               ::"r"(a), "r"(r0), "r"(r1), "r"(r2), "r"(r3) : "memory");
}
DEVI uint32_t lds32(uint32_t a) { uint32_t v; asm volatile("ld.shared.b32 %0, [%1];" : "=r"(v) : "r"(a) : "memory"); return v; }
DEVI float lds_f32(uint32_t a) { float v; asm volatile("ld.shared.f32 %0, [%1];" : "=f"(v) : "r"(a) : "memory"); return v; }
DEVI void sts32(uint32_t a, uint32_t v) { asm volatile("st.shared.b32 [%0], %1;" ::"r"(a), "r"(v) : "memory"); }
DEVI void sts_f32(uint32_t a, float v) { asm volatile("st.shared.f32 [%0], %1;" ::"r"(a), "f"(v) : "memory"); }
DEVI void sts_f32x2(uint32_t a, float x, float y) { asm volatile("st.shared.v2.f32 [%0], {%1,%2};" ::"r"(a), "f"(x), "f"(y) : "memory"); }
DEVI uint4 lds128(uint32_t a) {
  uint4 v;
  asm volatile("ld.shared.v4.b32 {%0,%1,%2,%3}, [%4];" : "=r"(v.x), "=r"(v.y), "=r"(v.z), "=r"(v.w) : "r"(a) : "memory");
  return v;
}
DEVI void sts128(uint32_t a, uint32_t x, uint32_t y, uint32_t z, uint32_t w) {
  asm volatile("st.shared.v4.b32 [%0], {%1,%2,%3,%4};" ::"r"(a), "r"(x), "r"(y), "r"(z), "r"(w) : "memory");
}

DEVI void mma_bf16(float (&d)[4], uint32_t a0, uint32_t a1, uint32_t a2, uint32_t a3, uint32_t b0, uint32_t b1) {
  asm("mma.sync.aligned.m16n8k16.row.col.f32.bf16.bf16.f32 {%0,%1,%2,%3}, {%4,%5,%6,%7}, {%8,%9}, {%0,%1,%2,%3};"
      : "+f"(d[0]), "+f"(d[1]), "+f"(d[2]), "+f"(d[3])
      : "r"(a0), "r"(a1), "r"(a2), "r"(a3), "r"(b0), "r"(b1));
}
DEVI void mma_f16(float (&d)[4], const uint32_t (&a)[4], uint32_t b0, uint32_t b1) {
  asm("mma.sync.aligned.m16n8k16.row.col.f32.f16.f16.f32 {%0,%1,%2,%3}, {%4,%5,%6,%7}, {%8,%9}, {%0,%1,%2,%3};"
      : "+f"(d[0]), "+f"(d[1]), "+f"(d[2]), "+f"(d[3])
      : "r"(a[0]), "r"(a[1]), "r"(a[2]), "r"(a[3]), "r"(b0), "r"(b1));
}
DEVI void mma_bf16v(float (&d)[4], const uint32_t (&a)[4], uint32_t b0, uint32_t b1) {
  asm volatile("mma.sync.aligned.m16n8k16.row.col.f32.bf16.bf16.f32 {%0,%1,%2,%3}, {%4,%5,%6,%7}, {%8,%9}, {%0,%1,%2,%3};"
               : "+f"(d[0]), "+f"(d[1]), "+f"(d[2]), "+f"(d[3])
               : "r"(a[0]), "r"(a[1]), "r"(a[2]), "r"(a[3]), "r"(b0), "r"(b1));
}
DEVI uint32_t pack_bf16(float lo, float hi) {
  uint32_t r;
  asm("cvt.rn.bf16x2.f32 %0, %1, %2;" : "=r"(r) : "f"(hi), "f"(lo));
  return r;
}
DEVI uint32_t pack_f16(float lo, float hi) {
  uint32_t r;
  asm("cvt.rn.f16x2.f32 %0, %1, %2;" : "=r"(r) : "f"(hi), "f"(lo));
  return r;
}
DEVI uint32_t ldg16(const __nv_bfloat16* p) {
  uint32_t v;
  asm volatile("ld.global.nc.u16 %0, [%1];" : "=r"(v) : "l"(p));
  return v;
}
DEVI bool elect_one() {
  uint32_t pred;
  asm volatile("{\n.reg .pred p;\nelect.sync _|p, 0xffffffff;\nselp.u32 %0, 1, 0, p;\n}" : "=r"(pred));
  return pred != 0;
}
DEVI float bf_lo(uint32_t v) { return __uint_as_float(v << 16); }
DEVI float bf_hi(uint32_t v) { return __uint_as_float(v & 0xffff0000u); }
DEVI float bf2f(__nv_bfloat16 v) { return __bfloat162float(v); }
DEVI float round_bf16(float v) { return __bfloat162float(__float2bfloat16_rn(v)); }
DEVI float rcp(float x) { float r; asm("rcp.approx.ftz.f32 %0, %1;" : "=f"(r) : "f"(x)); return r; }
DEVI float ex2(float x) { float r; asm("ex2.approx.ftz.f32 %0, %1;" : "=f"(r) : "f"(x)); return r; }

DEVI void wg_fence() { asm volatile("wgmma.fence.sync.aligned;" ::: "memory"); }
DEVI void wg_commit() { asm volatile("wgmma.commit_group.sync.aligned;" ::: "memory"); }
template <int N> DEVI void wg_wait() { asm volatile("wgmma.wait_group.sync.aligned %0;" ::"n"(N) : "memory"); }
constexpr uint32_t DESC_HI = (1u << 30) | (1024 >> 4);
constexpr uint32_t DESC_HI64 = (2u << 30) | (512 >> 4);
DEVI uint32_t mkdesc(uint32_t saddr, uint32_t lbo) { return ((saddr & 0x3FFFF) >> 4) | ((lbo >> 4) << 16); }

#define R8(b) "%" #b
DEVI void wgmma_n192(float (&d)[96], uint32_t da, uint32_t db, int scale_d) {
  asm volatile(
      "{\n.reg .pred p;\n.reg .b64 da, db;\nsetp.ne.b32 p, %98, 0;\nmov.b64 da, {%96, %100};\nmov.b64 db, {%97, %99};\n"
      "wgmma.mma_async.sync.aligned.m64n192k16.f32.bf16.bf16 "
      "{%0,%1,%2,%3,%4,%5,%6,%7,%8,%9,%10,%11,%12,%13,%14,%15,"
      "%16,%17,%18,%19,%20,%21,%22,%23,%24,%25,%26,%27,%28,%29,%30,%31,"
      "%32,%33,%34,%35,%36,%37,%38,%39,%40,%41,%42,%43,%44,%45,%46,%47,"
      "%48,%49,%50,%51,%52,%53,%54,%55,%56,%57,%58,%59,%60,%61,%62,%63,"
      "%64,%65,%66,%67,%68,%69,%70,%71,%72,%73,%74,%75,%76,%77,%78,%79,"
      "%80,%81,%82,%83,%84,%85,%86,%87,%88,%89,%90,%91,%92,%93,%94,%95}, "
      "da, db, p, 1, 1, 0, 1;\n}"
      : "+f"(d[0]), "+f"(d[1]), "+f"(d[2]), "+f"(d[3]), "+f"(d[4]), "+f"(d[5]), "+f"(d[6]), "+f"(d[7]),
        "+f"(d[8]), "+f"(d[9]), "+f"(d[10]), "+f"(d[11]), "+f"(d[12]), "+f"(d[13]), "+f"(d[14]), "+f"(d[15]),
        "+f"(d[16]), "+f"(d[17]), "+f"(d[18]), "+f"(d[19]), "+f"(d[20]), "+f"(d[21]), "+f"(d[22]), "+f"(d[23]),
        "+f"(d[24]), "+f"(d[25]), "+f"(d[26]), "+f"(d[27]), "+f"(d[28]), "+f"(d[29]), "+f"(d[30]), "+f"(d[31]),
        "+f"(d[32]), "+f"(d[33]), "+f"(d[34]), "+f"(d[35]), "+f"(d[36]), "+f"(d[37]), "+f"(d[38]), "+f"(d[39]),
        "+f"(d[40]), "+f"(d[41]), "+f"(d[42]), "+f"(d[43]), "+f"(d[44]), "+f"(d[45]), "+f"(d[46]), "+f"(d[47]),
        "+f"(d[48]), "+f"(d[49]), "+f"(d[50]), "+f"(d[51]), "+f"(d[52]), "+f"(d[53]), "+f"(d[54]), "+f"(d[55]),
        "+f"(d[56]), "+f"(d[57]), "+f"(d[58]), "+f"(d[59]), "+f"(d[60]), "+f"(d[61]), "+f"(d[62]), "+f"(d[63]),
        "+f"(d[64]), "+f"(d[65]), "+f"(d[66]), "+f"(d[67]), "+f"(d[68]), "+f"(d[69]), "+f"(d[70]), "+f"(d[71]),
        "+f"(d[72]), "+f"(d[73]), "+f"(d[74]), "+f"(d[75]), "+f"(d[76]), "+f"(d[77]), "+f"(d[78]), "+f"(d[79]),
        "+f"(d[80]), "+f"(d[81]), "+f"(d[82]), "+f"(d[83]), "+f"(d[84]), "+f"(d[85]), "+f"(d[86]), "+f"(d[87]),
        "+f"(d[88]), "+f"(d[89]), "+f"(d[90]), "+f"(d[91]), "+f"(d[92]), "+f"(d[93]), "+f"(d[94]), "+f"(d[95])
      : "r"(da), "r"(db), "r"(scale_d), "n"(DESC_HI), "n"(DESC_HI64));
}
DEVI void wgmma_n64(float (&d)[32], uint32_t da, uint32_t db, int scale_d) {
  asm volatile(
      "{\n.reg .pred p;\n.reg .b64 da, db;\nsetp.ne.b32 p, %34, 0;\nmov.b64 da, {%32, %35};\nmov.b64 db, {%33, %35};\n"
      "wgmma.mma_async.sync.aligned.m64n64k16.f32.bf16.bf16 "
      "{%0,%1,%2,%3,%4,%5,%6,%7,%8,%9,%10,%11,%12,%13,%14,%15,"
      "%16,%17,%18,%19,%20,%21,%22,%23,%24,%25,%26,%27,%28,%29,%30,%31}, "
      "da, db, p, 1, 1, 0, 1;\n}"
      : "+f"(d[0]), "+f"(d[1]), "+f"(d[2]), "+f"(d[3]), "+f"(d[4]), "+f"(d[5]), "+f"(d[6]), "+f"(d[7]),
        "+f"(d[8]), "+f"(d[9]), "+f"(d[10]), "+f"(d[11]), "+f"(d[12]), "+f"(d[13]), "+f"(d[14]), "+f"(d[15]),
        "+f"(d[16]), "+f"(d[17]), "+f"(d[18]), "+f"(d[19]), "+f"(d[20]), "+f"(d[21]), "+f"(d[22]), "+f"(d[23]),
        "+f"(d[24]), "+f"(d[25]), "+f"(d[26]), "+f"(d[27]), "+f"(d[28]), "+f"(d[29]), "+f"(d[30]), "+f"(d[31])
      : "r"(da), "r"(db), "r"(scale_d), "n"(DESC_HI));
}

struct C32 { float re, im; };
DEVI C32 csq(C32 a) { return {a.re * a.re - a.im * a.im, 2.f * a.re * a.im}; }
DEVI C32 cmul(C32 a, C32 b) { return {a.re * b.re - a.im * b.im, a.re * b.im + a.im * b.re}; }
DEVI C32 cfresh(float zl, float zi, float m) {
  float mag = ex2(zl * m), ph = zi * m;
  return {mag * __cosf(ph), mag * __sinf(ph)};
}
struct HMul { uint32_t b, bp; };
DEVI HMul mk_mul(float re, float im) { return {pack_f16(re, im), pack_f16(-im, re)}; }
DEVI uint32_t hcmul(uint32_t a, const HMul& m) {
  __half2 ah = *reinterpret_cast<__half2*>(&a);
  __half2 b = *reinterpret_cast<const __half2*>(&m.b), bp = *reinterpret_cast<const __half2*>(&m.bp);
  __half2 r = __hfma2(__high2half2(ah), bp, __hmul2(__low2half2(ah), b));
  return *reinterpret_cast<uint32_t*>(&r);
}
DEVI uint32_t badd(uint32_t a, uint32_t b) {
  __nv_bfloat162 r = __hadd2(*reinterpret_cast<__nv_bfloat162*>(&a), *reinterpret_cast<__nv_bfloat162*>(&b));
  return *reinterpret_cast<uint32_t*>(&r);
}
template <int MU0, int NMU, int DMAX>
DEVI void conv_tail(float (&acc)[16][4], uint32_t p_lane, uint32_t v_base, int back, bool edge, int lane) {
  const int hsel = (lane >> 3) & 1;
  const int row = (lane & 7) + ((lane >> 4) << 3) + PADV - 8 - (back & (hsel ^ 1));
  const uint32_t la = v_base + row * 32 + (((hsel ^ back) ^ ((row >> 2) & 1)) << 4);
  uint32_t M[3][4];
  ldsm_x4_t(M[0], la);
  ldsm_x4_t(M[1], la + 256);
  uint32_t H[2 * NMU];
#pragma unroll
  for (int i = 0; i < 2 * NMU; ++i) H[i ^ 1] = lds32(p_lane + (uint32_t)(MU0 - 1 + i) * 32);
  if (edge) {
    const uint32_t a[4] = {0u, 0u, M[0][0], M[0][1]};
#pragma unroll
    for (int k = 1; k < NMU; ++k) mma_bf16v(acc[MU0 - 2 + 2 * k], a, H[2 * k], H[2 * k + 1]);
  }
#pragma unroll
  for (int delta = -1; delta <= DMAX; ++delta) {
    if (delta + 2 <= DMAX) ldsm_x4_t(M[(delta + 3) % 3], la + (delta + 3) * 256);
#pragma unroll
    for (int k = 0; k < NMU; ++k)
      if (delta + MU0 + 2 * k < 16) mma_bf16v(acc[delta + MU0 + 2 * k], M[(delta + 1) % 3], H[2 * k], H[2 * k + 1]);
  }
}

__global__ void __cluster_dims__(2, 1, 1) __launch_bounds__(NTHREADS, 1)
fused_kernel(const __grid_constant__ Maps maps, const Ptrs p) {
  extern __shared__ __align__(1024) uint8_t smem[];
  const uint32_t sb = s2u(smem);
  const int tid = threadIdx.x, lane = tid & 31;
  const int warp = __shfl_sync(0xffffffffu, tid >> 5, 0);
  const int cta = blockIdx.x;
  const uint32_t rank = cta & 1;
  const int ti = 2 * (cta >> 4) + rank;
  const int tj = (cta >> 1) & 7;
  const uint32_t bars = sb + SM_BAR;
#define BAR(i) (bars + 8 * (i))
  const int g = lane >> 2, q = lane & 3;

  const int kch = warp & 3, krd = warp >> 2;
  float zr, zi, wr, wi;
  {
    const size_t po = (size_t)(cta * 4 + kch) * 128 + krd * 32 + lane;
    const uint32_t r_ar = ldg16(p.A_re + po), r_ai = ldg16(p.A_im + po), r_br = ldg16(p.B_re + po), r_bi = ldg16(p.B_im + po);
    const uint32_t r_cr = ldg16(p.C_re + po), r_ci = ldg16(p.C_im + po), r_ldt = ldg16(p.log_dt + cta * 4 + kch);
    uint4 pt;
    if (tid < 128) pt = __ldg((const uint4*)g_ptab.v + tid);
    if (tid == 384) {
      TS(0);
#pragma unroll
      for (int i = 0; i < B_COUNT; ++i) mbar_init(BAR(i), bar_count(i));
      asm volatile("fence.mbarrier_init.release.cluster;" ::: "memory");
      prefetch_tmap(&maps.x); prefetch_tmap(&maps.w); prefetch_tmap(&maps.u);
    }
    __syncthreads();
    cluster_arrive();
    if (warp >= 12) {
      cluster_wait();
      if (elect_one()) {
        if (warp == 13) {
          mbar_expect_tx(BAR(B_TILE), 16384);
          tma_load_2d(sb + SM_U, &maps.u, tj * 64, ti * 128, BAR(B_TILE));
          l2_prefetch((const char*)p.wqkv + 224 * 3072 + cta * 6912, 6912);
          l2_prefetch((const char*)p.x + (size_t)cta * 16384, 16384);
          l2_prefetch((const char*)p.wo + (size_t)cta * 4096, 4096);
        } else {
          if (warp == 12) TS(61);
#pragma unroll 1
          for (int ks = warp == 12 ? 0 : warp - 13; ks < NSTG; ks += 3) {
            const uint32_t st = sb + ks * STG_BYTES, fb = BAR(B_FULL + ks);
            mbar_expect_tx(fb, STG_BYTES);
            tma_load_2d(st + STG_X, &maps.x, ks * 32, ti * 128, fb);
            tma_load_3d_mc(st + STG_W + rank * 6144, &maps.w, tj * 64, ks * 32 + rank * 16, 0, fb, 3);
          }
          if (warp == 15) {
            prefetch_tmap(&maps.uT); prefetch_tmap(&maps.wo); prefetch_tmap(&maps.o); prefetch_tmap(&maps.yT);
            prefetch_tmap(&maps.out);
          }
        }
      }
      __syncwarp();
    }
    if (tid < 128) sts128(sb + SM_PTAB + tid * 16, pt.x, pt.y, pt.z, pt.w);
    const float dt = round_bf16(expf(bf_lo(r_ldt)));
    zr = dt * bf_lo(r_ar); zi = dt * bf_lo(r_ai);
    const float dbr = dt * bf_lo(r_br), dbi = dt * bf_lo(r_bi), cr = bf_lo(r_cr), ci = bf_lo(r_ci);
    wr = cr * dbr - ci * dbi; wi = cr * dbi + ci * dbr;
  }
  {
    const float mz = __uint_as_float(__reduce_max_sync(0xffffffffu, __float_as_uint(fmaxf(zr, 0.f))));
    const int E = min(max((int)(__reduce_max_sync(0xffffffffu, __float_as_uint(fmaxf(fabsf(wr), fabsf(wi)))) >> 23), 1), 252);
    const float sc = __int_as_float((253 - E) << 23), inv = __int_as_float((E + 1) << 23);
    const float zl = (zr - mz) * 1.4426950408889634f;
    const uint32_t tb = sb + SM_VV + kch * VV_BYTES + krd * KG_BYTES;
    const uint32_t sta = tb + (((lane >> 2) << 4) | ((lane & 3) << 2));
    auto put = [&](int r, uint32_t v) { sts32((sta ^ ((r & 7) << 4)) + r * 128, v); };
    const uint32_t lda = tb + ((lane & 7) + (((lane >> 3) & 1) << 3)) * 128;
    const uint32_t ldb = tb + ((lane & 7) + ((lane >> 4) << 3)) * 128;
    C32 e1 = cfresh(zl, zi, 1.f), e2 = csq(e1), e4 = csq(e2), e8 = csq(e4);
    C32 e16 = cfresh(zl, zi, 16.f), e32 = csq(e16), e64 = csq(e32), e128 = csq(e64);
    C32 e256 = cfresh(zl, zi, 256.f), e512 = csq(e256), e1024 = csq(e512), e768 = cmul(e512, e256);
    uint32_t XA[2][4][4];
    {
      const HMul m16 = mk_mul(e16.re, e16.im), m32 = mk_mul(e32.re, e32.im), m64 = mk_mul(e64.re, e64.im);
      const HMul m128 = mk_mul(e128.re, e128.im);
      uint32_t X[16];
      X[0] = 0x00003c00u; X[1] = pack_f16(e8.re, e8.im); X[2] = m16.b; X[4] = m32.b; X[8] = m64.b;
      X[3] = hcmul(X[1], m16); X[5] = hcmul(X[1], m32); X[6] = hcmul(X[2], m32); X[7] = hcmul(X[3], m32);
#pragma unroll
      for (int r = 1; r < 8; ++r) X[8 + r] = hcmul(X[r], m64);
#pragma unroll
      for (int h = 0; h < 2; ++h) {
#pragma unroll
        for (int r = 0; r < 16; ++r) put(r, h == 0 ? X[r] : r == 0 ? m128.b : hcmul(X[r], m128));
        __syncwarp();
#pragma unroll
        for (int k = 0; k < 4; ++k) ldsm_x4(XA[h][k], lda + (((2 * k + (lane >> 4)) ^ (lane & 7)) << 4));
        __syncwarp();
      }
    }
    float D[2][3][4];
#pragma unroll
    for (int t = 0; t < 6; ++t) D[t / 3][t % 3][0] = D[t / 3][t % 3][1] = D[t / 3][t % 3][2] = D[t / 3][t % 3][3] = 0.f;
    auto contract = [&](int t0, int nt) {
      __syncwarp();
#pragma unroll
      for (int k = 0; k < 4; ++k) {
        uint32_t b[4];
        ldsm_x4(b, ldb + (((2 * k + ((lane >> 3) & 1)) ^ (lane & 7)) << 4));
#pragma unroll
        for (int h = 0; h < 2; ++h) {
          mma_f16(D[h][t0], XA[h][k], b[0], b[1]);
          if (nt == 2) mma_f16(D[h][t0 + 1], XA[h][k], b[2], b[3]);
        }
      }
      __syncwarp();
    };
    const HMul c1 = mk_mul(e1.re, -e1.im), c2 = mk_mul(e2.re, -e2.im), c4 = mk_mul(e4.re, -e4.im);
    const HMul c256 = mk_mul(e256.re, -e256.im), c512 = mk_mul(e512.re, -e512.im), c768 = mk_mul(e768.re, -e768.im);
    const HMul c1024 = mk_mul(e1024.re, -e1024.im);
    uint32_t W[8];
    W[0] = pack_f16(wr * sc, -wi * sc);
    W[1] = hcmul(W[0], c1); W[2] = hcmul(W[0], c2); W[3] = hcmul(W[1], c2);
    W[4] = hcmul(W[0], c4); W[5] = hcmul(W[1], c4); W[6] = hcmul(W[2], c4); W[7] = hcmul(W[3], c4);
#pragma unroll
    for (int i = 0; i < 8; ++i) put(i, W[i]);
#pragma unroll
    for (int i = 0; i < 4; ++i) put(8 + i, hcmul(W[2 * i], c256));
    put(12, hcmul(W[0], c512)); put(13, hcmul(W[4], c512)); put(14, hcmul(W[0], c768)); put(15, hcmul(W[4], c768));
    contract(0, 2);
    const uint32_t v0 = hcmul(W[0], c1024);
    put(0, v0); put(1, hcmul(v0, c256)); put(2, hcmul(v0, c512)); put(3, hcmul(v0, c768)); put(4, hcmul(v0, c1024));
    contract(2, 1);
    const uint32_t a = tb + (g * 24 + 2 * q) * 4;
#pragma unroll
    for (int t = 0; t < 6; ++t) {
      const float(&d)[4] = D[t / 3][t % 3];
      sts_f32x2(a + (t / 3) * 1536 + (t % 3) * 32, d[0] * inv, d[1] * inv);
      sts_f32x2(a + (t / 3) * 1536 + (t % 3) * 32 + 768, d[2] * inv, d[3] * inv);
    }
    if (mz > 0.f) {
      __syncwarp();
#pragma unroll 1
      for (int i = lane; i < 768; i += 32) {
        const int r = i / 24, y = i - 24 * r;
        sts_f32(tb + i * 4, lds_f32(tb + i * 4) * ex2(mz * 1.4426950408889634f * (koff(y) + 8 * r)));
      }
    }
  }
  if (tid == 0) TS(2);
  if (warp < 12) cluster_wait();
  __syncthreads();

  if (warp < 4) {
    asm volatile("setmaxnreg.inc.sync.aligned.u32 152;");
    const unsigned epoch = __ldcg(&g_epoch);
    const int d = cta * 4 + warp;
    const uint32_t vv = sb + SM_VV + warp * VV_BYTES;
    const uint32_t ub = sb + SM_U + warp * U_BYTES;
    const uint32_t pb = sb + SM_P + warp * P_BYTES;
    const float dskip = bf2f(p.Dskip[d]);
#pragma unroll 1
    for (int pass = 0; pass < 2; ++pass) {
      if (pass == 1) {
        const uint32_t kf = vv;
#pragma unroll 2
        for (int i = 0; i < 6; ++i) {
          const uint32_t a = kf + (i * 32 + lane) * 16;
          const uint4 x0 = lds128(a), x1 = lds128(a + KG_BYTES), x2 = lds128(a + 2 * KG_BYTES), x3 = lds128(a + 3 * KG_BYTES);
          auto s4 = [](uint32_t a0, uint32_t a1, uint32_t a2, uint32_t a3) {
            return __float_as_uint((__uint_as_float(a0) + __uint_as_float(a1)) + (__uint_as_float(a2) + __uint_as_float(a3)));
          };
          sts128(a, s4(x0.x, x1.x, x2.x, x3.x), s4(x0.y, x1.y, x2.y, x3.y), s4(x0.z, x1.z, x2.z, x3.z), s4(x0.w, x1.w, x2.w, x3.w));
        }
        __syncwarp();
        const float k1024 = lds_f32(kf + kidx_c(1024) * 4);
        if (lane == 0) {
          sts_f32(kf + SL_ZERO * 4, 0.f);
          sts_f32(kf + SL_510 * 4, lds_f32(kf + kidx_c(510) * 4) - lds_f32(kf + kidx_c(512) * 4));
          sts_f32(kf + SL_0 * 4, lds_f32(kf) + dskip);
        }
        __syncwarp();
        mbar_wait_long(BAR(B_PFREE), 0);
        {
          float prev = 0.f;
#pragma unroll 1
          for (int i0 = 0; i0 < 16; i0 += 4) {
            uint32_t e[4];
            float a[4], b[4];
#pragma unroll
            for (int i = 0; i < 4; ++i) e[i] = lds32(sb + SM_PTAB + ((i0 + i) * 32 + lane) * 4);
#pragma unroll
            for (int i = 0; i < 4; ++i) { a[i] = lds_f32(kf + (e[i] & 0xffff)); b[i] = lds_f32(kf + (e[i] >> 16)); }
#pragma unroll
            for (int i = 0; i < 4; ++i) {
              const uint32_t w = pb + (31 * lane + 2 * (i0 + i)) * 4;
              if (i0 + i > 0) sts32(w - 4, pack_bf16(a[i], prev));
              sts32(w, pack_bf16(b[i], a[i]));
              prev = b[i];
            }
          }
        }
        __syncwarp();
        bar_arrive(7, 384);
        if (lane == 0) TS(4);
        const int gq = g - 2 * q;
        uint32_t h127, h128;
        {
          const uint32_t kf2 = pack_bf16(k1024, k1024) ^ 0x80008000u;
          h127 = (gq == 4 ? 0x0000ffffu : gq == 5 ? 0xffffffffu : gq == 6 ? 0xffff0000u : 0u) & kf2;
          h128 = (gq == -4 ? 0x0000ffffu : gq == -3 ? 0xffffffffu : gq == -2 ? 0xffff0000u : 0u) & kf2;
        }
        bar_sync(4, 384);
        mbar_wait_long(BAR(B_UCH + warp), 0);
        if (lane == 0) TS(7);
        float acc[16][4];
#pragma unroll
        for (int i = 0; i < 16; ++i) { acc[i][0] = acc[i][1] = acc[i][2] = acc[i][3] = 0.f; }
        {
          const uint32_t pd_lane = pb + (PD_OFF + 16 + gq) * 4;
          const int prow0 = 8 + (lane & 7) + ((lane >> 4) << 3), hs = (lane >> 3) & 1;
          uint32_t B[2][4][4];
          uint32_t A[4][4];
          const uint32_t la0 = ub + prow0 * 32 + ((hs ^ ((prow0 >> 2) & 1)) << 4);
#pragma unroll
          for (int m2 = 0; m2 < 4; ++m2) ldsm_x4(B[0][m2], la0 + m2 * 512);
#pragma unroll
          for (int i = 0; i < 4; ++i) {
            const uint32_t a = pd_lane + i * 512;
            A[i][0] = lds32(a); A[i][1] = lds32(a + 32); A[i][2] = lds32(a - 32); A[i][3] = A[i][0];
          }
          uint32_t la = la0;
#pragma unroll 1
          for (int rho = 0; rho < 8; ++rho) {
#pragma unroll
            for (int m2 = 0; m2 < 4; ++m2) ldsm_x4(B[1][m2], la + (4 + m2) * 512);
#pragma unroll
            for (int i = 0; i < 4; ++i)
#pragma unroll
              for (int m = 0; m < 8; ++m) mma_bf16v(acc[m + i], A[i], B[0][m >> 1][2 * (m & 1)], B[0][m >> 1][2 * (m & 1) + 1]);
            const int prow = prow0 - min(rho + 1, 7);
            la = ub + prow * 32 + ((hs ^ ((prow >> 2) & 1)) << 4);
#pragma unroll
            for (int m2 = 0; m2 < 4; ++m2) ldsm_x4(B[0][m2], la + m2 * 512);
            const uint32_t pa = pd_lane + (rho + 1) * 64;
#pragma unroll
            for (int i = 0; i < 4; ++i) {
#pragma unroll
              for (int m = 0; m < 8 - i; ++m)
                mma_bf16v(acc[8 + m + i], A[i], B[1][m >> 1][2 * (m & 1)], B[1][m >> 1][2 * (m & 1) + 1]);
              A[i][0] = lds32(pa + i * 512); A[i][1] = lds32(pa + i * 512 + 32); A[i][2] = lds32(pa + i * 512 - 32);
              A[i][3] = A[i][0];
            }
          }
          if (lane == 0) TS(40);
          {
            uint32_t b8[4];
            ldsm_x4(b8, la + 4 * 512);
            const uint32_t h63 = lds32(pd_lane + 63 * 32), h64 = lds32(pd_lane + 64 * 32);
            const uint32_t a63[4] = {0u, h127, 0u, 0u}, a32[4] = {h64, 0u, h63, h64}, a64[4] = {h128, 0u, h127, h128};
#pragma unroll
            for (int m2 = 0; m2 < 4; ++m2) ldsm_x4(B[1][m2], la0 + m2 * 512);
#pragma unroll
            for (int m = 0; m < 8; ++m) mma_bf16v(acc[m + 7], a63, B[0][m >> 1][2 * (m & 1)], B[0][m >> 1][2 * (m & 1) + 1]);
#pragma unroll
            for (int m2 = 0; m2 < 2; ++m2) ldsm_x4(B[0][m2], la0 + (4 + m2) * 512);
#pragma unroll
            for (int m = 0; m < 8; ++m) mma_bf16v(acc[m + 4], a32, B[1][m >> 1][2 * (m & 1)], B[1][m >> 1][2 * (m & 1) + 1]);
            mma_bf16v(acc[15], a63, b8[0], b8[1]);
#pragma unroll
            for (int m = 0; m < 8; ++m) mma_bf16v(acc[m + 8], a64, B[1][m >> 1][2 * (m & 1)], B[1][m >> 1][2 * (m & 1) + 1]);
#pragma unroll
            for (int m = 0; m < 4; ++m) mma_bf16v(acc[m + 12], a32, B[0][m >> 1][2 * (m & 1)], B[0][m >> 1][2 * (m & 1) + 1]);
          }
          if (lane == 0) TS(41);
          bar_sync(5, 384);
#pragma unroll 1
          for (int v = 0; v < 4; ++v)
            conv_tail<4, 3, 11>(acc, pb + (P2_OFF + 56 * v + gq - 16) * 4, vv + ((v & 1) ? VV_U3 : VV_U5), v >> 1, v == 0, lane);
          if (lane == 0) TS(42);
#pragma unroll 1
          for (int pi = 0; pi < 2; ++pi)
            conv_tail<8, 5, 7>(acc, pb + (P3_OFF + 88 * pi + gq - 48) * 4, vv + (pi ? VV_U7 : VV_U9), pi, pi == 0, lane);
        }
        if (lane == 0) TS(8);
        __syncwarp();
        {
          const int mt = lane >> 3;
          const uint32_t a = pb + (128 * (mt >> 1) + 16 * (lane & 7) + 8 * (mt & 1)) * 2;
#pragma unroll
          for (int ab = 0; ab < 16; ab += 2)
            stsm_x4_t(a + ab * 256, pack_bf16(acc[ab][0], acc[ab][1]), pack_bf16(acc[ab][2], acc[ab][3]),
                      pack_bf16(acc[ab + 1][0], acc[ab + 1][1]), pack_bf16(acc[ab + 1][2], acc[ab + 1][3]));
        }
        fence_async_smem();
        __syncwarp();
        if (lane == 0) mbar_arrive(BAR(B_CONVD));
        bar_arrive(3, 384);
        if (elect_one()) {
          bulk_store(p.yT + (size_t)d * 2048, pb, 4096);
          bulk_commit();
          bulk_wait0();
          red_relaxed_add(&g_cnt[(C_Y + (cta >> 4)) * 32], 1);
          TS(9);
        }
        bar_sync(2, 128);
        if (warp == 0 && elect_one()) {
          wait_counter(&g_cnt[(C_Y + tj) * 32], (epoch + 1) * 64);
          TS(28);
          mbar_expect_tx(BAR(B_TILE), 16384);
          tma_load_2d(sb + SM_U, &maps.yT, ti * 128, tj * 64, BAR(B_TILE));
          tma_load_2d(sb + SM_U + 8192, &maps.yT, ti * 128 + 64, tj * 64, BAR(B_TILE));
        }
        __syncwarp();
      }
      mbar_wait_long(BAR(B_TILE), pass);
      if (lane == 0) TS(26 + 3 * pass);
      {
        const int m = lane >> 3, r = lane & 7;
#pragma unroll 2
        for (int it = 0; it < 8; ++it) {
          const int tb = warp * 4 + (it >> 1), cb = (it & 1) * 4 + m;
          const uint32_t at = (tb * 8 + r) * 128 + ((cb ^ r) << 4);
          const uint32_t ac = (tb >> 3) * 8192 + (cb * 8 + r) * 128 + (((tb & 7) ^ (pass ? 0 : tb >> 3) ^ r) << 4);
          uint32_t v[4];
          ldsm_x4_t(v, sb + SM_U + (pass ? ac : at));
          stsm_x4(sb + SM_P + (pass ? at : ac), v[0], v[1], v[2], v[3]);
        }
      }
      fence_async_smem();
      if (pass == 0) {
        bar_arrive(6, 160);
      } else {
        bar_sync(2, 128);
        if (warp == 0 && elect_one()) {
          tma_store_2d(&maps.out, sb + SM_P, 64 * tj, 128 * ti);
          bulk_commit();
          bulk_wait_read0();
          TS(30);
        }
      }
    }
  } else if (warp < 12) {
    asm volatile("setmaxnreg.inc.sync.aligned.u32 160;");
    const int w8 = warp - 4;
    const int row = w8 * 16 + (lane & 7) + (((lane >> 3) & 1) << 3);
    {
      float acc[96];
#pragma unroll 1
      for (int ks = 0, s = 0, ph = 0; ks < 16; ++ks) {
        mbar_wait(BAR(B_FULL + s), ph);
        if (tid == 128 && !(ks & 1)) TSR(16, ks == 0 ? 16 : 9 + (ks >> 1) + (ks > 12 ? 46 : 0));
        const uint32_t st = sb + s * STG_BYTES;
        const uint32_t da = mkdesc(st + STG_X + (w8 >> 2) * 4096, 16);
        const uint32_t db = mkdesc(st + STG_W, 2048);
        wg_fence();
        wgmma_n192(acc, da, db, ks != 0);
        wgmma_n192(acc, da + 2, db + 384, 1);
        wg_commit();
        const uint32_t eprev = BAR(B_EMPTY + (s == 0 ? NSTG - 1 : s - 1));
        if (++s == NSTG) { s = 0; ph ^= 1; }
        if (ks > 0) {
          wg_wait<1>();
          if (lane < 2) mbar_arrive_cluster(eprev, lane);
        }
      }
      wg_wait<0>();
      bar_arrive(4, 384);
      if (tid == 128) TS(17);
      bar_sync(1, 256);
#pragma unroll
      for (int i = 0; i < 24; i += 2)
        stsm_x4(sb + SM_QS + row * 128 + (i >> 3) * 16384 + ((((i & 7) + (lane >> 4)) ^ (row & 7)) << 4),
                pack_bf16(acc[4 * i], acc[4 * i + 1]), pack_bf16(acc[4 * i + 2], acc[4 * i + 3]),
                pack_bf16(acc[4 * i + 4], acc[4 * i + 5]), pack_bf16(acc[4 * i + 6], acc[4 * i + 7]));
    }
    __syncwarp();
#pragma unroll 1
    for (int part = 1; part >= 0; --part) {
      const uint32_t pa = sb + SM_QS + part * 16384 + w8 * 2048 + lane * 16;
#pragma unroll 1
      for (int it = 0; it < 4; ++it) {
        uint4 t = lds128(pa + it * 512);
        uint32_t* tw = &t.x;
#pragma unroll
        for (int j = 0; j < 4; ++j) {
          const uint32_t x = tw[j];
          const __nv_bfloat162 xb = *reinterpret_cast<const __nv_bfloat162*>(&x);
          const uint32_t e = pack_bf16(ex2(bf_lo(x) * 1.4426950408889634f), ex2(bf_hi(x) * 1.4426950408889634f));
          const uint32_t m = __hgt2_mask(xb, __floats2bfloat162_rn(0.f, 0.f));
          const uint32_t sel = (badd(x, 0x3f803f80u) & m) | (e & ~m);
          tw[j] = pack_bf16(bf_lo(sel) + 1e-6f, bf_hi(sel) + 1e-6f);
        }
        sts128(pa + it * 512, t.x, t.y, t.z, t.w);
      }
      if (part == 1) {
        if (tid == 128) TS(53);
        bar_sync(1, 256);
        const int hh = w8 >> 1, dtile = w8 & 1;
        float kv[4] = {0.f, 0.f, 0.f, 0.f}, zz[4] = {0.f, 0.f, 0.f, 0.f};
        const int m = lane >> 3;
        const uint32_t aa = sb + SM_VS + ((lane & 7) + ((m >> 1) << 3)) * 128 + (((2 * hh + (m & 1)) ^ (lane & 7)) << 4);
        const uint32_t ab = sb + SM_PK + (lane & 15) * 128 + (((2 * hh + dtile) ^ (lane & 7)) << 4);
#pragma unroll 2
        for (int ks = 0; ks < 8; ++ks) {
          uint32_t a[4], b0, b1;
          ldsm_x4_t(a, aa + ks * 2048);
          ldsm_x2_t(b0, b1, ab + ks * 2048);
          mma_bf16(kv, a[0], a[1], a[2], a[3], b0, b1);
          mma_bf16(zz, 0x3f803f80u, 0x3f803f80u, 0x3f803f80u, 0x3f803f80u, b0, b1);
        }
        const uint32_t kp = sb + SM_KV + hh * 1088;
        sts128(kp + dtile * 512 + lane * 16, __float_as_uint(kv[0]), __float_as_uint(kv[1]), __float_as_uint(kv[2]),
               __float_as_uint(kv[3]));
        if (g == 0) sts_f32x2(kp + 1024 + dtile * 32 + q * 8, zz[0], zz[1]);
        fence_async_smem();
        __syncwarp();
        if (lane == 0) mbar_arrive(BAR(B_KVP));
        if (tid == 128) TS(55);
      }
    }
    if (tid == 128) TS(56);
    {
      const int ch = w8 >> 1;
      bar_sync(7, 384);
      mbar_wait_long(BAR(B_UCH + ch), 0);
#pragma unroll 1
      for (int it = w8 & 1; it < 8; it += 2) {
          const int k = -18 + it * 32 + lane;
          const int kr = min(max(k, -2), 208);
          uint32_t E[12];
#pragma unroll
          for (int c = 0; c < 3; ++c) {
            const int kk = kr - 1 + c, r = (kk >> 1) + 8;
            const uint4 t = lds128(sb + SM_U + ch * U_BYTES + r * 32 + (((kk & 1) ^ ((r >> 2) & 1)) << 4));
            E[4 * c] = t.x; E[4 * c + 1] = t.y; E[4 * c + 2] = t.z; E[4 * c + 3] = t.w;
          }
          uint32_t O[8];
#pragma unroll
          for (int j = 0; j < 8; ++j) O[j] = __byte_perm(E[j + 1], E[j + 2], 0x5432);
          uint32_t s3[6], s5[4], s7[4], s9[4];
#pragma unroll
          for (int j = 0; j < 6; ++j) s3[j] = badd(badd(O[j], O[j + 1]), E[j + 2]);
#pragma unroll
          for (int j = 0; j < 4; ++j) {
            s5[j] = badd(s3[j + 2], badd(E[j + 3], E[j + 5]));
            s7[j] = badd(s5[j], badd(O[j + 1], O[j + 4]));
            s9[j] = badd(s7[j], badd(E[j + 2], E[j + 6]));
          }
          const int r = (k >> 1) + PADV;
          const uint32_t a = sb + SM_VV + ch * VV_BYTES + r * 32 + (((k & 1) ^ ((r >> 2) & 1)) << 4);
          if (k < 208) { sts128(a + VV_U3, s3[0], s3[1], s3[2], s3[3]); sts128(a + VV_U5, s5[0], s5[1], s5[2], s5[3]); }
          if (k < 144) { sts128(a + VV_U7, s7[0], s7[1], s7[2], s7[3]); sts128(a + VV_U9, s9[0], s9[1], s9[2], s9[3]); }
      }
      bar_arrive(5, 384);
    }
    if (tid == 128) TS(6);
    mbar_wait_long(BAR(B_KVF), 0);
    if (tid == 128) TS(19);
#pragma unroll 1
    for (int h = 0; h < 4; ++h) {
      uint32_t a[4];
      const uint32_t qa = sb + SM_QS + row * 128 + (((2 * h + (lane >> 4)) ^ (row & 7)) << 4);
      ldsm_x4(a, qa);
      const uint32_t kp = sb + SM_KV + h * 1088;
      const uint4 k0 = lds128(kp + lane * 16), k1 = lds128(kp + 512 + lane * 16);
      const uint32_t za = kp + 1024 + q * 8;
      auto pk2 = [](uint32_t x, uint32_t y) { return pack_bf16(__uint_as_float(x), __uint_as_float(y)); };
      float n0[4] = {0.f, 0.f, 0.f, 0.f}, n1[4] = {0.f, 0.f, 0.f, 0.f}, dn[4] = {0.f, 0.f, 0.f, 0.f};
      mma_bf16(n0, a[0], a[1], a[2], a[3], pk2(k0.x, k0.y), pk2(k1.x, k1.y));
      mma_bf16(n1, a[0], a[1], a[2], a[3], pk2(k0.z, k0.w), pk2(k1.z, k1.w));
      mma_bf16(dn, a[0], a[1], a[2], a[3], pack_bf16(lds_f32(za), lds_f32(za + 4)), pack_bf16(lds_f32(za + 32), lds_f32(za + 36)));
      const uint32_t dd = pack_bf16(dn[0], dn[2]);
      const uint32_t d2 = pack_bf16(bf_lo(dd) + 1e-6f, bf_hi(dd) + 1e-6f);
      const float r0 = rcp(bf_lo(d2)), r1 = rcp(bf_hi(d2));
      const uint32_t x0 = pack_bf16(n0[0], n0[1]), x1 = pack_bf16(n0[2], n0[3]);
      const uint32_t x2 = pack_bf16(n1[0], n1[1]), x3 = pack_bf16(n1[2], n1[3]);
      stsm_x4(qa, pack_bf16(bf_lo(x0) * r0, bf_hi(x0) * r0), pack_bf16(bf_lo(x1) * r1, bf_hi(x1) * r1),
              pack_bf16(bf_lo(x2) * r0, bf_hi(x2) * r0), pack_bf16(bf_lo(x3) * r1, bf_hi(x3) * r1));
    }
    fence_async_smem();
    __syncwarp();
    if (lane == 0) mbar_arrive(BAR(B_OST));
    if (tid == 128) TS(57);
    mbar_wait_long(BAR(B_WO), 0);
    bar_sync(3, 384);
    {
      float o[32];
#pragma unroll 1
      for (int c = 0; c < 8; ++c) {
        mbar_wait_long(BAR(B_RF + c), 0);
        if (tid == 128) TSR(22, c == 0 ? 22 : 43 + c);
        const uint32_t slot = c < 4 ? SM_QS + c * 16384 : c < 7 ? SM_VV + (c - 4) * 16384 : SM_QS;
        const uint32_t da = mkdesc(sb + slot + (w8 >> 2) * 8192, 16);
        const uint32_t db = mkdesc(sb + SM_WO + c * 8192, 8192);
        wg_fence();
#pragma unroll
        for (int k = 0; k < 4; ++k) wgmma_n64(o, da + 2 * k, db + 128 * k, (c | k) != 0);
        wg_commit();
        if (c == 1) {
          wg_wait<1>();
          if (lane == 0) mbar_arrive(BAR(B_RE));
        }
      }
      wg_wait<0>();
      if (tid == 128) TS(51);
      bar_sync(1, 256);
#pragma unroll
      for (int i = 0; i < 8; i += 2)
        stsm_x4(sb + SM_BOUT + row * 128 + (((i + (lane >> 4)) ^ (row & 7)) << 4), pack_bf16(o[4 * i], o[4 * i + 1]),
                pack_bf16(o[4 * i + 2], o[4 * i + 3]), pack_bf16(o[4 * i + 4], o[4 * i + 5]), pack_bf16(o[4 * i + 6], o[4 * i + 7]));
      fence_async_smem();
      bar_sync(1, 256);
      if (tid == 128) TS(52);
      if (warp == 4 && elect_one()) {
        tma_store_2d(&maps.out, sb + SM_BOUT, 512 + 64 * tj, 128 * ti);
        bulk_commit();
        bulk_wait_read0();
        TS(23);
      }
    }
  } else {
    asm volatile("setmaxnreg.dec.sync.aligned.u32 40;");
    if (warp == 12) {
      if (elect_one()) {
        const unsigned epoch = __ldcg(&g_epoch);
#pragma unroll 1
        for (int ks = NSTG, s = 0, ph = 0; ks < 16; ++ks) {
          mbar_wait(BAR(B_EMPTY + s), ph);
          TSR(38, 31 + ks);
          const uint32_t st = sb + s * STG_BYTES, fb = BAR(B_FULL + s);
          mbar_expect_tx(fb, STG_BYTES);
          tma_load_2d(st + STG_X, &maps.x, ks * 32, ti * 128, fb);
          tma_load_3d_mc(st + STG_W + rank * 6144, &maps.w, tj * 64, ks * 32 + rank * 16, 0, fb, 3);
          if (++s == NSTG) { s = 0; ph ^= 1; }
        }
        mbar_wait(BAR(B_EMPTY + 3), 1);
        mbar_wait(BAR(B_EMPTY + 6), 1);
        mbar_expect_tx(BAR(B_WO), 65536);
        tma_load_2d_mc(sb + SM_WO + rank * 32768, &maps.wo, tj * 64, rank * 256, BAR(B_WO), 3);
        float* kvg = &g_kv[epoch & 1][tj][0];
        mbar_wait_long(BAR(B_KVP), 0);
        bulk_reduce_add_f32(kvg, sb + SM_KV, 4352);
        bulk_commit();
        bulk_wait0();
        red_relaxed_add(&g_cnt[(C_KV + tj) * 32], 1);
        TS(18);
        wait_counter(&g_cnt[(C_KV + tj) * 32], (epoch + 1) * 16);
        mbar_expect_tx(BAR(B_KVF), 4352);
        bulk_load(sb + SM_KV, kvg, 4352, BAR(B_KVF));
        mbar_wait_long(BAR(B_OST), 0);
        tma_store_2d(&maps.o, sb + SM_QS, tj * 64, ti * 128);
        bulk_commit();
        bulk_wait0();
        red_relaxed_add(&g_cnt[(C_O + ti) * 32], 1);
        TS(20);
        wait_counter(&g_cnt[(C_O + ti) * 32], (epoch + 1) * 8);
        if (cta == 0) g_epoch = epoch + 1;
        TS(21);
#pragma unroll 1
        for (int c = 0; c < 8; ++c) {
          if (c == 4) mbar_wait_long(BAR(B_CONVD), 0);
          if (c == 7) mbar_wait(BAR(B_RE), 0);
          const uint32_t slot = c < 4 ? SM_QS + c * 16384 : c < 7 ? SM_VV + (c - 4) * 16384 : SM_QS;
          mbar_expect_tx(BAR(B_RF + c), 16384);
          tma_load_2d(sb + slot, &maps.o, c * 64, ti * 128, BAR(B_RF + c));
        }
      }
    } else if (warp == 13) {
      bar_sync(6, 160);
      sts128(sb + SM_U + (lane >> 4) * U_BYTES + (lane & 15) * 16, 0, 0, 0, 0);
      sts128(sb + SM_U + (2 + (lane >> 4)) * U_BYTES + (lane & 15) * 16, 0, 0, 0, 0);
      __syncwarp();
      if (elect_one()) {
        const unsigned epoch = __ldcg(&g_epoch);
        tma_store_2d(&maps.uT, sb + SM_P, ti * 128, tj * 64);
        tma_store_2d(&maps.uT, sb + SM_P + 8192, ti * 128 + 64, tj * 64);
        bulk_commit();
        bulk_wait_read0();
        mbar_arrive(BAR(B_PFREE));
        bulk_wait0();
        red_relaxed_add(&g_cnt[(C_U + tj) * 32], 1);
        TS(27);
        wait_counter(&g_cnt[(C_U + (cta >> 4)) * 32], (epoch + 1) * 16);
#pragma unroll 1
        for (int c = 0; c < 4; ++c) {
          mbar_expect_tx(BAR(B_UCH + c), 4096);
          bulk_load(sb + SM_U + c * U_BYTES + 256, p.uT + (size_t)(cta * 4 + c) * 2048, 4096, BAR(B_UCH + c));
        }
        TS(3);
      }
      __syncwarp();
      if (ti == 0) {
        float4* z = (float4*)&g_kv[(__ldcg(&g_epoch) & 1) ^ 1][tj][0];
#pragma unroll 1
        for (int i = lane; i < 272; i += 32) z[i] = make_float4(0.f, 0.f, 0.f, 0.f);
      }
    }
  }
  __syncwarp();
  cluster_arrive();
  cluster_wait();
  if (tid == 0) TS(31);
#undef BAR
}

typedef CUresult (*EncodeFn)(CUtensorMap*, CUtensorMapDataType, cuuint32_t, void*, const cuuint64_t*, const cuuint64_t*,
                             const cuuint32_t*, const cuuint32_t*, CUtensorMapInterleave, CUtensorMapSwizzle,
                             CUtensorMapL2promotion, CUtensorMapFloatOOBfill);

static void make_map(EncodeFn enc, CUtensorMap* m, const void* base, uint64_t inner, uint64_t outer, uint32_t box_in,
                     uint32_t box_out, CUtensorMapSwizzle swz = CU_TENSOR_MAP_SWIZZLE_128B) {
  cuuint64_t gd[2] = {inner, outer};
  cuuint64_t gs[1] = {inner * 2};
  cuuint32_t bd[2] = {box_in, box_out};
  cuuint32_t es[2] = {1, 1};
  enc(m, CU_TENSOR_MAP_DATA_TYPE_BFLOAT16, 2, const_cast<void*>(base), gd, gs, bd, es, CU_TENSOR_MAP_INTERLEAVE_NONE,
      swz, CU_TENSOR_MAP_L2_PROMOTION_L2_128B, CU_TENSOR_MAP_FLOAT_OOB_FILL_NONE);
}

}

extern "C" void kernel_launch(void* const* d_in, const int* in_sizes, int n_in, void* d_out, int out_size) {
  using namespace s4la;
  (void)in_sizes; (void)n_in; (void)out_size;
  static EncodeFn enc = nullptr;
  static void *uT = nullptr, *yT = nullptr, *oS = nullptr;
  if (!enc) {
    void* fn = nullptr;
    cudaDriverEntryPointQueryResult qr;
    cudaGetDriverEntryPoint("cuTensorMapEncodeTiled", &fn, cudaEnableDefault, &qr);
    enc = (EncodeFn)fn;
    cudaGetSymbolAddress(&uT, g_uT);
    cudaGetSymbolAddress(&yT, g_yT);
    cudaGetSymbolAddress(&oS, g_o);
    cudaFuncSetAttribute(fused_kernel, cudaFuncAttributeMaxDynamicSharedMemorySize, SM_TOTAL);
  }
  const __nv_bfloat16* const* in = (const __nv_bfloat16* const*)d_in;
  Maps maps;
  make_map(enc, &maps.x, in[9], 512, 2048, 32, 128, CU_TENSOR_MAP_SWIZZLE_64B);
  {
    cuuint64_t gd[3] = {512, 512, 3};
    cuuint64_t gs[2] = {3072, 1024};
    cuuint32_t bd[3] = {64, 16, 3};
    cuuint32_t es[3] = {1, 1, 1};
    enc(&maps.w, CU_TENSOR_MAP_DATA_TYPE_BFLOAT16, 3, const_cast<__nv_bfloat16*>(in[10]), gd, gs, bd, es,
        CU_TENSOR_MAP_INTERLEAVE_NONE, CU_TENSOR_MAP_SWIZZLE_128B, CU_TENSOR_MAP_L2_PROMOTION_L2_128B,
        CU_TENSOR_MAP_FLOAT_OOB_FILL_NONE);
  }
  make_map(enc, &maps.wo, in[11], 512, 512, 64, 256);
  make_map(enc, &maps.u, in[0], 512, 2048, 64, 128);
  make_map(enc, &maps.uT, uT, 2048, 512, 64, 64);
  make_map(enc, &maps.yT, yT, 2048, 512, 64, 64);
  make_map(enc, &maps.o, oS, 512, 2048, 64, 128);
  make_map(enc, &maps.out, d_out, 1024, 2048, 64, 128);
  Ptrs p;
  p.A_re = in[1]; p.A_im = in[2]; p.B_re = in[3]; p.B_im = in[4]; p.C_re = in[5]; p.C_im = in[6];
  p.log_dt = in[7]; p.Dskip = in[8]; p.x = in[9]; p.wqkv = in[10]; p.wo = in[11];
  p.uT = (__nv_bfloat16*)uT; p.yT = (__nv_bfloat16*)yT;
  fused_kernel<<<NCTA, NTHREADS, SM_TOTAL, cudaStreamPerThread>>>(maps, p);
}
```

```cpp
#include <cuda_runtime.h>
#include <cuda_bf16.h>
#include <cuda_fp16.h>
#include <cuda.h>
#include <stdint.h>

#define DEVI __device__ __forceinline__

namespace s4la {

constexpr int NTHREADS = 512;
constexpr int NCTA = 128;

constexpr int NSTG = 7;
constexpr uint32_t STG_BYTES = 20480, STG_X = 0, STG_W = 8192;
constexpr uint32_t SM_QS = 0;
constexpr uint32_t SM_PK = SM_QS + 16384, SM_VS = SM_QS + 32768;
constexpr uint32_t SM_WO = 65536;
constexpr uint32_t SM_KV = 131072;
constexpr uint32_t SM_BOUT = 16384;
constexpr uint32_t SM_U = 143360, U_BYTES = 4352;
constexpr uint32_t SM_P = 160768, P_BYTES = 4096;
constexpr uint32_t SM_VV = 177152, VV_BYTES = 12800;
constexpr uint32_t VV_U5 = 0, VV_U3 = 3712, VV_U9 = 7424, VV_U7 = 10112;
constexpr uint32_t KG_BYTES = 3200;
constexpr uint32_t SM_BAR = SM_VV + 4 * VV_BYTES;
constexpr uint32_t SM_PTAB = SM_BAR + 320;
constexpr uint32_t SM_TOTAL = SM_PTAB + 2048;
static_assert(SM_TOTAL <= 232448, "shared memory");
constexpr int PADV = 12;

enum { B_FULL = 0, B_EMPTY = 7, B_TILE = 14, B_UCH = 15, B_KVP = 19, B_KVF = 20, B_OST = 21, B_RF = 22, B_WO = 30, B_RE = 31, B_PFREE = 32, B_CONVD = 33, B_SLOT = 34, B_COUNT = 35 };
__host__ __device__ constexpr int bar_count(int i) {
  return (i >= B_EMPTY && i < B_TILE) ? 16 : (i == B_KVP || i == B_OST || i == B_CONVD) ? 8 : i == B_RE ? 16 : i == B_SLOT ? 2 : 1;
}

constexpr int PD_OFF = 0, P2_OFF = 544, P3_OFF = 768;

constexpr int SL_K2048 = 20, SL_ZERO = 21, SL_510 = 22, SL_0 = 23;
__host__ __device__ constexpr int koff(int y) {
  return y < 8 ? y : y < 12 ? 256 + 2 * (y - 8) : y < 16 ? 512 + 256 * ((y - 12) >> 1) + 4 * (y & 1) : 1024 + 256 * (y - 16);
}
__host__ __device__ constexpr int kidx_c(int l) {
  const int y = l < 256 ? (l & 7) : l < 512 ? 8 + ((l & 7) >> 1) : l < 1024 ? 12 + (((l - 512) >> 8) << 1) + ((l >> 2) & 1)
                                                                            : 16 + ((l - 1024) >> 8);
  return ((l >> 3) & 31) * 24 + y;
}
constexpr int slot_direct(int l) {
  if (l < 0 || l > 510) return SL_ZERO;
  if (l == 510) return SL_510;
  if (l == 0) return SL_0;
  return kidx_c(l < 256 ? l : ((l + ((l >> 1) & 1)) & ~1));
}
constexpr int slot_seg2(int v, int k) { return (k >= 32 && k < 64) ? kidx_c(16 * k + 4 * v) : SL_ZERO; }
constexpr int slot_seg3(int pi, int k) {
  return (k >= 64 && k < 128) ? kidx_c(16 * k + 8 * pi) : ((k == 128 && pi == 0) ? SL_K2048 : SL_ZERO);
}
constexpr int slot_word(int w) {
  return w < 0 ? SL_ZERO : w < 544 ? slot_direct(w - 16) : w < 768 ? slot_seg2((w - 544) / 56, 16 + (w - 544) % 56)
       : w < 944 ? slot_seg3((w - 768) / 88, 48 + (w - 768) % 88) : SL_ZERO;
}
struct PTab { uint32_t v[512]; };
constexpr PTab make_ptab() {
  PTab t{};
  for (int lane = 0; lane < 32; ++lane)
    for (int i = 0; i < 16; ++i)
      t.v[i * 32 + lane] = (slot_word(31 * lane - 1 + 2 * i) * 4) | ((slot_word(31 * lane + 2 * i) * 4) << 16);
  return t;
}
__device__ const PTab g_ptab = make_ptab();

__device__ __nv_bfloat16 g_uT[512 * 2048];
__device__ __nv_bfloat16 g_yT[512 * 2048];
__device__ __nv_bfloat16 g_o[2048 * 512];
__device__ float g_kv[2][8][4 * 272];
__device__ unsigned g_cnt[64 * 32];
__device__ unsigned g_epoch;
#define TS(slot) do { } while (0)
#define TSR(on, slot) do { } while (0)
#define TSD(slot) do { } while (0)
enum { C_U = 0, C_KV = 8, C_O = 16, C_Y = 32 };

struct Maps {
  CUtensorMap x, w, wo, u, uT, yT, o, out;
};
struct Ptrs {
  const __nv_bfloat16 *A_re, *A_im, *B_re, *B_im, *C_re, *C_im, *log_dt, *Dskip;
  const __nv_bfloat16 *x, *wqkv, *wo;
  __nv_bfloat16 *uT, *yT;
};

DEVI uint32_t s2u(const void* p) { return (uint32_t)__cvta_generic_to_shared(p); }
DEVI void mbar_init(uint32_t b, uint32_t c) { asm volatile("mbarrier.init.shared::cta.b64 [%0], %1;" ::"r"(b), "r"(c) : "memory"); }
DEVI void mbar_expect_tx(uint32_t b, uint32_t bytes) {
  asm volatile("mbarrier.arrive.expect_tx.shared::cta.b64 _, [%0], %1;" ::"r"(b), "r"(bytes) : "memory");
}
DEVI void mbar_arrive(uint32_t b) { asm volatile("mbarrier.arrive.shared::cta.b64 _, [%0];" ::"r"(b) : "memory"); }
DEVI void mbar_arrive_cluster(uint32_t b, uint32_t cta) {
  asm volatile("{\n.reg .b32 r;\nmapa.shared::cluster.u32 r, %0, %1;\nmbarrier.arrive.shared::cluster.b64 _, [r];\n}"
               ::"r"(b), "r"(cta) : "memory");
}
DEVI void mbar_wait(uint32_t b, uint32_t parity) {
  asm volatile("{\n.reg .pred p;\nLAB_WAIT:\nmbarrier.try_wait.parity.shared::cta.b64 p, [%0], %1;\n@!p bra LAB_WAIT;\n}"
               ::"r"(b), "r"(parity) : "memory");
}
DEVI void mbar_wait_long(uint32_t b, uint32_t parity) {
  asm volatile("{\n.reg .pred p;\nLAB_WAIT:\nmbarrier.try_wait.parity.shared::cta.b64 p, [%0], %1, 0x989680;\n@!p bra LAB_WAIT;\n}"
               ::"r"(b), "r"(parity) : "memory");
}
DEVI void bar_sync(int id, int n) { asm volatile("bar.sync %0, %1;" ::"r"(id), "r"(n) : "memory"); }
DEVI void bar_arrive(int id, int n) { asm volatile("bar.arrive %0, %1;" ::"r"(id), "r"(n) : "memory"); }
DEVI void fence_async_smem() { asm volatile("fence.proxy.async.shared::cta;" ::: "memory"); }
DEVI void fence_async_all() { asm volatile("fence.proxy.async;" ::: "memory"); }
DEVI void cluster_arrive() { asm volatile("barrier.cluster.arrive.relaxed.aligned;" ::: "memory"); }
DEVI void cluster_wait() { asm volatile("barrier.cluster.wait.aligned;" ::: "memory"); }

DEVI void tma_load_2d(uint32_t dst, const CUtensorMap* m, int c0, int c1, uint32_t bar) {
  asm volatile("cp.async.bulk.tensor.2d.shared::cluster.global.mbarrier::complete_tx::bytes [%0], [%1, {%3, %4}], [%2];"
               ::"r"(dst), "l"(m), "r"(bar), "r"(c0), "r"(c1) : "memory");
}
DEVI void tma_load_2d_mc(uint32_t dst, const CUtensorMap* m, int c0, int c1, uint32_t bar, uint16_t mask) {
  asm volatile("cp.async.bulk.tensor.2d.shared::cluster.global.mbarrier::complete_tx::bytes.multicast::cluster [%0], [%1, {%3, %4}], [%2], %5;"
               ::"r"(dst), "l"(m), "r"(bar), "r"(c0), "r"(c1), "h"(mask) : "memory");
}
DEVI void tma_load_3d_mc(uint32_t dst, const CUtensorMap* m, int c0, int c1, int c2, uint32_t bar, uint16_t mask) {
  asm volatile("cp.async.bulk.tensor.3d.shared::cluster.global.mbarrier::complete_tx::bytes.multicast::cluster [%0], [%1, {%3, %4, %5}], [%2], %6;"
               ::"r"(dst), "l"(m), "r"(bar), "r"(c0), "r"(c1), "r"(c2), "h"(mask) : "memory");
}
DEVI void tma_store_2d(const CUtensorMap* m, uint32_t src, int c0, int c1) {
  asm volatile("cp.async.bulk.tensor.2d.global.shared::cta.bulk_group [%0, {%2, %3}], [%1];"
               ::"l"(m), "r"(src), "r"(c0), "r"(c1) : "memory");
}
DEVI void bulk_load(uint32_t dst, const void* src, uint32_t bytes, uint32_t bar) {
  asm volatile("cp.async.bulk.shared::cluster.global.mbarrier::complete_tx::bytes [%0], [%1], %2, [%3];"
               ::"r"(dst), "l"(src), "r"(bytes), "r"(bar) : "memory");
}
DEVI void bulk_store(void* dst, uint32_t src, uint32_t bytes) {
  asm volatile("cp.async.bulk.global.shared::cta.bulk_group [%0], [%1], %2;" ::"l"(dst), "r"(src), "r"(bytes) : "memory");
}
DEVI void bulk_reduce_add_f32(void* dst, uint32_t src, uint32_t bytes) {
  asm volatile("cp.reduce.async.bulk.global.shared::cta.bulk_group.add.f32 [%0], [%1], %2;" ::"l"(dst), "r"(src), "r"(bytes) : "memory");
}
DEVI void bulk_commit() { asm volatile("cp.async.bulk.commit_group;" ::: "memory"); }
DEVI void bulk_wait0() { asm volatile("cp.async.bulk.wait_group 0;" ::: "memory"); }
DEVI void bulk_wait_read0() { asm volatile("cp.async.bulk.wait_group.read 0;" ::: "memory"); }
DEVI void l2_prefetch(const void* p, uint32_t bytes) {
  asm volatile("cp.async.bulk.prefetch.L2.global [%0], %1;" ::"l"(p), "r"(bytes) : "memory");
}
DEVI void prefetch_tmap(const CUtensorMap* m) { asm volatile("prefetch.tensormap [%0];" ::"l"(m) : "memory"); }

DEVI void red_release_add(unsigned* p, unsigned v) {
  asm volatile("red.release.gpu.global.add.u32 [%0], %1;" ::"l"(p), "r"(v) : "memory");
}
DEVI void red_relaxed_add(unsigned* p, unsigned v) {
  asm volatile("red.relaxed.gpu.global.add.u32 [%0], %1;" ::"l"(p), "r"(v) : "memory");
}
DEVI unsigned ld_relaxed(const unsigned* p) {
  unsigned v;
  asm volatile("ld.relaxed.gpu.global.u32 %0, [%1];" : "=r"(v) : "l"(p) : "memory");
  return v;
}
DEVI void wait_counter(const unsigned* p, unsigned target) {
#pragma unroll 1
  for (int it = 0; (int)(ld_relaxed(p) - target) < 0; ++it)
    if (it > (1 << 22)) __trap();
}

DEVI void ldsm_x4(uint32_t (&r)[4], uint32_t a) {
  asm volatile("ldmatrix.sync.aligned.m8n8.x4.shared.b16 {%0,%1,%2,%3}, [%4];"
               : "=r"(r[0]), "=r"(r[1]), "=r"(r[2]), "=r"(r[3]) : "r"(a) : "memory");
}
DEVI void ldsm_x4_t(uint32_t (&r)[4], uint32_t a) {
  asm volatile("ldmatrix.sync.aligned.m8n8.x4.trans.shared.b16 {%0,%1,%2,%3}, [%4];"
               : "=r"(r[0]), "=r"(r[1]), "=r"(r[2]), "=r"(r[3]) : "r"(a) : "memory");
}
DEVI void ldsm_x2_t(uint32_t& r0, uint32_t& r1, uint32_t a) {
  asm volatile("ldmatrix.sync.aligned.m8n8.x2.trans.shared.b16 {%0,%1}, [%2];" : "=r"(r0), "=r"(r1) : "r"(a) : "memory");
}
DEVI void stsm_x4(uint32_t a, uint32_t r0, uint32_t r1, uint32_t r2, uint32_t r3) {
  asm volatile("stmatrix.sync.aligned.m8n8.x4.shared.b16 [%0], {%1,%2,%3,%4};"
               ::"r"(a), "r"(r0), "r"(r1), "r"(r2), "r"(r3) : "memory");
}
DEVI void stsm_x4_t(uint32_t a, uint32_t r0, uint32_t r1, uint32_t r2, uint32_t r3) {
  asm volatile("stmatrix.sync.aligned.m8n8.x4.trans.shared.b16 [%0], {%1,%2,%3,%4};"
               ::"r"(a), "r"(r0), "r"(r1), "r"(r2), "r"(r3) : "memory");
}
DEVI uint32_t lds32(uint32_t a) { uint32_t v; asm volatile("ld.shared.b32 %0, [%1];" : "=r"(v) : "r"(a) : "memory"); return v; }
DEVI float lds_f32(uint32_t a) { float v; asm volatile("ld.shared.f32 %0, [%1];" : "=f"(v) : "r"(a) : "memory"); return v; }
DEVI void sts32(uint32_t a, uint32_t v) { asm volatile("st.shared.b32 [%0], %1;" ::"r"(a), "r"(v) : "memory"); }
DEVI void sts_f32(uint32_t a, float v) { asm volatile("st.shared.f32 [%0], %1;" ::"r"(a), "f"(v) : "memory"); }
DEVI void sts_f32x2(uint32_t a, float x, float y) { asm volatile("st.shared.v2.f32 [%0], {%1,%2};" ::"r"(a), "f"(x), "f"(y) : "memory"); }
DEVI uint4 lds128(uint32_t a) {
  uint4 v;
  asm volatile("ld.shared.v4.b32 {%0,%1,%2,%3}, [%4];" : "=r"(v.x), "=r"(v.y), "=r"(v.z), "=r"(v.w) : "r"(a) : "memory");
  return v;
}
DEVI void sts128(uint32_t a, uint32_t x, uint32_t y, uint32_t z, uint32_t w) {
  asm volatile("st.shared.v4.b32 [%0], {%1,%2,%3,%4};" ::"r"(a), "r"(x), "r"(y), "r"(z), "r"(w) : "memory");
}

DEVI void mma_bf16(float (&d)[4], uint32_t a0, uint32_t a1, uint32_t a2, uint32_t a3, uint32_t b0, uint32_t b1) {
  asm("mma.sync.aligned.m16n8k16.row.col.f32.bf16.bf16.f32 {%0,%1,%2,%3}, {%4,%5,%6,%7}, {%8,%9}, {%0,%1,%2,%3};"
      : "+f"(d[0]), "+f"(d[1]), "+f"(d[2]), "+f"(d[3])
      : "r"(a0), "r"(a1), "r"(a2), "r"(a3), "r"(b0), "r"(b1));
}
DEVI void mma_f16(float (&d)[4], const uint32_t (&a)[4], uint32_t b0, uint32_t b1) {
  asm("mma.sync.aligned.m16n8k16.row.col.f32.f16.f16.f32 {%0,%1,%2,%3}, {%4,%5,%6,%7}, {%8,%9}, {%0,%1,%2,%3};"
      : "+f"(d[0]), "+f"(d[1]), "+f"(d[2]), "+f"(d[3])
      : "r"(a[0]), "r"(a[1]), "r"(a[2]), "r"(a[3]), "r"(b0), "r"(b1));
}
DEVI void mma_bf16v(float (&d)[4], const uint32_t (&a)[4], uint32_t b0, uint32_t b1) {
  asm volatile("mma.sync.aligned.m16n8k16.row.col.f32.bf16.bf16.f32 {%0,%1,%2,%3}, {%4,%5,%6,%7}, {%8,%9}, {%0,%1,%2,%3};"
               : "+f"(d[0]), "+f"(d[1]), "+f"(d[2]), "+f"(d[3])
               : "r"(a[0]), "r"(a[1]), "r"(a[2]), "r"(a[3]), "r"(b0), "r"(b1));
}
DEVI uint32_t pack_bf16(float lo, float hi) {
  uint32_t r;
  asm("cvt.rn.bf16x2.f32 %0, %1, %2;" : "=r"(r) : "f"(hi), "f"(lo));
  return r;
}
DEVI uint32_t pack_f16(float lo, float hi) {
  uint32_t r;
  asm("cvt.rn.f16x2.f32 %0, %1, %2;" : "=r"(r) : "f"(hi), "f"(lo));
  return r;
}
DEVI uint32_t ldg16(const __nv_bfloat16* p) {
  uint32_t v;
  asm volatile("ld.global.nc.u16 %0, [%1];" : "=r"(v) : "l"(p));
  return v;
}
DEVI bool elect_one() {
  uint32_t pred;
  asm volatile("{\n.reg .pred p;\nelect.sync _|p, 0xffffffff;\nselp.u32 %0, 1, 0, p;\n}" : "=r"(pred));
  return pred != 0;
}
DEVI float bf_lo(uint32_t v) { return __uint_as_float(v << 16); }
DEVI float bf_hi(uint32_t v) { return __uint_as_float(v & 0xffff0000u); }
DEVI float bf2f(__nv_bfloat16 v) { return __bfloat162float(v); }
DEVI float round_bf16(float v) { return __bfloat162float(__float2bfloat16_rn(v)); }
DEVI float rcp(float x) { float r; asm("rcp.approx.ftz.f32 %0, %1;" : "=f"(r) : "f"(x)); return r; }
DEVI float ex2(float x) { float r; asm("ex2.approx.ftz.f32 %0, %1;" : "=f"(r) : "f"(x)); return r; }

DEVI void wg_fence() { asm volatile("wgmma.fence.sync.aligned;" ::: "memory"); }
DEVI void wg_commit() { asm volatile("wgmma.commit_group.sync.aligned;" ::: "memory"); }
template <int N> DEVI void wg_wait() { asm volatile("wgmma.wait_group.sync.aligned %0;" ::"n"(N) : "memory"); }
constexpr uint32_t DESC_HI = (1u << 30) | (1024 >> 4);
constexpr uint32_t DESC_HI64 = (2u << 30) | (512 >> 4);
DEVI uint32_t mkdesc(uint32_t saddr, uint32_t lbo) { return ((saddr & 0x3FFFF) >> 4) | ((lbo >> 4) << 16); }

#define R8(b) "%" #b
DEVI void wgmma_n192(float (&d)[96], uint32_t da, uint32_t db, int scale_d) {
  asm volatile(
      "{\n.reg .pred p;\n.reg .b64 da, db;\nsetp.ne.b32 p, %98, 0;\nmov.b64 da, {%96, %100};\nmov.b64 db, {%97, %99};\n"
      "wgmma.mma_async.sync.aligned.m64n192k16.f32.bf16.bf16 "
      "{%0,%1,%2,%3,%4,%5,%6,%7,%8,%9,%10,%11,%12,%13,%14,%15,"
      "%16,%17,%18,%19,%20,%21,%22,%23,%24,%25,%26,%27,%28,%29,%30,%31,"
      "%32,%33,%34,%35,%36,%37,%38,%39,%40,%41,%42,%43,%44,%45,%46,%47,"
      "%48,%49,%50,%51,%52,%53,%54,%55,%56,%57,%58,%59,%60,%61,%62,%63,"
      "%64,%65,%66,%67,%68,%69,%70,%71,%72,%73,%74,%75,%76,%77,%78,%79,"
      "%80,%81,%82,%83,%84,%85,%86,%87,%88,%89,%90,%91,%92,%93,%94,%95}, "
      "da, db, p, 1, 1, 0, 1;\n}"
      : "+f"(d[0]), "+f"(d[1]), "+f"(d[2]), "+f"(d[3]), "+f"(d[4]), "+f"(d[5]), "+f"(d[6]), "+f"(d[7]),
        "+f"(d[8]), "+f"(d[9]), "+f"(d[10]), "+f"(d[11]), "+f"(d[12]), "+f"(d[13]), "+f"(d[14]), "+f"(d[15]),
        "+f"(d[16]), "+f"(d[17]), "+f"(d[18]), "+f"(d[19]), "+f"(d[20]), "+f"(d[21]), "+f"(d[22]), "+f"(d[23]),
        "+f"(d[24]), "+f"(d[25]), "+f"(d[26]), "+f"(d[27]), "+f"(d[28]), "+f"(d[29]), "+f"(d[30]), "+f"(d[31]),
        "+f"(d[32]), "+f"(d[33]), "+f"(d[34]), "+f"(d[35]), "+f"(d[36]), "+f"(d[37]), "+f"(d[38]), "+f"(d[39]),
        "+f"(d[40]), "+f"(d[41]), "+f"(d[42]), "+f"(d[43]), "+f"(d[44]), "+f"(d[45]), "+f"(d[46]), "+f"(d[47]),
        "+f"(d[48]), "+f"(d[49]), "+f"(d[50]), "+f"(d[51]), "+f"(d[52]), "+f"(d[53]), "+f"(d[54]), "+f"(d[55]),
        "+f"(d[56]), "+f"(d[57]), "+f"(d[58]), "+f"(d[59]), "+f"(d[60]), "+f"(d[61]), "+f"(d[62]), "+f"(d[63]),
        "+f"(d[64]), "+f"(d[65]), "+f"(d[66]), "+f"(d[67]), "+f"(d[68]), "+f"(d[69]), "+f"(d[70]), "+f"(d[71]),
        "+f"(d[72]), "+f"(d[73]), "+f"(d[74]), "+f"(d[75]), "+f"(d[76]), "+f"(d[77]), "+f"(d[78]), "+f"(d[79]),
        "+f"(d[80]), "+f"(d[81]), "+f"(d[82]), "+f"(d[83]), "+f"(d[84]), "+f"(d[85]), "+f"(d[86]), "+f"(d[87]),
        "+f"(d[88]), "+f"(d[89]), "+f"(d[90]), "+f"(d[91]), "+f"(d[92]), "+f"(d[93]), "+f"(d[94]), "+f"(d[95])
      : "r"(da), "r"(db), "r"(scale_d), "n"(DESC_HI), "n"(DESC_HI64));
}
DEVI void wgmma_n64(float (&d)[32], uint32_t da, uint32_t db, int scale_d) {
  asm volatile(
      "{\n.reg .pred p;\n.reg .b64 da, db;\nsetp.ne.b32 p, %34, 0;\nmov.b64 da, {%32, %35};\nmov.b64 db, {%33, %35};\n"
      "wgmma.mma_async.sync.aligned.m64n64k16.f32.bf16.bf16 "
      "{%0,%1,%2,%3,%4,%5,%6,%7,%8,%9,%10,%11,%12,%13,%14,%15,"
      "%16,%17,%18,%19,%20,%21,%22,%23,%24,%25,%26,%27,%28,%29,%30,%31}, "
      "da, db, p, 1, 1, 0, 1;\n}"
      : "+f"(d[0]), "+f"(d[1]), "+f"(d[2]), "+f"(d[3]), "+f"(d[4]), "+f"(d[5]), "+f"(d[6]), "+f"(d[7]),
        "+f"(d[8]), "+f"(d[9]), "+f"(d[10]), "+f"(d[11]), "+f"(d[12]), "+f"(d[13]), "+f"(d[14]), "+f"(d[15]),
        "+f"(d[16]), "+f"(d[17]), "+f"(d[18]), "+f"(d[19]), "+f"(d[20]), "+f"(d[21]), "+f"(d[22]), "+f"(d[23]),
        "+f"(d[24]), "+f"(d[25]), "+f"(d[26]), "+f"(d[27]), "+f"(d[28]), "+f"(d[29]), "+f"(d[30]), "+f"(d[31])
      : "r"(da), "r"(db), "r"(scale_d), "n"(DESC_HI));
}

struct C32 { float re, im; };
DEVI C32 csq(C32 a) { return {a.re * a.re - a.im * a.im, 2.f * a.re * a.im}; }
DEVI C32 cmul(C32 a, C32 b) { return {a.re * b.re - a.im * b.im, a.re * b.im + a.im * b.re}; }
DEVI C32 cfresh(float zl, float zi, float m) {
  float mag = ex2(zl * m), ph = zi * m;
  return {mag * __cosf(ph), mag * __sinf(ph)};
}
struct HMul { uint32_t b, bp; };
DEVI HMul mk_mul(float re, float im) { return {pack_f16(re, im), pack_f16(-im, re)}; }
DEVI uint32_t hcmul(uint32_t a, const HMul& m) {
  __half2 ah = *reinterpret_cast<__half2*>(&a);
  __half2 b = *reinterpret_cast<const __half2*>(&m.b), bp = *reinterpret_cast<const __half2*>(&m.bp);
  __half2 r = __hfma2(__high2half2(ah), bp, __hmul2(__low2half2(ah), b));
  return *reinterpret_cast<uint32_t*>(&r);
}
DEVI uint32_t badd(uint32_t a, uint32_t b) {
  __nv_bfloat162 r = __hadd2(*reinterpret_cast<__nv_bfloat162*>(&a), *reinterpret_cast<__nv_bfloat162*>(&b));
  return *reinterpret_cast<uint32_t*>(&r);
}
template <int MU0, int NMU, int DMAX>
DEVI void conv_tail(float (&acc)[16][4], uint32_t p_lane, uint32_t v_base, int back, bool edge, int lane) {
  const int hsel = (lane >> 3) & 1;
  const int row = (lane & 7) + ((lane >> 4) << 3) + PADV - 8 - (back & (hsel ^ 1));
  const uint32_t la = v_base + row * 32 + (((hsel ^ back) ^ ((row >> 2) & 1)) << 4);
  uint32_t M[3][4];
  ldsm_x4_t(M[0], la);
  ldsm_x4_t(M[1], la + 256);
  uint32_t H[2 * NMU];
#pragma unroll
  for (int i = 0; i < 2 * NMU; ++i) H[i ^ 1] = lds32(p_lane + (uint32_t)(MU0 - 1 + i) * 32);
  if (edge) {
    const uint32_t a[4] = {0u, 0u, M[0][0], M[0][1]};
#pragma unroll
    for (int k = 1; k < NMU; ++k) mma_bf16v(acc[MU0 - 2 + 2 * k], a, H[2 * k], H[2 * k + 1]);
  }
#pragma unroll
  for (int delta = -1; delta <= DMAX; ++delta) {
    if (delta + 2 <= DMAX) ldsm_x4_t(M[(delta + 3) % 3], la + (delta + 3) * 256);
#pragma unroll
    for (int k = 0; k < NMU; ++k)
      if (delta + MU0 + 2 * k < 16) mma_bf16v(acc[delta + MU0 + 2 * k], M[(delta + 1) % 3], H[2 * k], H[2 * k + 1]);
  }
}

__global__ void __cluster_dims__(2, 1, 1) __launch_bounds__(NTHREADS, 1)
fused_kernel(const __grid_constant__ Maps maps, const Ptrs p) {
  extern __shared__ __align__(1024) uint8_t smem[];
  const uint32_t sb = s2u(smem);
  const int tid = threadIdx.x, lane = tid & 31;
  const int warp = __shfl_sync(0xffffffffu, tid >> 5, 0);
  const int cta = blockIdx.x;
  const uint32_t rank = cta & 1;
  const int ti = 2 * (cta >> 4) + rank;
  const int tj = (cta >> 1) & 7;
  const int pi = cta >> 3, pj = cta & 7;
  const uint32_t bars = sb + SM_BAR;
#define BAR(i) (bars + 8 * (i))
  const int g = lane >> 2, q = lane & 3;

  const int kch = warp & 3, krd = warp >> 2;
  float zr, zi, wr, wi;
  unsigned epoch;
  uint32_t r_dskip;
  {
    const size_t po = (size_t)(cta * 4 + kch) * 128 + krd * 32 + lane;
    const uint32_t r_ar = ldg16(p.A_re + po), r_ai = ldg16(p.A_im + po), r_br = ldg16(p.B_re + po), r_bi = ldg16(p.B_im + po);
    const uint32_t r_cr = ldg16(p.C_re + po), r_ci = ldg16(p.C_im + po), r_ldt = ldg16(p.log_dt + cta * 4 + kch);
    epoch = __ldcg(&g_epoch);
    r_dskip = ldg16(p.Dskip + cta * 4 + kch);
    uint4 pt;
    if (tid < 128) pt = __ldg((const uint4*)g_ptab.v + tid);
    if (tid == 384) {
      TS(0);
#pragma unroll
      for (int i = 0; i < B_COUNT; ++i) mbar_init(BAR(i), bar_count(i));
      asm volatile("fence.mbarrier_init.release.cluster;" ::: "memory");
      prefetch_tmap(&maps.x); prefetch_tmap(&maps.w); prefetch_tmap(&maps.u);
    }
    __syncthreads();
    cluster_arrive();
    if (warp >= 12) {
      cluster_wait();
      if (elect_one()) {
        if (warp == 13) {
          mbar_expect_tx(BAR(B_TILE), 16384);
          tma_load_2d(sb + SM_U, &maps.u, tj * 64, ti * 128, BAR(B_TILE));
          l2_prefetch((const char*)p.wqkv + 224 * 3072 + cta * 6912, 6912);
          l2_prefetch((const char*)p.x + (size_t)cta * 16384, 16384);
          l2_prefetch((const char*)p.wo + (size_t)cta * 4096, 4096);
        } else {
          if (warp == 12) TS(61);
#pragma unroll 1
          for (int ks = warp == 12 ? 0 : warp - 13; ks < NSTG; ks += 3) {
            const uint32_t st = sb + ks * STG_BYTES, fb = BAR(B_FULL + ks);
            mbar_expect_tx(fb, STG_BYTES);
            tma_load_2d(st + STG_X, &maps.x, ks * 32, ti * 128, fb);
            tma_load_3d_mc(st + STG_W + rank * 6144, &maps.w, tj * 64, ks * 32 + rank * 16, 0, fb, 3);
          }
          if (warp == 15) {
            prefetch_tmap(&maps.uT); prefetch_tmap(&maps.wo); prefetch_tmap(&maps.o); prefetch_tmap(&maps.yT);
            prefetch_tmap(&maps.out);
          }
        }
      }
      __syncwarp();
    }
    if (tid < 128) sts128(sb + SM_PTAB + tid * 16, pt.x, pt.y, pt.z, pt.w);
    const float dt = round_bf16(expf(bf_lo(r_ldt)));
    zr = dt * bf_lo(r_ar); zi = dt * bf_lo(r_ai);
    const float dbr = dt * bf_lo(r_br), dbi = dt * bf_lo(r_bi), cr = bf_lo(r_cr), ci = bf_lo(r_ci);
    wr = cr * dbr - ci * dbi; wi = cr * dbi + ci * dbr;
  }
  {
    const float mz = __uint_as_float(__reduce_max_sync(0xffffffffu, __float_as_uint(fmaxf(zr, 0.f))));
    const int E = min(max((int)(__reduce_max_sync(0xffffffffu, __float_as_uint(fmaxf(fabsf(wr), fabsf(wi)))) >> 23), 1), 252);
    const float sc = __int_as_float((253 - E) << 23), inv = __int_as_float((E + 1) << 23);
    const float zl = (zr - mz) * 1.4426950408889634f;
    const uint32_t tb = sb + SM_VV + kch * VV_BYTES + krd * KG_BYTES;
    const uint32_t sta = tb + (((lane >> 2) << 4) | ((lane & 3) << 2));
    auto put = [&](int r, uint32_t v) { sts32((sta ^ ((r & 7) << 4)) + r * 128, v); };
    const uint32_t lda = tb + ((lane & 7) + (((lane >> 3) & 1) << 3)) * 128;
    const uint32_t ldb = tb + ((lane & 7) + ((lane >> 4) << 3)) * 128;
    C32 e1 = cfresh(zl, zi, 1.f), e2 = csq(e1), e4 = csq(e2), e8 = csq(e4);
    C32 e16 = cfresh(zl, zi, 16.f), e32 = csq(e16), e64 = csq(e32), e128 = csq(e64);
    C32 e256 = cfresh(zl, zi, 256.f), e512 = csq(e256), e1024 = csq(e512), e768 = cmul(e512, e256);
    uint32_t XA[2][4][4];
    {
      const HMul m16 = mk_mul(e16.re, e16.im), m32 = mk_mul(e32.re, e32.im), m64 = mk_mul(e64.re, e64.im);
      const HMul m128 = mk_mul(e128.re, e128.im);
      uint32_t X[16];
      X[0] = 0x00003c00u; X[1] = pack_f16(e8.re, e8.im); X[2] = m16.b; X[4] = m32.b; X[8] = m64.b;
      X[3] = hcmul(X[1], m16); X[5] = hcmul(X[1], m32); X[6] = hcmul(X[2], m32); X[7] = hcmul(X[3], m32);
#pragma unroll
      for (int r = 1; r < 8; ++r) X[8 + r] = hcmul(X[r], m64);
#pragma unroll
      for (int h = 0; h < 2; ++h) {
#pragma unroll
        for (int r = 0; r < 16; ++r) put(r, h == 0 ? X[r] : r == 0 ? m128.b : hcmul(X[r], m128));
        __syncwarp();
#pragma unroll
        for (int k = 0; k < 4; ++k) ldsm_x4(XA[h][k], lda + (((2 * k + (lane >> 4)) ^ (lane & 7)) << 4));
        __syncwarp();
      }
    }
    float D[2][3][4];
#pragma unroll
    for (int t = 0; t < 6; ++t) D[t / 3][t % 3][0] = D[t / 3][t % 3][1] = D[t / 3][t % 3][2] = D[t / 3][t % 3][3] = 0.f;
    auto contract = [&](int t0, int nt) {
      __syncwarp();
#pragma unroll
      for (int k = 0; k < 4; ++k) {
        uint32_t b[4];
        ldsm_x4(b, ldb + (((2 * k + ((lane >> 3) & 1)) ^ (lane & 7)) << 4));
#pragma unroll
        for (int h = 0; h < 2; ++h) {
          mma_f16(D[h][t0], XA[h][k], b[0], b[1]);
          if (nt == 2) mma_f16(D[h][t0 + 1], XA[h][k], b[2], b[3]);
        }
      }
      __syncwarp();
    };
    const HMul c1 = mk_mul(e1.re, -e1.im), c2 = mk_mul(e2.re, -e2.im), c4 = mk_mul(e4.re, -e4.im);
    const HMul c256 = mk_mul(e256.re, -e256.im), c512 = mk_mul(e512.re, -e512.im), c768 = mk_mul(e768.re, -e768.im);
    const HMul c1024 = mk_mul(e1024.re, -e1024.im);
    uint32_t W[8];
    W[0] = pack_f16(wr * sc, -wi * sc);
    W[1] = hcmul(W[0], c1); W[2] = hcmul(W[0], c2); W[3] = hcmul(W[1], c2);
    W[4] = hcmul(W[0], c4); W[5] = hcmul(W[1], c4); W[6] = hcmul(W[2], c4); W[7] = hcmul(W[3], c4);
#pragma unroll
    for (int i = 0; i < 8; ++i) put(i, W[i]);
#pragma unroll
    for (int i = 0; i < 4; ++i) put(8 + i, hcmul(W[2 * i], c256));
    put(12, hcmul(W[0], c512)); put(13, hcmul(W[4], c512)); put(14, hcmul(W[0], c768)); put(15, hcmul(W[4], c768));
    contract(0, 2);
    const uint32_t v0 = hcmul(W[0], c1024);
    put(0, v0); put(1, hcmul(v0, c256)); put(2, hcmul(v0, c512)); put(3, hcmul(v0, c768)); put(4, hcmul(v0, c1024));
    contract(2, 1);
    const uint32_t a = tb + (g * 24 + 2 * q) * 4;
#pragma unroll
    for (int t = 0; t < 6; ++t) {
      const float(&d)[4] = D[t / 3][t % 3];
      sts_f32x2(a + (t / 3) * 1536 + (t % 3) * 32, d[0] * inv, d[1] * inv);
      sts_f32x2(a + (t / 3) * 1536 + (t % 3) * 32 + 768, d[2] * inv, d[3] * inv);
    }
    if (mz > 0.f) {
      __syncwarp();
#pragma unroll 1
      for (int i = lane; i < 768; i += 32) {
        const int r = i / 24, y = i - 24 * r;
        sts_f32(tb + i * 4, lds_f32(tb + i * 4) * ex2(mz * 1.4426950408889634f * (koff(y) + 8 * r)));
      }
    }
  }
  if (tid == 0) TS(2);
  if (warp < 12) cluster_wait();
  if (tid == 0) TS(32);
  __syncthreads();
  if (tid == 0) TSD(33);

  if (warp < 4) {
    asm volatile("setmaxnreg.inc.sync.aligned.u32 152;");
    if (tid == 0) TS(34);
    const int d = cta * 4 + warp;
    const uint32_t vv = sb + SM_VV + warp * VV_BYTES;
    const uint32_t ub = sb + SM_U + warp * U_BYTES;
    const uint32_t pb = sb + SM_P + warp * P_BYTES;
    const float dskip = bf_lo(r_dskip);
#pragma unroll 1
    for (int pass = 0; pass < 2; ++pass) {
      if (pass == 1) {
        const uint32_t kf = vv;
#pragma unroll 2
        for (int i = 0; i < 6; ++i) {
          const uint32_t a = kf + (i * 32 + lane) * 16;
          const uint4 x0 = lds128(a), x1 = lds128(a + KG_BYTES), x2 = lds128(a + 2 * KG_BYTES), x3 = lds128(a + 3 * KG_BYTES);
          auto s4 = [](uint32_t a0, uint32_t a1, uint32_t a2, uint32_t a3) {
            return __float_as_uint((__uint_as_float(a0) + __uint_as_float(a1)) + (__uint_as_float(a2) + __uint_as_float(a3)));
          };
          sts128(a, s4(x0.x, x1.x, x2.x, x3.x), s4(x0.y, x1.y, x2.y, x3.y), s4(x0.z, x1.z, x2.z, x3.z), s4(x0.w, x1.w, x2.w, x3.w));
        }
        __syncwarp();
        const float k1024 = lds_f32(kf + kidx_c(1024) * 4);
        if (lane == 0) {
          sts_f32(kf + SL_ZERO * 4, 0.f);
          sts_f32(kf + SL_510 * 4, lds_f32(kf + kidx_c(510) * 4) - lds_f32(kf + kidx_c(512) * 4));
          sts_f32(kf + SL_0 * 4, lds_f32(kf) + dskip);
        }
        __syncwarp();
        if (tid == 0) TS(36);
        mbar_wait_long(BAR(B_PFREE), 0);
        if (tid == 0) TS(37);
        {
          float prev = 0.f;
#pragma unroll 1
          for (int i0 = 0; i0 < 16; i0 += 4) {
            uint32_t e[4];
            float a[4], b[4];
#pragma unroll
            for (int i = 0; i < 4; ++i) e[i] = lds32(sb + SM_PTAB + ((i0 + i) * 32 + lane) * 4);
#pragma unroll
            for (int i = 0; i < 4; ++i) { a[i] = lds_f32(kf + (e[i] & 0xffff)); b[i] = lds_f32(kf + (e[i] >> 16)); }
#pragma unroll
            for (int i = 0; i < 4; ++i) {
              const uint32_t w = pb + (31 * lane + 2 * (i0 + i)) * 4;
              if (i0 + i > 0) sts32(w - 4, pack_bf16(a[i], prev));
              sts32(w, pack_bf16(b[i], a[i]));
              prev = b[i];
            }
          }
        }
        __syncwarp();
        bar_arrive(7, 384);
        if (lane == 0) TS(4);
        const int gq = g - 2 * q;
        uint32_t h127, h128;
        {
          const uint32_t kf2 = pack_bf16(k1024, k1024) ^ 0x80008000u;
          h127 = (gq == 4 ? 0x0000ffffu : gq == 5 ? 0xffffffffu : gq == 6 ? 0xffff0000u : 0u) & kf2;
          h128 = (gq == -4 ? 0x0000ffffu : gq == -3 ? 0xffffffffu : gq == -2 ? 0xffff0000u : 0u) & kf2;
        }
        bar_sync(4, 384);
        mbar_wait_long(BAR(B_UCH + warp), 0);
        if (lane == 0) TS(7);
        float acc[16][4];
#pragma unroll
        for (int i = 0; i < 16; ++i) { acc[i][0] = acc[i][1] = acc[i][2] = acc[i][3] = 0.f; }
        {
          const uint32_t pd_lane = pb + (PD_OFF + 16 + gq) * 4;
          const int prow0 = 8 + (lane & 7) + ((lane >> 4) << 3), hs = (lane >> 3) & 1;
          uint32_t B[2][4][4];
          uint32_t A[4][4];
          const uint32_t la0 = ub + prow0 * 32 + ((hs ^ ((prow0 >> 2) & 1)) << 4);
#pragma unroll
          for (int m2 = 0; m2 < 4; ++m2) ldsm_x4(B[0][m2], la0 + m2 * 512);
#pragma unroll
          for (int i = 0; i < 4; ++i) {
            const uint32_t a = pd_lane + i * 512;
            A[i][0] = lds32(a); A[i][1] = lds32(a + 32); A[i][2] = lds32(a - 32); A[i][3] = A[i][0];
          }
          uint32_t la = la0;
#pragma unroll 1
          for (int rho = 0; rho < 8; ++rho) {
#pragma unroll
            for (int m2 = 0; m2 < 4; ++m2) ldsm_x4(B[1][m2], la + (4 + m2) * 512);
#pragma unroll
            for (int i = 0; i < 4; ++i)
#pragma unroll
              for (int m = 0; m < 8; ++m) mma_bf16v(acc[m + i], A[i], B[0][m >> 1][2 * (m & 1)], B[0][m >> 1][2 * (m & 1) + 1]);
            const int prow = prow0 - min(rho + 1, 7);
            la = ub + prow * 32 + ((hs ^ ((prow >> 2) & 1)) << 4);
#pragma unroll
            for (int m2 = 0; m2 < 4; ++m2) ldsm_x4(B[0][m2], la + m2 * 512);
            const uint32_t pa = pd_lane + (rho + 1) * 64;
#pragma unroll
            for (int i = 0; i < 4; ++i) {
#pragma unroll
              for (int m = 0; m < 8 - i; ++m)
                mma_bf16v(acc[8 + m + i], A[i], B[1][m >> 1][2 * (m & 1)], B[1][m >> 1][2 * (m & 1) + 1]);
              A[i][0] = lds32(pa + i * 512); A[i][1] = lds32(pa + i * 512 + 32); A[i][2] = lds32(pa + i * 512 - 32);
              A[i][3] = A[i][0];
            }
          }
          if (lane == 0) TS(40);
          {
            uint32_t b8[4];
            ldsm_x4(b8, la + 4 * 512);
            const uint32_t h63 = lds32(pd_lane + 63 * 32), h64 = lds32(pd_lane + 64 * 32);
            const uint32_t a63[4] = {0u, h127, 0u, 0u}, a32[4] = {h64, 0u, h63, h64}, a64[4] = {h128, 0u, h127, h128};
#pragma unroll
            for (int m2 = 0; m2 < 4; ++m2) ldsm_x4(B[1][m2], la0 + m2 * 512);
#pragma unroll
            for (int m = 0; m < 8; ++m) mma_bf16v(acc[m + 7], a63, B[0][m >> 1][2 * (m & 1)], B[0][m >> 1][2 * (m & 1) + 1]);
#pragma unroll
            for (int m2 = 0; m2 < 2; ++m2) ldsm_x4(B[0][m2], la0 + (4 + m2) * 512);
#pragma unroll
            for (int m = 0; m < 8; ++m) mma_bf16v(acc[m + 4], a32, B[1][m >> 1][2 * (m & 1)], B[1][m >> 1][2 * (m & 1) + 1]);
            mma_bf16v(acc[15], a63, b8[0], b8[1]);
#pragma unroll
            for (int m = 0; m < 8; ++m) mma_bf16v(acc[m + 8], a64, B[1][m >> 1][2 * (m & 1)], B[1][m >> 1][2 * (m & 1) + 1]);
#pragma unroll
            for (int m = 0; m < 4; ++m) mma_bf16v(acc[m + 12], a32, B[0][m >> 1][2 * (m & 1)], B[0][m >> 1][2 * (m & 1) + 1]);
          }
          if (lane == 0) TS(41);
          bar_sync(5, 384);
#pragma unroll 1
          for (int v = 0; v < 4; ++v)
            conv_tail<4, 3, 11>(acc, pb + (P2_OFF + 56 * v + gq - 16) * 4, vv + ((v & 1) ? VV_U3 : VV_U5), v >> 1, v == 0, lane);
          if (lane == 0) TS(42);
#pragma unroll 1
          for (int pi = 0; pi < 2; ++pi)
            conv_tail<8, 5, 7>(acc, pb + (P3_OFF + 88 * pi + gq - 48) * 4, vv + (pi ? VV_U7 : VV_U9), pi, pi == 0, lane);
        }
        if (lane == 0) TS(8);
        __syncwarp();
        {
          const int mt = lane >> 3;
          const uint32_t a = pb + (128 * (mt >> 1) + 16 * (lane & 7) + 8 * (mt & 1)) * 2;
#pragma unroll
          for (int ab = 0; ab < 16; ab += 2)
            stsm_x4_t(a + ab * 256, pack_bf16(acc[ab][0], acc[ab][1]), pack_bf16(acc[ab][2], acc[ab][3]),
                      pack_bf16(acc[ab + 1][0], acc[ab + 1][1]), pack_bf16(acc[ab + 1][2], acc[ab + 1][3]));
        }
        fence_async_smem();
        __syncwarp();
        if (lane < 2) mbar_arrive_cluster(BAR(B_CONVD), lane);
        bar_arrive(3, 384);
        if (elect_one()) {
          bulk_store(p.yT + (size_t)d * 2048, pb, 4096);
          bulk_commit();
          bulk_wait0();
          red_relaxed_add(&g_cnt[(C_Y + (cta >> 4)) * 32], 1);
          TS(9);
        }
        bar_sync(2, 128);
        if (warp == 0 && elect_one()) {
          wait_counter(&g_cnt[(C_Y + tj) * 32], (epoch + 1) * 64);
          TS(28);
          mbar_expect_tx(BAR(B_TILE), 16384);
          tma_load_2d(sb + SM_U, &maps.yT, ti * 128, tj * 64, BAR(B_TILE));
          tma_load_2d(sb + SM_U + 8192, &maps.yT, ti * 128 + 64, tj * 64, BAR(B_TILE));
        }
        __syncwarp();
      }
      mbar_wait_long(BAR(B_TILE), pass);
      if (lane == 0) TS(26 + 3 * pass);
      {
        const int m = lane >> 3, r = lane & 7;
#pragma unroll 2
        for (int it = 0; it < 8; ++it) {
          const int tb = warp * 4 + (it >> 1), cb = (it & 1) * 4 + m;
          const uint32_t at = (tb * 8 + r) * 128 + ((cb ^ r) << 4);
          const uint32_t ac = (tb >> 3) * 8192 + (cb * 8 + r) * 128 + (((tb & 7) ^ (pass ? 0 : tb >> 3) ^ r) << 4);
          uint32_t v[4];
          ldsm_x4_t(v, sb + SM_U + (pass ? ac : at));
          stsm_x4(sb + SM_P + (pass ? at : ac), v[0], v[1], v[2], v[3]);
        }
      }
      if (pass == 0 && tid == 0) TS(35);
      fence_async_smem();
      if (pass == 0) {
        bar_arrive(6, 160);
      } else {
        bar_sync(2, 128);
        if (warp == 0 && elect_one()) {
          tma_store_2d(&maps.out, sb + SM_P, 64 * tj, 128 * ti);
          bulk_commit();
          bulk_wait_read0();
          TS(30);
        }
      }
    }
  } else if (warp < 12) {
    asm volatile("setmaxnreg.inc.sync.aligned.u32 160;");
    const int w8 = warp - 4;
    const int row = w8 * 16 + (lane & 7) + (((lane >> 3) & 1) << 3);
    {
      float acc[96];
#pragma unroll 1
      for (int ks = 0, s = 0, ph = 0; ks < 16; ++ks) {
        mbar_wait(BAR(B_FULL + s), ph);
        if (tid == 128 && !(ks & 1)) TSR(16, ks == 0 ? 16 : 9 + (ks >> 1) + (ks > 12 ? 46 : 0));
        const uint32_t st = sb + s * STG_BYTES;
        const uint32_t da = mkdesc(st + STG_X + (w8 >> 2) * 4096, 16);
        const uint32_t db = mkdesc(st + STG_W, 2048);
        wg_fence();
        wgmma_n192(acc, da, db, ks != 0);
        wgmma_n192(acc, da + 2, db + 384, 1);
        wg_commit();
        const uint32_t eprev = BAR(B_EMPTY + (s == 0 ? NSTG - 1 : s - 1));
        if (++s == NSTG) { s = 0; ph ^= 1; }
        if (ks > 0) {
          wg_wait<1>();
          if (lane < 2) mbar_arrive_cluster(eprev, lane);
        }
      }
      wg_wait<0>();
      bar_arrive(4, 384);
      if (tid == 128) TS(17);
      bar_sync(1, 256);
#pragma unroll
      for (int i = 0; i < 24; i += 2)
        stsm_x4(sb + SM_QS + row * 128 + (i >> 3) * 16384 + ((((i & 7) + (lane >> 4)) ^ (row & 7)) << 4),
                pack_bf16(acc[4 * i], acc[4 * i + 1]), pack_bf16(acc[4 * i + 2], acc[4 * i + 3]),
                pack_bf16(acc[4 * i + 4], acc[4 * i + 5]), pack_bf16(acc[4 * i + 6], acc[4 * i + 7]));
    }
    __syncwarp();
#pragma unroll 1
    for (int part = 1; part >= 0; --part) {
      const uint32_t pa = sb + SM_QS + part * 16384 + w8 * 2048 + lane * 16;
#pragma unroll 1
      for (int it = 0; it < 4; ++it) {
        uint4 t = lds128(pa + it * 512);
        uint32_t* tw = &t.x;
#pragma unroll
        for (int j = 0; j < 4; ++j) {
          const uint32_t x = tw[j];
          const __nv_bfloat162 xb = *reinterpret_cast<const __nv_bfloat162*>(&x);
          const uint32_t e = pack_bf16(ex2(bf_lo(x) * 1.4426950408889634f), ex2(bf_hi(x) * 1.4426950408889634f));
          const uint32_t m = __hgt2_mask(xb, __floats2bfloat162_rn(0.f, 0.f));
          const uint32_t sel = (badd(x, 0x3f803f80u) & m) | (e & ~m);
          tw[j] = pack_bf16(bf_lo(sel) + 1e-6f, bf_hi(sel) + 1e-6f);
        }
        sts128(pa + it * 512, t.x, t.y, t.z, t.w);
      }
      if (part == 1) {
        if (tid == 128) TS(53);
        bar_sync(1, 256);
        const int hh = w8 >> 1, dtile = w8 & 1;
        float kv[4] = {0.f, 0.f, 0.f, 0.f}, zz[4] = {0.f, 0.f, 0.f, 0.f};
        const int m = lane >> 3;
        const uint32_t aa = sb + SM_VS + ((lane & 7) + ((m >> 1) << 3)) * 128 + (((2 * hh + (m & 1)) ^ (lane & 7)) << 4);
        const uint32_t ab = sb + SM_PK + (lane & 15) * 128 + (((2 * hh + dtile) ^ (lane & 7)) << 4);
#pragma unroll 2
        for (int ks = 0; ks < 8; ++ks) {
          uint32_t a[4], b0, b1;
          ldsm_x4_t(a, aa + ks * 2048);
          ldsm_x2_t(b0, b1, ab + ks * 2048);
          mma_bf16(kv, a[0], a[1], a[2], a[3], b0, b1);
          mma_bf16(zz, 0x3f803f80u, 0x3f803f80u, 0x3f803f80u, 0x3f803f80u, b0, b1);
        }
        const uint32_t kp = sb + SM_KV + hh * 1088;
        sts128(kp + dtile * 512 + lane * 16, __float_as_uint(kv[0]), __float_as_uint(kv[1]), __float_as_uint(kv[2]),
               __float_as_uint(kv[3]));
        if (g == 0) sts_f32x2(kp + 1024 + dtile * 32 + q * 8, zz[0], zz[1]);
        fence_async_smem();
        __syncwarp();
        if (lane == 0) mbar_arrive(BAR(B_KVP));
        if (tid == 128) TS(55);
      }
    }
    if (tid == 128) TS(56);
    {
      const int ch = w8 >> 1;
      bar_sync(7, 384);
      mbar_wait_long(BAR(B_UCH + ch), 0);
#pragma unroll 1
      for (int it = w8 & 1; it < 8; it += 2) {
          const int k = -18 + it * 32 + lane;
          const int kr = min(max(k, -2), 208);
          uint32_t E[12];
#pragma unroll
          for (int c = 0; c < 3; ++c) {
            const int kk = kr - 1 + c, r = (kk >> 1) + 8;
            const uint4 t = lds128(sb + SM_U + ch * U_BYTES + r * 32 + (((kk & 1) ^ ((r >> 2) & 1)) << 4));
            E[4 * c] = t.x; E[4 * c + 1] = t.y; E[4 * c + 2] = t.z; E[4 * c + 3] = t.w;
          }
          uint32_t O[8];
#pragma unroll
          for (int j = 0; j < 8; ++j) O[j] = __byte_perm(E[j + 1], E[j + 2], 0x5432);
          uint32_t s3[6], s5[4], s7[4], s9[4];
#pragma unroll
          for (int j = 0; j < 6; ++j) s3[j] = badd(badd(O[j], O[j + 1]), E[j + 2]);
#pragma unroll
          for (int j = 0; j < 4; ++j) {
            s5[j] = badd(s3[j + 2], badd(E[j + 3], E[j + 5]));
            s7[j] = badd(s5[j], badd(O[j + 1], O[j + 4]));
            s9[j] = badd(s7[j], badd(E[j + 2], E[j + 6]));
          }
          const int r = (k >> 1) + PADV;
          const uint32_t a = sb + SM_VV + ch * VV_BYTES + r * 32 + (((k & 1) ^ ((r >> 2) & 1)) << 4);
          if (k < 208) { sts128(a + VV_U3, s3[0], s3[1], s3[2], s3[3]); sts128(a + VV_U5, s5[0], s5[1], s5[2], s5[3]); }
          if (k < 144) { sts128(a + VV_U7, s7[0], s7[1], s7[2], s7[3]); sts128(a + VV_U9, s9[0], s9[1], s9[2], s9[3]); }
      }
      bar_arrive(5, 384);
    }
    if (tid == 128) TS(6);
    mbar_wait_long(BAR(B_KVF), 0);
    if (tid == 128) TS(19);
#pragma unroll 1
    for (int h = 0; h < 4; ++h) {
      uint32_t a[4];
      const uint32_t qa = sb + SM_QS + row * 128 + (((2 * h + (lane >> 4)) ^ (row & 7)) << 4);
      ldsm_x4(a, qa);
      const uint32_t kp = sb + SM_KV + h * 1088;
      const uint4 k0 = lds128(kp + lane * 16), k1 = lds128(kp + 512 + lane * 16);
      const uint32_t za = kp + 1024 + q * 8;
      auto pk2 = [](uint32_t x, uint32_t y) { return pack_bf16(__uint_as_float(x), __uint_as_float(y)); };
      float n0[4] = {0.f, 0.f, 0.f, 0.f}, n1[4] = {0.f, 0.f, 0.f, 0.f}, dn[4] = {0.f, 0.f, 0.f, 0.f};
      mma_bf16(n0, a[0], a[1], a[2], a[3], pk2(k0.x, k0.y), pk2(k1.x, k1.y));
      mma_bf16(n1, a[0], a[1], a[2], a[3], pk2(k0.z, k0.w), pk2(k1.z, k1.w));
      mma_bf16(dn, a[0], a[1], a[2], a[3], pack_bf16(lds_f32(za), lds_f32(za + 4)), pack_bf16(lds_f32(za + 32), lds_f32(za + 36)));
      const uint32_t dd = pack_bf16(dn[0], dn[2]);
      const uint32_t d2 = pack_bf16(bf_lo(dd) + 1e-6f, bf_hi(dd) + 1e-6f);
      const float r0 = rcp(bf_lo(d2)), r1 = rcp(bf_hi(d2));
      const uint32_t x0 = pack_bf16(n0[0], n0[1]), x1 = pack_bf16(n0[2], n0[3]);
      const uint32_t x2 = pack_bf16(n1[0], n1[1]), x3 = pack_bf16(n1[2], n1[3]);
      stsm_x4(qa, pack_bf16(bf_lo(x0) * r0, bf_hi(x0) * r0), pack_bf16(bf_lo(x1) * r1, bf_hi(x1) * r1),
              pack_bf16(bf_lo(x2) * r0, bf_hi(x2) * r0), pack_bf16(bf_lo(x3) * r1, bf_hi(x3) * r1));
    }
    fence_async_smem();
    __syncwarp();
    if (lane == 0) mbar_arrive(BAR(B_OST));
    if (tid == 128) TS(57);
    mbar_wait_long(BAR(B_WO), 0);
    bar_sync(3, 384);
    {
      float o[32];
#pragma unroll 1
      for (int c = 0; c < 8; ++c) {
        mbar_wait_long(BAR(B_RF + c), 0);
        if (tid == 128) TSR(22, c == 0 ? 22 : 43 + c);
        const uint32_t slot = c < 4 ? SM_QS + c * 16384 : c < 7 ? SM_VV + (c - 4) * 16384 : SM_QS;
        const uint32_t da = mkdesc(sb + slot + (w8 >> 2) * 8192, 16);
        const uint32_t db = mkdesc(sb + SM_WO + c * 8192, 8192);
        wg_fence();
#pragma unroll
        for (int k = 0; k < 4; ++k) wgmma_n64(o, da + 2 * k, db + 128 * k, (c | k) != 0);
        wg_commit();
        if (c == 1) {
          wg_wait<1>();
          if (lane < 2) mbar_arrive_cluster(BAR(B_RE), lane);
        }
      }
      wg_wait<0>();
      if (tid == 128) TS(51);
      bar_sync(1, 256);
#pragma unroll
      for (int i = 0; i < 8; i += 2)
        stsm_x4(sb + SM_BOUT + row * 128 + (((i + (lane >> 4)) ^ (row & 7)) << 4), pack_bf16(o[4 * i], o[4 * i + 1]),
                pack_bf16(o[4 * i + 2], o[4 * i + 3]), pack_bf16(o[4 * i + 4], o[4 * i + 5]), pack_bf16(o[4 * i + 6], o[4 * i + 7]));
      fence_async_smem();
      bar_sync(1, 256);
      if (tid == 128) TS(52);
      if (warp == 4 && elect_one()) {
        tma_store_2d(&maps.out, sb + SM_BOUT, 512 + 64 * pj, 128 * pi);
        bulk_commit();
        bulk_wait_read0();
        TS(23);
      }
    }
  } else {
    asm volatile("setmaxnreg.dec.sync.aligned.u32 40;");
    if (warp == 12) {
      if (elect_one()) {
#pragma unroll 1
        for (int ks = NSTG, s = 0, ph = 0; ks < 16; ++ks) {
          mbar_wait(BAR(B_EMPTY + s), ph);
          TSR(38, 31 + ks);
          const uint32_t st = sb + s * STG_BYTES, fb = BAR(B_FULL + s);
          mbar_expect_tx(fb, STG_BYTES);
          tma_load_2d(st + STG_X, &maps.x, ks * 32, ti * 128, fb);
          tma_load_3d_mc(st + STG_W + rank * 6144, &maps.w, tj * 64, ks * 32 + rank * 16, 0, fb, 3);
          if (++s == NSTG) { s = 0; ph ^= 1; }
        }
        mbar_wait(BAR(B_EMPTY + 6), 1);
        mbar_expect_tx(BAR(B_WO), 65536);
        tma_load_2d(sb + SM_WO, &maps.wo, pj * 64, 0, BAR(B_WO));
        tma_load_2d(sb + SM_WO + 32768, &maps.wo, pj * 64, 256, BAR(B_WO));
        float* kvg = &g_kv[epoch & 1][tj][0];
        mbar_wait_long(BAR(B_KVP), 0);
        bulk_reduce_add_f32(kvg, sb + SM_KV, 4352);
        bulk_commit();
        bulk_wait0();
        red_relaxed_add(&g_cnt[(C_KV + tj) * 32], 1);
        TS(18);
        wait_counter(&g_cnt[(C_KV + tj) * 32], (epoch + 1) * 16);
        mbar_expect_tx(BAR(B_KVF), 4352);
        bulk_load(sb + SM_KV, kvg, 4352, BAR(B_KVF));
        mbar_wait_long(BAR(B_OST), 0);
        tma_store_2d(&maps.o, sb + SM_QS, tj * 64, ti * 128);
        tma_store_2d(&maps.o, sb + SM_QS + 8192, tj * 64, ti * 128 + 64);
        bulk_commit();
        bulk_wait0();
        red_relaxed_add(&g_cnt[(C_O + ti) * 32], 1);
        TS(20);
        mbar_arrive_cluster(BAR(B_SLOT), 0);
        mbar_arrive_cluster(BAR(B_SLOT), 1);
        wait_counter(&g_cnt[(C_O + pi) * 32], (epoch + 1) * 8);
        if (cta == 0) g_epoch = epoch + 1;
        mbar_wait(BAR(B_SLOT), 0);
        TS(21);
#pragma unroll 1
        for (int c = 0; c < 8; ++c) {
          if (c == 4) mbar_wait_long(BAR(B_CONVD), 0);
          if (c == 7) mbar_wait(BAR(B_RE), 0);
          const uint32_t slot = c < 4 ? SM_QS + c * 16384 : c < 7 ? SM_VV + (c - 4) * 16384 : SM_QS;
          mbar_expect_tx(BAR(B_RF + c), 16384);
          tma_load_2d_mc(sb + slot + rank * 8192, &maps.o, c * 64, pi * 128 + rank * 64, BAR(B_RF + c), 3);
        }
      }
    } else if (warp == 13) {
      bar_sync(6, 160);
      sts128(sb + SM_U + (lane >> 4) * U_BYTES + (lane & 15) * 16, 0, 0, 0, 0);
      sts128(sb + SM_U + (2 + (lane >> 4)) * U_BYTES + (lane & 15) * 16, 0, 0, 0, 0);
      __syncwarp();
      if (elect_one()) {
        tma_store_2d(&maps.uT, sb + SM_P, ti * 128, tj * 64);
        tma_store_2d(&maps.uT, sb + SM_P + 8192, ti * 128 + 64, tj * 64);
        bulk_commit();
        bulk_wait_read0();
        mbar_arrive(BAR(B_PFREE));
        bulk_wait0();
        red_relaxed_add(&g_cnt[(C_U + tj) * 32], 1);
        TS(27);
        wait_counter(&g_cnt[(C_U + (cta >> 4)) * 32], (epoch + 1) * 16);
#pragma unroll 1
        for (int c = 0; c < 4; ++c) {
          mbar_expect_tx(BAR(B_UCH + c), 4096);
          bulk_load(sb + SM_U + c * U_BYTES + 256, p.uT + (size_t)(cta * 4 + c) * 2048, 4096, BAR(B_UCH + c));
        }
        TS(3);
      }
      __syncwarp();
      if (ti == 0) {
        float4* z = (float4*)&g_kv[(epoch & 1) ^ 1][tj][0];
#pragma unroll 1
        for (int i = lane; i < 272; i += 32) z[i] = make_float4(0.f, 0.f, 0.f, 0.f);
      }
    }
  }
  __syncwarp();
  cluster_arrive();
  cluster_wait();
  if (tid == 0) TS(31);
#undef BAR
}

typedef CUresult (*EncodeFn)(CUtensorMap*, CUtensorMapDataType, cuuint32_t, void*, const cuuint64_t*, const cuuint64_t*,
                             const cuuint32_t*, const cuuint32_t*, CUtensorMapInterleave, CUtensorMapSwizzle,
                             CUtensorMapL2promotion, CUtensorMapFloatOOBfill);

static void make_map(EncodeFn enc, CUtensorMap* m, const void* base, uint64_t inner, uint64_t outer, uint32_t box_in,
                     uint32_t box_out, CUtensorMapSwizzle swz = CU_TENSOR_MAP_SWIZZLE_128B) {
  cuuint64_t gd[2] = {inner, outer};
  cuuint64_t gs[1] = {inner * 2};
  cuuint32_t bd[2] = {box_in, box_out};
  cuuint32_t es[2] = {1, 1};
  enc(m, CU_TENSOR_MAP_DATA_TYPE_BFLOAT16, 2, const_cast<void*>(base), gd, gs, bd, es, CU_TENSOR_MAP_INTERLEAVE_NONE,
      swz, CU_TENSOR_MAP_L2_PROMOTION_L2_128B, CU_TENSOR_MAP_FLOAT_OOB_FILL_NONE);
}

}

extern "C" void kernel_launch(void* const* d_in, const int* in_sizes, int n_in, void* d_out, int out_size) {
  using namespace s4la;
  (void)in_sizes; (void)n_in; (void)out_size;
  static EncodeFn enc = nullptr;
  static void *uT = nullptr, *yT = nullptr, *oS = nullptr;
  if (!enc) {
    void* fn = nullptr;
    cudaDriverEntryPointQueryResult qr;
    cudaGetDriverEntryPoint("cuTensorMapEncodeTiled", &fn, cudaEnableDefault, &qr);
    enc = (EncodeFn)fn;
    cudaGetSymbolAddress(&uT, g_uT);
    cudaGetSymbolAddress(&yT, g_yT);
    cudaGetSymbolAddress(&oS, g_o);
    cudaFuncSetAttribute(fused_kernel, cudaFuncAttributeMaxDynamicSharedMemorySize, SM_TOTAL);
  }
  const __nv_bfloat16* const* in = (const __nv_bfloat16* const*)d_in;
  Maps maps;
  make_map(enc, &maps.x, in[9], 512, 2048, 32, 128, CU_TENSOR_MAP_SWIZZLE_64B);
  {
    cuuint64_t gd[3] = {512, 512, 3};
    cuuint64_t gs[2] = {3072, 1024};
    cuuint32_t bd[3] = {64, 16, 3};
    cuuint32_t es[3] = {1, 1, 1};
    enc(&maps.w, CU_TENSOR_MAP_DATA_TYPE_BFLOAT16, 3, const_cast<__nv_bfloat16*>(in[10]), gd, gs, bd, es,
        CU_TENSOR_MAP_INTERLEAVE_NONE, CU_TENSOR_MAP_SWIZZLE_128B, CU_TENSOR_MAP_L2_PROMOTION_L2_128B,
        CU_TENSOR_MAP_FLOAT_OOB_FILL_NONE);
  }
  make_map(enc, &maps.wo, in[11], 512, 512, 64, 256);
  make_map(enc, &maps.u, in[0], 512, 2048, 64, 128);
  make_map(enc, &maps.uT, uT, 2048, 512, 64, 64);
  make_map(enc, &maps.yT, yT, 2048, 512, 64, 64);
  make_map(enc, &maps.o, oS, 512, 2048, 64, 64);
  make_map(enc, &maps.out, d_out, 1024, 2048, 64, 128);
  Ptrs p;
  p.A_re = in[1]; p.A_im = in[2]; p.B_re = in[3]; p.B_im = in[4]; p.C_re = in[5]; p.C_im = in[6];
  p.log_dt = in[7]; p.Dskip = in[8]; p.x = in[9]; p.wqkv = in[10]; p.wo = in[11];
  p.uT = (__nv_bfloat16*)uT; p.yT = (__nv_bfloat16*)yT;
  fused_kernel<<<NCTA, NTHREADS, SM_TOTAL, cudaStreamPerThread>>>(maps, p);
}
```

```cpp
#include <cuda_runtime.h>
#include <cuda_bf16.h>
#include <cuda_fp16.h>
#include <cuda.h>
#include <stdint.h>

#define DEVI __device__ __forceinline__

namespace s4la {

constexpr int NTHREADS = 512;
constexpr int NCTA = 128;

constexpr int NSTG = 7;
constexpr uint32_t STG_BYTES = 20480, STG_X = 0, STG_W = 8192;
constexpr uint32_t SM_QS = 0;
constexpr uint32_t SM_PK = SM_QS + 16384, SM_VS = SM_QS + 32768;
constexpr uint32_t SM_WO = 65536;
constexpr uint32_t SM_KV = 131072;
constexpr uint32_t SM_BOUT = 16384;
constexpr uint32_t SM_U = 143360, U_BYTES = 4352;
constexpr uint32_t SM_P = 160768, P_BYTES = 4096;
constexpr uint32_t SM_VV = 177152, VV_BYTES = 12800;
constexpr uint32_t VV_U5 = 0, VV_U3 = 3712, VV_U9 = 7424, VV_U7 = 10112;
constexpr uint32_t KG_BYTES = 3200;
constexpr uint32_t SM_BAR = SM_VV + 4 * VV_BYTES;
constexpr uint32_t SM_PTAB = SM_BAR + 320;
constexpr uint32_t SM_TOTAL = SM_PTAB + 2048;
static_assert(SM_TOTAL <= 232448, "shared memory");
constexpr int PADV = 12;

enum { B_FULL = 0, B_EMPTY = 7, B_TILE = 14, B_UCH = 15, B_KVP = 19, B_KVF = 20, B_OST = 21, B_RF = 22, B_WO = 30, B_RE = 31, B_PFREE = 32, B_CONVD = 33, B_SLOT = 34, B_COUNT = 35 };
__host__ __device__ constexpr int bar_count(int i) {
  return (i >= B_EMPTY && i < B_TILE) ? 16 : (i == B_KVP || i == B_OST || i == B_CONVD) ? 8 : i == B_RE ? 16 : i == B_SLOT ? 2 : 1;
}

constexpr int PD_OFF = 0, P2_OFF = 544, P3_OFF = 768;

constexpr int SL_K2048 = 20, SL_ZERO = 21, SL_510 = 22, SL_0 = 23;
__host__ __device__ constexpr int koff(int y) {
  return y < 8 ? y : y < 12 ? 256 + 2 * (y - 8) : y < 16 ? 512 + 256 * ((y - 12) >> 1) + 4 * (y & 1) : 1024 + 256 * (y - 16);
}
__host__ __device__ constexpr int kidx_c(int l) {
  const int y = l < 256 ? (l & 7) : l < 512 ? 8 + ((l & 7) >> 1) : l < 1024 ? 12 + (((l - 512) >> 8) << 1) + ((l >> 2) & 1)
                                                                            : 16 + ((l - 1024) >> 8);
  return ((l >> 3) & 31) * 24 + y;
}
constexpr int slot_direct(int l) {
  if (l < 0 || l > 510) return SL_ZERO;
  if (l == 510) return SL_510;
  if (l == 0) return SL_0;
  return kidx_c(l < 256 ? l : ((l + ((l >> 1) & 1)) & ~1));
}
constexpr int slot_seg2(int v, int k) { return (k >= 32 && k < 64) ? kidx_c(16 * k + 4 * v) : SL_ZERO; }
constexpr int slot_seg3(int pi, int k) {
  return (k >= 64 && k < 128) ? kidx_c(16 * k + 8 * pi) : ((k == 128 && pi == 0) ? SL_K2048 : SL_ZERO);
}
constexpr int slot_word(int w) {
  return w < 0 ? SL_ZERO : w < 544 ? slot_direct(w - 16) : w < 768 ? slot_seg2((w - 544) / 56, 16 + (w - 544) % 56)
       : w < 944 ? slot_seg3((w - 768) / 88, 48 + (w - 768) % 88) : SL_ZERO;
}
struct PTab { uint32_t v[512]; };
constexpr PTab make_ptab() {
  PTab t{};
  for (int lane = 0; lane < 32; ++lane)
    for (int i = 0; i < 16; ++i)
      t.v[i * 32 + lane] = (slot_word(31 * lane - 1 + 2 * i) * 4) | ((slot_word(31 * lane + 2 * i) * 4) << 16);
  return t;
}
__device__ const PTab g_ptab = make_ptab();

__device__ __nv_bfloat16 g_uT[512 * 2048];
__device__ __nv_bfloat16 g_yT[512 * 2048];
__device__ __nv_bfloat16 g_o[2048 * 512];
__device__ float g_kv[2][8][4 * 272];
__device__ unsigned g_cnt[64 * 32];
__device__ unsigned g_epoch;
#define TS(slot) do { } while (0)
#define TSR(on, slot) do { } while (0)
#define TSD(slot) do { } while (0)
enum { C_U = 0, C_KV = 8, C_O = 16, C_Y = 32 };

struct Maps {
  CUtensorMap x, w, wo, u, uT, yT, o, out;
};
struct Ptrs {
  const __nv_bfloat16 *A_re, *A_im, *B_re, *B_im, *C_re, *C_im, *log_dt, *Dskip;
  const __nv_bfloat16 *x, *wqkv, *wo;
  __nv_bfloat16 *uT, *yT;
};

DEVI uint32_t s2u(const void* p) { return (uint32_t)__cvta_generic_to_shared(p); }
DEVI void mbar_init(uint32_t b, uint32_t c) { asm volatile("mbarrier.init.shared::cta.b64 [%0], %1;" ::"r"(b), "r"(c) : "memory"); }
DEVI void mbar_expect_tx(uint32_t b, uint32_t bytes) {
  asm volatile("mbarrier.arrive.expect_tx.shared::cta.b64 _, [%0], %1;" ::"r"(b), "r"(bytes) : "memory");
}
DEVI void mbar_arrive(uint32_t b) { asm volatile("mbarrier.arrive.shared::cta.b64 _, [%0];" ::"r"(b) : "memory"); }
DEVI void mbar_arrive_cluster(uint32_t b, uint32_t cta) {
  asm volatile("{\n.reg .b32 r;\nmapa.shared::cluster.u32 r, %0, %1;\nmbarrier.arrive.shared::cluster.b64 _, [r];\n}"
               ::"r"(b), "r"(cta) : "memory");
}
DEVI void mbar_wait(uint32_t b, uint32_t parity) {
  asm volatile("{\n.reg .pred p;\nLAB_WAIT:\nmbarrier.try_wait.parity.shared::cta.b64 p, [%0], %1;\n@!p bra LAB_WAIT;\n}"
               ::"r"(b), "r"(parity) : "memory");
}
DEVI void mbar_wait_long(uint32_t b, uint32_t parity) {
  asm volatile("{\n.reg .pred p;\nLAB_WAIT:\nmbarrier.try_wait.parity.shared::cta.b64 p, [%0], %1, 0x989680;\n@!p bra LAB_WAIT;\n}"
               ::"r"(b), "r"(parity) : "memory");
}
DEVI void bar_sync(int id, int n) { asm volatile("bar.sync %0, %1;" ::"r"(id), "r"(n) : "memory"); }
DEVI void bar_arrive(int id, int n) { asm volatile("bar.arrive %0, %1;" ::"r"(id), "r"(n) : "memory"); }
DEVI void fence_async_smem() { asm volatile("fence.proxy.async.shared::cta;" ::: "memory"); }
DEVI void fence_async_all() { asm volatile("fence.proxy.async;" ::: "memory"); }
DEVI void cluster_arrive() { asm volatile("barrier.cluster.arrive.relaxed.aligned;" ::: "memory"); }
DEVI void cluster_wait() { asm volatile("barrier.cluster.wait.aligned;" ::: "memory"); }

DEVI void tma_load_2d(uint32_t dst, const CUtensorMap* m, int c0, int c1, uint32_t bar) {
  asm volatile("cp.async.bulk.tensor.2d.shared::cluster.global.mbarrier::complete_tx::bytes [%0], [%1, {%3, %4}], [%2];"
               ::"r"(dst), "l"(m), "r"(bar), "r"(c0), "r"(c1) : "memory");
}
DEVI void tma_load_2d_mc(uint32_t dst, const CUtensorMap* m, int c0, int c1, uint32_t bar, uint16_t mask) {
  asm volatile("cp.async.bulk.tensor.2d.shared::cluster.global.mbarrier::complete_tx::bytes.multicast::cluster [%0], [%1, {%3, %4}], [%2], %5;"
               ::"r"(dst), "l"(m), "r"(bar), "r"(c0), "r"(c1), "h"(mask) : "memory");
}
DEVI void tma_load_3d_mc(uint32_t dst, const CUtensorMap* m, int c0, int c1, int c2, uint32_t bar, uint16_t mask) {
  asm volatile("cp.async.bulk.tensor.3d.shared::cluster.global.mbarrier::complete_tx::bytes.multicast::cluster [%0], [%1, {%3, %4, %5}], [%2], %6;"
               ::"r"(dst), "l"(m), "r"(bar), "r"(c0), "r"(c1), "r"(c2), "h"(mask) : "memory");
}
DEVI void tma_store_2d(const CUtensorMap* m, uint32_t src, int c0, int c1) {
  asm volatile("cp.async.bulk.tensor.2d.global.shared::cta.bulk_group [%0, {%2, %3}], [%1];"
               ::"l"(m), "r"(src), "r"(c0), "r"(c1) : "memory");
}
DEVI void bulk_load(uint32_t dst, const void* src, uint32_t bytes, uint32_t bar) {
  asm volatile("cp.async.bulk.shared::cluster.global.mbarrier::complete_tx::bytes [%0], [%1], %2, [%3];"
               ::"r"(dst), "l"(src), "r"(bytes), "r"(bar) : "memory");
}
DEVI void bulk_store(void* dst, uint32_t src, uint32_t bytes) {
  asm volatile("cp.async.bulk.global.shared::cta.bulk_group [%0], [%1], %2;" ::"l"(dst), "r"(src), "r"(bytes) : "memory");
}
DEVI void bulk_reduce_add_f32(void* dst, uint32_t src, uint32_t bytes) {
  asm volatile("cp.reduce.async.bulk.global.shared::cta.bulk_group.add.f32 [%0], [%1], %2;" ::"l"(dst), "r"(src), "r"(bytes) : "memory");
}
DEVI void bulk_commit() { asm volatile("cp.async.bulk.commit_group;" ::: "memory"); }
DEVI void bulk_wait0() { asm volatile("cp.async.bulk.wait_group 0;" ::: "memory"); }
DEVI void bulk_wait_read0() { asm volatile("cp.async.bulk.wait_group.read 0;" ::: "memory"); }
DEVI void l2_prefetch(const void* p, uint32_t bytes) {
  asm volatile("cp.async.bulk.prefetch.L2.global [%0], %1;" ::"l"(p), "r"(bytes) : "memory");
}
DEVI void prefetch_tmap(const CUtensorMap* m) { asm volatile("prefetch.tensormap [%0];" ::"l"(m) : "memory"); }

DEVI void red_release_add(unsigned* p, unsigned v) {
  asm volatile("red.release.gpu.global.add.u32 [%0], %1;" ::"l"(p), "r"(v) : "memory");
}
DEVI void red_relaxed_add(unsigned* p, unsigned v) {
  asm volatile("red.relaxed.gpu.global.add.u32 [%0], %1;" ::"l"(p), "r"(v) : "memory");
}
DEVI unsigned ld_relaxed(const unsigned* p) {
  unsigned v;
  asm volatile("ld.relaxed.gpu.global.u32 %0, [%1];" : "=r"(v) : "l"(p) : "memory");
  return v;
}
DEVI void wait_counter(const unsigned* p, unsigned target) {
#pragma unroll 1
  for (int it = 0; (int)(ld_relaxed(p) - target) < 0; ++it)
    if (it > (1 << 22)) __trap();
}

DEVI void ldsm_x4(uint32_t (&r)[4], uint32_t a) {
  asm volatile("ldmatrix.sync.aligned.m8n8.x4.shared.b16 {%0,%1,%2,%3}, [%4];"
               : "=r"(r[0]), "=r"(r[1]), "=r"(r[2]), "=r"(r[3]) : "r"(a) : "memory");
}
DEVI void ldsm_x4_t(uint32_t (&r)[4], uint32_t a) {
  asm volatile("ldmatrix.sync.aligned.m8n8.x4.trans.shared.b16 {%0,%1,%2,%3}, [%4];"
               : "=r"(r[0]), "=r"(r[1]), "=r"(r[2]), "=r"(r[3]) : "r"(a) : "memory");
}
DEVI void ldsm_x2_t(uint32_t& r0, uint32_t& r1, uint32_t a) {
  asm volatile("ldmatrix.sync.aligned.m8n8.x2.trans.shared.b16 {%0,%1}, [%2];" : "=r"(r0), "=r"(r1) : "r"(a) : "memory");
}
DEVI void stsm_x4(uint32_t a, uint32_t r0, uint32_t r1, uint32_t r2, uint32_t r3) {
  asm volatile("stmatrix.sync.aligned.m8n8.x4.shared.b16 [%0], {%1,%2,%3,%4};"
               ::"r"(a), "r"(r0), "r"(r1), "r"(r2), "r"(r3) : "memory");
}
DEVI void stsm_x4_t(uint32_t a, uint32_t r0, uint32_t r1, uint32_t r2, uint32_t r3) {
  asm volatile("stmatrix.sync.aligned.m8n8.x4.trans.shared.b16 [%0], {%1,%2,%3,%4};"
               ::"r"(a), "r"(r0), "r"(r1), "r"(r2), "r"(r3) : "memory");
}
DEVI uint32_t lds32(uint32_t a) { uint32_t v; asm volatile("ld.shared.b32 %0, [%1];" : "=r"(v) : "r"(a) : "memory"); return v; }
DEVI float lds_f32(uint32_t a) { float v; asm volatile("ld.shared.f32 %0, [%1];" : "=f"(v) : "r"(a) : "memory"); return v; }
DEVI void sts32(uint32_t a, uint32_t v) { asm volatile("st.shared.b32 [%0], %1;" ::"r"(a), "r"(v) : "memory"); }
DEVI void sts_f32(uint32_t a, float v) { asm volatile("st.shared.f32 [%0], %1;" ::"r"(a), "f"(v) : "memory"); }
DEVI void sts_f32x2(uint32_t a, float x, float y) { asm volatile("st.shared.v2.f32 [%0], {%1,%2};" ::"r"(a), "f"(x), "f"(y) : "memory"); }
DEVI uint4 lds128(uint32_t a) {
  uint4 v;
  asm volatile("ld.shared.v4.b32 {%0,%1,%2,%3}, [%4];" : "=r"(v.x), "=r"(v.y), "=r"(v.z), "=r"(v.w) : "r"(a) : "memory");
  return v;
}
DEVI void sts128(uint32_t a, uint32_t x, uint32_t y, uint32_t z, uint32_t w) {
  asm volatile("st.shared.v4.b32 [%0], {%1,%2,%3,%4};" ::"r"(a), "r"(x), "r"(y), "r"(z), "r"(w) : "memory");
}

DEVI void mma_bf16(float (&d)[4], uint32_t a0, uint32_t a1, uint32_t a2, uint32_t a3, uint32_t b0, uint32_t b1) {
  asm("mma.sync.aligned.m16n8k16.row.col.f32.bf16.bf16.f32 {%0,%1,%2,%3}, {%4,%5,%6,%7}, {%8,%9}, {%0,%1,%2,%3};"
      : "+f"(d[0]), "+f"(d[1]), "+f"(d[2]), "+f"(d[3])
      : "r"(a0), "r"(a1), "r"(a2), "r"(a3), "r"(b0), "r"(b1));
}
DEVI void mma_f16(float (&d)[4], const uint32_t (&a)[4], uint32_t b0, uint32_t b1) {
  asm("mma.sync.aligned.m16n8k16.row.col.f32.f16.f16.f32 {%0,%1,%2,%3}, {%4,%5,%6,%7}, {%8,%9}, {%0,%1,%2,%3};"
      : "+f"(d[0]), "+f"(d[1]), "+f"(d[2]), "+f"(d[3])
      : "r"(a[0]), "r"(a[1]), "r"(a[2]), "r"(a[3]), "r"(b0), "r"(b1));
}
DEVI void mma_bf16v(float (&d)[4], const uint32_t (&a)[4], uint32_t b0, uint32_t b1) {
  asm volatile("mma.sync.aligned.m16n8k16.row.col.f32.bf16.bf16.f32 {%0,%1,%2,%3}, {%4,%5,%6,%7}, {%8,%9}, {%0,%1,%2,%3};"
               : "+f"(d[0]), "+f"(d[1]), "+f"(d[2]), "+f"(d[3])
               : "r"(a[0]), "r"(a[1]), "r"(a[2]), "r"(a[3]), "r"(b0), "r"(b1));
}
DEVI uint32_t pack_bf16(float lo, float hi) {
  uint32_t r;
  asm("cvt.rn.bf16x2.f32 %0, %1, %2;" : "=r"(r) : "f"(hi), "f"(lo));
  return r;
}
DEVI uint32_t pack_f16(float lo, float hi) {
  uint32_t r;
  asm("cvt.rn.f16x2.f32 %0, %1, %2;" : "=r"(r) : "f"(hi), "f"(lo));
  return r;
}
DEVI uint32_t ldg16(const __nv_bfloat16* p) {
  uint32_t v;
  asm volatile("ld.global.nc.u16 %0, [%1];" : "=r"(v) : "l"(p));
  return v;
}
DEVI bool elect_one() {
  uint32_t pred;
  asm volatile("{\n.reg .pred p;\nelect.sync _|p, 0xffffffff;\nselp.u32 %0, 1, 0, p;\n}" : "=r"(pred));
  return pred != 0;
}
DEVI float bf_lo(uint32_t v) { return __uint_as_float(v << 16); }
DEVI float bf_hi(uint32_t v) { return __uint_as_float(v & 0xffff0000u); }
DEVI float bf2f(__nv_bfloat16 v) { return __bfloat162float(v); }
DEVI float round_bf16(float v) { return __bfloat162float(__float2bfloat16_rn(v)); }
DEVI float rcp(float x) { float r; asm("rcp.approx.ftz.f32 %0, %1;" : "=f"(r) : "f"(x)); return r; }
DEVI float ex2(float x) { float r; asm("ex2.approx.ftz.f32 %0, %1;" : "=f"(r) : "f"(x)); return r; }

DEVI void wg_fence() { asm volatile("wgmma.fence.sync.aligned;" ::: "memory"); }
DEVI void wg_commit() { asm volatile("wgmma.commit_group.sync.aligned;" ::: "memory"); }
template <int N> DEVI void wg_wait() { asm volatile("wgmma.wait_group.sync.aligned %0;" ::"n"(N) : "memory"); }
constexpr uint32_t DESC_HI = (1u << 30) | (1024 >> 4);
constexpr uint32_t DESC_HI64 = (2u << 30) | (512 >> 4);
DEVI uint32_t mkdesc(uint32_t saddr, uint32_t lbo) { return ((saddr & 0x3FFFF) >> 4) | ((lbo >> 4) << 16); }

#define R8(b) "%" #b
DEVI void wgmma_n192(float (&d)[96], uint32_t da, uint32_t db, int scale_d) {
  asm volatile(
      "{\n.reg .pred p;\n.reg .b64 da, db;\nsetp.ne.b32 p, %98, 0;\nmov.b64 da, {%96, %100};\nmov.b64 db, {%97, %99};\n"
      "wgmma.mma_async.sync.aligned.m64n192k16.f32.bf16.bf16 "
      "{%0,%1,%2,%3,%4,%5,%6,%7,%8,%9,%10,%11,%12,%13,%14,%15,"
      "%16,%17,%18,%19,%20,%21,%22,%23,%24,%25,%26,%27,%28,%29,%30,%31,"
      "%32,%33,%34,%35,%36,%37,%38,%39,%40,%41,%42,%43,%44,%45,%46,%47,"
      "%48,%49,%50,%51,%52,%53,%54,%55,%56,%57,%58,%59,%60,%61,%62,%63,"
      "%64,%65,%66,%67,%68,%69,%70,%71,%72,%73,%74,%75,%76,%77,%78,%79,"
      "%80,%81,%82,%83,%84,%85,%86,%87,%88,%89,%90,%91,%92,%93,%94,%95}, "
      "da, db, p, 1, 1, 0, 1;\n}"
      : "+f"(d[0]), "+f"(d[1]), "+f"(d[2]), "+f"(d[3]), "+f"(d[4]), "+f"(d[5]), "+f"(d[6]), "+f"(d[7]),
        "+f"(d[8]), "+f"(d[9]), "+f"(d[10]), "+f"(d[11]), "+f"(d[12]), "+f"(d[13]), "+f"(d[14]), "+f"(d[15]),
        "+f"(d[16]), "+f"(d[17]), "+f"(d[18]), "+f"(d[19]), "+f"(d[20]), "+f"(d[21]), "+f"(d[22]), "+f"(d[23]),
        "+f"(d[24]), "+f"(d[25]), "+f"(d[26]), "+f"(d[27]), "+f"(d[28]), "+f"(d[29]), "+f"(d[30]), "+f"(d[31]),
        "+f"(d[32]), "+f"(d[33]), "+f"(d[34]), "+f"(d[35]), "+f"(d[36]), "+f"(d[37]), "+f"(d[38]), "+f"(d[39]),
        "+f"(d[40]), "+f"(d[41]), "+f"(d[42]), "+f"(d[43]), "+f"(d[44]), "+f"(d[45]), "+f"(d[46]), "+f"(d[47]),
        "+f"(d[48]), "+f"(d[49]), "+f"(d[50]), "+f"(d[51]), "+f"(d[52]), "+f"(d[53]), "+f"(d[54]), "+f"(d[55]),
        "+f"(d[56]), "+f"(d[57]), "+f"(d[58]), "+f"(d[59]), "+f"(d[60]), "+f"(d[61]), "+f"(d[62]), "+f"(d[63]),
        "+f"(d[64]), "+f"(d[65]), "+f"(d[66]), "+f"(d[67]), "+f"(d[68]), "+f"(d[69]), "+f"(d[70]), "+f"(d[71]),
        "+f"(d[72]), "+f"(d[73]), "+f"(d[74]), "+f"(d[75]), "+f"(d[76]), "+f"(d[77]), "+f"(d[78]), "+f"(d[79]),
        "+f"(d[80]), "+f"(d[81]), "+f"(d[82]), "+f"(d[83]), "+f"(d[84]), "+f"(d[85]), "+f"(d[86]), "+f"(d[87]),
        "+f"(d[88]), "+f"(d[89]), "+f"(d[90]), "+f"(d[91]), "+f"(d[92]), "+f"(d[93]), "+f"(d[94]), "+f"(d[95])
      : "r"(da), "r"(db), "r"(scale_d), "n"(DESC_HI), "n"(DESC_HI64));
}
DEVI void wgmma_n64(float (&d)[32], uint32_t da, uint32_t db, int scale_d) {
  asm volatile(
      "{\n.reg .pred p;\n.reg .b64 da, db;\nsetp.ne.b32 p, %34, 0;\nmov.b64 da, {%32, %35};\nmov.b64 db, {%33, %35};\n"
      "wgmma.mma_async.sync.aligned.m64n64k16.f32.bf16.bf16 "
      "{%0,%1,%2,%3,%4,%5,%6,%7,%8,%9,%10,%11,%12,%13,%14,%15,"
      "%16,%17,%18,%19,%20,%21,%22,%23,%24,%25,%26,%27,%28,%29,%30,%31}, "
      "da, db, p, 1, 1, 0, 1;\n}"
      : "+f"(d[0]), "+f"(d[1]), "+f"(d[2]), "+f"(d[3]), "+f"(d[4]), "+f"(d[5]), "+f"(d[6]), "+f"(d[7]),
        "+f"(d[8]), "+f"(d[9]), "+f"(d[10]), "+f"(d[11]), "+f"(d[12]), "+f"(d[13]), "+f"(d[14]), "+f"(d[15]),
        "+f"(d[16]), "+f"(d[17]), "+f"(d[18]), "+f"(d[19]), "+f"(d[20]), "+f"(d[21]), "+f"(d[22]), "+f"(d[23]),
        "+f"(d[24]), "+f"(d[25]), "+f"(d[26]), "+f"(d[27]), "+f"(d[28]), "+f"(d[29]), "+f"(d[30]), "+f"(d[31])
      : "r"(da), "r"(db), "r"(scale_d), "n"(DESC_HI));
}

struct C32 { float re, im; };
DEVI C32 csq(C32 a) { return {a.re * a.re - a.im * a.im, 2.f * a.re * a.im}; }
DEVI C32 cmul(C32 a, C32 b) { return {a.re * b.re - a.im * b.im, a.re * b.im + a.im * b.re}; }
DEVI C32 cfresh(float zl, float zi, float m) {
  float mag = ex2(zl * m), ph = zi * m;
  return {mag * __cosf(ph), mag * __sinf(ph)};
}
struct HMul { uint32_t b, bp; };
DEVI HMul mk_mul(float re, float im) { return {pack_f16(re, im), pack_f16(-im, re)}; }
DEVI uint32_t hcmul(uint32_t a, const HMul& m) {
  __half2 ah = *reinterpret_cast<__half2*>(&a);
  __half2 b = *reinterpret_cast<const __half2*>(&m.b), bp = *reinterpret_cast<const __half2*>(&m.bp);
  __half2 r = __hfma2(__high2half2(ah), bp, __hmul2(__low2half2(ah), b));
  return *reinterpret_cast<uint32_t*>(&r);
}
DEVI uint32_t badd(uint32_t a, uint32_t b) {
  __nv_bfloat162 r = __hadd2(*reinterpret_cast<__nv_bfloat162*>(&a), *reinterpret_cast<__nv_bfloat162*>(&b));
  return *reinterpret_cast<uint32_t*>(&r);
}
template <int MU0, int NMU, int DMAX>
DEVI void conv_tail(float (&acc)[16][4], uint32_t p_lane, uint32_t v_base, int back, bool edge, int lane) {
  const int hsel = (lane >> 3) & 1;
  const int row = (lane & 7) + ((lane >> 4) << 3) + PADV - 8 - (back & (hsel ^ 1));
  const uint32_t la = v_base + row * 32 + (((hsel ^ back) ^ ((row >> 2) & 1)) << 4);
  uint32_t M[3][4];
  ldsm_x4_t(M[0], la);
  ldsm_x4_t(M[1], la + 256);
  uint32_t H[2 * NMU];
#pragma unroll
  for (int i = 0; i < 2 * NMU; ++i) H[i ^ 1] = lds32(p_lane + (uint32_t)(MU0 - 1 + i) * 32);
  if (edge) {
    const uint32_t a[4] = {0u, 0u, M[0][0], M[0][1]};
#pragma unroll
    for (int k = 1; k < NMU; ++k) mma_bf16v(acc[MU0 - 2 + 2 * k], a, H[2 * k], H[2 * k + 1]);
  }
#pragma unroll
  for (int delta = -1; delta <= DMAX; ++delta) {
    if (delta + 2 <= DMAX) ldsm_x4_t(M[(delta + 3) % 3], la + (delta + 3) * 256);
#pragma unroll
    for (int k = 0; k < NMU; ++k)
      if (delta + MU0 + 2 * k < 16) mma_bf16v(acc[delta + MU0 + 2 * k], M[(delta + 1) % 3], H[2 * k], H[2 * k + 1]);
  }
}

__global__ void __cluster_dims__(2, 1, 1) __launch_bounds__(NTHREADS, 1)
fused_kernel(const __grid_constant__ Maps maps, const Ptrs p) {
  extern __shared__ __align__(1024) uint8_t smem[];
  const uint32_t sb = s2u(smem);
  const int tid = threadIdx.x, lane = tid & 31;
  const int warp = __shfl_sync(0xffffffffu, tid >> 5, 0);
  const int cta = blockIdx.x;
  const uint32_t rank = cta & 1;
  const int ti = 2 * (cta >> 4) + rank;
  const int tj = (cta >> 1) & 7;
  const int pi = cta >> 3, pj = cta & 7;
  const uint32_t bars = sb + SM_BAR;
#define BAR(i) (bars + 8 * (i))
  const int g = lane >> 2, q = lane & 3;

  auto issue_stage = [&](int ks, int s) {
    const uint32_t st = sb + s * STG_BYTES, fb = BAR(B_FULL + s);
    mbar_expect_tx(fb, STG_BYTES);
    tma_load_2d(st + STG_X, &maps.x, ks * 32, ti * 128, fb);
    tma_load_3d_mc(st + STG_W + rank * 6144, &maps.w, tj * 64, ks * 32 + rank * 16, 0, fb, 3);
  };

  const int kch = warp & 3, krd = warp >> 2;
  float zr, zi, wr, wi;
  unsigned epoch;
  uint32_t r_dskip;
  {
    const size_t po = (size_t)(cta * 4 + kch) * 128 + krd * 32 + lane;
    const uint32_t r_ar = ldg16(p.A_re + po), r_ai = ldg16(p.A_im + po), r_br = ldg16(p.B_re + po), r_bi = ldg16(p.B_im + po);
    const uint32_t r_cr = ldg16(p.C_re + po), r_ci = ldg16(p.C_im + po), r_ldt = ldg16(p.log_dt + cta * 4 + kch);
    epoch = __ldcg(&g_epoch);
    r_dskip = ldg16(p.Dskip + cta * 4 + kch);
    uint4 pt;
    if (tid < 128) pt = __ldg((const uint4*)g_ptab.v + tid);
    if (tid == 384) {
      TS(0);
#pragma unroll
      for (int i = 0; i < B_COUNT; ++i) mbar_init(BAR(i), bar_count(i));
      asm volatile("fence.mbarrier_init.release.cluster;" ::: "memory");
      prefetch_tmap(&maps.x); prefetch_tmap(&maps.w); prefetch_tmap(&maps.u);
    }
    __syncthreads();
    cluster_arrive();
    if (warp >= 12) {
      cluster_wait();
      if (elect_one()) {
        if (warp == 13) {
          mbar_expect_tx(BAR(B_TILE), 16384);
          tma_load_2d(sb + SM_U, &maps.u, tj * 64, ti * 128, BAR(B_TILE));
          prefetch_tmap(&maps.uT); prefetch_tmap(&maps.wo); prefetch_tmap(&maps.o); prefetch_tmap(&maps.yT);
          prefetch_tmap(&maps.out);
        } else {
          if (warp == 12) TS(61);
          { const int ks = warp == 12 ? 0 : warp - 13; issue_stage(ks, ks); }
        }
      }
      __syncwarp();
    }
    if (tid < 128) sts128(sb + SM_PTAB + tid * 16, pt.x, pt.y, pt.z, pt.w);
    const float dt = round_bf16(expf(bf_lo(r_ldt)));
    zr = dt * bf_lo(r_ar); zi = dt * bf_lo(r_ai);
    const float dbr = dt * bf_lo(r_br), dbi = dt * bf_lo(r_bi), cr = bf_lo(r_cr), ci = bf_lo(r_ci);
    wr = cr * dbr - ci * dbi; wi = cr * dbi + ci * dbr;
  }
  {
    const float mz = __uint_as_float(__reduce_max_sync(0xffffffffu, __float_as_uint(fmaxf(zr, 0.f))));
    const int E = min(max((int)(__reduce_max_sync(0xffffffffu, __float_as_uint(fmaxf(fabsf(wr), fabsf(wi)))) >> 23), 1), 252);
    const float sc = __int_as_float((253 - E) << 23), inv = __int_as_float((E + 1) << 23);
    const float zl = (zr - mz) * 1.4426950408889634f;
    const uint32_t tb = sb + SM_VV + kch * VV_BYTES + krd * KG_BYTES;
    const uint32_t sta = tb + (((lane >> 2) << 4) | ((lane & 3) << 2));
    auto put = [&](int r, uint32_t v) { sts32((sta ^ ((r & 7) << 4)) + r * 128, v); };
    const uint32_t lda = tb + ((lane & 7) + (((lane >> 3) & 1) << 3)) * 128;
    const uint32_t ldb = tb + ((lane & 7) + ((lane >> 4) << 3)) * 128;
    C32 e1 = cfresh(zl, zi, 1.f), e2 = csq(e1), e4 = csq(e2), e8 = csq(e4);
    C32 e16 = cfresh(zl, zi, 16.f), e32 = csq(e16), e64 = csq(e32), e128 = csq(e64);
    C32 e256 = cfresh(zl, zi, 256.f), e512 = csq(e256), e1024 = csq(e512), e768 = cmul(e512, e256);
    uint32_t XA[2][4][4];
    {
      const HMul m16 = mk_mul(e16.re, e16.im), m32 = mk_mul(e32.re, e32.im), m64 = mk_mul(e64.re, e64.im);
      const HMul m128 = mk_mul(e128.re, e128.im);
      uint32_t X[16];
      X[0] = 0x00003c00u; X[1] = pack_f16(e8.re, e8.im); X[2] = m16.b; X[4] = m32.b; X[8] = m64.b;
      X[3] = hcmul(X[1], m16); X[5] = hcmul(X[1], m32); X[6] = hcmul(X[2], m32); X[7] = hcmul(X[3], m32);
#pragma unroll
      for (int r = 1; r < 8; ++r) X[8 + r] = hcmul(X[r], m64);
#pragma unroll
      for (int h = 0; h < 2; ++h) {
#pragma unroll
        for (int r = 0; r < 16; ++r) put(r, h == 0 ? X[r] : r == 0 ? m128.b : hcmul(X[r], m128));
        __syncwarp();
#pragma unroll
        for (int k = 0; k < 4; ++k) ldsm_x4(XA[h][k], lda + (((2 * k + (lane >> 4)) ^ (lane & 7)) << 4));
        __syncwarp();
      }
    }
    if (warp >= 14 && elect_one()) {
      issue_stage(warp - 11, warp - 11);
      issue_stage(warp - 9, warp - 9);
      if (warp == 14) l2_prefetch((const char*)p.wqkv + 224 * 3072 + cta * 6912, 6912);
      else l2_prefetch((const char*)p.x + (size_t)cta * 16384, 16384);
    }
    __syncwarp();
    float D[2][3][4];
#pragma unroll
    for (int t = 0; t < 6; ++t) D[t / 3][t % 3][0] = D[t / 3][t % 3][1] = D[t / 3][t % 3][2] = D[t / 3][t % 3][3] = 0.f;
    auto contract = [&](int t0, int nt) {
      __syncwarp();
#pragma unroll
      for (int k = 0; k < 4; ++k) {
        uint32_t b[4];
        ldsm_x4(b, ldb + (((2 * k + ((lane >> 3) & 1)) ^ (lane & 7)) << 4));
#pragma unroll
        for (int h = 0; h < 2; ++h) {
          mma_f16(D[h][t0], XA[h][k], b[0], b[1]);
          if (nt == 2) mma_f16(D[h][t0 + 1], XA[h][k], b[2], b[3]);
        }
      }
      __syncwarp();
    };
    const HMul c1 = mk_mul(e1.re, -e1.im), c2 = mk_mul(e2.re, -e2.im), c4 = mk_mul(e4.re, -e4.im);
    const HMul c256 = mk_mul(e256.re, -e256.im), c512 = mk_mul(e512.re, -e512.im), c768 = mk_mul(e768.re, -e768.im);
    const HMul c1024 = mk_mul(e1024.re, -e1024.im);
    uint32_t W[8];
    W[0] = pack_f16(wr * sc, -wi * sc);
    W[1] = hcmul(W[0], c1); W[2] = hcmul(W[0], c2); W[3] = hcmul(W[1], c2);
    W[4] = hcmul(W[0], c4); W[5] = hcmul(W[1], c4); W[6] = hcmul(W[2], c4); W[7] = hcmul(W[3], c4);
#pragma unroll
    for (int i = 0; i < 8; ++i) put(i, W[i]);
#pragma unroll
    for (int i = 0; i < 4; ++i) put(8 + i, hcmul(W[2 * i], c256));
    put(12, hcmul(W[0], c512)); put(13, hcmul(W[4], c512)); put(14, hcmul(W[0], c768)); put(15, hcmul(W[4], c768));
    contract(0, 2);
    const uint32_t v0 = hcmul(W[0], c1024);
    put(0, v0); put(1, hcmul(v0, c256)); put(2, hcmul(v0, c512)); put(3, hcmul(v0, c768)); put(4, hcmul(v0, c1024));
    contract(2, 1);
    const uint32_t a = tb + (g * 24 + 2 * q) * 4;
#pragma unroll
    for (int t = 0; t < 6; ++t) {
      const float(&d)[4] = D[t / 3][t % 3];
      sts_f32x2(a + (t / 3) * 1536 + (t % 3) * 32, d[0] * inv, d[1] * inv);
      sts_f32x2(a + (t / 3) * 1536 + (t % 3) * 32 + 768, d[2] * inv, d[3] * inv);
    }
    if (mz > 0.f) {
      __syncwarp();
#pragma unroll 1
      for (int i = lane; i < 768; i += 32) {
        const int r = i / 24, y = i - 24 * r;
        sts_f32(tb + i * 4, lds_f32(tb + i * 4) * ex2(mz * 1.4426950408889634f * (koff(y) + 8 * r)));
      }
    }
  }
  if (tid == 0) TS(2);
  if (warp < 12) cluster_wait();
  if (tid == 0) TS(32);
  __syncthreads();
  if (tid == 0) TSD(33);

  if (warp < 4) {
    asm volatile("setmaxnreg.inc.sync.aligned.u32 152;");
    if (tid == 0) TS(34);
    const int d = cta * 4 + warp;
    const uint32_t vv = sb + SM_VV + warp * VV_BYTES;
    const uint32_t ub = sb + SM_U + warp * U_BYTES;
    const uint32_t pb = sb + SM_P + warp * P_BYTES;
    const float dskip = bf_lo(r_dskip);
#pragma unroll 1
    for (int pass = 0; pass < 2; ++pass) {
      if (pass == 1) {
        const uint32_t kf = vv;
#pragma unroll 2
        for (int i = 0; i < 6; ++i) {
          const uint32_t a = kf + (i * 32 + lane) * 16;
          const uint4 x0 = lds128(a), x1 = lds128(a + KG_BYTES), x2 = lds128(a + 2 * KG_BYTES), x3 = lds128(a + 3 * KG_BYTES);
          auto s4 = [](uint32_t a0, uint32_t a1, uint32_t a2, uint32_t a3) {
            return __float_as_uint((__uint_as_float(a0) + __uint_as_float(a1)) + (__uint_as_float(a2) + __uint_as_float(a3)));
          };
          sts128(a, s4(x0.x, x1.x, x2.x, x3.x), s4(x0.y, x1.y, x2.y, x3.y), s4(x0.z, x1.z, x2.z, x3.z), s4(x0.w, x1.w, x2.w, x3.w));
        }
        __syncwarp();
        const float k1024 = lds_f32(kf + kidx_c(1024) * 4);
        if (lane == 0) {
          sts_f32(kf + SL_ZERO * 4, 0.f);
          sts_f32(kf + SL_510 * 4, lds_f32(kf + kidx_c(510) * 4) - lds_f32(kf + kidx_c(512) * 4));
          sts_f32(kf + SL_0 * 4, lds_f32(kf) + dskip);
        }
        __syncwarp();
        if (tid == 0) TS(36);
        mbar_wait_long(BAR(B_PFREE), 0);
        if (tid == 0) TS(37);
        {
          float prev = 0.f;
#pragma unroll 1
          for (int i0 = 0; i0 < 16; i0 += 4) {
            uint32_t e[4];
            float a[4], b[4];
#pragma unroll
            for (int i = 0; i < 4; ++i) e[i] = lds32(sb + SM_PTAB + ((i0 + i) * 32 + lane) * 4);
#pragma unroll
            for (int i = 0; i < 4; ++i) { a[i] = lds_f32(kf + (e[i] & 0xffff)); b[i] = lds_f32(kf + (e[i] >> 16)); }
#pragma unroll
            for (int i = 0; i < 4; ++i) {
              const uint32_t w = pb + (31 * lane + 2 * (i0 + i)) * 4;
              if (i0 + i > 0) sts32(w - 4, pack_bf16(a[i], prev));
              sts32(w, pack_bf16(b[i], a[i]));
              prev = b[i];
            }
          }
        }
        __syncwarp();
        bar_arrive(7, 384);
        if (lane == 0) TS(4);
        const int gq = g - 2 * q;
        uint32_t h127, h128;
        {
          const uint32_t kf2 = pack_bf16(k1024, k1024) ^ 0x80008000u;
          h127 = (gq == 4 ? 0x0000ffffu : gq == 5 ? 0xffffffffu : gq == 6 ? 0xffff0000u : 0u) & kf2;
          h128 = (gq == -4 ? 0x0000ffffu : gq == -3 ? 0xffffffffu : gq == -2 ? 0xffff0000u : 0u) & kf2;
        }
        bar_sync(4, 384);
        mbar_wait_long(BAR(B_UCH + warp), 0);
        if (lane == 0) TS(7);
        float acc[16][4];
#pragma unroll
        for (int i = 0; i < 16; ++i) { acc[i][0] = acc[i][1] = acc[i][2] = acc[i][3] = 0.f; }
        {
          const uint32_t pd_lane = pb + (PD_OFF + 16 + gq) * 4;
          const int prow0 = 8 + (lane & 7) + ((lane >> 4) << 3), hs = (lane >> 3) & 1;
          uint32_t B[2][4][4];
          uint32_t A[4][4];
          const uint32_t la0 = ub + prow0 * 32 + ((hs ^ ((prow0 >> 2) & 1)) << 4);
#pragma unroll
          for (int m2 = 0; m2 < 4; ++m2) ldsm_x4(B[0][m2], la0 + m2 * 512);
#pragma unroll
          for (int i = 0; i < 4; ++i) {
            const uint32_t a = pd_lane + i * 512;
            A[i][0] = lds32(a); A[i][1] = lds32(a + 32); A[i][2] = lds32(a - 32); A[i][3] = A[i][0];
          }
          uint32_t la = la0;
#pragma unroll 1
          for (int rho = 0; rho < 8; ++rho) {
#pragma unroll
            for (int m2 = 0; m2 < 4; ++m2) ldsm_x4(B[1][m2], la + (4 + m2) * 512);
#pragma unroll
            for (int i = 0; i < 4; ++i)
#pragma unroll
              for (int m = 0; m < 8; ++m) mma_bf16v(acc[m + i], A[i], B[0][m >> 1][2 * (m & 1)], B[0][m >> 1][2 * (m & 1) + 1]);
            const int prow = prow0 - min(rho + 1, 7);
            la = ub + prow * 32 + ((hs ^ ((prow >> 2) & 1)) << 4);
#pragma unroll
            for (int m2 = 0; m2 < 4; ++m2) ldsm_x4(B[0][m2], la + m2 * 512);
            const uint32_t pa = pd_lane + (rho + 1) * 64;
#pragma unroll
            for (int i = 0; i < 4; ++i) {
#pragma unroll
              for (int m = 0; m < 8 - i; ++m)
                mma_bf16v(acc[8 + m + i], A[i], B[1][m >> 1][2 * (m & 1)], B[1][m >> 1][2 * (m & 1) + 1]);
              A[i][0] = lds32(pa + i * 512); A[i][1] = lds32(pa + i * 512 + 32); A[i][2] = lds32(pa + i * 512 - 32);
              A[i][3] = A[i][0];
            }
          }
          if (lane == 0) TS(40);
          {
            uint32_t b8[4];
            ldsm_x4(b8, la + 4 * 512);
            const uint32_t h63 = lds32(pd_lane + 63 * 32), h64 = lds32(pd_lane + 64 * 32);
            const uint32_t a63[4] = {0u, h127, 0u, 0u}, a32[4] = {h64, 0u, h63, h64}, a64[4] = {h128, 0u, h127, h128};
#pragma unroll
            for (int m2 = 0; m2 < 4; ++m2) ldsm_x4(B[1][m2], la0 + m2 * 512);
#pragma unroll
            for (int m = 0; m < 8; ++m) mma_bf16v(acc[m + 7], a63, B[0][m >> 1][2 * (m & 1)], B[0][m >> 1][2 * (m & 1) + 1]);
#pragma unroll
            for (int m2 = 0; m2 < 2; ++m2) ldsm_x4(B[0][m2], la0 + (4 + m2) * 512);
#pragma unroll
            for (int m = 0; m < 8; ++m) mma_bf16v(acc[m + 4], a32, B[1][m >> 1][2 * (m & 1)], B[1][m >> 1][2 * (m & 1) + 1]);
            mma_bf16v(acc[15], a63, b8[0], b8[1]);
#pragma unroll
            for (int m = 0; m < 8; ++m) mma_bf16v(acc[m + 8], a64, B[1][m >> 1][2 * (m & 1)], B[1][m >> 1][2 * (m & 1) + 1]);
#pragma unroll
            for (int m = 0; m < 4; ++m) mma_bf16v(acc[m + 12], a32, B[0][m >> 1][2 * (m & 1)], B[0][m >> 1][2 * (m & 1) + 1]);
          }
          if (lane == 0) TS(41);
          bar_sync(5, 384);
#pragma unroll 1
          for (int v = 0; v < 4; ++v)
            conv_tail<4, 3, 11>(acc, pb + (P2_OFF + 56 * v + gq - 16) * 4, vv + ((v & 1) ? VV_U3 : VV_U5), v >> 1, v == 0, lane);
          if (lane == 0) TS(42);
#pragma unroll 1
          for (int pi = 0; pi < 2; ++pi)
            conv_tail<8, 5, 7>(acc, pb + (P3_OFF + 88 * pi + gq - 48) * 4, vv + (pi ? VV_U7 : VV_U9), pi, pi == 0, lane);
        }
        if (lane == 0) TS(8);
        __syncwarp();
        {
          const int mt = lane >> 3;
          const uint32_t a = pb + (128 * (mt >> 1) + 16 * (lane & 7) + 8 * (mt & 1)) * 2;
#pragma unroll
          for (int ab = 0; ab < 16; ab += 2)
            stsm_x4_t(a + ab * 256, pack_bf16(acc[ab][0], acc[ab][1]), pack_bf16(acc[ab][2], acc[ab][3]),
                      pack_bf16(acc[ab + 1][0], acc[ab + 1][1]), pack_bf16(acc[ab + 1][2], acc[ab + 1][3]));
        }
        fence_async_smem();
        __syncwarp();
        if (lane < 2) mbar_arrive_cluster(BAR(B_CONVD), lane);
        bar_arrive(3, 384);
        if (elect_one()) {
          bulk_store(p.yT + (size_t)d * 2048, pb, 4096);
          bulk_commit();
          bulk_wait0();
          red_relaxed_add(&g_cnt[(C_Y + (cta >> 4)) * 32], 1);
          TS(9);
        }
        bar_sync(2, 128);
        if (warp == 0 && elect_one()) {
          wait_counter(&g_cnt[(C_Y + tj) * 32], (epoch + 1) * 64);
          TS(28);
          mbar_expect_tx(BAR(B_TILE), 16384);
          tma_load_2d(sb + SM_U, &maps.yT, ti * 128, tj * 64, BAR(B_TILE));
          tma_load_2d(sb + SM_U + 8192, &maps.yT, ti * 128 + 64, tj * 64, BAR(B_TILE));
        }
        __syncwarp();
      }
      mbar_wait_long(BAR(B_TILE), pass);
      if (lane == 0) TS(26 + 3 * pass);
      {
        const int m = lane >> 3, r = lane & 7;
#pragma unroll 2
        for (int it = 0; it < 8; ++it) {
          const int tb = warp * 4 + (it >> 1), cb = (it & 1) * 4 + m;
          const uint32_t at = (tb * 8 + r) * 128 + ((cb ^ r) << 4);
          const uint32_t ac = (tb >> 3) * 8192 + (cb * 8 + r) * 128 + (((tb & 7) ^ (pass ? 0 : tb >> 3) ^ r) << 4);
          uint32_t v[4];
          ldsm_x4_t(v, sb + SM_U + (pass ? ac : at));
          stsm_x4(sb + SM_P + (pass ? at : ac), v[0], v[1], v[2], v[3]);
        }
      }
      if (pass == 0 && tid == 0) TS(35);
      fence_async_smem();
      if (pass == 0) {
        bar_arrive(6, 160);
      } else {
        bar_sync(2, 128);
        if (warp == 0 && elect_one()) {
          tma_store_2d(&maps.out, sb + SM_P, 64 * tj, 128 * ti);
          bulk_commit();
          bulk_wait_read0();
          TS(30);
        }
      }
    }
  } else if (warp < 12) {
    asm volatile("setmaxnreg.inc.sync.aligned.u32 160;");
    const int w8 = warp - 4;
    const int row = w8 * 16 + (lane & 7) + (((lane >> 3) & 1) << 3);
    {
      float acc[96];
#pragma unroll 1
      for (int ks = 0, s = 0, ph = 0; ks < 16; ++ks) {
        mbar_wait(BAR(B_FULL + s), ph);
        if (tid == 128 && !(ks & 1)) TSR(16, ks == 0 ? 16 : 9 + (ks >> 1) + (ks > 12 ? 46 : 0));
        const uint32_t st = sb + s * STG_BYTES;
        const uint32_t da = mkdesc(st + STG_X + (w8 >> 2) * 4096, 16);
        const uint32_t db = mkdesc(st + STG_W, 2048);
        wg_fence();
        wgmma_n192(acc, da, db, ks != 0);
        wgmma_n192(acc, da + 2, db + 384, 1);
        wg_commit();
        const uint32_t eprev = BAR(B_EMPTY + (s == 0 ? NSTG - 1 : s - 1));
        if (++s == NSTG) { s = 0; ph ^= 1; }
        if (ks > 0) {
          wg_wait<1>();
          if (lane < 2) mbar_arrive_cluster(eprev, lane);
        }
      }
      wg_wait<0>();
      bar_arrive(4, 384);
      if (tid == 128) TS(17);
      bar_sync(1, 256);
#pragma unroll
      for (int i = 0; i < 24; i += 2)
        stsm_x4(sb + SM_QS + row * 128 + (i >> 3) * 16384 + ((((i & 7) + (lane >> 4)) ^ (row & 7)) << 4),
                pack_bf16(acc[4 * i], acc[4 * i + 1]), pack_bf16(acc[4 * i + 2], acc[4 * i + 3]),
                pack_bf16(acc[4 * i + 4], acc[4 * i + 5]), pack_bf16(acc[4 * i + 6], acc[4 * i + 7]));
    }
    __syncwarp();
#pragma unroll 1
    for (int part = 1; part >= 0; --part) {
      const uint32_t pa = sb + SM_QS + part * 16384 + w8 * 2048 + lane * 16;
#pragma unroll 1
      for (int it = 0; it < 4; ++it) {
        uint4 t = lds128(pa + it * 512);
        uint32_t* tw = &t.x;
#pragma unroll
        for (int j = 0; j < 4; ++j) {
          const uint32_t x = tw[j];
          const __nv_bfloat162 xb = *reinterpret_cast<const __nv_bfloat162*>(&x);
          const uint32_t e = pack_bf16(ex2(bf_lo(x) * 1.4426950408889634f), ex2(bf_hi(x) * 1.4426950408889634f));
          const uint32_t m = __hgt2_mask(xb, __floats2bfloat162_rn(0.f, 0.f));
          const uint32_t sel = (badd(x, 0x3f803f80u) & m) | (e & ~m);
          tw[j] = pack_bf16(bf_lo(sel) + 1e-6f, bf_hi(sel) + 1e-6f);
        }
        sts128(pa + it * 512, t.x, t.y, t.z, t.w);
      }
      if (part == 1) {
        if (tid == 128) TS(53);
        bar_sync(1, 256);
        const int hh = w8 >> 1, dtile = w8 & 1;
        float kv[4] = {0.f, 0.f, 0.f, 0.f}, zz[4] = {0.f, 0.f, 0.f, 0.f};
        const int m = lane >> 3;
        const uint32_t aa = sb + SM_VS + ((lane & 7) + ((m >> 1) << 3)) * 128 + (((2 * hh + (m & 1)) ^ (lane & 7)) << 4);
        const uint32_t ab = sb + SM_PK + (lane & 15) * 128 + (((2 * hh + dtile) ^ (lane & 7)) << 4);
#pragma unroll 2
        for (int ks = 0; ks < 8; ++ks) {
          uint32_t a[4], b0, b1;
          ldsm_x4_t(a, aa + ks * 2048);
          ldsm_x2_t(b0, b1, ab + ks * 2048);
          mma_bf16(kv, a[0], a[1], a[2], a[3], b0, b1);
          mma_bf16(zz, 0x3f803f80u, 0x3f803f80u, 0x3f803f80u, 0x3f803f80u, b0, b1);
        }
        const uint32_t kp = sb + SM_KV + hh * 1088;
        sts128(kp + dtile * 512 + lane * 16, __float_as_uint(kv[0]), __float_as_uint(kv[1]), __float_as_uint(kv[2]),
               __float_as_uint(kv[3]));
        if (g == 0) sts_f32x2(kp + 1024 + dtile * 32 + q * 8, zz[0], zz[1]);
        fence_async_smem();
        __syncwarp();
        if (lane == 0) mbar_arrive(BAR(B_KVP));
        if (tid == 128) TS(55);
      }
    }
    if (tid == 128) TS(56);
    {
      const int ch = w8 >> 1;
      bar_sync(7, 384);
      mbar_wait_long(BAR(B_UCH + ch), 0);
#pragma unroll 1
      for (int it = w8 & 1; it < 8; it += 2) {
          const int k = -18 + it * 32 + lane;
          const int kr = min(max(k, -2), 208);
          uint32_t E[12];
#pragma unroll
          for (int c = 0; c < 3; ++c) {
            const int kk = kr - 1 + c, r = (kk >> 1) + 8;
            const uint4 t = lds128(sb + SM_U + ch * U_BYTES + r * 32 + (((kk & 1) ^ ((r >> 2) & 1)) << 4));
            E[4 * c] = t.x; E[4 * c + 1] = t.y; E[4 * c + 2] = t.z; E[4 * c + 3] = t.w;
          }
          uint32_t O[8];
#pragma unroll
          for (int j = 0; j < 8; ++j) O[j] = __byte_perm(E[j + 1], E[j + 2], 0x5432);
          uint32_t s3[6], s5[4], s7[4], s9[4];
#pragma unroll
          for (int j = 0; j < 6; ++j) s3[j] = badd(badd(O[j], O[j + 1]), E[j + 2]);
#pragma unroll
          for (int j = 0; j < 4; ++j) {
            s5[j] = badd(s3[j + 2], badd(E[j + 3], E[j + 5]));
            s7[j] = badd(s5[j], badd(O[j + 1], O[j + 4]));
            s9[j] = badd(s7[j], badd(E[j + 2], E[j + 6]));
          }
          const int r = (k >> 1) + PADV;
          const uint32_t a = sb + SM_VV + ch * VV_BYTES + r * 32 + (((k & 1) ^ ((r >> 2) & 1)) << 4);
          if (k < 208) { sts128(a + VV_U3, s3[0], s3[1], s3[2], s3[3]); sts128(a + VV_U5, s5[0], s5[1], s5[2], s5[3]); }
          if (k < 144) { sts128(a + VV_U7, s7[0], s7[1], s7[2], s7[3]); sts128(a + VV_U9, s9[0], s9[1], s9[2], s9[3]); }
      }
      bar_arrive(5, 384);
    }
    if (tid == 128) TS(6);
    mbar_wait_long(BAR(B_KVF), 0);
    if (tid == 128) TS(19);
#pragma unroll 1
    for (int h = 0; h < 4; ++h) {
      uint32_t a[4];
      const uint32_t qa = sb + SM_QS + row * 128 + (((2 * h + (lane >> 4)) ^ (row & 7)) << 4);
      ldsm_x4(a, qa);
      const uint32_t kp = sb + SM_KV + h * 1088;
      const uint4 k0 = lds128(kp + lane * 16), k1 = lds128(kp + 512 + lane * 16);
      const uint32_t za = kp + 1024 + q * 8;
      auto pk2 = [](uint32_t x, uint32_t y) { return pack_bf16(__uint_as_float(x), __uint_as_float(y)); };
      float n0[4] = {0.f, 0.f, 0.f, 0.f}, n1[4] = {0.f, 0.f, 0.f, 0.f}, dn[4] = {0.f, 0.f, 0.f, 0.f};
      mma_bf16(n0, a[0], a[1], a[2], a[3], pk2(k0.x, k0.y), pk2(k1.x, k1.y));
      mma_bf16(n1, a[0], a[1], a[2], a[3], pk2(k0.z, k0.w), pk2(k1.z, k1.w));
      mma_bf16(dn, a[0], a[1], a[2], a[3], pack_bf16(lds_f32(za), lds_f32(za + 4)), pack_bf16(lds_f32(za + 32), lds_f32(za + 36)));
      const uint32_t dd = pack_bf16(dn[0], dn[2]);
      const uint32_t d2 = pack_bf16(bf_lo(dd) + 1e-6f, bf_hi(dd) + 1e-6f);
      const float r0 = rcp(bf_lo(d2)), r1 = rcp(bf_hi(d2));
      const uint32_t x0 = pack_bf16(n0[0], n0[1]), x1 = pack_bf16(n0[2], n0[3]);
      const uint32_t x2 = pack_bf16(n1[0], n1[1]), x3 = pack_bf16(n1[2], n1[3]);
      stsm_x4(qa, pack_bf16(bf_lo(x0) * r0, bf_hi(x0) * r0), pack_bf16(bf_lo(x1) * r1, bf_hi(x1) * r1),
              pack_bf16(bf_lo(x2) * r0, bf_hi(x2) * r0), pack_bf16(bf_lo(x3) * r1, bf_hi(x3) * r1));
    }
    fence_async_smem();
    __syncwarp();
    if (lane == 0) mbar_arrive(BAR(B_OST));
    if (tid == 128) TS(57);
    mbar_wait_long(BAR(B_WO), 0);
    bar_sync(3, 384);
    {
      float o[32];
#pragma unroll 1
      for (int c = 0; c < 8; ++c) {
        mbar_wait_long(BAR(B_RF + c), 0);
        if (tid == 128) TSR(22, c == 0 ? 22 : 43 + c);
        const uint32_t slot = c < 4 ? SM_QS + c * 16384 : c < 7 ? SM_VV + (c - 4) * 16384 : SM_QS;
        const uint32_t da = mkdesc(sb + slot + (w8 >> 2) * 8192, 16);
        const uint32_t db = mkdesc(sb + SM_WO + c * 8192, 8192);
        wg_fence();
#pragma unroll
        for (int k = 0; k < 4; ++k) wgmma_n64(o, da + 2 * k, db + 128 * k, (c | k) != 0);
        wg_commit();
        if (c == 1) {
          wg_wait<1>();
          if (lane < 2) mbar_arrive_cluster(BAR(B_RE), lane);
        }
      }
      wg_wait<0>();
      if (tid == 128) TS(51);
      bar_sync(1, 256);
#pragma unroll
      for (int i = 0; i < 8; i += 2)
        stsm_x4(sb + SM_BOUT + row * 128 + (((i + (lane >> 4)) ^ (row & 7)) << 4), pack_bf16(o[4 * i], o[4 * i + 1]),
                pack_bf16(o[4 * i + 2], o[4 * i + 3]), pack_bf16(o[4 * i + 4], o[4 * i + 5]), pack_bf16(o[4 * i + 6], o[4 * i + 7]));
      fence_async_smem();
      bar_sync(1, 256);
      if (tid == 128) TS(52);
      if (warp == 4 && elect_one()) {
        tma_store_2d(&maps.out, sb + SM_BOUT, 512 + 64 * pj, 128 * pi);
        bulk_commit();
        bulk_wait_read0();
        TS(23);
      }
    }
  } else {
    asm volatile("setmaxnreg.dec.sync.aligned.u32 40;");
    if (warp == 12) {
      if (elect_one()) {
#pragma unroll 1
        for (int ks = NSTG, s = 0, ph = 0; ks < 16; ++ks) {
          mbar_wait(BAR(B_EMPTY + s), ph);
          issue_stage(ks, s);
          if (ks == NSTG) l2_prefetch((const char*)p.wo + (size_t)cta * 4096, 4096);
          if (++s == NSTG) { s = 0; ph ^= 1; }
        }
        mbar_wait(BAR(B_EMPTY + 6), 1);
        mbar_expect_tx(BAR(B_WO), 65536);
        tma_load_2d(sb + SM_WO, &maps.wo, pj * 64, 0, BAR(B_WO));
        tma_load_2d(sb + SM_WO + 32768, &maps.wo, pj * 64, 256, BAR(B_WO));
        float* kvg = &g_kv[epoch & 1][tj][0];
        mbar_wait_long(BAR(B_KVP), 0);
        bulk_reduce_add_f32(kvg, sb + SM_KV, 4352);
        bulk_commit();
        bulk_wait0();
        red_relaxed_add(&g_cnt[(C_KV + tj) * 32], 1);
        TS(18);
        wait_counter(&g_cnt[(C_KV + tj) * 32], (epoch + 1) * 16);
        mbar_expect_tx(BAR(B_KVF), 4352);
        bulk_load(sb + SM_KV, kvg, 4352, BAR(B_KVF));
        mbar_wait_long(BAR(B_OST), 0);
        tma_store_2d(&maps.o, sb + SM_QS, tj * 64, ti * 128);
        tma_store_2d(&maps.o, sb + SM_QS + 8192, tj * 64, ti * 128 + 64);
        bulk_commit();
        bulk_wait0();
        red_relaxed_add(&g_cnt[(C_O + ti) * 32], 1);
        TS(20);
        mbar_arrive_cluster(BAR(B_SLOT), 0);
        mbar_arrive_cluster(BAR(B_SLOT), 1);
        wait_counter(&g_cnt[(C_O + pi) * 32], (epoch + 1) * 8);
        if (cta == 0) g_epoch = epoch + 1;
        mbar_wait(BAR(B_SLOT), 0);
        TS(21);
#pragma unroll 1
        for (int c = 0; c < 8; ++c) {
          if (c == 4) mbar_wait_long(BAR(B_CONVD), 0);
          if (c == 7) mbar_wait(BAR(B_RE), 0);
          const uint32_t slot = c < 4 ? SM_QS + c * 16384 : c < 7 ? SM_VV + (c - 4) * 16384 : SM_QS;
          mbar_expect_tx(BAR(B_RF + c), 16384);
          tma_load_2d_mc(sb + slot + rank * 8192, &maps.o, c * 64, pi * 128 + rank * 64, BAR(B_RF + c), 3);
        }
      }
    } else if (warp == 13) {
      bar_sync(6, 160);
      sts128(sb + SM_U + (lane >> 4) * U_BYTES + (lane & 15) * 16, 0, 0, 0, 0);
      sts128(sb + SM_U + (2 + (lane >> 4)) * U_BYTES + (lane & 15) * 16, 0, 0, 0, 0);
      __syncwarp();
      if (elect_one()) {
        tma_store_2d(&maps.uT, sb + SM_P, ti * 128, tj * 64);
        tma_store_2d(&maps.uT, sb + SM_P + 8192, ti * 128 + 64, tj * 64);
        bulk_commit();
        bulk_wait_read0();
        mbar_arrive(BAR(B_PFREE));
        bulk_wait0();
        red_relaxed_add(&g_cnt[(C_U + tj) * 32], 1);
        TS(27);
        wait_counter(&g_cnt[(C_U + (cta >> 4)) * 32], (epoch + 1) * 16);
#pragma unroll 1
        for (int c = 0; c < 4; ++c) {
          mbar_expect_tx(BAR(B_UCH + c), 4096);
          bulk_load(sb + SM_U + c * U_BYTES + 256, p.uT + (size_t)(cta * 4 + c) * 2048, 4096, BAR(B_UCH + c));
        }
        TS(3);
      }
      __syncwarp();
      if (ti == 0) {
        float4* z = (float4*)&g_kv[(epoch & 1) ^ 1][tj][0];
#pragma unroll 1
        for (int i = lane; i < 272; i += 32) z[i] = make_float4(0.f, 0.f, 0.f, 0.f);
      }
    }
  }
  __syncwarp();
  cluster_arrive();
  cluster_wait();
  if (tid == 0) TS(31);
#undef BAR
}

typedef CUresult (*EncodeFn)(CUtensorMap*, CUtensorMapDataType, cuuint32_t, void*, const cuuint64_t*, const cuuint64_t*,
                             const cuuint32_t*, const cuuint32_t*, CUtensorMapInterleave, CUtensorMapSwizzle,
                             CUtensorMapL2promotion, CUtensorMapFloatOOBfill);

static void make_map(EncodeFn enc, CUtensorMap* m, const void* base, uint64_t inner, uint64_t outer, uint32_t box_in,
                     uint32_t box_out, CUtensorMapSwizzle swz = CU_TENSOR_MAP_SWIZZLE_128B) {
  cuuint64_t gd[2] = {inner, outer};
  cuuint64_t gs[1] = {inner * 2};
  cuuint32_t bd[2] = {box_in, box_out};
  cuuint32_t es[2] = {1, 1};
  enc(m, CU_TENSOR_MAP_DATA_TYPE_BFLOAT16, 2, const_cast<void*>(base), gd, gs, bd, es, CU_TENSOR_MAP_INTERLEAVE_NONE,
      swz, CU_TENSOR_MAP_L2_PROMOTION_L2_128B, CU_TENSOR_MAP_FLOAT_OOB_FILL_NONE);
}

}

extern "C" void kernel_launch(void* const* d_in, const int* in_sizes, int n_in, void* d_out, int out_size) {
  using namespace s4la;
  (void)in_sizes; (void)n_in; (void)out_size;
  static EncodeFn enc = nullptr;
  static void *uT = nullptr, *yT = nullptr, *oS = nullptr;
  if (!enc) {
    void* fn = nullptr;
    cudaDriverEntryPointQueryResult qr;
    cudaGetDriverEntryPoint("cuTensorMapEncodeTiled", &fn, cudaEnableDefault, &qr);
    enc = (EncodeFn)fn;
    cudaGetSymbolAddress(&uT, g_uT);
    cudaGetSymbolAddress(&yT, g_yT);
    cudaGetSymbolAddress(&oS, g_o);
    cudaFuncSetAttribute(fused_kernel, cudaFuncAttributeMaxDynamicSharedMemorySize, SM_TOTAL);
  }
  const __nv_bfloat16* const* in = (const __nv_bfloat16* const*)d_in;
  Maps maps;
  make_map(enc, &maps.x, in[9], 512, 2048, 32, 128, CU_TENSOR_MAP_SWIZZLE_64B);
  {
    cuuint64_t gd[3] = {512, 512, 3};
    cuuint64_t gs[2] = {3072, 1024};
    cuuint32_t bd[3] = {64, 16, 3};
    cuuint32_t es[3] = {1, 1, 1};
    enc(&maps.w, CU_TENSOR_MAP_DATA_TYPE_BFLOAT16, 3, const_cast<__nv_bfloat16*>(in[10]), gd, gs, bd, es,
        CU_TENSOR_MAP_INTERLEAVE_NONE, CU_TENSOR_MAP_SWIZZLE_128B, CU_TENSOR_MAP_L2_PROMOTION_L2_128B,
        CU_TENSOR_MAP_FLOAT_OOB_FILL_NONE);
  }
  make_map(enc, &maps.wo, in[11], 512, 512, 64, 256);
  make_map(enc, &maps.u, in[0], 512, 2048, 64, 128);
  make_map(enc, &maps.uT, uT, 2048, 512, 64, 64);
  make_map(enc, &maps.yT, yT, 2048, 512, 64, 64);
  make_map(enc, &maps.o, oS, 512, 2048, 64, 64);
  make_map(enc, &maps.out, d_out, 1024, 2048, 64, 128);
  Ptrs p;
  p.A_re = in[1]; p.A_im = in[2]; p.B_re = in[3]; p.B_im = in[4]; p.C_re = in[5]; p.C_im = in[6];
  p.log_dt = in[7]; p.Dskip = in[8]; p.x = in[9]; p.wqkv = in[10]; p.wo = in[11];
  p.uT = (__nv_bfloat16*)uT; p.yT = (__nv_bfloat16*)yT;
  fused_kernel<<<NCTA, NTHREADS, SM_TOTAL, cudaStreamPerThread>>>(maps, p);
}
```

```cpp
#include <cuda_runtime.h>
#include <cuda_bf16.h>
#include <cuda_fp16.h>
#include <cuda.h>
#include <stdint.h>

#define DEVI __device__ __forceinline__

namespace s4la {

constexpr int NTHREADS = 512;
constexpr int NCTA = 128;

constexpr int NSTG = 7;
constexpr uint32_t STG_BYTES = 20480, STG_X = 0, STG_W = 8192;
constexpr uint32_t SM_QS = 0;
constexpr uint32_t SM_PK = SM_QS + 16384, SM_VS = SM_QS + 32768;
constexpr uint32_t SM_WO = 65536;
constexpr uint32_t SM_KV = 131072;
constexpr uint32_t SM_BOUT = 16384;
constexpr uint32_t SM_U = 143360, U_BYTES = 4352;
constexpr uint32_t SM_P = 160768, P_BYTES = 4096;
constexpr uint32_t SM_VV = 177152, VV_BYTES = 12800;
constexpr uint32_t VV_U5 = 0, VV_U3 = 3712, VV_U9 = 7424, VV_U7 = 10112;
constexpr uint32_t KG_BYTES = 3200;
constexpr uint32_t SM_BAR = SM_VV + 4 * VV_BYTES;
constexpr uint32_t SM_PTAB = SM_BAR + 320;
constexpr uint32_t SM_TOTAL = SM_PTAB + 2048;
static_assert(SM_TOTAL <= 232448, "shared memory");
constexpr int PADV = 12;

enum { B_FULL = 0, B_EMPTY = 7, B_TILE = 14, B_UCH = 15, B_KVP = 19, B_KVF = 20, B_OST = 21, B_RF = 22, B_WO = 30, B_RE = 31, B_PFREE = 32, B_CONVD = 33, B_SLOT = 34, B_COUNT = 35 };
__host__ __device__ constexpr int bar_count(int i) {
  return (i >= B_EMPTY && i < B_TILE) ? 16 : (i == B_KVP || i == B_OST || i == B_CONVD) ? 8 : i == B_RE ? 16 : i == B_SLOT ? 2 : 1;
}

constexpr int PD_OFF = 0, P2_OFF = 544, P3_OFF = 768;

constexpr int SL_K2048 = 20, SL_ZERO = 21, SL_510 = 22, SL_0 = 23;
__host__ __device__ constexpr int koff(int y) {
  return y < 8 ? y : y < 12 ? 256 + 2 * (y - 8) : y < 16 ? 512 + 256 * ((y - 12) >> 1) + 4 * (y & 1) : 1024 + 256 * (y - 16);
}
__host__ __device__ constexpr int kidx_c(int l) {
  const int y = l < 256 ? (l & 7) : l < 512 ? 8 + ((l & 7) >> 1) : l < 1024 ? 12 + (((l - 512) >> 8) << 1) + ((l >> 2) & 1)
                                                                            : 16 + ((l - 1024) >> 8);
  return ((l >> 3) & 31) * 24 + y;
}
constexpr int slot_direct(int l) {
  if (l < 0 || l > 510) return SL_ZERO;
  if (l == 510) return SL_510;
  if (l == 0) return SL_0;
  return kidx_c(l < 256 ? l : ((l + ((l >> 1) & 1)) & ~1));
}
constexpr int slot_seg2(int v, int k) { return (k >= 32 && k < 64) ? kidx_c(16 * k + 4 * v) : SL_ZERO; }
constexpr int slot_seg3(int pi, int k) {
  return (k >= 64 && k < 128) ? kidx_c(16 * k + 8 * pi) : ((k == 128 && pi == 0) ? SL_K2048 : SL_ZERO);
}
constexpr int slot_word(int w) {
  return w < 0 ? SL_ZERO : w < 544 ? slot_direct(w - 16) : w < 768 ? slot_seg2((w - 544) / 56, 16 + (w - 544) % 56)
       : w < 944 ? slot_seg3((w - 768) / 88, 48 + (w - 768) % 88) : SL_ZERO;
}
struct PTab { uint32_t v[512]; };
constexpr PTab make_ptab() {
  PTab t{};
  for (int lane = 0; lane < 32; ++lane)
    for (int i = 0; i < 16; ++i)
      t.v[i * 32 + lane] = (slot_word(31 * lane - 1 + 2 * i) * 4) | ((slot_word(31 * lane + 2 * i) * 4) << 16);
  return t;
}
__device__ const PTab g_ptab = make_ptab();

__device__ __nv_bfloat16 g_uT[512 * 2048];
__device__ __nv_bfloat16 g_yT[512 * 2048];
__device__ __nv_bfloat16 g_o[2048 * 512];
__device__ float g_kv[2][8][4 * 272];
__device__ unsigned g_cnt[64 * 32];
__device__ unsigned g_epoch;
#define TS(slot) do { } while (0)
#define TSR(on, slot) do { } while (0)
#define TSD(slot) do { } while (0)
enum { C_U = 0, C_KV = 8, C_O = 16, C_Y = 32 };

struct Maps {
  CUtensorMap x, w, wo, u, uT, yT, o, out;
};
struct Ptrs {
  const __nv_bfloat16 *A_re, *A_im, *B_re, *B_im, *C_re, *C_im, *log_dt, *Dskip;
  const __nv_bfloat16 *x, *wqkv, *wo;
  __nv_bfloat16 *uT, *yT;
};

DEVI uint32_t s2u(const void* p) { return (uint32_t)__cvta_generic_to_shared(p); }
DEVI void mbar_init(uint32_t b, uint32_t c) { asm volatile("mbarrier.init.shared::cta.b64 [%0], %1;" ::"r"(b), "r"(c) : "memory"); }
DEVI void mbar_expect_tx(uint32_t b, uint32_t bytes) {
  asm volatile("mbarrier.arrive.expect_tx.shared::cta.b64 _, [%0], %1;" ::"r"(b), "r"(bytes) : "memory");
}
DEVI void mbar_arrive(uint32_t b) { asm volatile("mbarrier.arrive.shared::cta.b64 _, [%0];" ::"r"(b) : "memory"); }
DEVI void mbar_arrive_cluster(uint32_t b, uint32_t cta) {
  asm volatile("{\n.reg .b32 r;\nmapa.shared::cluster.u32 r, %0, %1;\nmbarrier.arrive.shared::cluster.b64 _, [r];\n}"
               ::"r"(b), "r"(cta) : "memory");
}
DEVI void mbar_wait(uint32_t b, uint32_t parity) {
  asm volatile("{\n.reg .pred p;\nLAB_WAIT:\nmbarrier.try_wait.parity.shared::cta.b64 p, [%0], %1;\n@!p bra LAB_WAIT;\n}"
               ::"r"(b), "r"(parity) : "memory");
}
DEVI void mbar_wait_long(uint32_t b, uint32_t parity) {
  asm volatile("{\n.reg .pred p;\nLAB_WAIT:\nmbarrier.try_wait.parity.shared::cta.b64 p, [%0], %1, 0x989680;\n@!p bra LAB_WAIT;\n}"
               ::"r"(b), "r"(parity) : "memory");
}
DEVI void bar_sync(int id, int n) { asm volatile("bar.sync %0, %1;" ::"r"(id), "r"(n) : "memory"); }
DEVI void bar_arrive(int id, int n) { asm volatile("bar.arrive %0, %1;" ::"r"(id), "r"(n) : "memory"); }
DEVI void fence_async_smem() { asm volatile("fence.proxy.async.shared::cta;" ::: "memory"); }
DEVI void fence_async_all() { asm volatile("fence.proxy.async;" ::: "memory"); }
DEVI void cluster_arrive() { asm volatile("barrier.cluster.arrive.relaxed.aligned;" ::: "memory"); }
DEVI void cluster_wait() { asm volatile("barrier.cluster.wait.aligned;" ::: "memory"); }

DEVI void tma_load_2d(uint32_t dst, const CUtensorMap* m, int c0, int c1, uint32_t bar) {
  asm volatile("cp.async.bulk.tensor.2d.shared::cluster.global.mbarrier::complete_tx::bytes [%0], [%1, {%3, %4}], [%2];"
               ::"r"(dst), "l"(m), "r"(bar), "r"(c0), "r"(c1) : "memory");
}
DEVI void tma_load_2d_mc(uint32_t dst, const CUtensorMap* m, int c0, int c1, uint32_t bar, uint16_t mask) {
  asm volatile("cp.async.bulk.tensor.2d.shared::cluster.global.mbarrier::complete_tx::bytes.multicast::cluster [%0], [%1, {%3, %4}], [%2], %5;"
               ::"r"(dst), "l"(m), "r"(bar), "r"(c0), "r"(c1), "h"(mask) : "memory");
}
DEVI void tma_load_3d_mc(uint32_t dst, const CUtensorMap* m, int c0, int c1, int c2, uint32_t bar, uint16_t mask) {
  asm volatile("cp.async.bulk.tensor.3d.shared::cluster.global.mbarrier::complete_tx::bytes.multicast::cluster [%0], [%1, {%3, %4, %5}], [%2], %6;"
               ::"r"(dst), "l"(m), "r"(bar), "r"(c0), "r"(c1), "r"(c2), "h"(mask) : "memory");
}
DEVI void tma_store_2d(const CUtensorMap* m, uint32_t src, int c0, int c1) {
  asm volatile("cp.async.bulk.tensor.2d.global.shared::cta.bulk_group [%0, {%2, %3}], [%1];"
               ::"l"(m), "r"(src), "r"(c0), "r"(c1) : "memory");
}
DEVI void bulk_load(uint32_t dst, const void* src, uint32_t bytes, uint32_t bar) {
  asm volatile("cp.async.bulk.shared::cluster.global.mbarrier::complete_tx::bytes [%0], [%1], %2, [%3];"
               ::"r"(dst), "l"(src), "r"(bytes), "r"(bar) : "memory");
}
DEVI void bulk_store(void* dst, uint32_t src, uint32_t bytes) {
  asm volatile("cp.async.bulk.global.shared::cta.bulk_group [%0], [%1], %2;" ::"l"(dst), "r"(src), "r"(bytes) : "memory");
}
DEVI void bulk_reduce_add_f32(void* dst, uint32_t src, uint32_t bytes) {
  asm volatile("cp.reduce.async.bulk.global.shared::cta.bulk_group.add.f32 [%0], [%1], %2;" ::"l"(dst), "r"(src), "r"(bytes) : "memory");
}
DEVI void bulk_commit() { asm volatile("cp.async.bulk.commit_group;" ::: "memory"); }
DEVI void bulk_wait0() { asm volatile("cp.async.bulk.wait_group 0;" ::: "memory"); }
DEVI void bulk_wait_read0() { asm volatile("cp.async.bulk.wait_group.read 0;" ::: "memory"); }
DEVI void l2_prefetch(const void* p, uint32_t bytes) {
  asm volatile("cp.async.bulk.prefetch.L2.global [%0], %1;" ::"l"(p), "r"(bytes) : "memory");
}
DEVI void prefetch_tmap(const CUtensorMap* m) { asm volatile("prefetch.tensormap [%0];" ::"l"(m) : "memory"); }

DEVI void red_release_add(unsigned* p, unsigned v) {
  asm volatile("red.release.gpu.global.add.u32 [%0], %1;" ::"l"(p), "r"(v) : "memory");
}
DEVI void red_relaxed_add(unsigned* p, unsigned v) {
  asm volatile("red.relaxed.gpu.global.add.u32 [%0], %1;" ::"l"(p), "r"(v) : "memory");
}
DEVI unsigned ld_relaxed(const unsigned* p) {
  unsigned v;
  asm volatile("ld.relaxed.gpu.global.u32 %0, [%1];" : "=r"(v) : "l"(p) : "memory");
  return v;
}
DEVI void wait_counter(const unsigned* p, unsigned target) {
#pragma unroll 1
  for (int it = 0; (int)(ld_relaxed(p) - target) < 0; ++it)
    if (it > (1 << 22)) __trap();
}

DEVI void ldsm_x4(uint32_t (&r)[4], uint32_t a) {
  asm volatile("ldmatrix.sync.aligned.m8n8.x4.shared.b16 {%0,%1,%2,%3}, [%4];"
               : "=r"(r[0]), "=r"(r[1]), "=r"(r[2]), "=r"(r[3]) : "r"(a) : "memory");
}
DEVI void ldsm_x4_t(uint32_t (&r)[4], uint32_t a) {
  asm volatile("ldmatrix.sync.aligned.m8n8.x4.trans.shared.b16 {%0,%1,%2,%3}, [%4];"
               : "=r"(r[0]), "=r"(r[1]), "=r"(r[2]), "=r"(r[3]) : "r"(a) : "memory");
}
DEVI void ldsm_x2_t(uint32_t& r0, uint32_t& r1, uint32_t a) {
  asm volatile("ldmatrix.sync.aligned.m8n8.x2.trans.shared.b16 {%0,%1}, [%2];" : "=r"(r0), "=r"(r1) : "r"(a) : "memory");
}
DEVI void stsm_x4(uint32_t a, uint32_t r0, uint32_t r1, uint32_t r2, uint32_t r3) {
  asm volatile("stmatrix.sync.aligned.m8n8.x4.shared.b16 [%0], {%1,%2,%3,%4};"
               ::"r"(a), "r"(r0), "r"(r1), "r"(r2), "r"(r3) : "memory");
}
DEVI void stsm_x4_t(uint32_t a, uint32_t r0, uint32_t r1, uint32_t r2, uint32_t r3) {
  asm volatile("stmatrix.sync.aligned.m8n8.x4.trans.shared.b16 [%0], {%1,%2,%3,%4};"
               ::"r"(a), "r"(r0), "r"(r1), "r"(r2), "r"(r3) : "memory");
}
DEVI uint32_t lds32(uint32_t a) { uint32_t v; asm volatile("ld.shared.b32 %0, [%1];" : "=r"(v) : "r"(a) : "memory"); return v; }
DEVI float lds_f32(uint32_t a) { float v; asm volatile("ld.shared.f32 %0, [%1];" : "=f"(v) : "r"(a) : "memory"); return v; }
DEVI void sts32(uint32_t a, uint32_t v) { asm volatile("st.shared.b32 [%0], %1;" ::"r"(a), "r"(v) : "memory"); }
DEVI void sts_f32(uint32_t a, float v) { asm volatile("st.shared.f32 [%0], %1;" ::"r"(a), "f"(v) : "memory"); }
DEVI void sts_f32x2(uint32_t a, float x, float y) { asm volatile("st.shared.v2.f32 [%0], {%1,%2};" ::"r"(a), "f"(x), "f"(y) : "memory"); }
DEVI uint4 lds128(uint32_t a) {
  uint4 v;
  asm volatile("ld.shared.v4.b32 {%0,%1,%2,%3}, [%4];" : "=r"(v.x), "=r"(v.y), "=r"(v.z), "=r"(v.w) : "r"(a) : "memory");
  return v;
}
DEVI void sts128(uint32_t a, uint32_t x, uint32_t y, uint32_t z, uint32_t w) {
  asm volatile("st.shared.v4.b32 [%0], {%1,%2,%3,%4};" ::"r"(a), "r"(x), "r"(y), "r"(z), "r"(w) : "memory");
}

DEVI void mma_bf16(float (&d)[4], uint32_t a0, uint32_t a1, uint32_t a2, uint32_t a3, uint32_t b0, uint32_t b1) {
  asm("mma.sync.aligned.m16n8k16.row.col.f32.bf16.bf16.f32 {%0,%1,%2,%3}, {%4,%5,%6,%7}, {%8,%9}, {%0,%1,%2,%3};"
      : "+f"(d[0]), "+f"(d[1]), "+f"(d[2]), "+f"(d[3])
      : "r"(a0), "r"(a1), "r"(a2), "r"(a3), "r"(b0), "r"(b1));
}
DEVI void mma_f16(float (&d)[4], const uint32_t (&a)[4], uint32_t b0, uint32_t b1) {
  asm("mma.sync.aligned.m16n8k16.row.col.f32.f16.f16.f32 {%0,%1,%2,%3}, {%4,%5,%6,%7}, {%8,%9}, {%0,%1,%2,%3};"
      : "+f"(d[0]), "+f"(d[1]), "+f"(d[2]), "+f"(d[3])
      : "r"(a[0]), "r"(a[1]), "r"(a[2]), "r"(a[3]), "r"(b0), "r"(b1));
}
DEVI void mma_bf16v(float (&d)[4], const uint32_t (&a)[4], uint32_t b0, uint32_t b1) {
  asm volatile("mma.sync.aligned.m16n8k16.row.col.f32.bf16.bf16.f32 {%0,%1,%2,%3}, {%4,%5,%6,%7}, {%8,%9}, {%0,%1,%2,%3};"
               : "+f"(d[0]), "+f"(d[1]), "+f"(d[2]), "+f"(d[3])
               : "r"(a[0]), "r"(a[1]), "r"(a[2]), "r"(a[3]), "r"(b0), "r"(b1));
}
DEVI uint32_t pack_bf16(float lo, float hi) {
  uint32_t r;
  asm("cvt.rn.bf16x2.f32 %0, %1, %2;" : "=r"(r) : "f"(hi), "f"(lo));
  return r;
}
DEVI uint32_t pack_f16(float lo, float hi) {
  uint32_t r;
  asm("cvt.rn.f16x2.f32 %0, %1, %2;" : "=r"(r) : "f"(hi), "f"(lo));
  return r;
}
DEVI uint32_t ldg16(const __nv_bfloat16* p) {
  uint32_t v;
  asm volatile("ld.global.nc.u16 %0, [%1];" : "=r"(v) : "l"(p));
  return v;
}
DEVI bool elect_one() {
  uint32_t pred;
  asm volatile("{\n.reg .pred p;\nelect.sync _|p, 0xffffffff;\nselp.u32 %0, 1, 0, p;\n}" : "=r"(pred));
  return pred != 0;
}
DEVI float bf_lo(uint32_t v) { return __uint_as_float(v << 16); }
DEVI float bf_hi(uint32_t v) { return __uint_as_float(v & 0xffff0000u); }
DEVI float bf2f(__nv_bfloat16 v) { return __bfloat162float(v); }
DEVI float round_bf16(float v) { return __bfloat162float(__float2bfloat16_rn(v)); }
DEVI float rcp(float x) { float r; asm("rcp.approx.ftz.f32 %0, %1;" : "=f"(r) : "f"(x)); return r; }
DEVI float ex2(float x) { float r; asm("ex2.approx.ftz.f32 %0, %1;" : "=f"(r) : "f"(x)); return r; }

DEVI void wg_fence() { asm volatile("wgmma.fence.sync.aligned;" ::: "memory"); }
DEVI void wg_commit() { asm volatile("wgmma.commit_group.sync.aligned;" ::: "memory"); }
template <int N> DEVI void wg_wait() { asm volatile("wgmma.wait_group.sync.aligned %0;" ::"n"(N) : "memory"); }
constexpr uint32_t DESC_HI = (1u << 30) | (1024 >> 4);
constexpr uint32_t DESC_HI64 = (2u << 30) | (512 >> 4);
DEVI uint32_t mkdesc(uint32_t saddr, uint32_t lbo) { return ((saddr & 0x3FFFF) >> 4) | ((lbo >> 4) << 16); }

#define R8(b) "%" #b
DEVI void wgmma_n192(float (&d)[96], uint32_t da, uint32_t db, int scale_d) {
  asm volatile(
      "{\n.reg .pred p;\n.reg .b64 da, db;\nsetp.ne.b32 p, %98, 0;\nmov.b64 da, {%96, %100};\nmov.b64 db, {%97, %99};\n"
      "wgmma.mma_async.sync.aligned.m64n192k16.f32.bf16.bf16 "
      "{%0,%1,%2,%3,%4,%5,%6,%7,%8,%9,%10,%11,%12,%13,%14,%15,"
      "%16,%17,%18,%19,%20,%21,%22,%23,%24,%25,%26,%27,%28,%29,%30,%31,"
      "%32,%33,%34,%35,%36,%37,%38,%39,%40,%41,%42,%43,%44,%45,%46,%47,"
      "%48,%49,%50,%51,%52,%53,%54,%55,%56,%57,%58,%59,%60,%61,%62,%63,"
      "%64,%65,%66,%67,%68,%69,%70,%71,%72,%73,%74,%75,%76,%77,%78,%79,"
      "%80,%81,%82,%83,%84,%85,%86,%87,%88,%89,%90,%91,%92,%93,%94,%95}, "
      "da, db, p, 1, 1, 0, 1;\n}"
      : "+f"(d[0]), "+f"(d[1]), "+f"(d[2]), "+f"(d[3]), "+f"(d[4]), "+f"(d[5]), "+f"(d[6]), "+f"(d[7]),
        "+f"(d[8]), "+f"(d[9]), "+f"(d[10]), "+f"(d[11]), "+f"(d[12]), "+f"(d[13]), "+f"(d[14]), "+f"(d[15]),
        "+f"(d[16]), "+f"(d[17]), "+f"(d[18]), "+f"(d[19]), "+f"(d[20]), "+f"(d[21]), "+f"(d[22]), "+f"(d[23]),
        "+f"(d[24]), "+f"(d[25]), "+f"(d[26]), "+f"(d[27]), "+f"(d[28]), "+f"(d[29]), "+f"(d[30]), "+f"(d[31]),
        "+f"(d[32]), "+f"(d[33]), "+f"(d[34]), "+f"(d[35]), "+f"(d[36]), "+f"(d[37]), "+f"(d[38]), "+f"(d[39]),
        "+f"(d[40]), "+f"(d[41]), "+f"(d[42]), "+f"(d[43]), "+f"(d[44]), "+f"(d[45]), "+f"(d[46]), "+f"(d[47]),
        "+f"(d[48]), "+f"(d[49]), "+f"(d[50]), "+f"(d[51]), "+f"(d[52]), "+f"(d[53]), "+f"(d[54]), "+f"(d[55]),
        "+f"(d[56]), "+f"(d[57]), "+f"(d[58]), "+f"(d[59]), "+f"(d[60]), "+f"(d[61]), "+f"(d[62]), "+f"(d[63]),
        "+f"(d[64]), "+f"(d[65]), "+f"(d[66]), "+f"(d[67]), "+f"(d[68]), "+f"(d[69]), "+f"(d[70]), "+f"(d[71]),
        "+f"(d[72]), "+f"(d[73]), "+f"(d[74]), "+f"(d[75]), "+f"(d[76]), "+f"(d[77]), "+f"(d[78]), "+f"(d[79]),
        "+f"(d[80]), "+f"(d[81]), "+f"(d[82]), "+f"(d[83]), "+f"(d[84]), "+f"(d[85]), "+f"(d[86]), "+f"(d[87]),
        "+f"(d[88]), "+f"(d[89]), "+f"(d[90]), "+f"(d[91]), "+f"(d[92]), "+f"(d[93]), "+f"(d[94]), "+f"(d[95])
      : "r"(da), "r"(db), "r"(scale_d), "n"(DESC_HI), "n"(DESC_HI64));
}
DEVI void wgmma_n64(float (&d)[32], uint32_t da, uint32_t db, int scale_d) {
  asm volatile(
      "{\n.reg .pred p;\n.reg .b64 da, db;\nsetp.ne.b32 p, %34, 0;\nmov.b64 da, {%32, %35};\nmov.b64 db, {%33, %35};\n"
      "wgmma.mma_async.sync.aligned.m64n64k16.f32.bf16.bf16 "
      "{%0,%1,%2,%3,%4,%5,%6,%7,%8,%9,%10,%11,%12,%13,%14,%15,"
      "%16,%17,%18,%19,%20,%21,%22,%23,%24,%25,%26,%27,%28,%29,%30,%31}, "
      "da, db, p, 1, 1, 0, 1;\n}"
      : "+f"(d[0]), "+f"(d[1]), "+f"(d[2]), "+f"(d[3]), "+f"(d[4]), "+f"(d[5]), "+f"(d[6]), "+f"(d[7]),
        "+f"(d[8]), "+f"(d[9]), "+f"(d[10]), "+f"(d[11]), "+f"(d[12]), "+f"(d[13]), "+f"(d[14]), "+f"(d[15]),
        "+f"(d[16]), "+f"(d[17]), "+f"(d[18]), "+f"(d[19]), "+f"(d[20]), "+f"(d[21]), "+f"(d[22]), "+f"(d[23]),
        "+f"(d[24]), "+f"(d[25]), "+f"(d[26]), "+f"(d[27]), "+f"(d[28]), "+f"(d[29]), "+f"(d[30]), "+f"(d[31])
      : "r"(da), "r"(db), "r"(scale_d), "n"(DESC_HI));
}

struct C32 { float re, im; };
DEVI C32 csq(C32 a) { return {a.re * a.re - a.im * a.im, 2.f * a.re * a.im}; }
DEVI C32 cmul(C32 a, C32 b) { return {a.re * b.re - a.im * b.im, a.re * b.im + a.im * b.re}; }
DEVI C32 cfresh(float zl, float zi, float m) {
  float mag = ex2(zl * m), ph = zi * m;
  return {mag * __cosf(ph), mag * __sinf(ph)};
}
struct HMul { uint32_t b, bp; };
DEVI HMul mk_mul(float re, float im) { return {pack_f16(re, im), pack_f16(-im, re)}; }
DEVI uint32_t hcmul(uint32_t a, const HMul& m) {
  __half2 ah = *reinterpret_cast<__half2*>(&a);
  __half2 b = *reinterpret_cast<const __half2*>(&m.b), bp = *reinterpret_cast<const __half2*>(&m.bp);
  __half2 r = __hfma2(__high2half2(ah), bp, __hmul2(__low2half2(ah), b));
  return *reinterpret_cast<uint32_t*>(&r);
}
DEVI uint32_t badd(uint32_t a, uint32_t b) {
  __nv_bfloat162 r = __hadd2(*reinterpret_cast<__nv_bfloat162*>(&a), *reinterpret_cast<__nv_bfloat162*>(&b));
  return *reinterpret_cast<uint32_t*>(&r);
}
template <int MU0, int NMU, int DMAX>
DEVI void conv_tail(float (&acc)[16][4], uint32_t p_lane, uint32_t v_base, int back, bool edge, int lane) {
  const int hsel = (lane >> 3) & 1;
  const int row = (lane & 7) + ((lane >> 4) << 3) + PADV - 8 - (back & (hsel ^ 1));
  const uint32_t la = v_base + row * 32 + (((hsel ^ back) ^ ((row >> 2) & 1)) << 4);
  uint32_t M[3][4];
  ldsm_x4_t(M[0], la);
  ldsm_x4_t(M[1], la + 256);
  uint32_t H[2 * NMU];
#pragma unroll
  for (int i = 0; i < 2 * NMU; ++i) H[i ^ 1] = lds32(p_lane + (uint32_t)(MU0 - 1 + i) * 32);
  if (edge) {
    const uint32_t a[4] = {0u, 0u, M[0][0], M[0][1]};
#pragma unroll
    for (int k = 1; k < NMU; ++k) mma_bf16v(acc[MU0 - 2 + 2 * k], a, H[2 * k], H[2 * k + 1]);
  }
#pragma unroll
  for (int delta = -1; delta <= DMAX; ++delta) {
    if (delta + 2 <= DMAX) ldsm_x4_t(M[(delta + 3) % 3], la + (delta + 3) * 256);
#pragma unroll
    for (int k = 0; k < NMU; ++k)
      if (delta + MU0 + 2 * k < 16) mma_bf16v(acc[delta + MU0 + 2 * k], M[(delta + 1) % 3], H[2 * k], H[2 * k + 1]);
  }
}

__global__ void __cluster_dims__(2, 1, 1) __launch_bounds__(NTHREADS, 1)
fused_kernel(const __grid_constant__ Maps maps, const Ptrs p) {
  extern __shared__ __align__(1024) uint8_t smem[];
  const uint32_t sb = s2u(smem);
  const int tid = threadIdx.x, lane = tid & 31;
  const int warp = __shfl_sync(0xffffffffu, tid >> 5, 0);
  const int cta = blockIdx.x;
  const uint32_t rank = cta & 1;
  const int ti = 2 * (cta >> 4) + rank;
  const int tj = (cta >> 1) & 7;
  const int pi = cta >> 3, pj = cta & 7;
  const uint32_t bars = sb + SM_BAR;
#define BAR(i) (bars + 8 * (i))
  const int g = lane >> 2, q = lane & 3;

  auto issue_stage = [&](int ks, int s) {
    const uint32_t st = sb + s * STG_BYTES, fb = BAR(B_FULL + s);
    mbar_expect_tx(fb, STG_BYTES);
    tma_load_2d(st + STG_X, &maps.x, ks * 32, ti * 128, fb);
    tma_load_3d_mc(st + STG_W + rank * 6144, &maps.w, tj * 64, ks * 32 + rank * 16, 0, fb, 3);
  };

  const int kch = warp & 3, krd = warp >> 2;
  float zr, zi, wr, wi;
  unsigned epoch;
  uint32_t r_dskip;
  {
    const size_t po = (size_t)(cta * 4 + kch) * 128 + krd * 32 + lane;
    const uint32_t r_ar = ldg16(p.A_re + po), r_ai = ldg16(p.A_im + po), r_br = ldg16(p.B_re + po), r_bi = ldg16(p.B_im + po);
    const uint32_t r_cr = ldg16(p.C_re + po), r_ci = ldg16(p.C_im + po), r_ldt = ldg16(p.log_dt + cta * 4 + kch);
    epoch = __ldcg(&g_epoch);
    r_dskip = ldg16(p.Dskip + cta * 4 + kch);
    uint4 pt;
    if (tid < 128) pt = __ldg((const uint4*)g_ptab.v + tid);
    if (tid == 384) {
      TS(0);
#pragma unroll
      for (int i = 0; i < B_COUNT; ++i) mbar_init(BAR(i), bar_count(i));
      asm volatile("fence.mbarrier_init.release.cluster;" ::: "memory");
      prefetch_tmap(&maps.x); prefetch_tmap(&maps.w); prefetch_tmap(&maps.u);
    }
    __syncthreads();
    cluster_arrive();
    if (warp >= 12) {
      cluster_wait();
      if (elect_one()) {
        if (warp == 13) {
          mbar_expect_tx(BAR(B_TILE), 16384);
          tma_load_2d(sb + SM_U, &maps.u, tj * 64, ti * 128, BAR(B_TILE));
          prefetch_tmap(&maps.uT); prefetch_tmap(&maps.wo); prefetch_tmap(&maps.o); prefetch_tmap(&maps.yT);
          prefetch_tmap(&maps.out);
        } else {
          if (warp == 12) TS(61);
          { const int ks = warp == 12 ? 0 : warp - 13; issue_stage(ks, ks); }
        }
      }
      __syncwarp();
    }
    if (tid < 128) sts128(sb + SM_PTAB + tid * 16, pt.x, pt.y, pt.z, pt.w);
    const float dt = round_bf16(expf(bf_lo(r_ldt)));
    zr = dt * bf_lo(r_ar); zi = dt * bf_lo(r_ai);
    const float dbr = dt * bf_lo(r_br), dbi = dt * bf_lo(r_bi), cr = bf_lo(r_cr), ci = bf_lo(r_ci);
    wr = cr * dbr - ci * dbi; wi = cr * dbi + ci * dbr;
  }
  {
    const float mz = __uint_as_float(__reduce_max_sync(0xffffffffu, __float_as_uint(fmaxf(zr, 0.f))));
    const int E = min(max((int)(__reduce_max_sync(0xffffffffu, __float_as_uint(fmaxf(fabsf(wr), fabsf(wi)))) >> 23), 1), 252);
    const float sc = __int_as_float((253 - E) << 23), inv = __int_as_float((E + 1) << 23);
    const float zl = (zr - mz) * 1.4426950408889634f;
    const uint32_t tb = sb + SM_VV + kch * VV_BYTES + krd * KG_BYTES;
    const uint32_t sta = tb + (((lane >> 2) << 4) | ((lane & 3) << 2));
    auto put = [&](int r, uint32_t v) { sts32((sta ^ ((r & 7) << 4)) + r * 128, v); };
    const uint32_t lda = tb + ((lane & 7) + (((lane >> 3) & 1) << 3)) * 128;
    const uint32_t ldb = tb + ((lane & 7) + ((lane >> 4) << 3)) * 128;
    C32 e1 = cfresh(zl, zi, 1.f), e2 = csq(e1), e4 = csq(e2), e8 = csq(e4);
    C32 e16 = cfresh(zl, zi, 16.f), e32 = csq(e16), e64 = csq(e32), e128 = csq(e64);
    C32 e256 = cfresh(zl, zi, 256.f), e512 = csq(e256), e1024 = csq(e512), e768 = cmul(e512, e256);
    uint32_t XA[2][4][4];
    {
      const HMul m16 = mk_mul(e16.re, e16.im), m32 = mk_mul(e32.re, e32.im), m64 = mk_mul(e64.re, e64.im);
      const HMul m128 = mk_mul(e128.re, e128.im);
      uint32_t X[16];
      X[0] = 0x00003c00u; X[1] = pack_f16(e8.re, e8.im); X[2] = m16.b; X[4] = m32.b; X[8] = m64.b;
      X[3] = hcmul(X[1], m16); X[5] = hcmul(X[1], m32); X[6] = hcmul(X[2], m32); X[7] = hcmul(X[3], m32);
#pragma unroll
      for (int r = 1; r < 8; ++r) X[8 + r] = hcmul(X[r], m64);
#pragma unroll
      for (int h = 0; h < 2; ++h) {
#pragma unroll
        for (int r = 0; r < 16; ++r) put(r, h == 0 ? X[r] : r == 0 ? m128.b : hcmul(X[r], m128));
        __syncwarp();
#pragma unroll
        for (int k = 0; k < 4; ++k) ldsm_x4(XA[h][k], lda + (((2 * k + (lane >> 4)) ^ (lane & 7)) << 4));
        __syncwarp();
      }
    }
    if (warp >= 14 && elect_one()) {
      issue_stage(warp - 11, warp - 11);
      issue_stage(warp - 9, warp - 9);
      if (warp == 14) l2_prefetch((const char*)p.wqkv + 224 * 3072 + cta * 6912, 6912);
      else l2_prefetch((const char*)p.x + (size_t)cta * 16384, 16384);
    }
    __syncwarp();
    float D[2][3][4];
#pragma unroll
    for (int t = 0; t < 6; ++t) D[t / 3][t % 3][0] = D[t / 3][t % 3][1] = D[t / 3][t % 3][2] = D[t / 3][t % 3][3] = 0.f;
    auto contract = [&](int t0, int nt) {
      __syncwarp();
#pragma unroll
      for (int k = 0; k < 4; ++k) {
        uint32_t b[4];
        ldsm_x4(b, ldb + (((2 * k + ((lane >> 3) & 1)) ^ (lane & 7)) << 4));
#pragma unroll
        for (int h = 0; h < 2; ++h) {
          mma_f16(D[h][t0], XA[h][k], b[0], b[1]);
          if (nt == 2) mma_f16(D[h][t0 + 1], XA[h][k], b[2], b[3]);
        }
      }
      __syncwarp();
    };
    const HMul c1 = mk_mul(e1.re, -e1.im), c2 = mk_mul(e2.re, -e2.im), c4 = mk_mul(e4.re, -e4.im);
    const HMul c256 = mk_mul(e256.re, -e256.im), c512 = mk_mul(e512.re, -e512.im), c768 = mk_mul(e768.re, -e768.im);
    const HMul c1024 = mk_mul(e1024.re, -e1024.im);
    uint32_t W[8];
    W[0] = pack_f16(wr * sc, -wi * sc);
    W[1] = hcmul(W[0], c1); W[2] = hcmul(W[0], c2); W[3] = hcmul(W[1], c2);
    W[4] = hcmul(W[0], c4); W[5] = hcmul(W[1], c4); W[6] = hcmul(W[2], c4); W[7] = hcmul(W[3], c4);
#pragma unroll
    for (int i = 0; i < 8; ++i) put(i, W[i]);
#pragma unroll
    for (int i = 0; i < 4; ++i) put(8 + i, hcmul(W[2 * i], c256));
    put(12, hcmul(W[0], c512)); put(13, hcmul(W[4], c512)); put(14, hcmul(W[0], c768)); put(15, hcmul(W[4], c768));
    contract(0, 2);
    const uint32_t v0 = hcmul(W[0], c1024);
    put(0, v0); put(1, hcmul(v0, c256)); put(2, hcmul(v0, c512)); put(3, hcmul(v0, c768)); put(4, hcmul(v0, c1024));
    contract(2, 1);
    const uint32_t a = tb + (g * 24 + 2 * q) * 4;
#pragma unroll
    for (int t = 0; t < 6; ++t) {
      const float(&d)[4] = D[t / 3][t % 3];
      sts_f32x2(a + (t / 3) * 1536 + (t % 3) * 32, d[0] * inv, d[1] * inv);
      sts_f32x2(a + (t / 3) * 1536 + (t % 3) * 32 + 768, d[2] * inv, d[3] * inv);
    }
    if (mz > 0.f) {
      __syncwarp();
#pragma unroll 1
      for (int i = lane; i < 768; i += 32) {
        const int r = i / 24, y = i - 24 * r;
        sts_f32(tb + i * 4, lds_f32(tb + i * 4) * ex2(mz * 1.4426950408889634f * (koff(y) + 8 * r)));
      }
    }
  }
  if (tid == 0) TS(2);
  if (warp < 12) cluster_wait();
  if (tid == 0) TS(32);
  __syncthreads();
  if (tid == 0) TSD(33);

  if (warp < 4) {
    asm volatile("setmaxnreg.inc.sync.aligned.u32 152;");
    if (tid == 0) TS(34);
    const int d = cta * 4 + warp;
    const uint32_t vv = sb + SM_VV + warp * VV_BYTES;
    const uint32_t ub = sb + SM_U + warp * U_BYTES;
    const uint32_t pb = sb + SM_P + warp * P_BYTES;
    const float dskip = bf_lo(r_dskip);
#pragma unroll 1
    for (int pass = 0; pass < 2; ++pass) {
      if (pass == 1) {
        const uint32_t kf = vv;
#pragma unroll 2
        for (int i = 0; i < 6; ++i) {
          const uint32_t a = kf + (i * 32 + lane) * 16;
          const uint4 x0 = lds128(a), x1 = lds128(a + KG_BYTES), x2 = lds128(a + 2 * KG_BYTES), x3 = lds128(a + 3 * KG_BYTES);
          auto s4 = [](uint32_t a0, uint32_t a1, uint32_t a2, uint32_t a3) {
            return __float_as_uint((__uint_as_float(a0) + __uint_as_float(a1)) + (__uint_as_float(a2) + __uint_as_float(a3)));
          };
          sts128(a, s4(x0.x, x1.x, x2.x, x3.x), s4(x0.y, x1.y, x2.y, x3.y), s4(x0.z, x1.z, x2.z, x3.z), s4(x0.w, x1.w, x2.w, x3.w));
        }
        __syncwarp();
        const float k1024 = lds_f32(kf + kidx_c(1024) * 4);
        if (lane == 0) {
          sts_f32(kf + SL_ZERO * 4, 0.f);
          sts_f32(kf + SL_510 * 4, lds_f32(kf + kidx_c(510) * 4) - lds_f32(kf + kidx_c(512) * 4));
          sts_f32(kf + SL_0 * 4, lds_f32(kf) + dskip);
        }
        __syncwarp();
        if (tid == 0) TS(36);
        mbar_wait_long(BAR(B_PFREE), 0);
        if (tid == 0) TS(37);
        {
          float prev = 0.f;
#pragma unroll 1
          for (int i0 = 0; i0 < 16; i0 += 4) {
            uint32_t e[4];
            float a[4], b[4];
#pragma unroll
            for (int i = 0; i < 4; ++i) e[i] = lds32(sb + SM_PTAB + ((i0 + i) * 32 + lane) * 4);
#pragma unroll
            for (int i = 0; i < 4; ++i) { a[i] = lds_f32(kf + (e[i] & 0xffff)); b[i] = lds_f32(kf + (e[i] >> 16)); }
#pragma unroll
            for (int i = 0; i < 4; ++i) {
              const uint32_t w = pb + (31 * lane + 2 * (i0 + i)) * 4;
              if (i0 + i > 0) sts32(w - 4, pack_bf16(a[i], prev));
              sts32(w, pack_bf16(b[i], a[i]));
              prev = b[i];
            }
          }
        }
        __syncwarp();
        bar_arrive(7, 384);
        if (lane == 0) TS(4);
        const int gq = g - 2 * q;
        uint32_t h127, h128;
        {
          const uint32_t kf2 = pack_bf16(k1024, k1024) ^ 0x80008000u;
          h127 = (gq == 4 ? 0x0000ffffu : gq == 5 ? 0xffffffffu : gq == 6 ? 0xffff0000u : 0u) & kf2;
          h128 = (gq == -4 ? 0x0000ffffu : gq == -3 ? 0xffffffffu : gq == -2 ? 0xffff0000u : 0u) & kf2;
        }
        bar_sync(4, 384);
        mbar_wait_long(BAR(B_UCH + warp), 0);
        if (lane == 0) TS(7);
        float acc[16][4];
#pragma unroll
        for (int i = 0; i < 16; ++i) { acc[i][0] = acc[i][1] = acc[i][2] = acc[i][3] = 0.f; }
        {
          const uint32_t pd_lane = pb + (PD_OFF + 16 + gq) * 4;
          const int prow0 = 8 + (lane & 7) + ((lane >> 4) << 3), hs = (lane >> 3) & 1;
          const uint32_t zero = (uint32_t)cta >> 20;
          uint32_t B[2][4][4];
          uint32_t A[4][4];
          const uint32_t la0 = ub + prow0 * 32 + ((hs ^ ((prow0 >> 2) & 1)) << 4);
#pragma unroll
          for (int m2 = 0; m2 < 4; ++m2) ldsm_x4(B[0][m2], la0 + m2 * 512);
#pragma unroll
          for (int i = 0; i < 4; ++i) {
            const uint32_t a = pd_lane + i * 512;
            A[i][0] = lds32(a); A[i][1] = lds32(a + 32); A[i][2] = lds32(a - 32); A[i][3] = lds32(a + zero);
          }
          uint32_t la = la0;
#pragma unroll 1
          for (int rho = 0; rho < 8; ++rho) {
#pragma unroll
            for (int m2 = 0; m2 < 4; ++m2) ldsm_x4(B[1][m2], la + (4 + m2) * 512);
#pragma unroll
            for (int i = 0; i < 4; ++i)
#pragma unroll
              for (int m = 0; m < 8; ++m) mma_bf16v(acc[m + i], A[i], B[0][m >> 1][2 * (m & 1)], B[0][m >> 1][2 * (m & 1) + 1]);
            const int prow = prow0 - min(rho + 1, 7);
            la = ub + prow * 32 + ((hs ^ ((prow >> 2) & 1)) << 4);
#pragma unroll
            for (int m2 = 0; m2 < 4; ++m2) ldsm_x4(B[0][m2], la + m2 * 512);
            const uint32_t pa = pd_lane + (rho + 1) * 64;
#pragma unroll
            for (int i = 0; i < 4; ++i) {
#pragma unroll
              for (int m = 0; m < 8 - i; ++m)
                mma_bf16v(acc[8 + m + i], A[i], B[1][m >> 1][2 * (m & 1)], B[1][m >> 1][2 * (m & 1) + 1]);
              A[i][0] = lds32(pa + i * 512); A[i][1] = lds32(pa + i * 512 + 32); A[i][2] = lds32(pa + i * 512 - 32);
              A[i][3] = lds32(pa + i * 512 + zero);
            }
          }
          if (lane == 0) TS(40);
          {
            uint32_t b8[4];
            ldsm_x4(b8, la + 4 * 512);
            const uint32_t h63 = lds32(pd_lane + 63 * 32), h64 = lds32(pd_lane + 64 * 32);
            const uint32_t a63[4] = {0u, h127, 0u, 0u}, a32[4] = {h64, 0u, h63, h64}, a64[4] = {h128, 0u, h127, h128};
#pragma unroll
            for (int m2 = 0; m2 < 4; ++m2) ldsm_x4(B[1][m2], la0 + m2 * 512);
#pragma unroll
            for (int m = 0; m < 8; ++m) mma_bf16v(acc[m + 7], a63, B[0][m >> 1][2 * (m & 1)], B[0][m >> 1][2 * (m & 1) + 1]);
#pragma unroll
            for (int m2 = 0; m2 < 2; ++m2) ldsm_x4(B[0][m2], la0 + (4 + m2) * 512);
#pragma unroll
            for (int m = 0; m < 8; ++m) mma_bf16v(acc[m + 4], a32, B[1][m >> 1][2 * (m & 1)], B[1][m >> 1][2 * (m & 1) + 1]);
            mma_bf16v(acc[15], a63, b8[0], b8[1]);
#pragma unroll
            for (int m = 0; m < 8; ++m) mma_bf16v(acc[m + 8], a64, B[1][m >> 1][2 * (m & 1)], B[1][m >> 1][2 * (m & 1) + 1]);
#pragma unroll
            for (int m = 0; m < 4; ++m) mma_bf16v(acc[m + 12], a32, B[0][m >> 1][2 * (m & 1)], B[0][m >> 1][2 * (m & 1) + 1]);
          }
          if (lane == 0) TS(41);
          bar_sync(5, 384);
#pragma unroll 1
          for (int v = 0; v < 4; ++v)
            conv_tail<4, 3, 11>(acc, pb + (P2_OFF + 56 * v + gq - 16) * 4, vv + ((v & 1) ? VV_U3 : VV_U5), v >> 1, v == 0, lane);
          if (lane == 0) TS(42);
#pragma unroll 1
          for (int pi = 0; pi < 2; ++pi)
            conv_tail<8, 5, 7>(acc, pb + (P3_OFF + 88 * pi + gq - 48) * 4, vv + (pi ? VV_U7 : VV_U9), pi, pi == 0, lane);
        }
        if (lane == 0) TS(8);
        __syncwarp();
        {
          const int mt = lane >> 3;
          const uint32_t a = pb + (128 * (mt >> 1) + 16 * (lane & 7) + 8 * (mt & 1)) * 2;
#pragma unroll
          for (int ab = 0; ab < 16; ab += 2)
            stsm_x4_t(a + ab * 256, pack_bf16(acc[ab][0], acc[ab][1]), pack_bf16(acc[ab][2], acc[ab][3]),
                      pack_bf16(acc[ab + 1][0], acc[ab + 1][1]), pack_bf16(acc[ab + 1][2], acc[ab + 1][3]));
        }
        fence_async_smem();
        __syncwarp();
        if (lane < 2) mbar_arrive_cluster(BAR(B_CONVD), lane);
        bar_arrive(3, 384);
        if (elect_one()) {
          bulk_store(p.yT + (size_t)d * 2048, pb, 4096);
          bulk_commit();
          bulk_wait0();
          red_relaxed_add(&g_cnt[(C_Y + (cta >> 4)) * 32], 1);
          TS(9);
        }
        bar_sync(2, 128);
        if (warp == 0 && elect_one()) {
          wait_counter(&g_cnt[(C_Y + tj) * 32], (epoch + 1) * 64);
          TS(28);
          mbar_expect_tx(BAR(B_TILE), 16384);
          tma_load_2d(sb + SM_U, &maps.yT, ti * 128, tj * 64, BAR(B_TILE));
          tma_load_2d(sb + SM_U + 8192, &maps.yT, ti * 128 + 64, tj * 64, BAR(B_TILE));
        }
        __syncwarp();
      }
      mbar_wait_long(BAR(B_TILE), pass);
      if (lane == 0) TS(26 + 3 * pass);
      {
        const int m = lane >> 3, r = lane & 7;
#pragma unroll 2
        for (int it = 0; it < 8; ++it) {
          const int tb = warp * 4 + (it >> 1), cb = (it & 1) * 4 + m;
          const uint32_t at = (tb * 8 + r) * 128 + ((cb ^ r) << 4);
          const uint32_t ac = (tb >> 3) * 8192 + (cb * 8 + r) * 128 + (((tb & 7) ^ (pass ? 0 : tb >> 3) ^ r) << 4);
          uint32_t v[4];
          ldsm_x4_t(v, sb + SM_U + (pass ? ac : at));
          stsm_x4(sb + SM_P + (pass ? at : ac), v[0], v[1], v[2], v[3]);
        }
      }
      if (pass == 0 && tid == 0) TS(35);
      fence_async_smem();
      if (pass == 0) {
        bar_arrive(6, 160);
      } else {
        bar_sync(2, 128);
        if (warp == 0 && elect_one()) {
          tma_store_2d(&maps.out, sb + SM_P, 64 * tj, 128 * ti);
          bulk_commit();
          bulk_wait_read0();
          TS(30);
        }
      }
    }
  } else if (warp < 12) {
    asm volatile("setmaxnreg.inc.sync.aligned.u32 160;");
    const int w8 = warp - 4;
    const int row = w8 * 16 + (lane & 7) + (((lane >> 3) & 1) << 3);
    {
      float acc[96];
#pragma unroll 1
      for (int ks = 0, s = 0, ph = 0; ks < 16; ++ks) {
        mbar_wait(BAR(B_FULL + s), ph);
        if (tid == 128 && !(ks & 1)) TSR(16, ks == 0 ? 16 : 9 + (ks >> 1) + (ks > 12 ? 46 : 0));
        const uint32_t st = sb + s * STG_BYTES;
        const uint32_t da = mkdesc(st + STG_X + (w8 >> 2) * 4096, 16);
        const uint32_t db = mkdesc(st + STG_W, 2048);
        wg_fence();
        wgmma_n192(acc, da, db, ks != 0);
        wgmma_n192(acc, da + 2, db + 384, 1);
        wg_commit();
        const uint32_t eprev = BAR(B_EMPTY + (s == 0 ? NSTG - 1 : s - 1));
        if (++s == NSTG) { s = 0; ph ^= 1; }
        if (ks > 0) {
          wg_wait<1>();
          if (lane < 2) mbar_arrive_cluster(eprev, lane);
        }
      }
      wg_wait<0>();
      bar_arrive(4, 384);
      if (tid == 128) TS(17);
      bar_sync(1, 256);
#pragma unroll
      for (int i = 0; i < 24; i += 2)
        stsm_x4(sb + SM_QS + row * 128 + (i >> 3) * 16384 + ((((i & 7) + (lane >> 4)) ^ (row & 7)) << 4),
                pack_bf16(acc[4 * i], acc[4 * i + 1]), pack_bf16(acc[4 * i + 2], acc[4 * i + 3]),
                pack_bf16(acc[4 * i + 4], acc[4 * i + 5]), pack_bf16(acc[4 * i + 6], acc[4 * i + 7]));
    }
    __syncwarp();
#pragma unroll 1
    for (int part = 1; part >= 0; --part) {
      const uint32_t pa = sb + SM_QS + part * 16384 + w8 * 2048 + lane * 16;
#pragma unroll 1
      for (int it = 0; it < 4; ++it) {
        uint4 t = lds128(pa + it * 512);
        uint32_t* tw = &t.x;
#pragma unroll
        for (int j = 0; j < 4; ++j) {
          const uint32_t x = tw[j];
          const __nv_bfloat162 xb = *reinterpret_cast<const __nv_bfloat162*>(&x);
          const uint32_t e = pack_bf16(ex2(bf_lo(x) * 1.4426950408889634f), ex2(bf_hi(x) * 1.4426950408889634f));
          const uint32_t m = __hgt2_mask(xb, __floats2bfloat162_rn(0.f, 0.f));
          tw[j] = badd((badd(x, 0x3f803f80u) & m) | (e & ~m), 0x35863586u);
        }
        sts128(pa + it * 512, t.x, t.y, t.z, t.w);
      }
      if (part == 1) {
        if (tid == 128) TS(53);
        bar_sync(1, 256);
        const int hh = w8 >> 1, dtile = w8 & 1;
        float kv[4] = {0.f, 0.f, 0.f, 0.f}, zz[4] = {0.f, 0.f, 0.f, 0.f};
        const int m = lane >> 3;
        const uint32_t aa = sb + SM_VS + ((lane & 7) + ((m >> 1) << 3)) * 128 + (((2 * hh + (m & 1)) ^ (lane & 7)) << 4);
        const uint32_t ab = sb + SM_PK + (lane & 15) * 128 + (((2 * hh + dtile) ^ (lane & 7)) << 4);
#pragma unroll 2
        for (int ks = 0; ks < 8; ++ks) {
          uint32_t a[4], b0, b1;
          ldsm_x4_t(a, aa + ks * 2048);
          ldsm_x2_t(b0, b1, ab + ks * 2048);
          mma_bf16(kv, a[0], a[1], a[2], a[3], b0, b1);
          mma_bf16(zz, 0x3f803f80u, 0x3f803f80u, 0x3f803f80u, 0x3f803f80u, b0, b1);
        }
        const uint32_t kp = sb + SM_KV + hh * 1088;
        sts128(kp + dtile * 512 + lane * 16, __float_as_uint(kv[0]), __float_as_uint(kv[1]), __float_as_uint(kv[2]),
               __float_as_uint(kv[3]));
        if (g == 0) sts_f32x2(kp + 1024 + dtile * 32 + q * 8, zz[0], zz[1]);
        fence_async_smem();
        __syncwarp();
        if (lane == 0) mbar_arrive(BAR(B_KVP));
        if (tid == 128) TS(55);
      }
    }
    if (tid == 128) TS(56);
    {
      const int ch = w8 >> 1;
      bar_sync(7, 384);
      mbar_wait_long(BAR(B_UCH + ch), 0);
      const uint32_t vb = sb + SM_VV + ch * VV_BYTES;
      auto swz = [](int k, int pad) { const int r = (k >> 1) + pad; return (uint32_t)(r * 32 + (((k & 1) ^ ((r >> 2) & 1)) << 4)); };
      int k = -2 + (w8 & 1) * 32 + lane;
      const uint32_t ua = sb + SM_U + ch * U_BYTES;
      uint32_t a0 = ua + swz(k - 1, 8), a1 = ua + swz(k, 8), a2 = ua + swz(k + 1, 8), aw = vb + swz(k, PADV);
      if (lane < 16 && !(w8 & 1)) {
        const uint32_t az = vb + swz(lane - 18, PADV);
        sts128(az + VV_U3, 0, 0, 0, 0); sts128(az + VV_U5, 0, 0, 0, 0); sts128(az + VV_U7, 0, 0, 0, 0); sts128(az + VV_U9, 0, 0, 0, 0);
      }
#pragma unroll 1
      for (; k - lane < 208; k += 64, a0 += 1024, a1 += 1024, a2 += 1024, aw += 1024) {
        const uint4 t0 = lds128(a0), t1 = lds128(a1), t2 = lds128(a2);
        const uint32_t E[12] = {t0.x, t0.y, t0.z, t0.w, t1.x, t1.y, t1.z, t1.w, t2.x, t2.y, t2.z, t2.w};
        uint32_t O[8];
#pragma unroll
        for (int j = 0; j < 8; ++j) O[j] = __byte_perm(E[j + 1], E[j + 2], 0x5432);
        uint32_t s3[6], s5[4], s7[4], s9[4];
#pragma unroll
        for (int j = 0; j < 6; ++j) s3[j] = badd(badd(O[j], O[j + 1]), E[j + 2]);
#pragma unroll
        for (int j = 0; j < 4; ++j) {
          s5[j] = badd(s3[j + 2], badd(E[j + 3], E[j + 5]));
          s7[j] = badd(s5[j], badd(O[j + 1], O[j + 4]));
          s9[j] = badd(s7[j], badd(E[j + 2], E[j + 6]));
        }
        if (k < 208) { sts128(aw + VV_U3, s3[0], s3[1], s3[2], s3[3]); sts128(aw + VV_U5, s5[0], s5[1], s5[2], s5[3]); }
        if (k < 144) { sts128(aw + VV_U7, s7[0], s7[1], s7[2], s7[3]); sts128(aw + VV_U9, s9[0], s9[1], s9[2], s9[3]); }
      }
      bar_arrive(5, 384);
    }
    if (tid == 128) TS(6);
    mbar_wait_long(BAR(B_KVF), 0);
    if (tid == 128) TS(19);
#pragma unroll 1
    for (int h = 0; h < 4; ++h) {
      uint32_t a[4];
      const uint32_t qa = sb + SM_QS + row * 128 + (((2 * h + (lane >> 4)) ^ (row & 7)) << 4);
      ldsm_x4(a, qa);
      const uint32_t kp = sb + SM_KV + h * 1088;
      const uint4 k0 = lds128(kp + lane * 16), k1 = lds128(kp + 512 + lane * 16);
      const uint32_t za = kp + 1024 + q * 8;
      auto pk2 = [](uint32_t x, uint32_t y) { return pack_bf16(__uint_as_float(x), __uint_as_float(y)); };
      float n0[4] = {0.f, 0.f, 0.f, 0.f}, n1[4] = {0.f, 0.f, 0.f, 0.f}, dn[4] = {0.f, 0.f, 0.f, 0.f};
      mma_bf16(n0, a[0], a[1], a[2], a[3], pk2(k0.x, k0.y), pk2(k1.x, k1.y));
      mma_bf16(n1, a[0], a[1], a[2], a[3], pk2(k0.z, k0.w), pk2(k1.z, k1.w));
      mma_bf16(dn, a[0], a[1], a[2], a[3], pack_bf16(lds_f32(za), lds_f32(za + 4)), pack_bf16(lds_f32(za + 32), lds_f32(za + 36)));
      const uint32_t dd = pack_bf16(dn[0], dn[2]);
      const uint32_t d2 = pack_bf16(bf_lo(dd) + 1e-6f, bf_hi(dd) + 1e-6f);
      const float r0 = rcp(bf_lo(d2)), r1 = rcp(bf_hi(d2));
      const uint32_t x0 = pack_bf16(n0[0], n0[1]), x1 = pack_bf16(n0[2], n0[3]);
      const uint32_t x2 = pack_bf16(n1[0], n1[1]), x3 = pack_bf16(n1[2], n1[3]);
      stsm_x4(qa, pack_bf16(bf_lo(x0) * r0, bf_hi(x0) * r0), pack_bf16(bf_lo(x1) * r1, bf_hi(x1) * r1),
              pack_bf16(bf_lo(x2) * r0, bf_hi(x2) * r0), pack_bf16(bf_lo(x3) * r1, bf_hi(x3) * r1));
    }
    fence_async_smem();
    __syncwarp();
    if (lane == 0) mbar_arrive(BAR(B_OST));
    if (tid == 128) TS(57);
    mbar_wait_long(BAR(B_WO), 0);
    bar_sync(3, 384);
    {
      float o[32];
#pragma unroll 1
      for (int c = 0; c < 8; ++c) {
        mbar_wait_long(BAR(B_RF + c), 0);
        if (tid == 128) TSR(22, c == 0 ? 22 : 43 + c);
        const uint32_t slot = c < 4 ? SM_QS + c * 16384 : c < 7 ? SM_VV + (c - 4) * 16384 : SM_QS;
        const uint32_t da = mkdesc(sb + slot + (w8 >> 2) * 8192, 16);
        const uint32_t db = mkdesc(sb + SM_WO + c * 8192, 8192);
        wg_fence();
#pragma unroll
        for (int k = 0; k < 4; ++k) wgmma_n64(o, da + 2 * k, db + 128 * k, (c | k) != 0);
        wg_commit();
        if (c == 1) {
          wg_wait<1>();
          if (lane < 2) mbar_arrive_cluster(BAR(B_RE), lane);
        }
      }
      wg_wait<0>();
      if (tid == 128) TS(51);
      bar_sync(1, 256);
#pragma unroll
      for (int i = 0; i < 8; i += 2)
        stsm_x4(sb + SM_BOUT + row * 128 + (((i + (lane >> 4)) ^ (row & 7)) << 4), pack_bf16(o[4 * i], o[4 * i + 1]),
                pack_bf16(o[4 * i + 2], o[4 * i + 3]), pack_bf16(o[4 * i + 4], o[4 * i + 5]), pack_bf16(o[4 * i + 6], o[4 * i + 7]));
      fence_async_smem();
      bar_sync(1, 256);
      if (tid == 128) TS(52);
      if (warp == 4 && elect_one()) {
        tma_store_2d(&maps.out, sb + SM_BOUT, 512 + 64 * pj, 128 * pi);
        bulk_commit();
        bulk_wait_read0();
        TS(23);
      }
    }
  } else {
    asm volatile("setmaxnreg.dec.sync.aligned.u32 40;");
    if (warp == 12) {
      if (elect_one()) {
#pragma unroll 1
        for (int ks = NSTG, s = 0, ph = 0; ks < 16; ++ks) {
          mbar_wait(BAR(B_EMPTY + s), ph);
          issue_stage(ks, s);
          if (ks == NSTG) l2_prefetch((const char*)p.wo + (size_t)cta * 4096, 4096);
          if (++s == NSTG) { s = 0; ph ^= 1; }
        }
        mbar_wait(BAR(B_EMPTY + 6), 1);
        mbar_expect_tx(BAR(B_WO), 65536);
        tma_load_2d(sb + SM_WO, &maps.wo, pj * 64, 0, BAR(B_WO));
        tma_load_2d(sb + SM_WO + 32768, &maps.wo, pj * 64, 256, BAR(B_WO));
        float* kvg = &g_kv[epoch & 1][tj][0];
        mbar_wait_long(BAR(B_KVP), 0);
        bulk_reduce_add_f32(kvg, sb + SM_KV, 4352);
        bulk_commit();
        bulk_wait0();
        red_relaxed_add(&g_cnt[(C_KV + tj) * 32], 1);
        TS(18);
        wait_counter(&g_cnt[(C_KV + tj) * 32], (epoch + 1) * 16);
        mbar_expect_tx(BAR(B_KVF), 4352);
        bulk_load(sb + SM_KV, kvg, 4352, BAR(B_KVF));
        mbar_wait_long(BAR(B_OST), 0);
        tma_store_2d(&maps.o, sb + SM_QS, tj * 64, ti * 128);
        tma_store_2d(&maps.o, sb + SM_QS + 8192, tj * 64, ti * 128 + 64);
        bulk_commit();
        bulk_wait0();
        red_relaxed_add(&g_cnt[(C_O + ti) * 32], 1);
        TS(20);
        mbar_arrive_cluster(BAR(B_SLOT), 0);
        mbar_arrive_cluster(BAR(B_SLOT), 1);
        wait_counter(&g_cnt[(C_O + pi) * 32], (epoch + 1) * 8);
        if (cta == 0) g_epoch = epoch + 1;
        mbar_wait(BAR(B_SLOT), 0);
        TS(21);
#pragma unroll 1
        for (int c = 0; c < 8; ++c) {
          if (c == 4) mbar_wait_long(BAR(B_CONVD), 0);
          if (c == 7) mbar_wait(BAR(B_RE), 0);
          const uint32_t slot = c < 4 ? SM_QS + c * 16384 : c < 7 ? SM_VV + (c - 4) * 16384 : SM_QS;
          mbar_expect_tx(BAR(B_RF + c), 16384);
          tma_load_2d_mc(sb + slot + rank * 8192, &maps.o, c * 64, pi * 128 + rank * 64, BAR(B_RF + c), 3);
        }
      }
    } else if (warp == 13) {
      bar_sync(6, 160);
      sts128(sb + SM_U + (lane >> 4) * U_BYTES + (lane & 15) * 16, 0, 0, 0, 0);
      sts128(sb + SM_U + (2 + (lane >> 4)) * U_BYTES + (lane & 15) * 16, 0, 0, 0, 0);
      __syncwarp();
      if (elect_one()) {
        tma_store_2d(&maps.uT, sb + SM_P, ti * 128, tj * 64);
        tma_store_2d(&maps.uT, sb + SM_P + 8192, ti * 128 + 64, tj * 64);
        bulk_commit();
        bulk_wait_read0();
        mbar_arrive(BAR(B_PFREE));
        bulk_wait0();
        red_relaxed_add(&g_cnt[(C_U + tj) * 32], 1);
        TS(27);
        wait_counter(&g_cnt[(C_U + (cta >> 4)) * 32], (epoch + 1) * 16);
#pragma unroll 1
        for (int c = 0; c < 4; ++c) {
          mbar_expect_tx(BAR(B_UCH + c), 4096);
          bulk_load(sb + SM_U + c * U_BYTES + 256, p.uT + (size_t)(cta * 4 + c) * 2048, 4096, BAR(B_UCH + c));
        }
        TS(3);
      }
      __syncwarp();
      if (ti == 0) {
        float4* z = (float4*)&g_kv[(epoch & 1) ^ 1][tj][0];
#pragma unroll 1
        for (int i = lane; i < 272; i += 32) z[i] = make_float4(0.f, 0.f, 0.f, 0.f);
      }
    }
  }
  __syncwarp();
  cluster_arrive();
  cluster_wait();
  if (tid == 0) TS(31);
#undef BAR
}

typedef CUresult (*EncodeFn)(CUtensorMap*, CUtensorMapDataType, cuuint32_t, void*, const cuuint64_t*, const cuuint64_t*,
                             const cuuint32_t*, const cuuint32_t*, CUtensorMapInterleave, CUtensorMapSwizzle,
                             CUtensorMapL2promotion, CUtensorMapFloatOOBfill);

static void make_map(EncodeFn enc, CUtensorMap* m, const void* base, uint64_t inner, uint64_t outer, uint32_t box_in,
                     uint32_t box_out, CUtensorMapSwizzle swz = CU_TENSOR_MAP_SWIZZLE_128B) {
  cuuint64_t gd[2] = {inner, outer};
  cuuint64_t gs[1] = {inner * 2};
  cuuint32_t bd[2] = {box_in, box_out};
  cuuint32_t es[2] = {1, 1};
  enc(m, CU_TENSOR_MAP_DATA_TYPE_BFLOAT16, 2, const_cast<void*>(base), gd, gs, bd, es, CU_TENSOR_MAP_INTERLEAVE_NONE,
      swz, CU_TENSOR_MAP_L2_PROMOTION_L2_128B, CU_TENSOR_MAP_FLOAT_OOB_FILL_NONE);
}

}

extern "C" void kernel_launch(void* const* d_in, const int* in_sizes, int n_in, void* d_out, int out_size) {
  using namespace s4la;
  (void)in_sizes; (void)n_in; (void)out_size;
  static EncodeFn enc = nullptr;
  static void *uT = nullptr, *yT = nullptr, *oS = nullptr;
  if (!enc) {
    void* fn = nullptr;
    cudaDriverEntryPointQueryResult qr;
    cudaGetDriverEntryPoint("cuTensorMapEncodeTiled", &fn, cudaEnableDefault, &qr);
    enc = (EncodeFn)fn;
    cudaGetSymbolAddress(&uT, g_uT);
    cudaGetSymbolAddress(&yT, g_yT);
    cudaGetSymbolAddress(&oS, g_o);
    cudaFuncSetAttribute(fused_kernel, cudaFuncAttributeMaxDynamicSharedMemorySize, SM_TOTAL);
  }
  const __nv_bfloat16* const* in = (const __nv_bfloat16* const*)d_in;
  Maps maps;
  make_map(enc, &maps.x, in[9], 512, 2048, 32, 128, CU_TENSOR_MAP_SWIZZLE_64B);
  {
    cuuint64_t gd[3] = {512, 512, 3};
    cuuint64_t gs[2] = {3072, 1024};
    cuuint32_t bd[3] = {64, 16, 3};
    cuuint32_t es[3] = {1, 1, 1};
    enc(&maps.w, CU_TENSOR_MAP_DATA_TYPE_BFLOAT16, 3, const_cast<__nv_bfloat16*>(in[10]), gd, gs, bd, es,
        CU_TENSOR_MAP_INTERLEAVE_NONE, CU_TENSOR_MAP_SWIZZLE_128B, CU_TENSOR_MAP_L2_PROMOTION_L2_128B,
        CU_TENSOR_MAP_FLOAT_OOB_FILL_NONE);
  }
  make_map(enc, &maps.wo, in[11], 512, 512, 64, 256);
  make_map(enc, &maps.u, in[0], 512, 2048, 64, 128);
  make_map(enc, &maps.uT, uT, 2048, 512, 64, 64);
  make_map(enc, &maps.yT, yT, 2048, 512, 64, 64);
  make_map(enc, &maps.o, oS, 512, 2048, 64, 64);
  make_map(enc, &maps.out, d_out, 1024, 2048, 64, 128);
  Ptrs p;
  p.A_re = in[1]; p.A_im = in[2]; p.B_re = in[3]; p.B_im = in[4]; p.C_re = in[5]; p.C_im = in[6];
  p.log_dt = in[7]; p.Dskip = in[8]; p.x = in[9]; p.wqkv = in[10]; p.wo = in[11];
  p.uT = (__nv_bfloat16*)uT; p.yT = (__nv_bfloat16*)yT;
  fused_kernel<<<NCTA, NTHREADS, SM_TOTAL, cudaStreamPerThread>>>(maps, p);
}
```

```cpp
#include <cuda_runtime.h>
#include <cuda_bf16.h>
#include <cuda_fp16.h>
#include <cuda.h>
#include <stdint.h>

#define DEVI __device__ __forceinline__

namespace s4la {

constexpr int NTHREADS = 512;
constexpr int NCTA = 128;

constexpr int NSTG = 7;
constexpr uint32_t STG_BYTES = 20480, STG_X = 0, STG_W = 8192;
constexpr uint32_t SM_QS = 0;
constexpr uint32_t SM_PK = SM_QS + 16384, SM_VS = SM_QS + 32768;
constexpr uint32_t SM_WO = 65536;
constexpr uint32_t SM_KV = 131072;
constexpr uint32_t SM_BOUT = 16384;
constexpr uint32_t SM_U = 143360, U_BYTES = 4352;
constexpr uint32_t SM_P = 160768, P_BYTES = 4096;
constexpr uint32_t SM_VV = 177152, VV_BYTES = 12800;
constexpr uint32_t VV_U5 = 0, VV_U3 = 3712, VV_U9 = 7424, VV_U7 = 10112;
constexpr uint32_t KG_BYTES = 3200;
constexpr uint32_t SM_BAR = SM_VV + 4 * VV_BYTES;
constexpr uint32_t SM_PTAB = SM_BAR + 320;
constexpr uint32_t SM_TOTAL = SM_PTAB + 2048;
static_assert(SM_TOTAL <= 232448, "shared memory");
constexpr int PADV = 12;

enum { B_FULL = 0, B_EMPTY = 7, B_TILE = 14, B_UCH = 15, B_KVP = 19, B_KVF = 20, B_OST = 21, B_RF = 22, B_WO = 30, B_RE = 31, B_PFREE = 32, B_CONVD = 33, B_SLOT = 34, B_COUNT = 35 };
__host__ __device__ constexpr int bar_count(int i) {
  return (i >= B_EMPTY && i < B_TILE) ? 16 : (i == B_KVP || i == B_OST || i == B_CONVD) ? 8 : i == B_RE ? 16 : i == B_SLOT ? 2 : 1;
}

constexpr int PD_OFF = 0, P2_OFF = 544, P3_OFF = 768;

constexpr int SL_K2048 = 20, SL_ZERO = 21, SL_510 = 22, SL_0 = 23;
__host__ __device__ constexpr int koff(int y) {
  return y < 8 ? y : y < 12 ? 256 + 2 * (y - 8) : y < 16 ? 512 + 256 * ((y - 12) >> 1) + 4 * (y & 1) : 1024 + 256 * (y - 16);
}
__host__ __device__ constexpr int kidx_c(int l) {
  const int y = l < 256 ? (l & 7) : l < 512 ? 8 + ((l & 7) >> 1) : l < 1024 ? 12 + (((l - 512) >> 8) << 1) + ((l >> 2) & 1)
                                                                            : 16 + ((l - 1024) >> 8);
  return ((l >> 3) & 31) * 24 + y;
}
constexpr int slot_direct(int l) {
  if (l < 0 || l > 510) return SL_ZERO;
  if (l == 510) return SL_510;
  if (l == 0) return SL_0;
  return kidx_c(l < 256 ? l : ((l + ((l >> 1) & 1)) & ~1));
}
constexpr int slot_seg2(int v, int k) { return (k >= 32 && k < 64) ? kidx_c(16 * k + 4 * v) : SL_ZERO; }
constexpr int slot_seg3(int pi, int k) {
  return (k >= 64 && k < 128) ? kidx_c(16 * k + 8 * pi) : ((k == 128 && pi == 0) ? SL_K2048 : SL_ZERO);
}
constexpr int slot_word(int w) {
  return w < 0 ? SL_ZERO : w < 544 ? slot_direct(w - 16) : w < 768 ? slot_seg2((w - 544) / 56, 16 + (w - 544) % 56)
       : w < 944 ? slot_seg3((w - 768) / 88, 48 + (w - 768) % 88) : SL_ZERO;
}
struct PTab { uint32_t v[512]; };
constexpr PTab make_ptab() {
  PTab t{};
  for (int lane = 0; lane < 32; ++lane)
    for (int i = 0; i < 16; ++i)
      t.v[i * 32 + lane] = (slot_word(31 * lane - 1 + 2 * i) * 4) | ((slot_word(31 * lane + 2 * i) * 4) << 16);
  return t;
}
__device__ const PTab g_ptab = make_ptab();

__device__ __nv_bfloat16 g_uT[512 * 2048];
__device__ __nv_bfloat16 g_yT[512 * 2048];
__device__ __nv_bfloat16 g_o[2048 * 512];
__device__ float g_kv[2][8][4 * 272];
__device__ unsigned g_cnt[64 * 32];
__device__ unsigned g_epoch;
#define TS(slot) do { } while (0)
#define TSR(on, slot) do { } while (0)
#define TSD(slot) do { } while (0)
enum { C_U = 0, C_KV = 8, C_O = 16, C_Y = 32 };

struct Maps {
  CUtensorMap x, w, wo, u, uT, yT, o, out;
};
struct Ptrs {
  const __nv_bfloat16 *A_re, *A_im, *B_re, *B_im, *C_re, *C_im, *log_dt, *Dskip;
  const __nv_bfloat16 *x, *wqkv, *wo;
  __nv_bfloat16 *uT, *yT;
};

DEVI uint32_t s2u(const void* p) { return (uint32_t)__cvta_generic_to_shared(p); }
DEVI void mbar_init(uint32_t b, uint32_t c) { asm volatile("mbarrier.init.shared::cta.b64 [%0], %1;" ::"r"(b), "r"(c) : "memory"); }
DEVI void mbar_expect_tx(uint32_t b, uint32_t bytes) {
  asm volatile("mbarrier.arrive.expect_tx.shared::cta.b64 _, [%0], %1;" ::"r"(b), "r"(bytes) : "memory");
}
DEVI void mbar_arrive(uint32_t b) { asm volatile("mbarrier.arrive.shared::cta.b64 _, [%0];" ::"r"(b) : "memory"); }
DEVI void mbar_arrive_cluster(uint32_t b, uint32_t cta) {
  asm volatile("{\n.reg .b32 r;\nmapa.shared::cluster.u32 r, %0, %1;\nmbarrier.arrive.shared::cluster.b64 _, [r];\n}"
               ::"r"(b), "r"(cta) : "memory");
}
DEVI void mbar_wait(uint32_t b, uint32_t parity) {
  asm volatile("{\n.reg .pred p;\nLAB_WAIT:\nmbarrier.try_wait.parity.shared::cta.b64 p, [%0], %1;\n@!p bra LAB_WAIT;\n}"
               ::"r"(b), "r"(parity) : "memory");
}
DEVI void mbar_wait_long(uint32_t b, uint32_t parity) {
  asm volatile("{\n.reg .pred p;\nLAB_WAIT:\nmbarrier.try_wait.parity.shared::cta.b64 p, [%0], %1, 0x989680;\n@!p bra LAB_WAIT;\n}"
               ::"r"(b), "r"(parity) : "memory");
}
DEVI void bar_sync(int id, int n) { asm volatile("bar.sync %0, %1;" ::"r"(id), "r"(n) : "memory"); }
DEVI void bar_arrive(int id, int n) { asm volatile("bar.arrive %0, %1;" ::"r"(id), "r"(n) : "memory"); }
DEVI void fence_async_smem() { asm volatile("fence.proxy.async.shared::cta;" ::: "memory"); }
DEVI void fence_async_all() { asm volatile("fence.proxy.async;" ::: "memory"); }
DEVI void cluster_arrive() { asm volatile("barrier.cluster.arrive.relaxed.aligned;" ::: "memory"); }
DEVI void cluster_wait() { asm volatile("barrier.cluster.wait.aligned;" ::: "memory"); }

DEVI void tma_load_2d(uint32_t dst, const CUtensorMap* m, int c0, int c1, uint32_t bar) {
  asm volatile("cp.async.bulk.tensor.2d.shared::cluster.global.mbarrier::complete_tx::bytes [%0], [%1, {%3, %4}], [%2];"
               ::"r"(dst), "l"(m), "r"(bar), "r"(c0), "r"(c1) : "memory");
}
DEVI void tma_load_2d_mc(uint32_t dst, const CUtensorMap* m, int c0, int c1, uint32_t bar, uint16_t mask) {
  asm volatile("cp.async.bulk.tensor.2d.shared::cluster.global.mbarrier::complete_tx::bytes.multicast::cluster [%0], [%1, {%3, %4}], [%2], %5;"
               ::"r"(dst), "l"(m), "r"(bar), "r"(c0), "r"(c1), "h"(mask) : "memory");
}
DEVI void tma_load_3d_mc(uint32_t dst, const CUtensorMap* m, int c0, int c1, int c2, uint32_t bar, uint16_t mask) {
  asm volatile("cp.async.bulk.tensor.3d.shared::cluster.global.mbarrier::complete_tx::bytes.multicast::cluster [%0], [%1, {%3, %4, %5}], [%2], %6;"
               ::"r"(dst), "l"(m), "r"(bar), "r"(c0), "r"(c1), "r"(c2), "h"(mask) : "memory");
}
DEVI void tma_store_2d(const CUtensorMap* m, uint32_t src, int c0, int c1) {
  asm volatile("cp.async.bulk.tensor.2d.global.shared::cta.bulk_group [%0, {%2, %3}], [%1];"
               ::"l"(m), "r"(src), "r"(c0), "r"(c1) : "memory");
}
DEVI void bulk_load(uint32_t dst, const void* src, uint32_t bytes, uint32_t bar) {
  asm volatile("cp.async.bulk.shared::cluster.global.mbarrier::complete_tx::bytes [%0], [%1], %2, [%3];"
               ::"r"(dst), "l"(src), "r"(bytes), "r"(bar) : "memory");
}
DEVI void bulk_store(void* dst, uint32_t src, uint32_t bytes) {
  asm volatile("cp.async.bulk.global.shared::cta.bulk_group [%0], [%1], %2;" ::"l"(dst), "r"(src), "r"(bytes) : "memory");
}
DEVI void bulk_reduce_add_f32(void* dst, uint32_t src, uint32_t bytes) {
  asm volatile("cp.reduce.async.bulk.global.shared::cta.bulk_group.add.f32 [%0], [%1], %2;" ::"l"(dst), "r"(src), "r"(bytes) : "memory");
}
DEVI void bulk_commit() { asm volatile("cp.async.bulk.commit_group;" ::: "memory"); }
DEVI void bulk_wait0() { asm volatile("cp.async.bulk.wait_group 0;" ::: "memory"); }
DEVI void bulk_wait_read0() { asm volatile("cp.async.bulk.wait_group.read 0;" ::: "memory"); }
DEVI void l2_prefetch(const void* p, uint32_t bytes) {
  asm volatile("cp.async.bulk.prefetch.L2.global [%0], %1;" ::"l"(p), "r"(bytes) : "memory");
}
DEVI void prefetch_tmap(const CUtensorMap* m) { asm volatile("prefetch.tensormap [%0];" ::"l"(m) : "memory"); }

DEVI void red_release_add(unsigned* p, unsigned v) {
  asm volatile("red.release.gpu.global.add.u32 [%0], %1;" ::"l"(p), "r"(v) : "memory");
}
DEVI void red_relaxed_add(unsigned* p, unsigned v) {
  asm volatile("red.relaxed.gpu.global.add.u32 [%0], %1;" ::"l"(p), "r"(v) : "memory");
}
DEVI unsigned ld_relaxed(const unsigned* p) {
  unsigned v;
  asm volatile("ld.relaxed.gpu.global.u32 %0, [%1];" : "=r"(v) : "l"(p) : "memory");
  return v;
}
DEVI void wait_counter(const unsigned* p, unsigned target) {
#pragma unroll 1
  for (int it = 0; (int)(ld_relaxed(p) - target) < 0; ++it)
    if (it > (1 << 22)) __trap();
}

DEVI void ldsm_x4(uint32_t (&r)[4], uint32_t a) {
  asm volatile("ldmatrix.sync.aligned.m8n8.x4.shared.b16 {%0,%1,%2,%3}, [%4];"
               : "=r"(r[0]), "=r"(r[1]), "=r"(r[2]), "=r"(r[3]) : "r"(a) : "memory");
}
DEVI void ldsm_x4_t(uint32_t (&r)[4], uint32_t a) {
  asm volatile("ldmatrix.sync.aligned.m8n8.x4.trans.shared.b16 {%0,%1,%2,%3}, [%4];"
               : "=r"(r[0]), "=r"(r[1]), "=r"(r[2]), "=r"(r[3]) : "r"(a) : "memory");
}
DEVI void ldsm_x2_t(uint32_t& r0, uint32_t& r1, uint32_t a) {
  asm volatile("ldmatrix.sync.aligned.m8n8.x2.trans.shared.b16 {%0,%1}, [%2];" : "=r"(r0), "=r"(r1) : "r"(a) : "memory");
}
DEVI void stsm_x4(uint32_t a, uint32_t r0, uint32_t r1, uint32_t r2, uint32_t r3) {
  asm volatile("stmatrix.sync.aligned.m8n8.x4.shared.b16 [%0], {%1,%2,%3,%4};"
               ::"r"(a), "r"(r0), "r"(r1), "r"(r2), "r"(r3) : "memory");
}
DEVI void stsm_x4_t(uint32_t a, uint32_t r0, uint32_t r1, uint32_t r2, uint32_t r3) {
  asm volatile("stmatrix.sync.aligned.m8n8.x4.trans.shared.b16 [%0], {%1,%2,%3,%4};"
               ::"r"(a), "r"(r0), "r"(r1), "r"(r2), "r"(r3) : "memory");
}
DEVI uint32_t lds32(uint32_t a) { uint32_t v; asm volatile("ld.shared.b32 %0, [%1];" : "=r"(v) : "r"(a) : "memory"); return v; }
DEVI float lds_f32(uint32_t a) { float v; asm volatile("ld.shared.f32 %0, [%1];" : "=f"(v) : "r"(a) : "memory"); return v; }
DEVI void sts32(uint32_t a, uint32_t v) { asm volatile("st.shared.b32 [%0], %1;" ::"r"(a), "r"(v) : "memory"); }
DEVI void sts_f32(uint32_t a, float v) { asm volatile("st.shared.f32 [%0], %1;" ::"r"(a), "f"(v) : "memory"); }
DEVI void sts_f32x2(uint32_t a, float x, float y) { asm volatile("st.shared.v2.f32 [%0], {%1,%2};" ::"r"(a), "f"(x), "f"(y) : "memory"); }
DEVI uint4 lds128(uint32_t a) {
  uint4 v;
  asm volatile("ld.shared.v4.b32 {%0,%1,%2,%3}, [%4];" : "=r"(v.x), "=r"(v.y), "=r"(v.z), "=r"(v.w) : "r"(a) : "memory");
  return v;
}
DEVI void sts128(uint32_t a, uint32_t x, uint32_t y, uint32_t z, uint32_t w) {
  asm volatile("st.shared.v4.b32 [%0], {%1,%2,%3,%4};" ::"r"(a), "r"(x), "r"(y), "r"(z), "r"(w) : "memory");
}

DEVI void mma_bf16(float (&d)[4], uint32_t a0, uint32_t a1, uint32_t a2, uint32_t a3, uint32_t b0, uint32_t b1) {
  asm("mma.sync.aligned.m16n8k16.row.col.f32.bf16.bf16.f32 {%0,%1,%2,%3}, {%4,%5,%6,%7}, {%8,%9}, {%0,%1,%2,%3};"
      : "+f"(d[0]), "+f"(d[1]), "+f"(d[2]), "+f"(d[3])
      : "r"(a0), "r"(a1), "r"(a2), "r"(a3), "r"(b0), "r"(b1));
}
DEVI void mma_f16(float (&d)[4], const uint32_t (&a)[4], uint32_t b0, uint32_t b1) {
  asm("mma.sync.aligned.m16n8k16.row.col.f32.f16.f16.f32 {%0,%1,%2,%3}, {%4,%5,%6,%7}, {%8,%9}, {%0,%1,%2,%3};"
      : "+f"(d[0]), "+f"(d[1]), "+f"(d[2]), "+f"(d[3])
      : "r"(a[0]), "r"(a[1]), "r"(a[2]), "r"(a[3]), "r"(b0), "r"(b1));
}
DEVI void mma_bf16v(float (&d)[4], const uint32_t (&a)[4], uint32_t b0, uint32_t b1) {
  asm volatile("mma.sync.aligned.m16n8k16.row.col.f32.bf16.bf16.f32 {%0,%1,%2,%3}, {%4,%5,%6,%7}, {%8,%9}, {%0,%1,%2,%3};"
               : "+f"(d[0]), "+f"(d[1]), "+f"(d[2]), "+f"(d[3])
               : "r"(a[0]), "r"(a[1]), "r"(a[2]), "r"(a[3]), "r"(b0), "r"(b1));
}
DEVI uint32_t pack_bf16(float lo, float hi) {
  uint32_t r;
  asm("cvt.rn.bf16x2.f32 %0, %1, %2;" : "=r"(r) : "f"(hi), "f"(lo));
  return r;
}
DEVI uint32_t pack_f16(float lo, float hi) {
  uint32_t r;
  asm("cvt.rn.f16x2.f32 %0, %1, %2;" : "=r"(r) : "f"(hi), "f"(lo));
  return r;
}
DEVI uint32_t ldg16(const __nv_bfloat16* p) {
  uint32_t v;
  asm volatile("ld.global.nc.u16 %0, [%1];" : "=r"(v) : "l"(p));
  return v;
}
DEVI bool elect_one() {
  uint32_t pred;
  asm volatile("{\n.reg .pred p;\nelect.sync _|p, 0xffffffff;\nselp.u32 %0, 1, 0, p;\n}" : "=r"(pred));
  return pred != 0;
}
DEVI float bf_lo(uint32_t v) { return __uint_as_float(v << 16); }
DEVI float bf_hi(uint32_t v) { return __uint_as_float(v & 0xffff0000u); }
DEVI float bf2f(__nv_bfloat16 v) { return __bfloat162float(v); }
DEVI float round_bf16(float v) { return __bfloat162float(__float2bfloat16_rn(v)); }
DEVI float rcp(float x) { float r; asm("rcp.approx.ftz.f32 %0, %1;" : "=f"(r) : "f"(x)); return r; }
DEVI float ex2(float x) { float r; asm("ex2.approx.ftz.f32 %0, %1;" : "=f"(r) : "f"(x)); return r; }

DEVI void wg_fence() { asm volatile("wgmma.fence.sync.aligned;" ::: "memory"); }
DEVI void wg_commit() { asm volatile("wgmma.commit_group.sync.aligned;" ::: "memory"); }
template <int N> DEVI void wg_wait() { asm volatile("wgmma.wait_group.sync.aligned %0;" ::"n"(N) : "memory"); }
constexpr uint32_t DESC_HI = (1u << 30) | (1024 >> 4);
constexpr uint32_t DESC_HI64 = (2u << 30) | (512 >> 4);
DEVI uint32_t mkdesc(uint32_t saddr, uint32_t lbo) { return ((saddr & 0x3FFFF) >> 4) | ((lbo >> 4) << 16); }

#define R8(b) "%" #b
DEVI void wgmma_n192(float (&d)[96], uint32_t da, uint32_t db, int scale_d) {
  asm volatile(
      "{\n.reg .pred p;\n.reg .b64 da, db;\nsetp.ne.b32 p, %98, 0;\nmov.b64 da, {%96, %100};\nmov.b64 db, {%97, %99};\n"
      "wgmma.mma_async.sync.aligned.m64n192k16.f32.bf16.bf16 "
      "{%0,%1,%2,%3,%4,%5,%6,%7,%8,%9,%10,%11,%12,%13,%14,%15,"
      "%16,%17,%18,%19,%20,%21,%22,%23,%24,%25,%26,%27,%28,%29,%30,%31,"
      "%32,%33,%34,%35,%36,%37,%38,%39,%40,%41,%42,%43,%44,%45,%46,%47,"
      "%48,%49,%50,%51,%52,%53,%54,%55,%56,%57,%58,%59,%60,%61,%62,%63,"
      "%64,%65,%66,%67,%68,%69,%70,%71,%72,%73,%74,%75,%76,%77,%78,%79,"
      "%80,%81,%82,%83,%84,%85,%86,%87,%88,%89,%90,%91,%92,%93,%94,%95}, "
      "da, db, p, 1, 1, 0, 1;\n}"
      : "+f"(d[0]), "+f"(d[1]), "+f"(d[2]), "+f"(d[3]), "+f"(d[4]), "+f"(d[5]), "+f"(d[6]), "+f"(d[7]),
        "+f"(d[8]), "+f"(d[9]), "+f"(d[10]), "+f"(d[11]), "+f"(d[12]), "+f"(d[13]), "+f"(d[14]), "+f"(d[15]),
        "+f"(d[16]), "+f"(d[17]), "+f"(d[18]), "+f"(d[19]), "+f"(d[20]), "+f"(d[21]), "+f"(d[22]), "+f"(d[23]),
        "+f"(d[24]), "+f"(d[25]), "+f"(d[26]), "+f"(d[27]), "+f"(d[28]), "+f"(d[29]), "+f"(d[30]), "+f"(d[31]),
        "+f"(d[32]), "+f"(d[33]), "+f"(d[34]), "+f"(d[35]), "+f"(d[36]), "+f"(d[37]), "+f"(d[38]), "+f"(d[39]),
        "+f"(d[40]), "+f"(d[41]), "+f"(d[42]), "+f"(d[43]), "+f"(d[44]), "+f"(d[45]), "+f"(d[46]), "+f"(d[47]),
        "+f"(d[48]), "+f"(d[49]), "+f"(d[50]), "+f"(d[51]), "+f"(d[52]), "+f"(d[53]), "+f"(d[54]), "+f"(d[55]),
        "+f"(d[56]), "+f"(d[57]), "+f"(d[58]), "+f"(d[59]), "+f"(d[60]), "+f"(d[61]), "+f"(d[62]), "+f"(d[63]),
        "+f"(d[64]), "+f"(d[65]), "+f"(d[66]), "+f"(d[67]), "+f"(d[68]), "+f"(d[69]), "+f"(d[70]), "+f"(d[71]),
        "+f"(d[72]), "+f"(d[73]), "+f"(d[74]), "+f"(d[75]), "+f"(d[76]), "+f"(d[77]), "+f"(d[78]), "+f"(d[79]),
        "+f"(d[80]), "+f"(d[81]), "+f"(d[82]), "+f"(d[83]), "+f"(d[84]), "+f"(d[85]), "+f"(d[86]), "+f"(d[87]),
        "+f"(d[88]), "+f"(d[89]), "+f"(d[90]), "+f"(d[91]), "+f"(d[92]), "+f"(d[93]), "+f"(d[94]), "+f"(d[95])
      : "r"(da), "r"(db), "r"(scale_d), "n"(DESC_HI), "n"(DESC_HI64));
}
DEVI void wgmma_n64(float (&d)[32], uint32_t da, uint32_t db, int scale_d) {
  asm volatile(
      "{\n.reg .pred p;\n.reg .b64 da, db;\nsetp.ne.b32 p, %34, 0;\nmov.b64 da, {%32, %35};\nmov.b64 db, {%33, %35};\n"
      "wgmma.mma_async.sync.aligned.m64n64k16.f32.bf16.bf16 "
      "{%0,%1,%2,%3,%4,%5,%6,%7,%8,%9,%10,%11,%12,%13,%14,%15,"
      "%16,%17,%18,%19,%20,%21,%22,%23,%24,%25,%26,%27,%28,%29,%30,%31}, "
      "da, db, p, 1, 1, 0, 1;\n}"
      : "+f"(d[0]), "+f"(d[1]), "+f"(d[2]), "+f"(d[3]), "+f"(d[4]), "+f"(d[5]), "+f"(d[6]), "+f"(d[7]),
        "+f"(d[8]), "+f"(d[9]), "+f"(d[10]), "+f"(d[11]), "+f"(d[12]), "+f"(d[13]), "+f"(d[14]), "+f"(d[15]),
        "+f"(d[16]), "+f"(d[17]), "+f"(d[18]), "+f"(d[19]), "+f"(d[20]), "+f"(d[21]), "+f"(d[22]), "+f"(d[23]),
        "+f"(d[24]), "+f"(d[25]), "+f"(d[26]), "+f"(d[27]), "+f"(d[28]), "+f"(d[29]), "+f"(d[30]), "+f"(d[31])
      : "r"(da), "r"(db), "r"(scale_d), "n"(DESC_HI));
}

struct C32 { float re, im; };
DEVI C32 csq(C32 a) { return {a.re * a.re - a.im * a.im, 2.f * a.re * a.im}; }
DEVI C32 cmul(C32 a, C32 b) { return {a.re * b.re - a.im * b.im, a.re * b.im + a.im * b.re}; }
DEVI C32 cfresh(float zl, float zi, float m) {
  float mag = ex2(zl * m), ph = zi * m;
  return {mag * __cosf(ph), mag * __sinf(ph)};
}
struct HMul { uint32_t b, bp; };
DEVI HMul mk_mul(float re, float im) { return {pack_f16(re, im), pack_f16(-im, re)}; }
DEVI uint32_t hcmul(uint32_t a, const HMul& m) {
  __half2 ah = *reinterpret_cast<__half2*>(&a);
  __half2 b = *reinterpret_cast<const __half2*>(&m.b), bp = *reinterpret_cast<const __half2*>(&m.bp);
  __half2 r = __hfma2(__high2half2(ah), bp, __hmul2(__low2half2(ah), b));
  return *reinterpret_cast<uint32_t*>(&r);
}
DEVI uint32_t badd(uint32_t a, uint32_t b) {
  __nv_bfloat162 r = __hadd2(*reinterpret_cast<__nv_bfloat162*>(&a), *reinterpret_cast<__nv_bfloat162*>(&b));
  return *reinterpret_cast<uint32_t*>(&r);
}
template <int MU0, int NMU, int DMAX>
DEVI void conv_tail(float (&acc)[16][4], uint32_t p_lane, uint32_t v_base, int back, bool edge, int lane) {
  const int hsel = (lane >> 3) & 1;
  const int row = (lane & 7) + ((lane >> 4) << 3) + PADV - 8 - (back & (hsel ^ 1));
  const uint32_t la = v_base + row * 32 + (((hsel ^ back) ^ ((row >> 2) & 1)) << 4);
  uint32_t M[3][4];
  ldsm_x4_t(M[0], la);
  ldsm_x4_t(M[1], la + 256);
  uint32_t H[2 * NMU];
#pragma unroll
  for (int i = 0; i < 2 * NMU; ++i) H[i ^ 1] = lds32(p_lane + (uint32_t)(MU0 - 1 + i) * 32);
  if (edge) {
    const uint32_t a[4] = {0u, 0u, M[0][0], M[0][1]};
#pragma unroll
    for (int k = 1; k < NMU; ++k) mma_bf16v(acc[MU0 - 2 + 2 * k], a, H[2 * k], H[2 * k + 1]);
  }
#pragma unroll
  for (int delta = -1; delta <= DMAX; ++delta) {
    if (delta + 2 <= DMAX) ldsm_x4_t(M[(delta + 3) % 3], la + (delta + 3) * 256);
#pragma unroll
    for (int k = 0; k < NMU; ++k)
      if (delta + MU0 + 2 * k < 16) mma_bf16v(acc[delta + MU0 + 2 * k], M[(delta + 1) % 3], H[2 * k], H[2 * k + 1]);
  }
}

__global__ void __cluster_dims__(2, 1, 1) __launch_bounds__(NTHREADS, 1)
fused_kernel(const __grid_constant__ Maps maps, const Ptrs p) {
  extern __shared__ __align__(1024) uint8_t smem[];
  const uint32_t sb = s2u(smem);
  const int tid = threadIdx.x, lane = tid & 31;
  const int warp = __shfl_sync(0xffffffffu, tid >> 5, 0);
  const int cta = blockIdx.x;
  const uint32_t rank = cta & 1;
  const int ti = 2 * (cta >> 4) + rank;
  const int tj = (cta >> 1) & 7;
  const int pi = cta >> 3, pj = cta & 7;
  const uint32_t bars = sb + SM_BAR;
#define BAR(i) (bars + 8 * (i))
  const int g = lane >> 2, q = lane & 3;

  auto issue_stage = [&](int ks, int s) {
    const uint32_t st = sb + s * STG_BYTES, fb = BAR(B_FULL + s);
    mbar_expect_tx(fb, STG_BYTES);
    tma_load_2d(st + STG_X, &maps.x, ks * 32, ti * 128, fb);
    tma_load_3d_mc(st + STG_W + rank * 6144, &maps.w, tj * 64, ks * 32 + rank * 16, 0, fb, 3);
  };

  const int kch = warp & 3, krd = warp >> 2;
  float zr, zi, wr, wi;
  unsigned epoch;
  uint32_t r_dskip;
  {
    const size_t po = (size_t)(cta * 4 + kch) * 128 + krd * 32 + lane;
    const uint32_t r_ar = ldg16(p.A_re + po), r_ai = ldg16(p.A_im + po), r_br = ldg16(p.B_re + po), r_bi = ldg16(p.B_im + po);
    const uint32_t r_cr = ldg16(p.C_re + po), r_ci = ldg16(p.C_im + po), r_ldt = ldg16(p.log_dt + cta * 4 + kch);
    epoch = __ldcg(&g_epoch);
    r_dskip = ldg16(p.Dskip + cta * 4 + kch);
    uint4 pt;
    if (tid < 128) pt = __ldg((const uint4*)g_ptab.v + tid);
    if (tid == 384) {
      TS(0);
#pragma unroll
      for (int i = 0; i < B_COUNT; ++i) mbar_init(BAR(i), bar_count(i));
      asm volatile("fence.mbarrier_init.release.cluster;" ::: "memory");
      prefetch_tmap(&maps.x); prefetch_tmap(&maps.w); prefetch_tmap(&maps.u);
    }
    __syncthreads();
    cluster_arrive();
    if (warp >= 12) {
      cluster_wait();
      if (elect_one()) {
        if (warp == 13) {
          mbar_expect_tx(BAR(B_TILE), 16384);
          tma_load_2d(sb + SM_U, &maps.u, tj * 64, ti * 128, BAR(B_TILE));
          prefetch_tmap(&maps.uT); prefetch_tmap(&maps.wo); prefetch_tmap(&maps.o); prefetch_tmap(&maps.yT);
          prefetch_tmap(&maps.out);
        } else {
          if (warp == 12) TS(61);
          { const int ks = warp == 12 ? 0 : warp - 13; issue_stage(ks, ks); }
        }
      }
      __syncwarp();
    }
    if (tid < 128) sts128(sb + SM_PTAB + tid * 16, pt.x, pt.y, pt.z, pt.w);
    const float dt = round_bf16(expf(bf_lo(r_ldt)));
    zr = dt * bf_lo(r_ar); zi = dt * bf_lo(r_ai);
    const float dbr = dt * bf_lo(r_br), dbi = dt * bf_lo(r_bi), cr = bf_lo(r_cr), ci = bf_lo(r_ci);
    wr = cr * dbr - ci * dbi; wi = cr * dbi + ci * dbr;
  }
  {
    const float mz = __uint_as_float(__reduce_max_sync(0xffffffffu, __float_as_uint(fmaxf(zr, 0.f))));
    const int E = min(max((int)(__reduce_max_sync(0xffffffffu, __float_as_uint(fmaxf(fabsf(wr), fabsf(wi)))) >> 23), 1), 252);
    const float sc = __int_as_float((253 - E) << 23), inv = __int_as_float((E + 1) << 23);
    const float zl = (zr - mz) * 1.4426950408889634f;
    const uint32_t tb = sb + SM_VV + kch * VV_BYTES + krd * KG_BYTES;
    const uint32_t sta = tb + (((lane >> 2) << 4) | ((lane & 3) << 2));
    auto put = [&](int r, uint32_t v) { sts32((sta ^ ((r & 7) << 4)) + r * 128, v); };
    const uint32_t lda = tb + ((lane & 7) + (((lane >> 3) & 1) << 3)) * 128;
    const uint32_t ldb = tb + ((lane & 7) + ((lane >> 4) << 3)) * 128;
    C32 e1 = cfresh(zl, zi, 1.f), e2 = csq(e1), e4 = csq(e2), e8 = csq(e4);
    C32 e16 = cfresh(zl, zi, 16.f), e32 = csq(e16), e64 = csq(e32), e128 = csq(e64);
    C32 e256 = cfresh(zl, zi, 256.f), e512 = csq(e256), e1024 = csq(e512), e768 = cmul(e512, e256);
    uint32_t XA[2][4][4];
    {
      const HMul m16 = mk_mul(e16.re, e16.im), m32 = mk_mul(e32.re, e32.im), m64 = mk_mul(e64.re, e64.im);
      const HMul m128 = mk_mul(e128.re, e128.im);
      uint32_t X[16];
      X[0] = 0x00003c00u; X[1] = pack_f16(e8.re, e8.im); X[2] = m16.b; X[4] = m32.b; X[8] = m64.b;
      X[3] = hcmul(X[1], m16); X[5] = hcmul(X[1], m32); X[6] = hcmul(X[2], m32); X[7] = hcmul(X[3], m32);
#pragma unroll
      for (int r = 1; r < 8; ++r) X[8 + r] = hcmul(X[r], m64);
#pragma unroll
      for (int h = 0; h < 2; ++h) {
#pragma unroll
        for (int r = 0; r < 16; ++r) put(r, h == 0 ? X[r] : r == 0 ? m128.b : hcmul(X[r], m128));
        __syncwarp();
#pragma unroll
        for (int k = 0; k < 4; ++k) ldsm_x4(XA[h][k], lda + (((2 * k + (lane >> 4)) ^ (lane & 7)) << 4));
        __syncwarp();
      }
    }
    if (warp >= 14 && elect_one()) {
      issue_stage(warp - 11, warp - 11);
      issue_stage(warp - 9, warp - 9);
      if (warp == 14) l2_prefetch((const char*)p.wqkv + 224 * 3072 + cta * 6912, 6912);
      else l2_prefetch((const char*)p.x + (size_t)cta * 16384, 16384);
    }
    __syncwarp();
    float D[2][3][4];
#pragma unroll
    for (int t = 0; t < 6; ++t) D[t / 3][t % 3][0] = D[t / 3][t % 3][1] = D[t / 3][t % 3][2] = D[t / 3][t % 3][3] = 0.f;
    auto contract = [&](int t0, int nt) {
      __syncwarp();
#pragma unroll
      for (int k = 0; k < 4; ++k) {
        uint32_t b[4];
        ldsm_x4(b, ldb + (((2 * k + ((lane >> 3) & 1)) ^ (lane & 7)) << 4));
#pragma unroll
        for (int h = 0; h < 2; ++h) {
          mma_f16(D[h][t0], XA[h][k], b[0], b[1]);
          if (nt == 2) mma_f16(D[h][t0 + 1], XA[h][k], b[2], b[3]);
        }
      }
      __syncwarp();
    };
    const HMul c1 = mk_mul(e1.re, -e1.im), c2 = mk_mul(e2.re, -e2.im), c4 = mk_mul(e4.re, -e4.im);
    const HMul c256 = mk_mul(e256.re, -e256.im), c512 = mk_mul(e512.re, -e512.im), c768 = mk_mul(e768.re, -e768.im);
    const HMul c1024 = mk_mul(e1024.re, -e1024.im);
    uint32_t W[8];
    W[0] = pack_f16(wr * sc, -wi * sc);
    W[1] = hcmul(W[0], c1); W[2] = hcmul(W[0], c2); W[3] = hcmul(W[1], c2);
    W[4] = hcmul(W[0], c4); W[5] = hcmul(W[1], c4); W[6] = hcmul(W[2], c4); W[7] = hcmul(W[3], c4);
#pragma unroll
    for (int i = 0; i < 8; ++i) put(i, W[i]);
#pragma unroll
    for (int i = 0; i < 4; ++i) put(8 + i, hcmul(W[2 * i], c256));
    put(12, hcmul(W[0], c512)); put(13, hcmul(W[4], c512)); put(14, hcmul(W[0], c768)); put(15, hcmul(W[4], c768));
    contract(0, 2);
    const uint32_t v0 = hcmul(W[0], c1024);
    put(0, v0); put(1, hcmul(v0, c256)); put(2, hcmul(v0, c512)); put(3, hcmul(v0, c768)); put(4, hcmul(v0, c1024));
    contract(2, 1);
    const uint32_t a = tb + (g * 24 + 2 * q) * 4;
#pragma unroll
    for (int t = 0; t < 6; ++t) {
      const float(&d)[4] = D[t / 3][t % 3];
      sts_f32x2(a + (t / 3) * 1536 + (t % 3) * 32, d[0] * inv, d[1] * inv);
      sts_f32x2(a + (t / 3) * 1536 + (t % 3) * 32 + 768, d[2] * inv, d[3] * inv);
    }
    if (mz > 0.f) {
      __syncwarp();
#pragma unroll 1
      for (int i = lane; i < 768; i += 32) {
        const int r = i / 24, y = i - 24 * r;
        sts_f32(tb + i * 4, lds_f32(tb + i * 4) * ex2(mz * 1.4426950408889634f * (koff(y) + 8 * r)));
      }
    }
  }
  if (tid == 0) TS(2);
  if (warp < 12) cluster_wait();
  if (tid == 0) TS(32);
  __syncthreads();
  if (tid == 0) TSD(33);

  if (warp < 4) {
    asm volatile("setmaxnreg.inc.sync.aligned.u32 152;");
    if (tid == 0) TS(34);
    const int d = cta * 4 + warp;
    const uint32_t vv = sb + SM_VV + warp * VV_BYTES;
    const uint32_t ub = sb + SM_U + warp * U_BYTES;
    const uint32_t pb = sb + SM_P + warp * P_BYTES;
    const float dskip = bf_lo(r_dskip);
#pragma unroll 1
    for (int pass = 0; pass < 2; ++pass) {
      if (pass == 1) {
        const uint32_t kf = vv;
#pragma unroll 2
        for (int i = 0; i < 6; ++i) {
          const uint32_t a = kf + (i * 32 + lane) * 16;
          const uint4 x0 = lds128(a), x1 = lds128(a + KG_BYTES), x2 = lds128(a + 2 * KG_BYTES), x3 = lds128(a + 3 * KG_BYTES);
          auto s4 = [](uint32_t a0, uint32_t a1, uint32_t a2, uint32_t a3) {
            return __float_as_uint((__uint_as_float(a0) + __uint_as_float(a1)) + (__uint_as_float(a2) + __uint_as_float(a3)));
          };
          sts128(a, s4(x0.x, x1.x, x2.x, x3.x), s4(x0.y, x1.y, x2.y, x3.y), s4(x0.z, x1.z, x2.z, x3.z), s4(x0.w, x1.w, x2.w, x3.w));
        }
        __syncwarp();
        const float k1024 = lds_f32(kf + kidx_c(1024) * 4);
        if (lane == 0) {
          sts_f32(kf + SL_ZERO * 4, 0.f);
          sts_f32(kf + SL_510 * 4, lds_f32(kf + kidx_c(510) * 4) - lds_f32(kf + kidx_c(512) * 4));
          sts_f32(kf + SL_0 * 4, lds_f32(kf) + dskip);
        }
        __syncwarp();
        if (tid == 0) TS(36);
        mbar_wait_long(BAR(B_PFREE), 0);
        if (tid == 0) TS(37);
        {
          float prev = 0.f;
#pragma unroll 1
          for (int i0 = 0; i0 < 16; i0 += 4) {
            uint32_t e[4];
            float a[4], b[4];
#pragma unroll
            for (int i = 0; i < 4; ++i) e[i] = lds32(sb + SM_PTAB + ((i0 + i) * 32 + lane) * 4);
#pragma unroll
            for (int i = 0; i < 4; ++i) { a[i] = lds_f32(kf + (e[i] & 0xffff)); b[i] = lds_f32(kf + (e[i] >> 16)); }
#pragma unroll
            for (int i = 0; i < 4; ++i) {
              const uint32_t w = pb + (31 * lane + 2 * (i0 + i)) * 4;
              if (i0 + i > 0) sts32(w - 4, pack_bf16(a[i], prev));
              sts32(w, pack_bf16(b[i], a[i]));
              prev = b[i];
            }
          }
        }
        __syncwarp();
        if (lane == 0) TS(4);
        const int gq = g - 2 * q;
        uint32_t h127, h128;
        {
          const uint32_t kf2 = pack_bf16(k1024, k1024) ^ 0x80008000u;
          h127 = (gq == 4 ? 0x0000ffffu : gq == 5 ? 0xffffffffu : gq == 6 ? 0xffff0000u : 0u) & kf2;
          h128 = (gq == -4 ? 0x0000ffffu : gq == -3 ? 0xffffffffu : gq == -2 ? 0xffff0000u : 0u) & kf2;
        }
        bar_sync(4, 480);
        mbar_wait_long(BAR(B_UCH + warp), 0);
        if (lane == 0) TS(7);
        float acc[16][4];
#pragma unroll
        for (int i = 0; i < 16; ++i) { acc[i][0] = acc[i][1] = acc[i][2] = acc[i][3] = 0.f; }
        {
          const uint32_t pd_lane = pb + (PD_OFF + 16 + gq) * 4;
          const int prow0 = 8 + (lane & 7) + ((lane >> 4) << 3), hs = (lane >> 3) & 1;
          const uint32_t zero = (uint32_t)cta >> 20;
          uint32_t B[2][4][4];
          uint32_t A[4][4];
          const uint32_t la0 = ub + prow0 * 32 + ((hs ^ ((prow0 >> 2) & 1)) << 4);
#pragma unroll
          for (int m2 = 0; m2 < 4; ++m2) ldsm_x4(B[0][m2], la0 + m2 * 512);
#pragma unroll
          for (int i = 0; i < 4; ++i) {
            const uint32_t a = pd_lane + i * 512;
            A[i][0] = lds32(a); A[i][1] = lds32(a + 32); A[i][2] = lds32(a - 32); A[i][3] = lds32(a + zero);
          }
          uint32_t la = la0;
#pragma unroll 1
          for (int rho = 0; rho < 8; ++rho) {
#pragma unroll
            for (int m2 = 0; m2 < 4; ++m2) ldsm_x4(B[1][m2], la + (4 + m2) * 512);
#pragma unroll
            for (int i = 0; i < 4; ++i)
#pragma unroll
              for (int m = 0; m < 8; ++m) mma_bf16v(acc[m + i], A[i], B[0][m >> 1][2 * (m & 1)], B[0][m >> 1][2 * (m & 1) + 1]);
            const int prow = prow0 - min(rho + 1, 7);
            la = ub + prow * 32 + ((hs ^ ((prow >> 2) & 1)) << 4);
#pragma unroll
            for (int m2 = 0; m2 < 4; ++m2) ldsm_x4(B[0][m2], la + m2 * 512);
            const uint32_t pa = pd_lane + (rho + 1) * 64;
#pragma unroll
            for (int i = 0; i < 4; ++i) {
#pragma unroll
              for (int m = 0; m < 8 - i; ++m)
                mma_bf16v(acc[8 + m + i], A[i], B[1][m >> 1][2 * (m & 1)], B[1][m >> 1][2 * (m & 1) + 1]);
              A[i][0] = lds32(pa + i * 512); A[i][1] = lds32(pa + i * 512 + 32); A[i][2] = lds32(pa + i * 512 - 32);
              A[i][3] = lds32(pa + i * 512 + zero);
            }
          }
          if (lane == 0) TS(40);
          {
            uint32_t b8[4];
            ldsm_x4(b8, la + 4 * 512);
            const uint32_t h63 = lds32(pd_lane + 63 * 32), h64 = lds32(pd_lane + 64 * 32);
            const uint32_t a63[4] = {0u, h127, 0u, 0u}, a32[4] = {h64, 0u, h63, h64}, a64[4] = {h128, 0u, h127, h128};
#pragma unroll
            for (int m2 = 0; m2 < 4; ++m2) ldsm_x4(B[1][m2], la0 + m2 * 512);
#pragma unroll
            for (int m = 0; m < 8; ++m) mma_bf16v(acc[m + 7], a63, B[0][m >> 1][2 * (m & 1)], B[0][m >> 1][2 * (m & 1) + 1]);
#pragma unroll
            for (int m2 = 0; m2 < 2; ++m2) ldsm_x4(B[0][m2], la0 + (4 + m2) * 512);
#pragma unroll
            for (int m = 0; m < 8; ++m) mma_bf16v(acc[m + 4], a32, B[1][m >> 1][2 * (m & 1)], B[1][m >> 1][2 * (m & 1) + 1]);
            mma_bf16v(acc[15], a63, b8[0], b8[1]);
#pragma unroll
            for (int m = 0; m < 8; ++m) mma_bf16v(acc[m + 8], a64, B[1][m >> 1][2 * (m & 1)], B[1][m >> 1][2 * (m & 1) + 1]);
#pragma unroll
            for (int m = 0; m < 4; ++m) mma_bf16v(acc[m + 12], a32, B[0][m >> 1][2 * (m & 1)], B[0][m >> 1][2 * (m & 1) + 1]);
          }
          if (lane == 0) TS(41);
          bar_sync(5, 224);
#pragma unroll 1
          for (int v = 0; v < 4; ++v)
            conv_tail<4, 3, 11>(acc, pb + (P2_OFF + 56 * v + gq - 16) * 4, vv + ((v & 1) ? VV_U3 : VV_U5), v >> 1, v == 0, lane);
          if (lane == 0) TS(42);
#pragma unroll 1
          for (int pi = 0; pi < 2; ++pi)
            conv_tail<8, 5, 7>(acc, pb + (P3_OFF + 88 * pi + gq - 48) * 4, vv + (pi ? VV_U7 : VV_U9), pi, pi == 0, lane);
        }
        if (lane == 0) TS(8);
        __syncwarp();
        {
          const int mt = lane >> 3;
          const uint32_t a = pb + (128 * (mt >> 1) + 16 * (lane & 7) + 8 * (mt & 1)) * 2;
#pragma unroll
          for (int ab = 0; ab < 16; ab += 2)
            stsm_x4_t(a + ab * 256, pack_bf16(acc[ab][0], acc[ab][1]), pack_bf16(acc[ab][2], acc[ab][3]),
                      pack_bf16(acc[ab + 1][0], acc[ab + 1][1]), pack_bf16(acc[ab + 1][2], acc[ab + 1][3]));
        }
        fence_async_smem();
        __syncwarp();
        if (lane < 2) mbar_arrive_cluster(BAR(B_CONVD), lane);
        bar_arrive(3, 384);
        if (elect_one()) {
          bulk_store(p.yT + (size_t)d * 2048, pb, 4096);
          bulk_commit();
          bulk_wait0();
          red_relaxed_add(&g_cnt[(C_Y + (cta >> 4)) * 32], 1);
          TS(9);
        }
        bar_sync(2, 128);
        if (warp == 0 && elect_one()) {
          wait_counter(&g_cnt[(C_Y + tj) * 32], (epoch + 1) * 64);
          TS(28);
          mbar_expect_tx(BAR(B_TILE), 16384);
          tma_load_2d(sb + SM_U, &maps.yT, ti * 128, tj * 64, BAR(B_TILE));
          tma_load_2d(sb + SM_U + 8192, &maps.yT, ti * 128 + 64, tj * 64, BAR(B_TILE));
        }
        __syncwarp();
      }
      mbar_wait_long(BAR(B_TILE), pass);
      if (lane == 0) TS(26 + 3 * pass);
      {
        const int m = lane >> 3, r = lane & 7;
#pragma unroll 2
        for (int it = 0; it < 8; ++it) {
          const int tb = warp * 4 + (it >> 1), cb = (it & 1) * 4 + m;
          const uint32_t at = (tb * 8 + r) * 128 + ((cb ^ r) << 4);
          const uint32_t ac = (tb >> 3) * 8192 + (cb * 8 + r) * 128 + (((tb & 7) ^ (pass ? 0 : tb >> 3) ^ r) << 4);
          uint32_t v[4];
          ldsm_x4_t(v, sb + SM_U + (pass ? ac : at));
          stsm_x4(sb + SM_P + (pass ? at : ac), v[0], v[1], v[2], v[3]);
        }
      }
      if (pass == 0 && tid == 0) TS(35);
      fence_async_smem();
      if (pass == 0) {
        bar_arrive(6, 160);
      } else {
        bar_sync(2, 128);
        if (warp == 0 && elect_one()) {
          tma_store_2d(&maps.out, sb + SM_P, 64 * tj, 128 * ti);
          bulk_commit();
          bulk_wait_read0();
          TS(30);
        }
      }
    }
  } else if (warp < 12) {
    asm volatile("setmaxnreg.inc.sync.aligned.u32 160;");
    const int w8 = warp - 4;
    const int row = w8 * 16 + (lane & 7) + (((lane >> 3) & 1) << 3);
    {
      float acc[96];
#pragma unroll 1
      for (int ks = 0, s = 0, ph = 0; ks < 16; ++ks) {
        mbar_wait(BAR(B_FULL + s), ph);
        if (tid == 128 && !(ks & 1)) TSR(16, ks == 0 ? 16 : 9 + (ks >> 1) + (ks > 12 ? 46 : 0));
        const uint32_t st = sb + s * STG_BYTES;
        const uint32_t da = mkdesc(st + STG_X + (w8 >> 2) * 4096, 16);
        const uint32_t db = mkdesc(st + STG_W, 2048);
        wg_fence();
        wgmma_n192(acc, da, db, ks != 0);
        wgmma_n192(acc, da + 2, db + 384, 1);
        wg_commit();
        const uint32_t eprev = BAR(B_EMPTY + (s == 0 ? NSTG - 1 : s - 1));
        if (++s == NSTG) { s = 0; ph ^= 1; }
        if (ks > 0) {
          wg_wait<1>();
          if (lane < 2) mbar_arrive_cluster(eprev, lane);
        }
      }
      wg_wait<0>();
      if (tid == 128) TS(17);
      bar_sync(1, 256);
#pragma unroll
      for (int i = 0; i < 24; i += 2)
        stsm_x4(sb + SM_QS + row * 128 + (i >> 3) * 16384 + ((((i & 7) + (lane >> 4)) ^ (row & 7)) << 4),
                pack_bf16(acc[4 * i], acc[4 * i + 1]), pack_bf16(acc[4 * i + 2], acc[4 * i + 3]),
                pack_bf16(acc[4 * i + 4], acc[4 * i + 5]), pack_bf16(acc[4 * i + 6], acc[4 * i + 7]));
    }
    __syncwarp();
#pragma unroll 1
    for (int part = 1; part >= 0; --part) {
      const uint32_t pa = sb + SM_QS + part * 16384 + w8 * 2048 + lane * 16;
#pragma unroll 1
      for (int it = 0; it < 4; ++it) {
        uint4 t = lds128(pa + it * 512);
        uint32_t* tw = &t.x;
#pragma unroll
        for (int j = 0; j < 4; ++j) {
          const uint32_t x = tw[j];
          const __nv_bfloat162 xb = *reinterpret_cast<const __nv_bfloat162*>(&x);
          const uint32_t e = pack_bf16(ex2(bf_lo(x) * 1.4426950408889634f), ex2(bf_hi(x) * 1.4426950408889634f));
          const uint32_t m = __hgt2_mask(xb, __floats2bfloat162_rn(0.f, 0.f));
          tw[j] = badd((badd(x, 0x3f803f80u) & m) | (e & ~m), 0x35863586u);
        }
        sts128(pa + it * 512, t.x, t.y, t.z, t.w);
      }
      if (part == 1) {
        if (tid == 128) TS(53);
        bar_sync(1, 256);
        const int hh = w8 >> 1, dtile = w8 & 1;
        float kv[4] = {0.f, 0.f, 0.f, 0.f}, zz[4] = {0.f, 0.f, 0.f, 0.f};
        const int m = lane >> 3;
        const uint32_t aa = sb + SM_VS + ((lane & 7) + ((m >> 1) << 3)) * 128 + (((2 * hh + (m & 1)) ^ (lane & 7)) << 4);
        const uint32_t ab = sb + SM_PK + (lane & 15) * 128 + (((2 * hh + dtile) ^ (lane & 7)) << 4);
#pragma unroll 2
        for (int ks = 0; ks < 8; ++ks) {
          uint32_t a[4], b0, b1;
          ldsm_x4_t(a, aa + ks * 2048);
          ldsm_x2_t(b0, b1, ab + ks * 2048);
          mma_bf16(kv, a[0], a[1], a[2], a[3], b0, b1);
          mma_bf16(zz, 0x3f803f80u, 0x3f803f80u, 0x3f803f80u, 0x3f803f80u, b0, b1);
        }
        const uint32_t kp = sb + SM_KV + hh * 1088;
        sts128(kp + dtile * 512 + lane * 16, __float_as_uint(kv[0]), __float_as_uint(kv[1]), __float_as_uint(kv[2]),
               __float_as_uint(kv[3]));
        if (g == 0) sts_f32x2(kp + 1024 + dtile * 32 + q * 8, zz[0], zz[1]);
        fence_async_smem();
        __syncwarp();
        if (lane == 0) mbar_arrive(BAR(B_KVP));
        bar_arrive(4, 480);
        if (tid == 128) TS(55);
      }
    }
    if (tid == 128) TS(56);
    mbar_wait_long(BAR(B_KVF), 0);
    if (tid == 128) TS(19);
#pragma unroll 1
    for (int h = 0; h < 4; ++h) {
      uint32_t a[4];
      const uint32_t qa = sb + SM_QS + row * 128 + (((2 * h + (lane >> 4)) ^ (row & 7)) << 4);
      ldsm_x4(a, qa);
      const uint32_t kp = sb + SM_KV + h * 1088;
      const uint4 k0 = lds128(kp + lane * 16), k1 = lds128(kp + 512 + lane * 16);
      const uint32_t za = kp + 1024 + q * 8;
      auto pk2 = [](uint32_t x, uint32_t y) { return pack_bf16(__uint_as_float(x), __uint_as_float(y)); };
      float n0[4] = {0.f, 0.f, 0.f, 0.f}, n1[4] = {0.f, 0.f, 0.f, 0.f}, dn[4] = {0.f, 0.f, 0.f, 0.f};
      mma_bf16(n0, a[0], a[1], a[2], a[3], pk2(k0.x, k0.y), pk2(k1.x, k1.y));
      mma_bf16(n1, a[0], a[1], a[2], a[3], pk2(k0.z, k0.w), pk2(k1.z, k1.w));
      mma_bf16(dn, a[0], a[1], a[2], a[3], pack_bf16(lds_f32(za), lds_f32(za + 4)), pack_bf16(lds_f32(za + 32), lds_f32(za + 36)));
      const uint32_t dd = pack_bf16(dn[0], dn[2]);
      const uint32_t d2 = pack_bf16(bf_lo(dd) + 1e-6f, bf_hi(dd) + 1e-6f);
      const float r0 = rcp(bf_lo(d2)), r1 = rcp(bf_hi(d2));
      const uint32_t x0 = pack_bf16(n0[0], n0[1]), x1 = pack_bf16(n0[2], n0[3]);
      const uint32_t x2 = pack_bf16(n1[0], n1[1]), x3 = pack_bf16(n1[2], n1[3]);
      stsm_x4(qa, pack_bf16(bf_lo(x0) * r0, bf_hi(x0) * r0), pack_bf16(bf_lo(x1) * r1, bf_hi(x1) * r1),
              pack_bf16(bf_lo(x2) * r0, bf_hi(x2) * r0), pack_bf16(bf_lo(x3) * r1, bf_hi(x3) * r1));
    }
    fence_async_smem();
    __syncwarp();
    if (lane == 0) mbar_arrive(BAR(B_OST));
    if (tid == 128) TS(57);
    mbar_wait_long(BAR(B_WO), 0);
    bar_sync(3, 384);
    {
      float o[32];
#pragma unroll 1
      for (int c = 0; c < 8; ++c) {
        mbar_wait_long(BAR(B_RF + c), 0);
        if (tid == 128) TSR(22, c == 0 ? 22 : 43 + c);
        const uint32_t slot = c < 4 ? SM_QS + c * 16384 : c < 7 ? SM_VV + (c - 4) * 16384 : SM_QS;
        const uint32_t da = mkdesc(sb + slot + (w8 >> 2) * 8192, 16);
        const uint32_t db = mkdesc(sb + SM_WO + c * 8192, 8192);
        wg_fence();
#pragma unroll
        for (int k = 0; k < 4; ++k) wgmma_n64(o, da + 2 * k, db + 128 * k, (c | k) != 0);
        wg_commit();
        if (c == 1) {
          wg_wait<1>();
          if (lane < 2) mbar_arrive_cluster(BAR(B_RE), lane);
        }
      }
      wg_wait<0>();
      if (tid == 128) TS(51);
      bar_sync(1, 256);
#pragma unroll
      for (int i = 0; i < 8; i += 2)
        stsm_x4(sb + SM_BOUT + row * 128 + (((i + (lane >> 4)) ^ (row & 7)) << 4), pack_bf16(o[4 * i], o[4 * i + 1]),
                pack_bf16(o[4 * i + 2], o[4 * i + 3]), pack_bf16(o[4 * i + 4], o[4 * i + 5]), pack_bf16(o[4 * i + 6], o[4 * i + 7]));
      fence_async_smem();
      bar_sync(1, 256);
      if (tid == 128) TS(52);
      if (warp == 4 && elect_one()) {
        tma_store_2d(&maps.out, sb + SM_BOUT, 512 + 64 * pj, 128 * pi);
        bulk_commit();
        bulk_wait_read0();
        TS(23);
      }
    }
  } else {
    asm volatile("setmaxnreg.dec.sync.aligned.u32 40;");
    if (warp == 12) {
      if (elect_one()) {
#pragma unroll 1
        for (int ks = NSTG, s = 0, ph = 0; ks < 16; ++ks) {
          mbar_wait(BAR(B_EMPTY + s), ph);
          issue_stage(ks, s);
          if (ks == NSTG) l2_prefetch((const char*)p.wo + (size_t)cta * 4096, 4096);
          if (++s == NSTG) { s = 0; ph ^= 1; }
        }
        mbar_wait(BAR(B_EMPTY + 6), 1);
        mbar_expect_tx(BAR(B_WO), 65536);
        tma_load_2d(sb + SM_WO, &maps.wo, pj * 64, 0, BAR(B_WO));
        tma_load_2d(sb + SM_WO + 32768, &maps.wo, pj * 64, 256, BAR(B_WO));
        float* kvg = &g_kv[epoch & 1][tj][0];
        mbar_wait_long(BAR(B_KVP), 0);
        bulk_reduce_add_f32(kvg, sb + SM_KV, 4352);
        bulk_commit();
        bulk_wait0();
        red_relaxed_add(&g_cnt[(C_KV + tj) * 32], 1);
        TS(18);
        wait_counter(&g_cnt[(C_KV + tj) * 32], (epoch + 1) * 16);
        mbar_expect_tx(BAR(B_KVF), 4352);
        bulk_load(sb + SM_KV, kvg, 4352, BAR(B_KVF));
        mbar_wait_long(BAR(B_OST), 0);
        tma_store_2d(&maps.o, sb + SM_QS, tj * 64, ti * 128);
        tma_store_2d(&maps.o, sb + SM_QS + 8192, tj * 64, ti * 128 + 64);
        bulk_commit();
        bulk_wait0();
        red_relaxed_add(&g_cnt[(C_O + ti) * 32], 1);
        TS(20);
        mbar_arrive_cluster(BAR(B_SLOT), 0);
        mbar_arrive_cluster(BAR(B_SLOT), 1);
        wait_counter(&g_cnt[(C_O + pi) * 32], (epoch + 1) * 8);
        if (cta == 0) g_epoch = epoch + 1;
        mbar_wait(BAR(B_SLOT), 0);
        TS(21);
#pragma unroll 1
        for (int c = 0; c < 8; ++c) {
          if (c == 4) mbar_wait_long(BAR(B_CONVD), 0);
          if (c == 7) mbar_wait(BAR(B_RE), 0);
          const uint32_t slot = c < 4 ? SM_QS + c * 16384 : c < 7 ? SM_VV + (c - 4) * 16384 : SM_QS;
          mbar_expect_tx(BAR(B_RF + c), 16384);
          tma_load_2d_mc(sb + slot + rank * 8192, &maps.o, c * 64, pi * 128 + rank * 64, BAR(B_RF + c), 3);
        }
      }
    } else if (warp == 13) {
      bar_sync(6, 160);
      sts128(sb + SM_U + (lane >> 4) * U_BYTES + (lane & 15) * 16, 0, 0, 0, 0);
      sts128(sb + SM_U + (2 + (lane >> 4)) * U_BYTES + (lane & 15) * 16, 0, 0, 0, 0);
      __syncwarp();
      if (elect_one()) {
        tma_store_2d(&maps.uT, sb + SM_P, ti * 128, tj * 64);
        tma_store_2d(&maps.uT, sb + SM_P + 8192, ti * 128 + 64, tj * 64);
        bulk_commit();
        bulk_wait_read0();
        mbar_arrive(BAR(B_PFREE));
        bulk_wait0();
        red_relaxed_add(&g_cnt[(C_U + tj) * 32], 1);
        TS(27);
        wait_counter(&g_cnt[(C_U + (cta >> 4)) * 32], (epoch + 1) * 16);
#pragma unroll 1
        for (int c = 0; c < 4; ++c) {
          mbar_expect_tx(BAR(B_UCH + c), 4096);
          bulk_load(sb + SM_U + c * U_BYTES + 256, p.uT + (size_t)(cta * 4 + c) * 2048, 4096, BAR(B_UCH + c));
        }
        TS(3);
      }
      __syncwarp();
      if (ti == 0) {
        float4* z = (float4*)&g_kv[(epoch & 1) ^ 1][tj][0];
#pragma unroll 1
        for (int i = lane; i < 272; i += 32) z[i] = make_float4(0.f, 0.f, 0.f, 0.f);
      }
    }
    if (warp >= 13) {
      bar_sync(4, 480);
      auto swz = [](int k, int pad) { const int r = (k >> 1) + pad; return (uint32_t)(r * 32 + (((k & 1) ^ ((r >> 2) & 1)) << 4)); };
      const uint32_t o0 = swz(lane - 3, 8), o1 = swz(lane - 2, 8), o2 = swz(lane - 1, 8), ow = swz(lane - 2, PADV);
      const uint32_t oz = swz(lane - 18, PADV);
#pragma unroll 1
      for (int item = warp - 13; item < 28; item += 3) {
        const int ch = item / 7, it = item - 7 * ch;
        const int k = -2 + 32 * it + lane;
        const uint32_t ua = sb + SM_U + ch * U_BYTES + it * 512, vb = sb + SM_VV + ch * VV_BYTES;
        const uint32_t a0 = ua + o0, a1 = ua + o1, a2 = ua + o2, aw = vb + it * 512 + ow;
        mbar_wait_long(BAR(B_UCH + ch), 0);
        if (it == 0 && lane < 16) {
          sts128(vb + oz + VV_U3, 0, 0, 0, 0); sts128(vb + oz + VV_U5, 0, 0, 0, 0);
          sts128(vb + oz + VV_U7, 0, 0, 0, 0); sts128(vb + oz + VV_U9, 0, 0, 0, 0);
        }
        const uint4 t0 = lds128(a0), t1 = lds128(a1), t2 = lds128(a2);
        const uint32_t E[12] = {t0.x, t0.y, t0.z, t0.w, t1.x, t1.y, t1.z, t1.w, t2.x, t2.y, t2.z, t2.w};
        uint32_t O[8];
#pragma unroll
        for (int j = 0; j < 8; ++j) O[j] = __byte_perm(E[j + 1], E[j + 2], 0x5432);
        uint32_t s3[6], s5[4], s7[4], s9[4];
#pragma unroll
        for (int j = 0; j < 6; ++j) s3[j] = badd(badd(O[j], O[j + 1]), E[j + 2]);
#pragma unroll
        for (int j = 0; j < 4; ++j) {
          s5[j] = badd(s3[j + 2], badd(E[j + 3], E[j + 5]));
          s7[j] = badd(s5[j], badd(O[j + 1], O[j + 4]));
          s9[j] = badd(s7[j], badd(E[j + 2], E[j + 6]));
        }
        if (k < 208) { sts128(aw + VV_U3, s3[0], s3[1], s3[2], s3[3]); sts128(aw + VV_U5, s5[0], s5[1], s5[2], s5[3]); }
        if (k < 144) { sts128(aw + VV_U7, s7[0], s7[1], s7[2], s7[3]); sts128(aw + VV_U9, s9[0], s9[1], s9[2], s9[3]); }
      }
      if (tid == 416) TS(6);
      bar_arrive(5, 224);
    }
  }
  __syncwarp();
  cluster_arrive();
  cluster_wait();
  if (tid == 0) TS(31);
#undef BAR
}

typedef CUresult (*EncodeFn)(CUtensorMap*, CUtensorMapDataType, cuuint32_t, void*, const cuuint64_t*, const cuuint64_t*,
                             const cuuint32_t*, const cuuint32_t*, CUtensorMapInterleave, CUtensorMapSwizzle,
                             CUtensorMapL2promotion, CUtensorMapFloatOOBfill);

static void make_map(EncodeFn enc, CUtensorMap* m, const void* base, uint64_t inner, uint64_t outer, uint32_t box_in,
                     uint32_t box_out, CUtensorMapSwizzle swz = CU_TENSOR_MAP_SWIZZLE_128B) {
  cuuint64_t gd[2] = {inner, outer};
  cuuint64_t gs[1] = {inner * 2};
  cuuint32_t bd[2] = {box_in, box_out};
  cuuint32_t es[2] = {1, 1};
  enc(m, CU_TENSOR_MAP_DATA_TYPE_BFLOAT16, 2, const_cast<void*>(base), gd, gs, bd, es, CU_TENSOR_MAP_INTERLEAVE_NONE,
      swz, CU_TENSOR_MAP_L2_PROMOTION_L2_128B, CU_TENSOR_MAP_FLOAT_OOB_FILL_NONE);
}

}

extern "C" void kernel_launch(void* const* d_in, const int* in_sizes, int n_in, void* d_out, int out_size) {
  using namespace s4la;
  (void)in_sizes; (void)n_in; (void)out_size;
  static EncodeFn enc = nullptr;
  static void *uT = nullptr, *yT = nullptr, *oS = nullptr;
  if (!enc) {
    void* fn = nullptr;
    cudaDriverEntryPointQueryResult qr;
    cudaGetDriverEntryPoint("cuTensorMapEncodeTiled", &fn, cudaEnableDefault, &qr);
    enc = (EncodeFn)fn;
    cudaGetSymbolAddress(&uT, g_uT);
    cudaGetSymbolAddress(&yT, g_yT);
    cudaGetSymbolAddress(&oS, g_o);
    cudaFuncSetAttribute(fused_kernel, cudaFuncAttributeMaxDynamicSharedMemorySize, SM_TOTAL);
  }
  const __nv_bfloat16* const* in = (const __nv_bfloat16* const*)d_in;
  Maps maps;
  make_map(enc, &maps.x, in[9], 512, 2048, 32, 128, CU_TENSOR_MAP_SWIZZLE_64B);
  {
    cuuint64_t gd[3] = {512, 512, 3};
    cuuint64_t gs[2] = {3072, 1024};
    cuuint32_t bd[3] = {64, 16, 3};
    cuuint32_t es[3] = {1, 1, 1};
    enc(&maps.w, CU_TENSOR_MAP_DATA_TYPE_BFLOAT16, 3, const_cast<__nv_bfloat16*>(in[10]), gd, gs, bd, es,
        CU_TENSOR_MAP_INTERLEAVE_NONE, CU_TENSOR_MAP_SWIZZLE_128B, CU_TENSOR_MAP_L2_PROMOTION_L2_128B,
        CU_TENSOR_MAP_FLOAT_OOB_FILL_NONE);
  }
  make_map(enc, &maps.wo, in[11], 512, 512, 64, 256);
  make_map(enc, &maps.u, in[0], 512, 2048, 64, 128);
  make_map(enc, &maps.uT, uT, 2048, 512, 64, 64);
  make_map(enc, &maps.yT, yT, 2048, 512, 64, 64);
  make_map(enc, &maps.o, oS, 512, 2048, 64, 64);
  make_map(enc, &maps.out, d_out, 1024, 2048, 64, 128);
  Ptrs p;
  p.A_re = in[1]; p.A_im = in[2]; p.B_re = in[3]; p.B_im = in[4]; p.C_re = in[5]; p.C_im = in[6];
  p.log_dt = in[7]; p.Dskip = in[8]; p.x = in[9]; p.wqkv = in[10]; p.wo = in[11];
  p.uT = (__nv_bfloat16*)uT; p.yT = (__nv_bfloat16*)yT;
  fused_kernel<<<NCTA, NTHREADS, SM_TOTAL, cudaStreamPerThread>>>(maps, p);
}
```

```cpp
#include <cuda_runtime.h>
#include <cuda_bf16.h>
#include <cuda_fp16.h>
#include <cuda.h>
#include <stdint.h>

#define DEVI __device__ __forceinline__

namespace s4la {

constexpr int NTHREADS = 512;
constexpr int NCTA = 128;

constexpr int NSTG = 7;
constexpr uint32_t STG_BYTES = 20480, STG_X = 0, STG_W = 8192;
constexpr uint32_t SM_QS = 0;
constexpr uint32_t SM_PK = SM_QS + 16384, SM_VS = SM_QS + 32768;
constexpr uint32_t SM_WO = 65536;
constexpr uint32_t SM_KV = 131072;
constexpr uint32_t SM_BOUT = 16384;
constexpr uint32_t SM_U = 143360, U_BYTES = 4352;
constexpr uint32_t SM_P = 160768, P_BYTES = 4096;
constexpr uint32_t SM_VV = 177152, VV_BYTES = 12800;
constexpr uint32_t VV_U5 = 0, VV_U3 = 3712, VV_U9 = 7424, VV_U7 = 10112;
constexpr uint32_t KG_BYTES = 3200;
constexpr uint32_t SM_BAR = SM_VV + 4 * VV_BYTES;
constexpr uint32_t SM_PTAB = SM_BAR + 320;
constexpr uint32_t SM_TOTAL = SM_PTAB + 2048;
static_assert(SM_TOTAL <= 232448, "shared memory");
constexpr int PADV = 12;

enum { B_FULL = 0, B_EMPTY = 7, B_TILE = 14, B_UCH = 15, B_KVP = 19, B_KVF = 20, B_OST = 21, B_RF = 22, B_WO = 30, B_RE = 31, B_PFREE = 32, B_CONVD = 33, B_SLOT = 34, B_COUNT = 35 };
__host__ __device__ constexpr int bar_count(int i) {
  return (i >= B_EMPTY && i < B_TILE) ? 16 : i == B_KVP ? 8 : (i == B_RE || i == B_CONVD) ? 16 : i == B_SLOT ? 2 : 1;
}

constexpr int PD_OFF = 0, P2_OFF = 544, P3_OFF = 768;

constexpr int SL_K2048 = 20, SL_ZERO = 21, SL_510 = 22, SL_0 = 23;
__host__ __device__ constexpr int koff(int y) {
  return y < 8 ? y : y < 12 ? 256 + 2 * (y - 8) : y < 16 ? 512 + 256 * ((y - 12) >> 1) + 4 * (y & 1) : 1024 + 256 * (y - 16);
}
__host__ __device__ constexpr int kidx_c(int l) {
  const int y = l < 256 ? (l & 7) : l < 512 ? 8 + ((l & 7) >> 1) : l < 1024 ? 12 + (((l - 512) >> 8) << 1) + ((l >> 2) & 1)
                                                                            : 16 + ((l - 1024) >> 8);
  return ((l >> 3) & 31) * 24 + y;
}
constexpr int slot_direct(int l) {
  if (l < 0 || l > 510) return SL_ZERO;
  if (l == 510) return SL_510;
  if (l == 0) return SL_0;
  return kidx_c(l < 256 ? l : ((l + ((l >> 1) & 1)) & ~1));
}
constexpr int slot_seg2(int v, int k) { return (k >= 32 && k < 64) ? kidx_c(16 * k + 4 * v) : SL_ZERO; }
constexpr int slot_seg3(int pi, int k) {
  return (k >= 64 && k < 128) ? kidx_c(16 * k + 8 * pi) : ((k == 128 && pi == 0) ? SL_K2048 : SL_ZERO);
}
constexpr int slot_word(int w) {
  return w < 0 ? SL_ZERO : w < 544 ? slot_direct(w - 16) : w < 768 ? slot_seg2((w - 544) / 56, 16 + (w - 544) % 56)
       : w < 944 ? slot_seg3((w - 768) / 88, 48 + (w - 768) % 88) : SL_ZERO;
}
struct PTab { uint32_t v[512]; };
constexpr PTab make_ptab() {
  PTab t{};
  for (int lane = 0; lane < 32; ++lane)
    for (int i = 0; i < 16; ++i)
      t.v[i * 32 + lane] = (slot_word(31 * lane - 1 + 2 * i) * 4) | ((slot_word(31 * lane + 2 * i) * 4) << 16);
  return t;
}
__device__ const PTab g_ptab = make_ptab();

__device__ __nv_bfloat16 g_uT[512 * 2048];
__device__ __nv_bfloat16 g_yT[512 * 2048];
__device__ __nv_bfloat16 g_o[2048 * 512];
__device__ float g_kv[2][8][4 * 272];
__device__ unsigned g_cnt[64 * 32];
__device__ unsigned g_epoch;
#define TS(slot) do { } while (0)
#define TSR(on, slot) do { } while (0)
#define TSD(slot) do { } while (0)
enum { C_U = 0, C_KV = 8, C_O = 16, C_Y = 32 };

struct Maps {
  CUtensorMap x, w, wo, u, uT, yT, o, out;
};
struct Ptrs {
  const __nv_bfloat16 *A_re, *A_im, *B_re, *B_im, *C_re, *C_im, *log_dt, *Dskip;
  const __nv_bfloat16 *x, *wqkv, *wo;
  __nv_bfloat16 *uT, *yT;
};

DEVI uint32_t s2u(const void* p) { return (uint32_t)__cvta_generic_to_shared(p); }
DEVI void mbar_init(uint32_t b, uint32_t c) { asm volatile("mbarrier.init.shared::cta.b64 [%0], %1;" ::"r"(b), "r"(c) : "memory"); }
DEVI void mbar_expect_tx(uint32_t b, uint32_t bytes) {
  asm volatile("mbarrier.arrive.expect_tx.shared::cta.b64 _, [%0], %1;" ::"r"(b), "r"(bytes) : "memory");
}
DEVI void mbar_arrive(uint32_t b) { asm volatile("mbarrier.arrive.shared::cta.b64 _, [%0];" ::"r"(b) : "memory"); }
DEVI void mbar_arrive_cluster(uint32_t b, uint32_t cta) {
  asm volatile("{\n.reg .b32 r;\nmapa.shared::cluster.u32 r, %0, %1;\nmbarrier.arrive.shared::cluster.b64 _, [r];\n}"
               ::"r"(b), "r"(cta) : "memory");
}
DEVI void mbar_wait(uint32_t b, uint32_t parity) {
  asm volatile("{\n.reg .pred p;\nLAB_WAIT:\nmbarrier.try_wait.parity.shared::cta.b64 p, [%0], %1;\n@!p bra LAB_WAIT;\n}"
               ::"r"(b), "r"(parity) : "memory");
}
DEVI void mbar_wait_long(uint32_t b, uint32_t parity) {
  asm volatile("{\n.reg .pred p;\nLAB_WAIT:\nmbarrier.try_wait.parity.shared::cta.b64 p, [%0], %1, 0x989680;\n@!p bra LAB_WAIT;\n}"
               ::"r"(b), "r"(parity) : "memory");
}
DEVI void bar_sync(int id, int n) { asm volatile("bar.sync %0, %1;" ::"r"(id), "r"(n) : "memory"); }
DEVI void bar_arrive(int id, int n) { asm volatile("bar.arrive %0, %1;" ::"r"(id), "r"(n) : "memory"); }
DEVI void fence_async_smem() { asm volatile("fence.proxy.async.shared::cta;" ::: "memory"); }
DEVI void fence_async_all() { asm volatile("fence.proxy.async;" ::: "memory"); }
DEVI void cluster_arrive() { asm volatile("barrier.cluster.arrive.relaxed.aligned;" ::: "memory"); }
DEVI void cluster_wait() { asm volatile("barrier.cluster.wait.aligned;" ::: "memory"); }

DEVI void tma_load_2d(uint32_t dst, const CUtensorMap* m, int c0, int c1, uint32_t bar) {
  asm volatile("cp.async.bulk.tensor.2d.shared::cluster.global.mbarrier::complete_tx::bytes [%0], [%1, {%3, %4}], [%2];"
               ::"r"(dst), "l"(m), "r"(bar), "r"(c0), "r"(c1) : "memory");
}
DEVI void tma_load_2d_mc(uint32_t dst, const CUtensorMap* m, int c0, int c1, uint32_t bar, uint16_t mask) {
  asm volatile("cp.async.bulk.tensor.2d.shared::cluster.global.mbarrier::complete_tx::bytes.multicast::cluster [%0], [%1, {%3, %4}], [%2], %5;"
               ::"r"(dst), "l"(m), "r"(bar), "r"(c0), "r"(c1), "h"(mask) : "memory");
}
DEVI void tma_load_3d_mc(uint32_t dst, const CUtensorMap* m, int c0, int c1, int c2, uint32_t bar, uint16_t mask) {
  asm volatile("cp.async.bulk.tensor.3d.shared::cluster.global.mbarrier::complete_tx::bytes.multicast::cluster [%0], [%1, {%3, %4, %5}], [%2], %6;"
               ::"r"(dst), "l"(m), "r"(bar), "r"(c0), "r"(c1), "r"(c2), "h"(mask) : "memory");
}
DEVI void tma_store_2d(const CUtensorMap* m, uint32_t src, int c0, int c1) {
  asm volatile("cp.async.bulk.tensor.2d.global.shared::cta.bulk_group [%0, {%2, %3}], [%1];"
               ::"l"(m), "r"(src), "r"(c0), "r"(c1) : "memory");
}
DEVI void bulk_load(uint32_t dst, const void* src, uint32_t bytes, uint32_t bar) {
  asm volatile("cp.async.bulk.shared::cluster.global.mbarrier::complete_tx::bytes [%0], [%1], %2, [%3];"
               ::"r"(dst), "l"(src), "r"(bytes), "r"(bar) : "memory");
}
DEVI void bulk_store(void* dst, uint32_t src, uint32_t bytes) {
  asm volatile("cp.async.bulk.global.shared::cta.bulk_group [%0], [%1], %2;" ::"l"(dst), "r"(src), "r"(bytes) : "memory");
}
DEVI void bulk_reduce_add_f32(void* dst, uint32_t src, uint32_t bytes) {
  asm volatile("cp.reduce.async.bulk.global.shared::cta.bulk_group.add.f32 [%0], [%1], %2;" ::"l"(dst), "r"(src), "r"(bytes) : "memory");
}
DEVI void bulk_commit() { asm volatile("cp.async.bulk.commit_group;" ::: "memory"); }
DEVI void bulk_wait0() { asm volatile("cp.async.bulk.wait_group 0;" ::: "memory"); }
DEVI void bulk_wait_read0() { asm volatile("cp.async.bulk.wait_group.read 0;" ::: "memory"); }
DEVI void l2_prefetch(const void* p, uint32_t bytes) {
  asm volatile("cp.async.bulk.prefetch.L2.global [%0], %1;" ::"l"(p), "r"(bytes) : "memory");
}
DEVI void prefetch_tmap(const CUtensorMap* m) { asm volatile("prefetch.tensormap [%0];" ::"l"(m) : "memory"); }

DEVI void red_release_add(unsigned* p, unsigned v) {
  asm volatile("red.release.gpu.global.add.u32 [%0], %1;" ::"l"(p), "r"(v) : "memory");
}
DEVI void red_relaxed_add(unsigned* p, unsigned v) {
  asm volatile("red.relaxed.gpu.global.add.u32 [%0], %1;" ::"l"(p), "r"(v) : "memory");
}
DEVI unsigned ld_relaxed(const unsigned* p) {
  unsigned v;
  asm volatile("ld.relaxed.gpu.global.u32 %0, [%1];" : "=r"(v) : "l"(p) : "memory");
  return v;
}
DEVI void wait_counter(const unsigned* p, unsigned target) {
#pragma unroll 1
  for (int it = 0; (int)(ld_relaxed(p) - target) < 0; ++it)
    if (it > (1 << 22)) __trap();
}

DEVI void ldsm_x4(uint32_t (&r)[4], uint32_t a) {
  asm volatile("ldmatrix.sync.aligned.m8n8.x4.shared.b16 {%0,%1,%2,%3}, [%4];"
               : "=r"(r[0]), "=r"(r[1]), "=r"(r[2]), "=r"(r[3]) : "r"(a) : "memory");
}
DEVI void ldsm_x4_t(uint32_t (&r)[4], uint32_t a) {
  asm volatile("ldmatrix.sync.aligned.m8n8.x4.trans.shared.b16 {%0,%1,%2,%3}, [%4];"
               : "=r"(r[0]), "=r"(r[1]), "=r"(r[2]), "=r"(r[3]) : "r"(a) : "memory");
}
DEVI void ldsm_x2_t(uint32_t& r0, uint32_t& r1, uint32_t a) {
  asm volatile("ldmatrix.sync.aligned.m8n8.x2.trans.shared.b16 {%0,%1}, [%2];" : "=r"(r0), "=r"(r1) : "r"(a) : "memory");
}
DEVI void stsm_x4(uint32_t a, uint32_t r0, uint32_t r1, uint32_t r2, uint32_t r3) {
  asm volatile("stmatrix.sync.aligned.m8n8.x4.shared.b16 [%0], {%1,%2,%3,%4};"
               ::"r"(a), "r"(r0), "r"(r1), "r"(r2), "r"(r3) : "memory");
}
DEVI void stsm_x4_t(uint32_t a, uint32_t r0, uint32_t r1, uint32_t r2, uint32_t r3) {
  asm volatile("stmatrix.sync.aligned.m8n8.x4.trans.shared.b16 [%0], {%1,%2,%3,%4};"
               ::"r"(a), "r"(r0), "r"(r1), "r"(r2), "r"(r3) : "memory");
}
DEVI uint32_t lds32(uint32_t a) { uint32_t v; asm volatile("ld.shared.b32 %0, [%1];" : "=r"(v) : "r"(a) : "memory"); return v; }
DEVI float lds_f32(uint32_t a) { float v; asm volatile("ld.shared.f32 %0, [%1];" : "=f"(v) : "r"(a) : "memory"); return v; }
DEVI void sts32(uint32_t a, uint32_t v) { asm volatile("st.shared.b32 [%0], %1;" ::"r"(a), "r"(v) : "memory"); }
DEVI void sts_f32(uint32_t a, float v) { asm volatile("st.shared.f32 [%0], %1;" ::"r"(a), "f"(v) : "memory"); }
DEVI void sts_f32x2(uint32_t a, float x, float y) { asm volatile("st.shared.v2.f32 [%0], {%1,%2};" ::"r"(a), "f"(x), "f"(y) : "memory"); }
DEVI uint4 lds128(uint32_t a) {
  uint4 v;
  asm volatile("ld.shared.v4.b32 {%0,%1,%2,%3}, [%4];" : "=r"(v.x), "=r"(v.y), "=r"(v.z), "=r"(v.w) : "r"(a) : "memory");
  return v;
}
DEVI void sts128(uint32_t a, uint32_t x, uint32_t y, uint32_t z, uint32_t w) {
  asm volatile("st.shared.v4.b32 [%0], {%1,%2,%3,%4};" ::"r"(a), "r"(x), "r"(y), "r"(z), "r"(w) : "memory");
}

DEVI void mma_bf16(float (&d)[4], uint32_t a0, uint32_t a1, uint32_t a2, uint32_t a3, uint32_t b0, uint32_t b1) {
  asm("mma.sync.aligned.m16n8k16.row.col.f32.bf16.bf16.f32 {%0,%1,%2,%3}, {%4,%5,%6,%7}, {%8,%9}, {%0,%1,%2,%3};"
      : "+f"(d[0]), "+f"(d[1]), "+f"(d[2]), "+f"(d[3])
      : "r"(a0), "r"(a1), "r"(a2), "r"(a3), "r"(b0), "r"(b1));
}
DEVI void mma_f16(float (&d)[4], const uint32_t (&a)[4], uint32_t b0, uint32_t b1) {
  asm("mma.sync.aligned.m16n8k16.row.col.f32.f16.f16.f32 {%0,%1,%2,%3}, {%4,%5,%6,%7}, {%8,%9}, {%0,%1,%2,%3};"
      : "+f"(d[0]), "+f"(d[1]), "+f"(d[2]), "+f"(d[3])
      : "r"(a[0]), "r"(a[1]), "r"(a[2]), "r"(a[3]), "r"(b0), "r"(b1));
}
DEVI void mma_bf16v(float (&d)[4], const uint32_t (&a)[4], uint32_t b0, uint32_t b1) {
  asm volatile("mma.sync.aligned.m16n8k16.row.col.f32.bf16.bf16.f32 {%0,%1,%2,%3}, {%4,%5,%6,%7}, {%8,%9}, {%0,%1,%2,%3};"
               : "+f"(d[0]), "+f"(d[1]), "+f"(d[2]), "+f"(d[3])
               : "r"(a[0]), "r"(a[1]), "r"(a[2]), "r"(a[3]), "r"(b0), "r"(b1));
}
DEVI uint32_t pack_bf16(float lo, float hi) {
  uint32_t r;
  asm("cvt.rn.bf16x2.f32 %0, %1, %2;" : "=r"(r) : "f"(hi), "f"(lo));
  return r;
}
DEVI uint32_t pack_f16(float lo, float hi) {
  uint32_t r;
  asm("cvt.rn.f16x2.f32 %0, %1, %2;" : "=r"(r) : "f"(hi), "f"(lo));
  return r;
}
DEVI uint32_t ldg16(const __nv_bfloat16* p) {
  uint32_t v;
  asm volatile("ld.global.nc.u16 %0, [%1];" : "=r"(v) : "l"(p));
  return v;
}
DEVI bool elect_one() {
  uint32_t pred;
  asm volatile("{\n.reg .pred p;\nelect.sync _|p, 0xffffffff;\nselp.u32 %0, 1, 0, p;\n}" : "=r"(pred));
  return pred != 0;
}
DEVI float bf_lo(uint32_t v) { return __uint_as_float(v << 16); }
DEVI float bf_hi(uint32_t v) { return __uint_as_float(v & 0xffff0000u); }
DEVI float bf2f(__nv_bfloat16 v) { return __bfloat162float(v); }
DEVI float round_bf16(float v) { return __bfloat162float(__float2bfloat16_rn(v)); }
DEVI float rcp(float x) { float r; asm("rcp.approx.ftz.f32 %0, %1;" : "=f"(r) : "f"(x)); return r; }
DEVI float ex2(float x) { float r; asm("ex2.approx.ftz.f32 %0, %1;" : "=f"(r) : "f"(x)); return r; }

DEVI void wg_fence() { asm volatile("wgmma.fence.sync.aligned;" ::: "memory"); }
DEVI void wg_commit() { asm volatile("wgmma.commit_group.sync.aligned;" ::: "memory"); }
template <int N> DEVI void wg_wait() { asm volatile("wgmma.wait_group.sync.aligned %0;" ::"n"(N) : "memory"); }
constexpr uint32_t DESC_HI = (1u << 30) | (1024 >> 4);
constexpr uint32_t DESC_HI64 = (2u << 30) | (512 >> 4);
DEVI uint32_t mkdesc(uint32_t saddr, uint32_t lbo) { return ((saddr & 0x3FFFF) >> 4) | ((lbo >> 4) << 16); }

#define R8(b) "%" #b
DEVI void wgmma_n192(float (&d)[96], uint32_t da, uint32_t db, int scale_d) {
  asm volatile(
      "{\n.reg .pred p;\n.reg .b64 da, db;\nsetp.ne.b32 p, %98, 0;\nmov.b64 da, {%96, %100};\nmov.b64 db, {%97, %99};\n"
      "wgmma.mma_async.sync.aligned.m64n192k16.f32.bf16.bf16 "
      "{%0,%1,%2,%3,%4,%5,%6,%7,%8,%9,%10,%11,%12,%13,%14,%15,"
      "%16,%17,%18,%19,%20,%21,%22,%23,%24,%25,%26,%27,%28,%29,%30,%31,"
      "%32,%33,%34,%35,%36,%37,%38,%39,%40,%41,%42,%43,%44,%45,%46,%47,"
      "%48,%49,%50,%51,%52,%53,%54,%55,%56,%57,%58,%59,%60,%61,%62,%63,"
      "%64,%65,%66,%67,%68,%69,%70,%71,%72,%73,%74,%75,%76,%77,%78,%79,"
      "%80,%81,%82,%83,%84,%85,%86,%87,%88,%89,%90,%91,%92,%93,%94,%95}, "
      "da, db, p, 1, 1, 0, 1;\n}"
      : "+f"(d[0]), "+f"(d[1]), "+f"(d[2]), "+f"(d[3]), "+f"(d[4]), "+f"(d[5]), "+f"(d[6]), "+f"(d[7]),
        "+f"(d[8]), "+f"(d[9]), "+f"(d[10]), "+f"(d[11]), "+f"(d[12]), "+f"(d[13]), "+f"(d[14]), "+f"(d[15]),
        "+f"(d[16]), "+f"(d[17]), "+f"(d[18]), "+f"(d[19]), "+f"(d[20]), "+f"(d[21]), "+f"(d[22]), "+f"(d[23]),
        "+f"(d[24]), "+f"(d[25]), "+f"(d[26]), "+f"(d[27]), "+f"(d[28]), "+f"(d[29]), "+f"(d[30]), "+f"(d[31]),
        "+f"(d[32]), "+f"(d[33]), "+f"(d[34]), "+f"(d[35]), "+f"(d[36]), "+f"(d[37]), "+f"(d[38]), "+f"(d[39]),
        "+f"(d[40]), "+f"(d[41]), "+f"(d[42]), "+f"(d[43]), "+f"(d[44]), "+f"(d[45]), "+f"(d[46]), "+f"(d[47]),
        "+f"(d[48]), "+f"(d[49]), "+f"(d[50]), "+f"(d[51]), "+f"(d[52]), "+f"(d[53]), "+f"(d[54]), "+f"(d[55]),
        "+f"(d[56]), "+f"(d[57]), "+f"(d[58]), "+f"(d[59]), "+f"(d[60]), "+f"(d[61]), "+f"(d[62]), "+f"(d[63]),
        "+f"(d[64]), "+f"(d[65]), "+f"(d[66]), "+f"(d[67]), "+f"(d[68]), "+f"(d[69]), "+f"(d[70]), "+f"(d[71]),
        "+f"(d[72]), "+f"(d[73]), "+f"(d[74]), "+f"(d[75]), "+f"(d[76]), "+f"(d[77]), "+f"(d[78]), "+f"(d[79]),
        "+f"(d[80]), "+f"(d[81]), "+f"(d[82]), "+f"(d[83]), "+f"(d[84]), "+f"(d[85]), "+f"(d[86]), "+f"(d[87]),
        "+f"(d[88]), "+f"(d[89]), "+f"(d[90]), "+f"(d[91]), "+f"(d[92]), "+f"(d[93]), "+f"(d[94]), "+f"(d[95])
      : "r"(da), "r"(db), "r"(scale_d), "n"(DESC_HI), "n"(DESC_HI64));
}
DEVI void wgmma_n64(float (&d)[32], uint32_t da, uint32_t db, int scale_d) {
  asm volatile(
      "{\n.reg .pred p;\n.reg .b64 da, db;\nsetp.ne.b32 p, %34, 0;\nmov.b64 da, {%32, %35};\nmov.b64 db, {%33, %35};\n"
      "wgmma.mma_async.sync.aligned.m64n64k16.f32.bf16.bf16 "
      "{%0,%1,%2,%3,%4,%5,%6,%7,%8,%9,%10,%11,%12,%13,%14,%15,"
      "%16,%17,%18,%19,%20,%21,%22,%23,%24,%25,%26,%27,%28,%29,%30,%31}, "
      "da, db, p, 1, 1, 0, 1;\n}"
      : "+f"(d[0]), "+f"(d[1]), "+f"(d[2]), "+f"(d[3]), "+f"(d[4]), "+f"(d[5]), "+f"(d[6]), "+f"(d[7]),
        "+f"(d[8]), "+f"(d[9]), "+f"(d[10]), "+f"(d[11]), "+f"(d[12]), "+f"(d[13]), "+f"(d[14]), "+f"(d[15]),
        "+f"(d[16]), "+f"(d[17]), "+f"(d[18]), "+f"(d[19]), "+f"(d[20]), "+f"(d[21]), "+f"(d[22]), "+f"(d[23]),
        "+f"(d[24]), "+f"(d[25]), "+f"(d[26]), "+f"(d[27]), "+f"(d[28]), "+f"(d[29]), "+f"(d[30]), "+f"(d[31])
      : "r"(da), "r"(db), "r"(scale_d), "n"(DESC_HI));
}

struct C32 { float re, im; };
DEVI C32 csq(C32 a) { return {a.re * a.re - a.im * a.im, 2.f * a.re * a.im}; }
DEVI C32 cmul(C32 a, C32 b) { return {a.re * b.re - a.im * b.im, a.re * b.im + a.im * b.re}; }
DEVI C32 cfresh(float zl, float zi, float m) {
  float mag = ex2(zl * m), ph = zi * m;
  return {mag * __cosf(ph), mag * __sinf(ph)};
}
struct HMul { uint32_t b, bp; };
DEVI HMul mk_mul(float re, float im) { return {pack_f16(re, im), pack_f16(-im, re)}; }
DEVI uint32_t hcmul(uint32_t a, const HMul& m) {
  __half2 ah = *reinterpret_cast<__half2*>(&a);
  __half2 b = *reinterpret_cast<const __half2*>(&m.b), bp = *reinterpret_cast<const __half2*>(&m.bp);
  __half2 r = __hfma2(__high2half2(ah), bp, __hmul2(__low2half2(ah), b));
  return *reinterpret_cast<uint32_t*>(&r);
}
DEVI uint32_t badd(uint32_t a, uint32_t b) {
  __nv_bfloat162 r = __hadd2(*reinterpret_cast<__nv_bfloat162*>(&a), *reinterpret_cast<__nv_bfloat162*>(&b));
  return *reinterpret_cast<uint32_t*>(&r);
}
template <int MU0, int NMU, int DMAX, int LO>
DEVI void conv_tail(float (&acc)[8][4], uint32_t p_lane, uint32_t v_base, int back, bool edge, int lane) {
  constexpr int D0 = LO - (MU0 + 2 * (NMU - 1)) > -1 ? LO - (MU0 + 2 * (NMU - 1)) : -1;
  constexpr int D1 = LO + 7 - MU0 < DMAX ? LO + 7 - MU0 : DMAX;
  const int hsel = (lane >> 3) & 1;
  const int row = (lane & 7) + ((lane >> 4) << 3) + PADV + 8 * D0 - (back & (hsel ^ 1));
  const uint32_t la = v_base + row * 32 + (((hsel ^ back) ^ ((row >> 2) & 1)) << 4);
  uint32_t M[3][4];
  ldsm_x4_t(M[0], la);
  if (D1 > D0) ldsm_x4_t(M[1], la + 256);
  uint32_t H[2 * NMU];
#pragma unroll
  for (int i = 0; i < 2 * NMU; ++i) H[i ^ 1] = lds32(p_lane + (uint32_t)(MU0 - 1 + i) * 32);
  if (D0 == -1 && edge) {
    const uint32_t a[4] = {0u, 0u, M[0][0], M[0][1]};
#pragma unroll
    for (int k = 1; k < NMU; ++k)
      if (MU0 - 2 + 2 * k >= LO && MU0 - 2 + 2 * k < LO + 8) mma_bf16v(acc[MU0 - 2 + 2 * k - LO], a, H[2 * k], H[2 * k + 1]);
  }
#pragma unroll
  for (int delta = D0; delta <= D1; ++delta) {
    if (delta + 2 <= D1) ldsm_x4_t(M[(delta - D0 + 2) % 3], la + (delta - D0 + 2) * 256);
#pragma unroll
    for (int k = 0; k < NMU; ++k) {
      const int nb = delta + MU0 + 2 * k;
      if (nb >= LO && nb < LO + 8) mma_bf16v(acc[nb - LO], M[(delta - D0) % 3], H[2 * k], H[2 * k + 1]);
    }
  }
}

template <int LO>
DEVI void conv_half(uint32_t ub, uint32_t pb, uint32_t vv, int lane, uint32_t zero, int ch, __nv_bfloat16* yrow) {
  const int gq = (lane >> 2) - 2 * (lane & 3);
  float acc[8][4];
#pragma unroll
  for (int i = 0; i < 8; ++i) { acc[i][0] = acc[i][1] = acc[i][2] = acc[i][3] = 0.f; }
  const uint32_t pd_lane = pb + (PD_OFF + 16 + gq) * 4;
  const int prow0 = 8 + (lane & 7) + ((lane >> 4) << 3), hs = (lane >> 3) & 1;
  constexpr int M2 = LO ? 2 : 0, NM2 = LO ? 6 : 4;
#pragma unroll 1
  for (int rho = 0; rho < 8; ++rho) {
    const int prow = prow0 - rho;
    const uint32_t la = ub + prow * 32 + ((hs ^ ((prow >> 2) & 1)) << 4);
    uint32_t B[NM2][4], A[4][4];
#pragma unroll
    for (int m2 = 0; m2 < NM2; ++m2) ldsm_x4(B[m2], la + (M2 + m2) * 512);
#pragma unroll
    for (int i = 0; i < 4; ++i) {
      const uint32_t a = pd_lane + rho * 64 + i * 512;
      A[i][0] = lds32(a); A[i][1] = lds32(a + 32); A[i][2] = lds32(a - 32);
      A[i][3] = lds32(a + zero);
    }
#pragma unroll
    for (int i = 0; i < 4; ++i)
#pragma unroll
      for (int ab = LO; ab < LO + 8; ++ab) {
        const int m = ab - i;
        if (m >= 0) mma_bf16v(acc[ab - LO], A[i], B[(m >> 1) - M2][2 * (m & 1)], B[(m >> 1) - M2][2 * (m & 1) + 1]);
      }
  }
  {
    const uint32_t kw = lds32(pb + (P3_OFF + 16) * 4);
    const uint32_t kf2 = __byte_perm(kw, 0, 0x1010) ^ 0x80008000u;
    const uint32_t h127 = (gq == 4 ? 0x0000ffffu : gq == 5 ? 0xffffffffu : gq == 6 ? 0xffff0000u : 0u) & kf2;
    const uint32_t h128 = (gq == -4 ? 0x0000ffffu : gq == -3 ? 0xffffffffu : gq == -2 ? 0xffff0000u : 0u) & kf2;
    const uint32_t h63 = lds32(pd_lane + 63 * 32), h64 = lds32(pd_lane + 64 * 32);
    const uint32_t a63[4] = {0u, h127, 0u, 0u}, a32[4] = {h64, 0u, h63, h64}, a64[4] = {h128, 0u, h127, h128};
    const uint32_t la0 = ub + prow0 * 32 + ((hs ^ ((prow0 >> 2) & 1)) << 4);
    const uint32_t la7 = ub + (prow0 - 7) * 32 + ((hs ^ (((prow0 - 7) >> 2) & 1)) << 4);
    constexpr int N0 = LO ? 6 : 2, N7 = LO ? 5 : 1;
    uint32_t B0[N0][4], B7[N7][4];
#pragma unroll
    for (int m2 = 0; m2 < N7; ++m2) ldsm_x4(B7[m2], la7 + m2 * 512);
#pragma unroll
    for (int m2 = 0; m2 < N0; ++m2) ldsm_x4(B0[m2], la0 + m2 * 512);
#pragma unroll
    for (int ab = LO; ab < LO + 8; ++ab)
      if (ab >= 7) mma_bf16v(acc[ab - LO], a63, B7[(ab - 7) >> 1][2 * ((ab - 7) & 1)], B7[(ab - 7) >> 1][2 * ((ab - 7) & 1) + 1]);
#pragma unroll
    for (int ab = LO; ab < LO + 8; ++ab)
      if (ab >= 4) mma_bf16v(acc[ab - LO], a32, B0[(ab - 4) >> 1][2 * ((ab - 4) & 1)], B0[(ab - 4) >> 1][2 * ((ab - 4) & 1) + 1]);
#pragma unroll
    for (int ab = LO; ab < LO + 8; ++ab)
      if (ab >= 8) mma_bf16v(acc[ab - LO], a64, B0[(ab - 8) >> 1][2 * ((ab - 8) & 1)], B0[(ab - 8) >> 1][2 * ((ab - 8) & 1) + 1]);
  }
  if (LO) bar_sync(8 + ch, 64);
#pragma unroll 1
  for (int v = 0; v < 4; ++v)
    conv_tail<4, 3, 11, LO>(acc, pb + (P2_OFF + 56 * v + gq - 16) * 4, vv + ((v & 1) ? VV_U3 : VV_U5), v >> 1, v == 0, lane);
#pragma unroll 1
  for (int pi = 0; pi < (LO ? 2 : 1); ++pi)
    conv_tail<8, 5, 7, LO>(acc, pb + (P3_OFF + 88 * pi + gq - 48) * 4, vv + (pi ? VV_U7 : VV_U9), pi, pi == 0, lane);
  bar_sync(12 + ch, 64);
  const int mt = lane >> 3;
  const uint32_t a = pb + (128 * (LO + (mt >> 1)) + 16 * (lane & 7) + 8 * (mt & 1)) * 2;
#pragma unroll
  for (int t = 0; t < 8; t += 2)
    stsm_x4_t(a + t * 256, pack_bf16(acc[t][0], acc[t][1]), pack_bf16(acc[t][2], acc[t][3]),
              pack_bf16(acc[t + 1][0], acc[t + 1][1]), pack_bf16(acc[t + 1][2], acc[t + 1][3]));
  fence_async_smem();
  __syncwarp();
}

__global__ void __cluster_dims__(2, 1, 1) __launch_bounds__(NTHREADS, 1)
fused_kernel(const __grid_constant__ Maps maps, const Ptrs p) {
  extern __shared__ __align__(1024) uint8_t smem[];
  const uint32_t sb = s2u(smem);
  const int tid = threadIdx.x, lane = tid & 31;
  const int warp = __shfl_sync(0xffffffffu, tid >> 5, 0);
  const int cta = blockIdx.x;
  const uint32_t rank = cta & 1;
  const int ti = 2 * (cta >> 4) + rank;
  const int tj = (cta >> 1) & 7;
  const int pi = cta >> 3, pj = cta & 7;
  const uint32_t bars = sb + SM_BAR;
#define BAR(i) (bars + 8 * (i))
  const int g = lane >> 2, q = lane & 3;

  auto issue_stage = [&](int ks, int s) {
    const uint32_t st = sb + s * STG_BYTES, fb = BAR(B_FULL + s);
    mbar_expect_tx(fb, STG_BYTES);
    tma_load_2d(st + STG_X, &maps.x, ks * 32, ti * 128, fb);
    tma_load_3d_mc(st + STG_W + rank * 6144, &maps.w, tj * 64, ks * 32 + rank * 16, 0, fb, 3);
  };

  const int kch = warp & 3, krd = warp >> 2;
  float zr, zi, wr, wi;
  unsigned epoch;
  uint32_t r_dskip;
  {
    const size_t po = (size_t)(cta * 4 + kch) * 128 + krd * 32 + lane;
    const uint32_t r_ar = ldg16(p.A_re + po), r_ai = ldg16(p.A_im + po), r_br = ldg16(p.B_re + po), r_bi = ldg16(p.B_im + po);
    const uint32_t r_cr = ldg16(p.C_re + po), r_ci = ldg16(p.C_im + po), r_ldt = ldg16(p.log_dt + cta * 4 + kch);
    epoch = __ldcg(&g_epoch);
    r_dskip = ldg16(p.Dskip + cta * 4 + kch);
    uint4 pt;
    if (tid < 128) pt = __ldg((const uint4*)g_ptab.v + tid);
    if (tid == 384) {
      TS(0);
#pragma unroll
      for (int i = 0; i < B_COUNT; ++i) mbar_init(BAR(i), bar_count(i));
      asm volatile("fence.mbarrier_init.release.cluster;" ::: "memory");
      prefetch_tmap(&maps.x); prefetch_tmap(&maps.w); prefetch_tmap(&maps.u);
    }
    __syncthreads();
    cluster_arrive();
    if (warp >= 12) {
      cluster_wait();
      if (elect_one()) {
        if (warp == 13) {
          mbar_expect_tx(BAR(B_TILE), 16384);
          tma_load_2d(sb + SM_U, &maps.u, tj * 64, ti * 128, BAR(B_TILE));
          prefetch_tmap(&maps.uT); prefetch_tmap(&maps.wo); prefetch_tmap(&maps.o); prefetch_tmap(&maps.yT);
          prefetch_tmap(&maps.out);
        } else {
          if (warp == 12) TS(61);
          { const int ks = warp == 12 ? 0 : warp - 13; issue_stage(ks, ks); }
        }
      }
      __syncwarp();
    }
    if (tid < 128) sts128(sb + SM_PTAB + tid * 16, pt.x, pt.y, pt.z, pt.w);
    const float dt = round_bf16(expf(bf_lo(r_ldt)));
    zr = dt * bf_lo(r_ar); zi = dt * bf_lo(r_ai);
    const float dbr = dt * bf_lo(r_br), dbi = dt * bf_lo(r_bi), cr = bf_lo(r_cr), ci = bf_lo(r_ci);
    wr = cr * dbr - ci * dbi; wi = cr * dbi + ci * dbr;
  }
  {
    const float mz = __uint_as_float(__reduce_max_sync(0xffffffffu, __float_as_uint(fmaxf(zr, 0.f))));
    const int E = min(max((int)(__reduce_max_sync(0xffffffffu, __float_as_uint(fmaxf(fabsf(wr), fabsf(wi)))) >> 23), 1), 252);
    const float sc = __int_as_float((253 - E) << 23), inv = __int_as_float((E + 1) << 23);
    const float zl = (zr - mz) * 1.4426950408889634f;
    const uint32_t tb = sb + SM_VV + kch * VV_BYTES + krd * KG_BYTES;
    const uint32_t sta = tb + (((lane >> 2) << 4) | ((lane & 3) << 2));
    auto put = [&](int r, uint32_t v) { sts32((sta ^ ((r & 7) << 4)) + r * 128, v); };
    const uint32_t lda = tb + ((lane & 7) + (((lane >> 3) & 1) << 3)) * 128;
    const uint32_t ldb = tb + ((lane & 7) + ((lane >> 4) << 3)) * 128;
    C32 e1 = cfresh(zl, zi, 1.f), e2 = csq(e1), e4 = csq(e2), e8 = csq(e4);
    C32 e16 = cfresh(zl, zi, 16.f), e32 = csq(e16), e64 = csq(e32), e128 = csq(e64);
    C32 e256 = cfresh(zl, zi, 256.f), e512 = csq(e256), e1024 = csq(e512), e768 = cmul(e512, e256);
    uint32_t XA[2][4][4];
    {
      const HMul m16 = mk_mul(e16.re, e16.im), m32 = mk_mul(e32.re, e32.im), m64 = mk_mul(e64.re, e64.im);
      const HMul m128 = mk_mul(e128.re, e128.im);
      uint32_t X[16];
      X[0] = 0x00003c00u; X[1] = pack_f16(e8.re, e8.im); X[2] = m16.b; X[4] = m32.b; X[8] = m64.b;
      X[3] = hcmul(X[1], m16); X[5] = hcmul(X[1], m32); X[6] = hcmul(X[2], m32); X[7] = hcmul(X[3], m32);
#pragma unroll
      for (int r = 1; r < 8; ++r) X[8 + r] = hcmul(X[r], m64);
#pragma unroll
      for (int h = 0; h < 2; ++h) {
#pragma unroll
        for (int r = 0; r < 16; ++r) put(r, h == 0 ? X[r] : r == 0 ? m128.b : hcmul(X[r], m128));
        __syncwarp();
#pragma unroll
        for (int k = 0; k < 4; ++k) ldsm_x4(XA[h][k], lda + (((2 * k + (lane >> 4)) ^ (lane & 7)) << 4));
        __syncwarp();
      }
    }
    if (warp >= 14 && elect_one()) {
      issue_stage(warp - 11, warp - 11);
      issue_stage(warp - 9, warp - 9);
      if (warp == 14) l2_prefetch((const char*)p.wqkv + 224 * 3072 + cta * 6912, 6912);
      else l2_prefetch((const char*)p.x + (size_t)cta * 16384, 16384);
    }
    __syncwarp();
    float D[2][3][4];
#pragma unroll
    for (int t = 0; t < 6; ++t) D[t / 3][t % 3][0] = D[t / 3][t % 3][1] = D[t / 3][t % 3][2] = D[t / 3][t % 3][3] = 0.f;
    auto contract = [&](int t0, int nt) {
      __syncwarp();
#pragma unroll
      for (int k = 0; k < 4; ++k) {
        uint32_t b[4];
        ldsm_x4(b, ldb + (((2 * k + ((lane >> 3) & 1)) ^ (lane & 7)) << 4));
#pragma unroll
        for (int h = 0; h < 2; ++h) {
          mma_f16(D[h][t0], XA[h][k], b[0], b[1]);
          if (nt == 2) mma_f16(D[h][t0 + 1], XA[h][k], b[2], b[3]);
        }
      }
      __syncwarp();
    };
    const HMul c1 = mk_mul(e1.re, -e1.im), c2 = mk_mul(e2.re, -e2.im), c4 = mk_mul(e4.re, -e4.im);
    const HMul c256 = mk_mul(e256.re, -e256.im), c512 = mk_mul(e512.re, -e512.im), c768 = mk_mul(e768.re, -e768.im);
    const HMul c1024 = mk_mul(e1024.re, -e1024.im);
    uint32_t W[8];
    W[0] = pack_f16(wr * sc, -wi * sc);
    W[1] = hcmul(W[0], c1); W[2] = hcmul(W[0], c2); W[3] = hcmul(W[1], c2);
    W[4] = hcmul(W[0], c4); W[5] = hcmul(W[1], c4); W[6] = hcmul(W[2], c4); W[7] = hcmul(W[3], c4);
#pragma unroll
    for (int i = 0; i < 8; ++i) put(i, W[i]);
#pragma unroll
    for (int i = 0; i < 4; ++i) put(8 + i, hcmul(W[2 * i], c256));
    put(12, hcmul(W[0], c512)); put(13, hcmul(W[4], c512)); put(14, hcmul(W[0], c768)); put(15, hcmul(W[4], c768));
    contract(0, 2);
    const uint32_t v0 = hcmul(W[0], c1024);
    put(0, v0); put(1, hcmul(v0, c256)); put(2, hcmul(v0, c512)); put(3, hcmul(v0, c768)); put(4, hcmul(v0, c1024));
    contract(2, 1);
    const uint32_t a = tb + (g * 24 + 2 * q) * 4;
#pragma unroll
    for (int t = 0; t < 6; ++t) {
      const float(&d)[4] = D[t / 3][t % 3];
      sts_f32x2(a + (t / 3) * 1536 + (t % 3) * 32, d[0] * inv, d[1] * inv);
      sts_f32x2(a + (t / 3) * 1536 + (t % 3) * 32 + 768, d[2] * inv, d[3] * inv);
    }
    if (mz > 0.f) {
      __syncwarp();
#pragma unroll 1
      for (int i = lane; i < 768; i += 32) {
        const int r = i / 24, y = i - 24 * r;
        sts_f32(tb + i * 4, lds_f32(tb + i * 4) * ex2(mz * 1.4426950408889634f * (koff(y) + 8 * r)));
      }
    }
  }
  if (tid == 0) TS(2);
  if (warp < 12) cluster_wait();
  if (tid == 0) TS(32);
  __syncthreads();
  if (tid == 0) TSD(33);

  if (warp < 4) {
    asm volatile("setmaxnreg.inc.sync.aligned.u32 152;");
    if (tid == 0) TS(34);
    const int d = cta * 4 + warp;
    const uint32_t vv = sb + SM_VV + warp * VV_BYTES;
    const uint32_t ub = sb + SM_U + warp * U_BYTES;
    const uint32_t pb = sb + SM_P + warp * P_BYTES;
    const float dskip = bf_lo(r_dskip);
#pragma unroll 1
    for (int pass = 0; pass < 2; ++pass) {
      if (pass == 1) {
        const uint32_t kf = vv;
#pragma unroll 2
        for (int i = 0; i < 6; ++i) {
          const uint32_t a = kf + (i * 32 + lane) * 16;
          const uint4 x0 = lds128(a), x1 = lds128(a + KG_BYTES), x2 = lds128(a + 2 * KG_BYTES), x3 = lds128(a + 3 * KG_BYTES);
          auto s4 = [](uint32_t a0, uint32_t a1, uint32_t a2, uint32_t a3) {
            return __float_as_uint((__uint_as_float(a0) + __uint_as_float(a1)) + (__uint_as_float(a2) + __uint_as_float(a3)));
          };
          sts128(a, s4(x0.x, x1.x, x2.x, x3.x), s4(x0.y, x1.y, x2.y, x3.y), s4(x0.z, x1.z, x2.z, x3.z), s4(x0.w, x1.w, x2.w, x3.w));
        }
        __syncwarp();
        if (lane == 0) {
          sts_f32(kf + SL_ZERO * 4, 0.f);
          sts_f32(kf + SL_510 * 4, lds_f32(kf + kidx_c(510) * 4) - lds_f32(kf + kidx_c(512) * 4));
          sts_f32(kf + SL_0 * 4, lds_f32(kf) + dskip);
        }
        __syncwarp();
        if (tid == 0) TS(36);
        mbar_wait_long(BAR(B_PFREE), 0);
        if (tid == 0) TS(37);
        {
          float prev = 0.f;
#pragma unroll 1
          for (int i0 = 0; i0 < 16; i0 += 4) {
            uint32_t e[4];
            float a[4], b[4];
#pragma unroll
            for (int i = 0; i < 4; ++i) e[i] = lds32(sb + SM_PTAB + ((i0 + i) * 32 + lane) * 4);
#pragma unroll
            for (int i = 0; i < 4; ++i) { a[i] = lds_f32(kf + (e[i] & 0xffff)); b[i] = lds_f32(kf + (e[i] >> 16)); }
#pragma unroll
            for (int i = 0; i < 4; ++i) {
              const uint32_t w = pb + (31 * lane + 2 * (i0 + i)) * 4;
              if (i0 + i > 0) sts32(w - 4, pack_bf16(a[i], prev));
              sts32(w, pack_bf16(b[i], a[i]));
              prev = b[i];
            }
          }
        }
        __syncwarp();
        if (lane == 0) TS(4);
        bar_sync(4, 512);
        mbar_wait_long(BAR(B_UCH + warp), 0);
        if (lane == 0) TS(7);
        conv_half<8>(ub, pb, vv, lane, (uint32_t)cta >> 20, warp, p.yT + (size_t)d * 2048);
        if (lane == 0) TS(8);
        if (lane < 2) mbar_arrive_cluster(BAR(B_CONVD), lane);
        bar_arrive(3, 512);
        if (elect_one()) {
          bulk_store(p.yT + (size_t)d * 2048 + 1024, pb + 2048, 2048);
          bulk_commit();
          bulk_wait0();
          red_relaxed_add(&g_cnt[(C_Y + (cta >> 4)) * 32], 1);
          TS(9);
        }
        bar_sync(2, 256);
        if (warp == 0 && elect_one()) {
          wait_counter(&g_cnt[(C_Y + tj) * 32], (epoch + 1) * 128);
          TS(28);
          mbar_expect_tx(BAR(B_TILE), 16384);
          tma_load_2d(sb + SM_U, &maps.yT, ti * 128, tj * 64, BAR(B_TILE));
          tma_load_2d(sb + SM_U + 8192, &maps.yT, ti * 128 + 64, tj * 64, BAR(B_TILE));
        }
        __syncwarp();
      }
      mbar_wait_long(BAR(B_TILE), pass);
      if (lane == 0) TS(26 + 3 * pass);
      {
        const int m = lane >> 3, r = lane & 7;
#pragma unroll 2
        for (int it = 0; it < 8; ++it) {
          const int tb = warp * 4 + (it >> 1), cb = (it & 1) * 4 + m;
          const uint32_t at = (tb * 8 + r) * 128 + ((cb ^ r) << 4);
          const uint32_t ac = (tb >> 3) * 8192 + (cb * 8 + r) * 128 + (((tb & 7) ^ (pass ? 0 : tb >> 3) ^ r) << 4);
          uint32_t v[4];
          ldsm_x4_t(v, sb + SM_U + (pass ? ac : at));
          stsm_x4(sb + SM_P + (pass ? at : ac), v[0], v[1], v[2], v[3]);
        }
      }
      if (pass == 0 && tid == 0) TS(35);
      fence_async_smem();
      if (pass == 0) {
        bar_arrive(6, 160);
      } else {
        bar_sync(7, 128);
        if (warp == 0 && elect_one()) {
          tma_store_2d(&maps.out, sb + SM_P, 64 * tj, 128 * ti);
          bulk_commit();
          bulk_wait_read0();
          TS(30);
        }
      }
    }
  } else if (warp < 12) {
    asm volatile("setmaxnreg.inc.sync.aligned.u32 160;");
    const int w8 = warp - 4;
    const int row = w8 * 16 + (lane & 7) + (((lane >> 3) & 1) << 3);
    {
      float acc[96];
#pragma unroll 1
      for (int ks = 0, s = 0, ph = 0; ks < 16; ++ks) {
        mbar_wait(BAR(B_FULL + s), ph);
        if (tid == 128 && !(ks & 1)) TSR(16, ks == 0 ? 16 : 9 + (ks >> 1) + (ks > 12 ? 43 : 0));
        const uint32_t st = sb + s * STG_BYTES;
        const uint32_t da = mkdesc(st + STG_X + (w8 >> 2) * 4096, 16);
        const uint32_t db = mkdesc(st + STG_W, 2048);
        wg_fence();
        wgmma_n192(acc, da, db, ks != 0);
        wgmma_n192(acc, da + 2, db + 384, 1);
        wg_commit();
        const uint32_t eprev = BAR(B_EMPTY + (s == 0 ? NSTG - 1 : s - 1));
        if (++s == NSTG) { s = 0; ph ^= 1; }
        if (ks > 0) {
          wg_wait<1>();
          if (lane < 2) mbar_arrive_cluster(eprev, lane);
        }
      }
      wg_wait<0>();
      if (tid == 128) TS(17);
      bar_sync(1, 256);
#pragma unroll
      for (int i = 0; i < 24; i += 2)
        stsm_x4(sb + SM_QS + row * 128 + (i >> 3) * 16384 + ((((i & 7) + (lane >> 4)) ^ (row & 7)) << 4),
                pack_bf16(acc[4 * i], acc[4 * i + 1]), pack_bf16(acc[4 * i + 2], acc[4 * i + 3]),
                pack_bf16(acc[4 * i + 4], acc[4 * i + 5]), pack_bf16(acc[4 * i + 6], acc[4 * i + 7]));
    }
    asm volatile("setmaxnreg.dec.sync.aligned.u32 112;");
    __syncwarp();
    float* kvg = &g_kv[epoch & 1][tj][0];
#pragma unroll 1
    for (int part = 1; part >= 0; --part) {
      const uint32_t pa = sb + SM_QS + part * 16384 + w8 * 2048 + lane * 16;
#pragma unroll 1
      for (int it = 0; it < 4; ++it) {
        uint4 t = lds128(pa + it * 512);
        uint32_t* tw = &t.x;
#pragma unroll
        for (int j = 0; j < 4; ++j) {
          const uint32_t x = tw[j];
          const __nv_bfloat162 xb = *reinterpret_cast<const __nv_bfloat162*>(&x);
          const uint32_t e = pack_bf16(ex2(bf_lo(x) * 1.4426950408889634f), ex2(bf_hi(x) * 1.4426950408889634f));
          const uint32_t m = __hgt2_mask(xb, __floats2bfloat162_rn(0.f, 0.f));
          tw[j] = badd((badd(x, 0x3f803f80u) & m) | (e & ~m), 0x35863586u);
        }
        sts128(pa + it * 512, t.x, t.y, t.z, t.w);
      }
      if (part == 1) {
        if (tid == 128) TS(53);
        bar_sync(1, 256);
        const int hh = w8 >> 1, dtile = w8 & 1;
        float kv[4] = {0.f, 0.f, 0.f, 0.f}, zz[4] = {0.f, 0.f, 0.f, 0.f};
        const int m = lane >> 3;
        const uint32_t aa = sb + SM_VS + ((lane & 7) + ((m >> 1) << 3)) * 128 + (((2 * hh + (m & 1)) ^ (lane & 7)) << 4);
        const uint32_t ab = sb + SM_PK + (lane & 15) * 128 + (((2 * hh + dtile) ^ (lane & 7)) << 4);
#pragma unroll 2
        for (int ks = 0; ks < 8; ++ks) {
          uint32_t a[4], b0, b1;
          ldsm_x4_t(a, aa + ks * 2048);
          ldsm_x2_t(b0, b1, ab + ks * 2048);
          mma_bf16(kv, a[0], a[1], a[2], a[3], b0, b1);
          mma_bf16(zz, 0x3f803f80u, 0x3f803f80u, 0x3f803f80u, 0x3f803f80u, b0, b1);
        }
        const uint32_t kp = sb + SM_KV + hh * 1088;
        sts128(kp + dtile * 512 + lane * 16, __float_as_uint(kv[0]), __float_as_uint(kv[1]), __float_as_uint(kv[2]),
               __float_as_uint(kv[3]));
        if (g == 0) sts_f32x2(kp + 1024 + dtile * 32 + q * 8, zz[0], zz[1]);
        fence_async_smem();
        __syncwarp();
        if (lane == 0) mbar_arrive(BAR(B_KVP));
        bar_arrive(4, 512);
        if (tid == 128) TS(55);
        if (warp == 4 && elect_one()) {
          mbar_wait(BAR(B_KVP), 0);
          bulk_reduce_add_f32(kvg, sb + SM_KV, 4352);
          bulk_commit();
        }
        __syncwarp();
      }
    }
    if (tid == 128) TS(56);
    if (warp == 4 && elect_one()) {
      bulk_wait0();
      red_relaxed_add(&g_cnt[(C_KV + tj) * 32], 1);
      TS(18);
      wait_counter(&g_cnt[(C_KV + tj) * 32], (epoch + 1) * 16);
      mbar_expect_tx(BAR(B_KVF), 4352);
      bulk_load(sb + SM_KV, kvg, 4352, BAR(B_KVF));
    }
    __syncwarp();
    mbar_wait_long(BAR(B_KVF), 0);
    if (tid == 128) TS(19);
#pragma unroll 1
    for (int h = 0; h < 4; ++h) {
      uint32_t a[4];
      const uint32_t qa = sb + SM_QS + row * 128 + (((2 * h + (lane >> 4)) ^ (row & 7)) << 4);
      ldsm_x4(a, qa);
      const uint32_t kp = sb + SM_KV + h * 1088;
      const uint4 k0 = lds128(kp + lane * 16), k1 = lds128(kp + 512 + lane * 16);
      const uint32_t za = kp + 1024 + q * 8;
      auto pk2 = [](uint32_t x, uint32_t y) { return pack_bf16(__uint_as_float(x), __uint_as_float(y)); };
      float n0[4] = {0.f, 0.f, 0.f, 0.f}, n1[4] = {0.f, 0.f, 0.f, 0.f}, dn[4] = {0.f, 0.f, 0.f, 0.f};
      mma_bf16(n0, a[0], a[1], a[2], a[3], pk2(k0.x, k0.y), pk2(k1.x, k1.y));
      mma_bf16(n1, a[0], a[1], a[2], a[3], pk2(k0.z, k0.w), pk2(k1.z, k1.w));
      mma_bf16(dn, a[0], a[1], a[2], a[3], pack_bf16(lds_f32(za), lds_f32(za + 4)), pack_bf16(lds_f32(za + 32), lds_f32(za + 36)));
      const uint32_t dd = pack_bf16(dn[0], dn[2]);
      const uint32_t d2 = pack_bf16(bf_lo(dd) + 1e-6f, bf_hi(dd) + 1e-6f);
      const float r0 = rcp(bf_lo(d2)), r1 = rcp(bf_hi(d2));
      const uint32_t x0 = pack_bf16(n0[0], n0[1]), x1 = pack_bf16(n0[2], n0[3]);
      const uint32_t x2 = pack_bf16(n1[0], n1[1]), x3 = pack_bf16(n1[2], n1[3]);
      stsm_x4(qa, pack_bf16(bf_lo(x0) * r0, bf_hi(x0) * r0), pack_bf16(bf_lo(x1) * r1, bf_hi(x1) * r1),
              pack_bf16(bf_lo(x2) * r0, bf_hi(x2) * r0), pack_bf16(bf_lo(x3) * r1, bf_hi(x3) * r1));
    }
    fence_async_smem();
    bar_sync(1, 256);
    if (tid == 128) TS(57);
    if (warp == 4 && elect_one()) {
      tma_store_2d(&maps.o, sb + SM_QS, tj * 64, ti * 128);
      tma_store_2d(&maps.o, sb + SM_QS + 8192, tj * 64, ti * 128 + 64);
      bulk_commit();
      bulk_wait0();
      red_relaxed_add(&g_cnt[(C_O + ti) * 32], 1);
      TS(20);
      mbar_arrive_cluster(BAR(B_SLOT), 0);
      mbar_arrive_cluster(BAR(B_SLOT), 1);
      wait_counter(&g_cnt[(C_O + pi) * 32], (epoch + 1) * 8);
      if (cta == 0) g_epoch = epoch + 1;
      mbar_wait(BAR(B_SLOT), 0);
      TS(21);
#pragma unroll 1
      for (int c = 0; c < 4; ++c) {
        mbar_expect_tx(BAR(B_RF + c), 16384);
        tma_load_2d_mc(sb + SM_QS + c * 16384 + rank * 8192, &maps.o, c * 64, pi * 128 + rank * 64, BAR(B_RF + c), 3);
      }
      mbar_arrive(BAR(B_OST));
    }
    __syncwarp();
    mbar_wait_long(BAR(B_WO), 0);
    bar_sync(3, 512);
    {
      float o[32];
#pragma unroll 1
      for (int c = 0; c < 8; ++c) {
        mbar_wait_long(BAR(B_RF + c), 0);
        if (tid == 128) TSR(22, c == 0 ? 22 : 43 + c);
        const uint32_t slot = c < 4 ? SM_QS + c * 16384 : c < 7 ? SM_VV + (c - 4) * 16384 : SM_QS;
        const uint32_t da = mkdesc(sb + slot + (w8 >> 2) * 8192, 16);
        const uint32_t db = mkdesc(sb + SM_WO + c * 8192, 8192);
        wg_fence();
#pragma unroll
        for (int k = 0; k < 4; ++k) wgmma_n64(o, da + 2 * k, db + 128 * k, (c | k) != 0);
        wg_commit();
        if (c == 1) {
          wg_wait<1>();
          if (lane < 2) mbar_arrive_cluster(BAR(B_RE), lane);
        }
      }
      wg_wait<0>();
      if (tid == 128) TS(51);
      bar_sync(1, 256);
#pragma unroll
      for (int i = 0; i < 8; i += 2)
        stsm_x4(sb + SM_BOUT + row * 128 + (((i + (lane >> 4)) ^ (row & 7)) << 4), pack_bf16(o[4 * i], o[4 * i + 1]),
                pack_bf16(o[4 * i + 2], o[4 * i + 3]), pack_bf16(o[4 * i + 4], o[4 * i + 5]), pack_bf16(o[4 * i + 6], o[4 * i + 7]));
      fence_async_smem();
      bar_sync(1, 256);
      if (tid == 128) TS(52);
      if (warp == 4 && elect_one()) {
        tma_store_2d(&maps.out, sb + SM_BOUT, 512 + 64 * pj, 128 * pi);
        bulk_commit();
        bulk_wait_read0();
        TS(23);
      }
    }
  } else {
    asm volatile("setmaxnreg.dec.sync.aligned.u32 40;");
    if (warp == 12) {
      if (elect_one()) {
#pragma unroll 1
        for (int ks = NSTG, s = 0, ph = 0; ks < 16; ++ks) {
          mbar_wait(BAR(B_EMPTY + s), ph);
          issue_stage(ks, s);
          if (ks == NSTG) l2_prefetch((const char*)p.wo + (size_t)cta * 4096, 4096);
          if (++s == NSTG) { s = 0; ph ^= 1; }
        }
        mbar_wait(BAR(B_EMPTY + 6), 1);
        mbar_expect_tx(BAR(B_WO), 65536);
        tma_load_2d(sb + SM_WO, &maps.wo, pj * 64, 0, BAR(B_WO));
        tma_load_2d(sb + SM_WO + 32768, &maps.wo, pj * 64, 256, BAR(B_WO));
      }
    } else if (warp == 13) {
      bar_sync(6, 160);
      sts128(sb + SM_U + (lane >> 4) * U_BYTES + (lane & 15) * 16, 0, 0, 0, 0);
      sts128(sb + SM_U + (2 + (lane >> 4)) * U_BYTES + (lane & 15) * 16, 0, 0, 0, 0);
      __syncwarp();
      if (elect_one()) {
        tma_store_2d(&maps.uT, sb + SM_P, ti * 128, tj * 64);
        tma_store_2d(&maps.uT, sb + SM_P + 8192, ti * 128 + 64, tj * 64);
        bulk_commit();
        bulk_wait_read0();
        mbar_arrive(BAR(B_PFREE));
        bulk_wait0();
        red_relaxed_add(&g_cnt[(C_U + tj) * 32], 1);
        TS(27);
        wait_counter(&g_cnt[(C_U + (cta >> 4)) * 32], (epoch + 1) * 16);
#pragma unroll 1
        for (int c = 0; c < 4; ++c) {
          mbar_expect_tx(BAR(B_UCH + c), 4096);
          bulk_load(sb + SM_U + c * U_BYTES + 256, p.uT + (size_t)(cta * 4 + c) * 2048, 4096, BAR(B_UCH + c));
        }
        TS(3);
      }
      __syncwarp();
      if (ti == 0) {
        float4* z = (float4*)&g_kv[(epoch & 1) ^ 1][tj][0];
#pragma unroll 1
        for (int i = lane; i < 272; i += 32) z[i] = make_float4(0.f, 0.f, 0.f, 0.f);
      }
    }
    bar_sync(4, 512);
    asm volatile("setmaxnreg.inc.sync.aligned.u32 136;");
    {
      const int ch = warp - 12, d = cta * 4 + ch;
      const uint32_t ub = sb + SM_U + ch * U_BYTES, pb = sb + SM_P + ch * P_BYTES, vb = sb + SM_VV + ch * VV_BYTES;
      mbar_wait_long(BAR(B_UCH + ch), 0);
      auto swz = [](int k, int pad) { const int r = (k >> 1) + pad; return (uint32_t)(r * 32 + (((k & 1) ^ ((r >> 2) & 1)) << 4)); };
      uint32_t a0 = ub + swz(lane - 3, 8), a1 = ub + swz(lane - 2, 8), a2 = ub + swz(lane - 1, 8), aw = vb + swz(lane - 2, PADV);
      if (lane < 16) {
        const uint32_t az = vb + swz(lane - 18, PADV);
        sts128(az + VV_U3, 0, 0, 0, 0); sts128(az + VV_U5, 0, 0, 0, 0); sts128(az + VV_U7, 0, 0, 0, 0); sts128(az + VV_U9, 0, 0, 0, 0);
      }
#pragma unroll 1
      for (int k = lane - 2; k - lane < 208; k += 32, a0 += 512, a1 += 512, a2 += 512, aw += 512) {
        const uint4 t0 = lds128(a0), t1 = lds128(a1), t2 = lds128(a2);
        const uint32_t E[12] = {t0.x, t0.y, t0.z, t0.w, t1.x, t1.y, t1.z, t1.w, t2.x, t2.y, t2.z, t2.w};
        uint32_t O[8];
#pragma unroll
        for (int j = 0; j < 8; ++j) O[j] = __byte_perm(E[j + 1], E[j + 2], 0x5432);
        uint32_t s3[6], s5[4], s7[4], s9[4];
#pragma unroll
        for (int j = 0; j < 6; ++j) s3[j] = badd(badd(O[j], O[j + 1]), E[j + 2]);
#pragma unroll
        for (int j = 0; j < 4; ++j) {
          s5[j] = badd(s3[j + 2], badd(E[j + 3], E[j + 5]));
          s7[j] = badd(s5[j], badd(O[j + 1], O[j + 4]));
          s9[j] = badd(s7[j], badd(E[j + 2], E[j + 6]));
        }
        if (k < 208) { sts128(aw + VV_U3, s3[0], s3[1], s3[2], s3[3]); sts128(aw + VV_U5, s5[0], s5[1], s5[2], s5[3]); }
        if (k < 144) { sts128(aw + VV_U7, s7[0], s7[1], s7[2], s7[3]); sts128(aw + VV_U9, s9[0], s9[1], s9[2], s9[3]); }
      }
      __syncwarp();
      if (tid == 416) TS(6);
      bar_arrive(8 + ch, 64);
      conv_half<0>(ub, pb, vb, lane, (uint32_t)cta >> 20, ch, p.yT + (size_t)d * 2048);
      if (tid == 416) TS(40);
      if (lane < 2) mbar_arrive_cluster(BAR(B_CONVD), lane);
      bar_arrive(3, 512);
      if (elect_one()) {
        bulk_store(p.yT + (size_t)d * 2048, pb, 2048);
        bulk_commit();
        bulk_wait0();
        red_relaxed_add(&g_cnt[(C_Y + (cta >> 4)) * 32], 1);
      }
      __syncwarp();
      bar_arrive(2, 256);
      if (warp == 12 && elect_one()) {
        mbar_wait_long(BAR(B_OST), 0);
        mbar_wait_long(BAR(B_CONVD), 0);
#pragma unroll 1
        for (int c = 4; c < 8; ++c) {
          if (c == 7) mbar_wait(BAR(B_RE), 0);
          const uint32_t slot = c < 7 ? SM_VV + (c - 4) * 16384 : SM_QS;
          mbar_expect_tx(BAR(B_RF + c), 16384);
          tma_load_2d_mc(sb + slot + rank * 8192, &maps.o, c * 64, pi * 128 + rank * 64, BAR(B_RF + c), 3);
        }
      }
    }
  }
  __syncwarp();
  cluster_arrive();
  cluster_wait();
  if (tid == 0) TS(31);
#undef BAR
}

typedef CUresult (*EncodeFn)(CUtensorMap*, CUtensorMapDataType, cuuint32_t, void*, const cuuint64_t*, const cuuint64_t*,
                             const cuuint32_t*, const cuuint32_t*, CUtensorMapInterleave, CUtensorMapSwizzle,
                             CUtensorMapL2promotion, CUtensorMapFloatOOBfill);

static void make_map(EncodeFn enc, CUtensorMap* m, const void* base, uint64_t inner, uint64_t outer, uint32_t box_in,
                     uint32_t box_out, CUtensorMapSwizzle swz = CU_TENSOR_MAP_SWIZZLE_128B) {
  cuuint64_t gd[2] = {inner, outer};
  cuuint64_t gs[1] = {inner * 2};
  cuuint32_t bd[2] = {box_in, box_out};
  cuuint32_t es[2] = {1, 1};
  enc(m, CU_TENSOR_MAP_DATA_TYPE_BFLOAT16, 2, const_cast<void*>(base), gd, gs, bd, es, CU_TENSOR_MAP_INTERLEAVE_NONE,
      swz, CU_TENSOR_MAP_L2_PROMOTION_L2_128B, CU_TENSOR_MAP_FLOAT_OOB_FILL_NONE);
}

}

extern "C" void kernel_launch(void* const* d_in, const int* in_sizes, int n_in, void* d_out, int out_size) {
  using namespace s4la;
  (void)in_sizes; (void)n_in; (void)out_size;
  static EncodeFn enc = nullptr;
  static void *uT = nullptr, *yT = nullptr, *oS = nullptr;
  if (!enc) {
    void* fn = nullptr;
    cudaDriverEntryPointQueryResult qr;
    cudaGetDriverEntryPoint("cuTensorMapEncodeTiled", &fn, cudaEnableDefault, &qr);
    enc = (EncodeFn)fn;
    cudaGetSymbolAddress(&uT, g_uT);
    cudaGetSymbolAddress(&yT, g_yT);
    cudaGetSymbolAddress(&oS, g_o);
    cudaFuncSetAttribute(fused_kernel, cudaFuncAttributeMaxDynamicSharedMemorySize, SM_TOTAL);
  }
  const __nv_bfloat16* const* in = (const __nv_bfloat16* const*)d_in;
  Maps maps;
  make_map(enc, &maps.x, in[9], 512, 2048, 32, 128, CU_TENSOR_MAP_SWIZZLE_64B);
  {
    cuuint64_t gd[3] = {512, 512, 3};
    cuuint64_t gs[2] = {3072, 1024};
    cuuint32_t bd[3] = {64, 16, 3};
    cuuint32_t es[3] = {1, 1, 1};
    enc(&maps.w, CU_TENSOR_MAP_DATA_TYPE_BFLOAT16, 3, const_cast<__nv_bfloat16*>(in[10]), gd, gs, bd, es,
        CU_TENSOR_MAP_INTERLEAVE_NONE, CU_TENSOR_MAP_SWIZZLE_128B, CU_TENSOR_MAP_L2_PROMOTION_L2_128B,
        CU_TENSOR_MAP_FLOAT_OOB_FILL_NONE);
  }
  make_map(enc, &maps.wo, in[11], 512, 512, 64, 256);
  make_map(enc, &maps.u, in[0], 512, 2048, 64, 128);
  make_map(enc, &maps.uT, uT, 2048, 512, 64, 64);
  make_map(enc, &maps.yT, yT, 2048, 512, 64, 64);
  make_map(enc, &maps.o, oS, 512, 2048, 64, 64);
  make_map(enc, &maps.out, d_out, 1024, 2048, 64, 128);
  Ptrs p;
  p.A_re = in[1]; p.A_im = in[2]; p.B_re = in[3]; p.B_im = in[4]; p.C_re = in[5]; p.C_im = in[6];
  p.log_dt = in[7]; p.Dskip = in[8]; p.x = in[9]; p.wqkv = in[10]; p.wo = in[11];
  p.uT = (__nv_bfloat16*)uT; p.yT = (__nv_bfloat16*)yT;
  fused_kernel<<<NCTA, NTHREADS, SM_TOTAL, cudaStreamPerThread>>>(maps, p);
}
```

```cpp
#include <cuda_runtime.h>
#include <cuda_bf16.h>
#include <cuda_fp16.h>
#include <cuda.h>
#include <stdint.h>

#define DEVI __device__ __forceinline__

namespace s4la {

constexpr int NTHREADS = 512;
constexpr int NCTA = 128;

constexpr int NSTG = 7;
constexpr uint32_t STG_BYTES = 20480, STG_X = 0, STG_W = 8192;
constexpr uint32_t SM_QS = 0;
constexpr uint32_t SM_PK = SM_QS + 16384, SM_VS = SM_QS + 32768;
constexpr uint32_t SM_WO = 65536;
constexpr uint32_t SM_KV = 131072;
constexpr uint32_t SM_BOUT = 16384;
constexpr uint32_t SM_U = 143360, U_BYTES = 4352;
constexpr uint32_t SM_P = 160768, P_BYTES = 4096;
constexpr uint32_t SM_VV = 177152, VV_BYTES = 12800;
constexpr uint32_t VV_U5 = 0, VV_U3 = 3712, VV_U9 = 7424, VV_U7 = 10112;
constexpr uint32_t KG_BYTES = 3200;
constexpr uint32_t SM_BAR = SM_VV + 4 * VV_BYTES;
constexpr uint32_t SM_PTAB = SM_BAR + 320;
constexpr uint32_t SM_TOTAL = SM_PTAB + 2048;
static_assert(SM_TOTAL <= 232448, "shared memory");
constexpr int PADV = 12;

enum { B_FULL = 0, B_EMPTY = 7, B_TILE = 14, B_UCH = 15, B_KVP = 19, B_KVF = 20, B_OST = 21, B_RF = 22, B_WO = 30, B_RE = 31, B_PFREE = 32, B_CONVD = 33, B_SLOT = 34, B_COUNT = 35 };
__host__ __device__ constexpr int bar_count(int i) {
  return (i >= B_EMPTY && i < B_TILE) ? 16 : i == B_KVP ? 8 : (i == B_RE || i == B_CONVD) ? 16 : i == B_SLOT ? 2 : 1;
}

constexpr int PD_OFF = 0, P2_OFF = 544, P3_OFF = 768;

constexpr int SL_K2048 = 20, SL_ZERO = 21, SL_510 = 22, SL_0 = 23;
__host__ __device__ constexpr int koff(int y) {
  return y < 8 ? y : y < 12 ? 256 + 2 * (y - 8) : y < 16 ? 512 + 256 * ((y - 12) >> 1) + 4 * (y & 1) : 1024 + 256 * (y - 16);
}
__host__ __device__ constexpr int kidx_c(int l) {
  const int y = l < 256 ? (l & 7) : l < 512 ? 8 + ((l & 7) >> 1) : l < 1024 ? 12 + (((l - 512) >> 8) << 1) + ((l >> 2) & 1)
                                                                            : 16 + ((l - 1024) >> 8);
  return ((l >> 3) & 31) * 24 + y;
}
constexpr int slot_direct(int l) {
  if (l < 0 || l > 510) return SL_ZERO;
  if (l == 510) return SL_510;
  if (l == 0) return SL_0;
  return kidx_c(l < 256 ? l : ((l + ((l >> 1) & 1)) & ~1));
}
constexpr int slot_seg2(int v, int k) { return (k >= 32 && k < 64) ? kidx_c(16 * k + 4 * v) : SL_ZERO; }
constexpr int slot_seg3(int pi, int k) {
  return (k >= 64 && k < 128) ? kidx_c(16 * k + 8 * pi) : ((k == 128 && pi == 0) ? SL_K2048 : SL_ZERO);
}
constexpr int slot_word(int w) {
  return w < 0 ? SL_ZERO : w < 544 ? slot_direct(w - 16) : w < 768 ? slot_seg2((w - 544) / 56, 16 + (w - 544) % 56)
       : w < 944 ? slot_seg3((w - 768) / 88, 48 + (w - 768) % 88) : SL_ZERO;
}
struct PTab { uint32_t v[512]; };
constexpr PTab make_ptab() {
  PTab t{};
  for (int lane = 0; lane < 32; ++lane)
    for (int i = 0; i < 16; ++i)
      t.v[i * 32 + lane] = (slot_word(31 * lane - 1 + 2 * i) * 4) | ((slot_word(31 * lane + 2 * i) * 4) << 16);
  return t;
}
__device__ const PTab g_ptab = make_ptab();

__device__ __nv_bfloat16 g_uT[512 * 2048];
__device__ __nv_bfloat16 g_yT[512 * 2048];
__device__ __nv_bfloat16 g_o[2048 * 512];
__device__ float g_kv[2][8][4 * 272];
__device__ unsigned g_cnt[64 * 32];
__device__ unsigned g_epoch;
#define TS(slot) do { } while (0)
#define TSR(on, slot) do { } while (0)
#define TSD(slot) do { } while (0)
enum { C_U = 0, C_KV = 8, C_O = 16, C_Y = 32 };

struct Maps {
  CUtensorMap x, w, wo, u, uT, yT, o, out;
};
struct Ptrs {
  const __nv_bfloat16 *A_re, *A_im, *B_re, *B_im, *C_re, *C_im, *log_dt, *Dskip;
  const __nv_bfloat16 *x, *wqkv, *wo;
  __nv_bfloat16 *uT, *yT;
};

DEVI uint32_t s2u(const void* p) { return (uint32_t)__cvta_generic_to_shared(p); }
DEVI void mbar_init(uint32_t b, uint32_t c) { asm volatile("mbarrier.init.shared::cta.b64 [%0], %1;" ::"r"(b), "r"(c) : "memory"); }
DEVI void mbar_expect_tx(uint32_t b, uint32_t bytes) {
  asm volatile("mbarrier.arrive.expect_tx.shared::cta.b64 _, [%0], %1;" ::"r"(b), "r"(bytes) : "memory");
}
DEVI void mbar_arrive(uint32_t b) { asm volatile("mbarrier.arrive.shared::cta.b64 _, [%0];" ::"r"(b) : "memory"); }
DEVI void mbar_arrive_cluster(uint32_t b, uint32_t cta) {
  asm volatile("{\n.reg .b32 r;\nmapa.shared::cluster.u32 r, %0, %1;\nmbarrier.arrive.shared::cluster.b64 _, [r];\n}"
               ::"r"(b), "r"(cta) : "memory");
}
DEVI void mbar_wait(uint32_t b, uint32_t parity) {
  asm volatile("{\n.reg .pred p;\nLAB_WAIT:\nmbarrier.try_wait.parity.shared::cta.b64 p, [%0], %1;\n@!p bra LAB_WAIT;\n}"
               ::"r"(b), "r"(parity) : "memory");
}
DEVI void mbar_wait_long(uint32_t b, uint32_t parity) {
  asm volatile("{\n.reg .pred p;\nLAB_WAIT:\nmbarrier.try_wait.parity.shared::cta.b64 p, [%0], %1, 0x989680;\n@!p bra LAB_WAIT;\n}"
               ::"r"(b), "r"(parity) : "memory");
}
DEVI void bar_sync(int id, int n) { asm volatile("bar.sync %0, %1;" ::"r"(id), "r"(n) : "memory"); }
DEVI void bar_arrive(int id, int n) { asm volatile("bar.arrive %0, %1;" ::"r"(id), "r"(n) : "memory"); }
DEVI void fence_async_smem() { asm volatile("fence.proxy.async.shared::cta;" ::: "memory"); }
DEVI void fence_async_all() { asm volatile("fence.proxy.async;" ::: "memory"); }
DEVI void cluster_arrive() { asm volatile("barrier.cluster.arrive.relaxed.aligned;" ::: "memory"); }
DEVI void cluster_wait() { asm volatile("barrier.cluster.wait.aligned;" ::: "memory"); }

DEVI void tma_load_2d(uint32_t dst, const CUtensorMap* m, int c0, int c1, uint32_t bar) {
  asm volatile("cp.async.bulk.tensor.2d.shared::cluster.global.mbarrier::complete_tx::bytes [%0], [%1, {%3, %4}], [%2];"
               ::"r"(dst), "l"(m), "r"(bar), "r"(c0), "r"(c1) : "memory");
}
DEVI void tma_load_2d_mc(uint32_t dst, const CUtensorMap* m, int c0, int c1, uint32_t bar, uint16_t mask) {
  asm volatile("cp.async.bulk.tensor.2d.shared::cluster.global.mbarrier::complete_tx::bytes.multicast::cluster [%0], [%1, {%3, %4}], [%2], %5;"
               ::"r"(dst), "l"(m), "r"(bar), "r"(c0), "r"(c1), "h"(mask) : "memory");
}
DEVI void tma_load_3d_mc(uint32_t dst, const CUtensorMap* m, int c0, int c1, int c2, uint32_t bar, uint16_t mask) {
  asm volatile("cp.async.bulk.tensor.3d.shared::cluster.global.mbarrier::complete_tx::bytes.multicast::cluster [%0], [%1, {%3, %4, %5}], [%2], %6;"
               ::"r"(dst), "l"(m), "r"(bar), "r"(c0), "r"(c1), "r"(c2), "h"(mask) : "memory");
}
DEVI void tma_store_2d(const CUtensorMap* m, uint32_t src, int c0, int c1) {
  asm volatile("cp.async.bulk.tensor.2d.global.shared::cta.bulk_group [%0, {%2, %3}], [%1];"
               ::"l"(m), "r"(src), "r"(c0), "r"(c1) : "memory");
}
DEVI void bulk_load(uint32_t dst, const void* src, uint32_t bytes, uint32_t bar) {
  asm volatile("cp.async.bulk.shared::cluster.global.mbarrier::complete_tx::bytes [%0], [%1], %2, [%3];"
               ::"r"(dst), "l"(src), "r"(bytes), "r"(bar) : "memory");
}
DEVI void bulk_store(void* dst, uint32_t src, uint32_t bytes) {
  asm volatile("cp.async.bulk.global.shared::cta.bulk_group [%0], [%1], %2;" ::"l"(dst), "r"(src), "r"(bytes) : "memory");
}
DEVI void bulk_reduce_add_f32(void* dst, uint32_t src, uint32_t bytes) {
  asm volatile("cp.reduce.async.bulk.global.shared::cta.bulk_group.add.f32 [%0], [%1], %2;" ::"l"(dst), "r"(src), "r"(bytes) : "memory");
}
DEVI void bulk_commit() { asm volatile("cp.async.bulk.commit_group;" ::: "memory"); }
DEVI void bulk_wait0() { asm volatile("cp.async.bulk.wait_group 0;" ::: "memory"); }
DEVI void bulk_wait_read0() { asm volatile("cp.async.bulk.wait_group.read 0;" ::: "memory"); }
DEVI void l2_prefetch(const void* p, uint32_t bytes) {
  asm volatile("cp.async.bulk.prefetch.L2.global [%0], %1;" ::"l"(p), "r"(bytes) : "memory");
}
DEVI void prefetch_tmap(const CUtensorMap* m) { asm volatile("prefetch.tensormap [%0];" ::"l"(m) : "memory"); }

DEVI void red_release_add(unsigned* p, unsigned v) {
  asm volatile("red.release.gpu.global.add.u32 [%0], %1;" ::"l"(p), "r"(v) : "memory");
}
DEVI void red_relaxed_add(unsigned* p, unsigned v) {
  asm volatile("red.relaxed.gpu.global.add.u32 [%0], %1;" ::"l"(p), "r"(v) : "memory");
}
DEVI unsigned ld_relaxed(const unsigned* p) {
  unsigned v;
  asm volatile("ld.relaxed.gpu.global.u32 %0, [%1];" : "=r"(v) : "l"(p) : "memory");
  return v;
}
DEVI void wait_counter(const unsigned* p, unsigned target) {
#pragma unroll 1
  for (int it = 0; (int)(ld_relaxed(p) - target) < 0; ++it)
    if (it > (1 << 22)) __trap();
}

DEVI void ldsm_x4(uint32_t (&r)[4], uint32_t a) {
  asm volatile("ldmatrix.sync.aligned.m8n8.x4.shared.b16 {%0,%1,%2,%3}, [%4];"
               : "=r"(r[0]), "=r"(r[1]), "=r"(r[2]), "=r"(r[3]) : "r"(a) : "memory");
}
DEVI void ldsm_x4_t(uint32_t (&r)[4], uint32_t a) {
  asm volatile("ldmatrix.sync.aligned.m8n8.x4.trans.shared.b16 {%0,%1,%2,%3}, [%4];"
               : "=r"(r[0]), "=r"(r[1]), "=r"(r[2]), "=r"(r[3]) : "r"(a) : "memory");
}
DEVI void ldsm_x2_t(uint32_t& r0, uint32_t& r1, uint32_t a) {
  asm volatile("ldmatrix.sync.aligned.m8n8.x2.trans.shared.b16 {%0,%1}, [%2];" : "=r"(r0), "=r"(r1) : "r"(a) : "memory");
}
DEVI void stsm_x4(uint32_t a, uint32_t r0, uint32_t r1, uint32_t r2, uint32_t r3) {
  asm volatile("stmatrix.sync.aligned.m8n8.x4.shared.b16 [%0], {%1,%2,%3,%4};"
               ::"r"(a), "r"(r0), "r"(r1), "r"(r2), "r"(r3) : "memory");
}
DEVI void stsm_x4_t(uint32_t a, uint32_t r0, uint32_t r1, uint32_t r2, uint32_t r3) {
  asm volatile("stmatrix.sync.aligned.m8n8.x4.trans.shared.b16 [%0], {%1,%2,%3,%4};"
               ::"r"(a), "r"(r0), "r"(r1), "r"(r2), "r"(r3) : "memory");
}
DEVI uint32_t lds32(uint32_t a) { uint32_t v; asm volatile("ld.shared.b32 %0, [%1];" : "=r"(v) : "r"(a) : "memory"); return v; }
DEVI float lds_f32(uint32_t a) { float v; asm volatile("ld.shared.f32 %0, [%1];" : "=f"(v) : "r"(a) : "memory"); return v; }
DEVI void sts32(uint32_t a, uint32_t v) { asm volatile("st.shared.b32 [%0], %1;" ::"r"(a), "r"(v) : "memory"); }
DEVI void sts_f32(uint32_t a, float v) { asm volatile("st.shared.f32 [%0], %1;" ::"r"(a), "f"(v) : "memory"); }
DEVI void sts_f32x2(uint32_t a, float x, float y) { asm volatile("st.shared.v2.f32 [%0], {%1,%2};" ::"r"(a), "f"(x), "f"(y) : "memory"); }
DEVI uint4 lds128(uint32_t a) {
  uint4 v;
  asm volatile("ld.shared.v4.b32 {%0,%1,%2,%3}, [%4];" : "=r"(v.x), "=r"(v.y), "=r"(v.z), "=r"(v.w) : "r"(a) : "memory");
  return v;
}
DEVI void sts128(uint32_t a, uint32_t x, uint32_t y, uint32_t z, uint32_t w) {
  asm volatile("st.shared.v4.b32 [%0], {%1,%2,%3,%4};" ::"r"(a), "r"(x), "r"(y), "r"(z), "r"(w) : "memory");
}

DEVI void mma_bf16(float (&d)[4], uint32_t a0, uint32_t a1, uint32_t a2, uint32_t a3, uint32_t b0, uint32_t b1) {
  asm("mma.sync.aligned.m16n8k16.row.col.f32.bf16.bf16.f32 {%0,%1,%2,%3}, {%4,%5,%6,%7}, {%8,%9}, {%0,%1,%2,%3};"
      : "+f"(d[0]), "+f"(d[1]), "+f"(d[2]), "+f"(d[3])
      : "r"(a0), "r"(a1), "r"(a2), "r"(a3), "r"(b0), "r"(b1));
}
DEVI void mma_f16(float (&d)[4], const uint32_t (&a)[4], uint32_t b0, uint32_t b1) {
  asm("mma.sync.aligned.m16n8k16.row.col.f32.f16.f16.f32 {%0,%1,%2,%3}, {%4,%5,%6,%7}, {%8,%9}, {%0,%1,%2,%3};"
      : "+f"(d[0]), "+f"(d[1]), "+f"(d[2]), "+f"(d[3])
      : "r"(a[0]), "r"(a[1]), "r"(a[2]), "r"(a[3]), "r"(b0), "r"(b1));
}
DEVI void mma_bf16v(float (&d)[4], const uint32_t (&a)[4], uint32_t b0, uint32_t b1) {
  asm volatile("mma.sync.aligned.m16n8k16.row.col.f32.bf16.bf16.f32 {%0,%1,%2,%3}, {%4,%5,%6,%7}, {%8,%9}, {%0,%1,%2,%3};"
               : "+f"(d[0]), "+f"(d[1]), "+f"(d[2]), "+f"(d[3])
               : "r"(a[0]), "r"(a[1]), "r"(a[2]), "r"(a[3]), "r"(b0), "r"(b1));
}
DEVI uint32_t pack_bf16(float lo, float hi) {
  uint32_t r;
  asm("cvt.rn.bf16x2.f32 %0, %1, %2;" : "=r"(r) : "f"(hi), "f"(lo));
  return r;
}
DEVI uint32_t pack_f16(float lo, float hi) {
  uint32_t r;
  asm("cvt.rn.f16x2.f32 %0, %1, %2;" : "=r"(r) : "f"(hi), "f"(lo));
  return r;
}
DEVI uint32_t ldg16(const __nv_bfloat16* p) {
  uint32_t v;
  asm volatile("ld.global.nc.u16 %0, [%1];" : "=r"(v) : "l"(p));
  return v;
}
DEVI bool elect_one() {
  uint32_t pred;
  asm volatile("{\n.reg .pred p;\nelect.sync _|p, 0xffffffff;\nselp.u32 %0, 1, 0, p;\n}" : "=r"(pred));
  return pred != 0;
}
DEVI float bf_lo(uint32_t v) { return __uint_as_float(v << 16); }
DEVI float bf_hi(uint32_t v) { return __uint_as_float(v & 0xffff0000u); }
DEVI float bf2f(__nv_bfloat16 v) { return __bfloat162float(v); }
DEVI float round_bf16(float v) { return __bfloat162float(__float2bfloat16_rn(v)); }
DEVI float rcp(float x) { float r; asm("rcp.approx.ftz.f32 %0, %1;" : "=f"(r) : "f"(x)); return r; }
DEVI float ex2(float x) { float r; asm("ex2.approx.ftz.f32 %0, %1;" : "=f"(r) : "f"(x)); return r; }

DEVI void wg_fence() { asm volatile("wgmma.fence.sync.aligned;" ::: "memory"); }
DEVI void wg_commit() { asm volatile("wgmma.commit_group.sync.aligned;" ::: "memory"); }
template <int N> DEVI void wg_wait() { asm volatile("wgmma.wait_group.sync.aligned %0;" ::"n"(N) : "memory"); }
constexpr uint32_t DESC_HI = (1u << 30) | (1024 >> 4);
constexpr uint32_t DESC_HI64 = (2u << 30) | (512 >> 4);
DEVI uint32_t mkdesc(uint32_t saddr, uint32_t lbo) { return ((saddr & 0x3FFFF) >> 4) | ((lbo >> 4) << 16); }

#define R8(b) "%" #b
DEVI void wgmma_n192(float (&d)[96], uint32_t da, uint32_t db, int scale_d) {
  asm volatile(
      "{\n.reg .pred p;\n.reg .b64 da, db;\nsetp.ne.b32 p, %98, 0;\nmov.b64 da, {%96, %100};\nmov.b64 db, {%97, %99};\n"
      "wgmma.mma_async.sync.aligned.m64n192k16.f32.bf16.bf16 "
      "{%0,%1,%2,%3,%4,%5,%6,%7,%8,%9,%10,%11,%12,%13,%14,%15,"
      "%16,%17,%18,%19,%20,%21,%22,%23,%24,%25,%26,%27,%28,%29,%30,%31,"
      "%32,%33,%34,%35,%36,%37,%38,%39,%40,%41,%42,%43,%44,%45,%46,%47,"
      "%48,%49,%50,%51,%52,%53,%54,%55,%56,%57,%58,%59,%60,%61,%62,%63,"
      "%64,%65,%66,%67,%68,%69,%70,%71,%72,%73,%74,%75,%76,%77,%78,%79,"
      "%80,%81,%82,%83,%84,%85,%86,%87,%88,%89,%90,%91,%92,%93,%94,%95}, "
      "da, db, p, 1, 1, 0, 1;\n}"
      : "+f"(d[0]), "+f"(d[1]), "+f"(d[2]), "+f"(d[3]), "+f"(d[4]), "+f"(d[5]), "+f"(d[6]), "+f"(d[7]),
        "+f"(d[8]), "+f"(d[9]), "+f"(d[10]), "+f"(d[11]), "+f"(d[12]), "+f"(d[13]), "+f"(d[14]), "+f"(d[15]),
        "+f"(d[16]), "+f"(d[17]), "+f"(d[18]), "+f"(d[19]), "+f"(d[20]), "+f"(d[21]), "+f"(d[22]), "+f"(d[23]),
        "+f"(d[24]), "+f"(d[25]), "+f"(d[26]), "+f"(d[27]), "+f"(d[28]), "+f"(d[29]), "+f"(d[30]), "+f"(d[31]),
        "+f"(d[32]), "+f"(d[33]), "+f"(d[34]), "+f"(d[35]), "+f"(d[36]), "+f"(d[37]), "+f"(d[38]), "+f"(d[39]),
        "+f"(d[40]), "+f"(d[41]), "+f"(d[42]), "+f"(d[43]), "+f"(d[44]), "+f"(d[45]), "+f"(d[46]), "+f"(d[47]),
        "+f"(d[48]), "+f"(d[49]), "+f"(d[50]), "+f"(d[51]), "+f"(d[52]), "+f"(d[53]), "+f"(d[54]), "+f"(d[55]),
        "+f"(d[56]), "+f"(d[57]), "+f"(d[58]), "+f"(d[59]), "+f"(d[60]), "+f"(d[61]), "+f"(d[62]), "+f"(d[63]),
        "+f"(d[64]), "+f"(d[65]), "+f"(d[66]), "+f"(d[67]), "+f"(d[68]), "+f"(d[69]), "+f"(d[70]), "+f"(d[71]),
        "+f"(d[72]), "+f"(d[73]), "+f"(d[74]), "+f"(d[75]), "+f"(d[76]), "+f"(d[77]), "+f"(d[78]), "+f"(d[79]),
        "+f"(d[80]), "+f"(d[81]), "+f"(d[82]), "+f"(d[83]), "+f"(d[84]), "+f"(d[85]), "+f"(d[86]), "+f"(d[87]),
        "+f"(d[88]), "+f"(d[89]), "+f"(d[90]), "+f"(d[91]), "+f"(d[92]), "+f"(d[93]), "+f"(d[94]), "+f"(d[95])
      : "r"(da), "r"(db), "r"(scale_d), "n"(DESC_HI), "n"(DESC_HI64));
}
DEVI void wgmma_n64(float (&d)[32], uint32_t da, uint32_t db, int scale_d) {
  asm volatile(
      "{\n.reg .pred p;\n.reg .b64 da, db;\nsetp.ne.b32 p, %34, 0;\nmov.b64 da, {%32, %35};\nmov.b64 db, {%33, %35};\n"
      "wgmma.mma_async.sync.aligned.m64n64k16.f32.bf16.bf16 "
      "{%0,%1,%2,%3,%4,%5,%6,%7,%8,%9,%10,%11,%12,%13,%14,%15,"
      "%16,%17,%18,%19,%20,%21,%22,%23,%24,%25,%26,%27,%28,%29,%30,%31}, "
      "da, db, p, 1, 1, 0, 1;\n}"
      : "+f"(d[0]), "+f"(d[1]), "+f"(d[2]), "+f"(d[3]), "+f"(d[4]), "+f"(d[5]), "+f"(d[6]), "+f"(d[7]),
        "+f"(d[8]), "+f"(d[9]), "+f"(d[10]), "+f"(d[11]), "+f"(d[12]), "+f"(d[13]), "+f"(d[14]), "+f"(d[15]),
        "+f"(d[16]), "+f"(d[17]), "+f"(d[18]), "+f"(d[19]), "+f"(d[20]), "+f"(d[21]), "+f"(d[22]), "+f"(d[23]),
        "+f"(d[24]), "+f"(d[25]), "+f"(d[26]), "+f"(d[27]), "+f"(d[28]), "+f"(d[29]), "+f"(d[30]), "+f"(d[31])
      : "r"(da), "r"(db), "r"(scale_d), "n"(DESC_HI));
}

struct C32 { float re, im; };
DEVI C32 csq(C32 a) { return {a.re * a.re - a.im * a.im, 2.f * a.re * a.im}; }
DEVI C32 cmul(C32 a, C32 b) { return {a.re * b.re - a.im * b.im, a.re * b.im + a.im * b.re}; }
DEVI C32 cfresh(float zl, float zi, float m) {
  float mag = ex2(zl * m), ph = zi * m;
  return {mag * __cosf(ph), mag * __sinf(ph)};
}
struct HMul { uint32_t b, bp; };
DEVI HMul mk_mul(float re, float im) { return {pack_f16(re, im), pack_f16(-im, re)}; }
DEVI uint32_t hcmul(uint32_t a, const HMul& m) {
  __half2 ah = *reinterpret_cast<__half2*>(&a);
  __half2 b = *reinterpret_cast<const __half2*>(&m.b), bp = *reinterpret_cast<const __half2*>(&m.bp);
  __half2 r = __hfma2(__high2half2(ah), bp, __hmul2(__low2half2(ah), b));
  return *reinterpret_cast<uint32_t*>(&r);
}
DEVI uint32_t badd(uint32_t a, uint32_t b) {
  __nv_bfloat162 r = __hadd2(*reinterpret_cast<__nv_bfloat162*>(&a), *reinterpret_cast<__nv_bfloat162*>(&b));
  return *reinterpret_cast<uint32_t*>(&r);
}
template <int MU0, int NMU, int DMAX, int LO>
DEVI void conv_tail(float (&acc)[8][4], uint32_t p_lane, uint32_t v_base, int back, bool edge, int lane) {
  constexpr int D0 = LO - (MU0 + 2 * (NMU - 1)) > -1 ? LO - (MU0 + 2 * (NMU - 1)) : -1;
  constexpr int D1 = LO + 7 - MU0 < DMAX ? LO + 7 - MU0 : DMAX;
  const int hsel = (lane >> 3) & 1;
  const int row = (lane & 7) + ((lane >> 4) << 3) + PADV + 8 * D0 - (back & (hsel ^ 1));
  const uint32_t la = v_base + row * 32 + (((hsel ^ back) ^ ((row >> 2) & 1)) << 4);
  uint32_t M[3][4];
  ldsm_x4_t(M[0], la);
  if (D1 > D0) ldsm_x4_t(M[1], la + 256);
  uint32_t H[2 * NMU];
#pragma unroll
  for (int i = 0; i < 2 * NMU; ++i) H[i ^ 1] = lds32(p_lane + (uint32_t)(MU0 - 1 + i) * 32);
  if (D0 == -1 && edge) {
    const uint32_t a[4] = {0u, 0u, M[0][0], M[0][1]};
#pragma unroll
    for (int k = 1; k < NMU; ++k)
      if (MU0 - 2 + 2 * k >= LO && MU0 - 2 + 2 * k < LO + 8) mma_bf16v(acc[MU0 - 2 + 2 * k - LO], a, H[2 * k], H[2 * k + 1]);
  }
#pragma unroll
  for (int delta = D0; delta <= D1; ++delta) {
    if (delta + 2 <= D1) ldsm_x4_t(M[(delta - D0 + 2) % 3], la + (delta - D0 + 2) * 256);
#pragma unroll
    for (int k = 0; k < NMU; ++k) {
      const int nb = delta + MU0 + 2 * k;
      if (nb >= LO && nb < LO + 8) mma_bf16v(acc[nb - LO], M[(delta - D0) % 3], H[2 * k], H[2 * k + 1]);
    }
  }
}

template <int LO>
DEVI void conv_half(uint32_t ub, uint32_t pb, uint32_t vv, int lane, uint32_t zero, int ch, __nv_bfloat16* yrow) {
  const int gq = (lane >> 2) - 2 * (lane & 3);
  float acc[8][4];
#pragma unroll
  for (int i = 0; i < 8; ++i) { acc[i][0] = acc[i][1] = acc[i][2] = acc[i][3] = 0.f; }
  const uint32_t pd_lane = pb + (PD_OFF + 16 + gq) * 4;
  const int prow0 = 8 + (lane & 7) + ((lane >> 4) << 3), hs = (lane >> 3) & 1;
  constexpr int M2 = LO ? 2 : 0, NM2 = LO ? 6 : 4;
#pragma unroll 1
  for (int rho = 0; rho < 8; ++rho) {
    const int prow = prow0 - rho;
    const uint32_t la = ub + prow * 32 + ((hs ^ ((prow >> 2) & 1)) << 4);
    uint32_t B[NM2][4], A[4][4];
#pragma unroll
    for (int m2 = 0; m2 < NM2; ++m2) ldsm_x4(B[m2], la + (M2 + m2) * 512);
#pragma unroll
    for (int i = 0; i < 4; ++i) {
      const uint32_t a = pd_lane + rho * 64 + i * 512;
      A[i][0] = lds32(a); A[i][1] = lds32(a + 32); A[i][2] = lds32(a - 32);
      A[i][3] = lds32(a + zero);
    }
#pragma unroll
    for (int i = 0; i < 4; ++i)
#pragma unroll
      for (int ab = LO; ab < LO + 8; ++ab) {
        const int m = ab - i;
        if (m >= 0) mma_bf16v(acc[ab - LO], A[i], B[(m >> 1) - M2][2 * (m & 1)], B[(m >> 1) - M2][2 * (m & 1) + 1]);
      }
  }
  {
    const uint32_t kw = lds32(pb + (P3_OFF + 16) * 4);
    const uint32_t kf2 = __byte_perm(kw, 0, 0x1010) ^ 0x80008000u;
    const uint32_t h127 = (gq == 4 ? 0x0000ffffu : gq == 5 ? 0xffffffffu : gq == 6 ? 0xffff0000u : 0u) & kf2;
    const uint32_t h128 = (gq == -4 ? 0x0000ffffu : gq == -3 ? 0xffffffffu : gq == -2 ? 0xffff0000u : 0u) & kf2;
    const uint32_t h63 = lds32(pd_lane + 63 * 32), h64 = lds32(pd_lane + 64 * 32);
    const uint32_t a63[4] = {0u, h127, 0u, 0u}, a32[4] = {h64, 0u, h63, h64}, a64[4] = {h128, 0u, h127, h128};
    const uint32_t la0 = ub + prow0 * 32 + ((hs ^ ((prow0 >> 2) & 1)) << 4);
    const uint32_t la7 = ub + (prow0 - 7) * 32 + ((hs ^ (((prow0 - 7) >> 2) & 1)) << 4);
    constexpr int N0 = LO ? 6 : 2, N7 = LO ? 5 : 1;
    uint32_t B0[N0][4], B7[N7][4];
#pragma unroll
    for (int m2 = 0; m2 < N7; ++m2) ldsm_x4(B7[m2], la7 + m2 * 512);
#pragma unroll
    for (int m2 = 0; m2 < N0; ++m2) ldsm_x4(B0[m2], la0 + m2 * 512);
#pragma unroll
    for (int ab = LO; ab < LO + 8; ++ab)
      if (ab >= 7) mma_bf16v(acc[ab - LO], a63, B7[(ab - 7) >> 1][2 * ((ab - 7) & 1)], B7[(ab - 7) >> 1][2 * ((ab - 7) & 1) + 1]);
#pragma unroll
    for (int ab = LO; ab < LO + 8; ++ab)
      if (ab >= 4) mma_bf16v(acc[ab - LO], a32, B0[(ab - 4) >> 1][2 * ((ab - 4) & 1)], B0[(ab - 4) >> 1][2 * ((ab - 4) & 1) + 1]);
#pragma unroll
    for (int ab = LO; ab < LO + 8; ++ab)
      if (ab >= 8) mma_bf16v(acc[ab - LO], a64, B0[(ab - 8) >> 1][2 * ((ab - 8) & 1)], B0[(ab - 8) >> 1][2 * ((ab - 8) & 1) + 1]);
  }
  bar_sync(8 + ch, 128);
#pragma unroll 1
  for (int v = 0; v < 4; ++v)
    conv_tail<4, 3, 11, LO>(acc, pb + (P2_OFF + 56 * v + gq - 16) * 4, vv + ((v & 1) ? VV_U3 : VV_U5), v >> 1, v == 0, lane);
#pragma unroll 1
  for (int pi = 0; pi < (LO ? 2 : 1); ++pi)
    conv_tail<8, 5, 7, LO>(acc, pb + (P3_OFF + 88 * pi + gq - 48) * 4, vv + (pi ? VV_U7 : VV_U9), pi, pi == 0, lane);
  bar_sync(12 + ch, 64);
  const int mt = lane >> 3;
  const uint32_t a = pb + (128 * (LO + (mt >> 1)) + 16 * (lane & 7) + 8 * (mt & 1)) * 2;
#pragma unroll
  for (int t = 0; t < 8; t += 2)
    stsm_x4_t(a + t * 256, pack_bf16(acc[t][0], acc[t][1]), pack_bf16(acc[t][2], acc[t][3]),
              pack_bf16(acc[t + 1][0], acc[t + 1][1]), pack_bf16(acc[t + 1][2], acc[t + 1][3]));
  fence_async_smem();
  __syncwarp();
}

__global__ void __cluster_dims__(2, 1, 1) __launch_bounds__(NTHREADS, 1)
fused_kernel(const __grid_constant__ Maps maps, const Ptrs p) {
  extern __shared__ __align__(1024) uint8_t smem[];
  const uint32_t sb = s2u(smem);
  const int tid = threadIdx.x, lane = tid & 31;
  const int warp = __shfl_sync(0xffffffffu, tid >> 5, 0);
  const int cta = blockIdx.x;
  const uint32_t rank = cta & 1;
  const int ti = 2 * (cta >> 4) + rank;
  const int tj = (cta >> 1) & 7;
  const int pi = cta >> 3, pj = cta & 7;
  const uint32_t bars = sb + SM_BAR;
#define BAR(i) (bars + 8 * (i))
  const int g = lane >> 2, q = lane & 3;

  auto issue_stage = [&](int ks, int s) {
    const uint32_t st = sb + s * STG_BYTES, fb = BAR(B_FULL + s);
    mbar_expect_tx(fb, STG_BYTES);
    tma_load_2d(st + STG_X, &maps.x, ks * 32, ti * 128, fb);
    tma_load_3d_mc(st + STG_W + rank * 6144, &maps.w, tj * 64, ks * 32 + rank * 16, 0, fb, 3);
  };

  const int kch = warp & 3, krd = warp >> 2;
  float zr, zi, wr, wi;
  unsigned epoch;
  uint32_t r_dskip;
  {
    const size_t po = (size_t)(cta * 4 + kch) * 128 + krd * 32 + lane;
    const uint32_t r_ar = ldg16(p.A_re + po), r_ai = ldg16(p.A_im + po), r_br = ldg16(p.B_re + po), r_bi = ldg16(p.B_im + po);
    const uint32_t r_cr = ldg16(p.C_re + po), r_ci = ldg16(p.C_im + po), r_ldt = ldg16(p.log_dt + cta * 4 + kch);
    epoch = __ldcg(&g_epoch);
    r_dskip = ldg16(p.Dskip + cta * 4 + kch);
    uint4 pt;
    if (tid < 128) pt = __ldg((const uint4*)g_ptab.v + tid);
    if (tid == 384) {
      TS(0);
#pragma unroll
      for (int i = 0; i < B_COUNT; ++i) mbar_init(BAR(i), bar_count(i));
      asm volatile("fence.mbarrier_init.release.cluster;" ::: "memory");
      prefetch_tmap(&maps.x); prefetch_tmap(&maps.w); prefetch_tmap(&maps.u);
    }
    __syncthreads();
    cluster_arrive();
    if (warp >= 12) {
      cluster_wait();
      if (elect_one()) {
        if (warp == 13) {
          mbar_expect_tx(BAR(B_TILE), 16384);
          tma_load_2d(sb + SM_U, &maps.u, tj * 64, ti * 128, BAR(B_TILE));
          prefetch_tmap(&maps.uT); prefetch_tmap(&maps.wo); prefetch_tmap(&maps.o); prefetch_tmap(&maps.yT);
          prefetch_tmap(&maps.out);
        } else {
          if (warp == 12) TS(61);
          { const int ks = warp == 12 ? 0 : warp - 13; issue_stage(ks, ks); }
        }
      }
      __syncwarp();
    }
    if (tid < 128) sts128(sb + SM_PTAB + tid * 16, pt.x, pt.y, pt.z, pt.w);
    const float dt = round_bf16(expf(bf_lo(r_ldt)));
    zr = dt * bf_lo(r_ar); zi = dt * bf_lo(r_ai);
    const float dbr = dt * bf_lo(r_br), dbi = dt * bf_lo(r_bi), cr = bf_lo(r_cr), ci = bf_lo(r_ci);
    wr = cr * dbr - ci * dbi; wi = cr * dbi + ci * dbr;
  }
  {
    const float mz = __uint_as_float(__reduce_max_sync(0xffffffffu, __float_as_uint(fmaxf(zr, 0.f))));
    const int E = min(max((int)(__reduce_max_sync(0xffffffffu, __float_as_uint(fmaxf(fabsf(wr), fabsf(wi)))) >> 23), 1), 252);
    const float sc = __int_as_float((253 - E) << 23), inv = __int_as_float((E + 1) << 23);
    const float zl = (zr - mz) * 1.4426950408889634f;
    const uint32_t tb = sb + SM_VV + kch * VV_BYTES + krd * KG_BYTES;
    const uint32_t sta = tb + (((lane >> 2) << 4) | ((lane & 3) << 2));
    auto put = [&](int r, uint32_t v) { sts32((sta ^ ((r & 7) << 4)) + r * 128, v); };
    const uint32_t lda = tb + ((lane & 7) + (((lane >> 3) & 1) << 3)) * 128;
    const uint32_t ldb = tb + ((lane & 7) + ((lane >> 4) << 3)) * 128;
    C32 e1 = cfresh(zl, zi, 1.f), e2 = csq(e1), e4 = csq(e2), e8 = csq(e4);
    C32 e16 = cfresh(zl, zi, 16.f), e32 = csq(e16), e64 = csq(e32), e128 = csq(e64);
    C32 e256 = cfresh(zl, zi, 256.f), e512 = csq(e256), e1024 = csq(e512), e768 = cmul(e512, e256);
    uint32_t XA[2][4][4];
    {
      const HMul m16 = mk_mul(e16.re, e16.im), m32 = mk_mul(e32.re, e32.im), m64 = mk_mul(e64.re, e64.im);
      const HMul m128 = mk_mul(e128.re, e128.im);
      uint32_t X[16];
      X[0] = 0x00003c00u; X[1] = pack_f16(e8.re, e8.im); X[2] = m16.b; X[4] = m32.b; X[8] = m64.b;
      X[3] = hcmul(X[1], m16); X[5] = hcmul(X[1], m32); X[6] = hcmul(X[2], m32); X[7] = hcmul(X[3], m32);
#pragma unroll
      for (int r = 1; r < 8; ++r) X[8 + r] = hcmul(X[r], m64);
#pragma unroll
      for (int h = 0; h < 2; ++h) {
#pragma unroll
        for (int r = 0; r < 16; ++r) put(r, h == 0 ? X[r] : r == 0 ? m128.b : hcmul(X[r], m128));
        __syncwarp();
#pragma unroll
        for (int k = 0; k < 4; ++k) ldsm_x4(XA[h][k], lda + (((2 * k + (lane >> 4)) ^ (lane & 7)) << 4));
        __syncwarp();
      }
    }
    if (warp >= 14 && elect_one()) {
      issue_stage(warp - 11, warp - 11);
      issue_stage(warp - 9, warp - 9);
      if (warp == 14) l2_prefetch((const char*)p.wqkv + 224 * 3072 + cta * 6912, 6912);
      else l2_prefetch((const char*)p.x + (size_t)cta * 16384, 16384);
    }
    __syncwarp();
    float D[2][3][4];
#pragma unroll
    for (int t = 0; t < 6; ++t) D[t / 3][t % 3][0] = D[t / 3][t % 3][1] = D[t / 3][t % 3][2] = D[t / 3][t % 3][3] = 0.f;
    auto contract = [&](int t0, int nt) {
      __syncwarp();
#pragma unroll
      for (int k = 0; k < 4; ++k) {
        uint32_t b[4];
        ldsm_x4(b, ldb + (((2 * k + ((lane >> 3) & 1)) ^ (lane & 7)) << 4));
#pragma unroll
        for (int h = 0; h < 2; ++h) {
          mma_f16(D[h][t0], XA[h][k], b[0], b[1]);
          if (nt == 2) mma_f16(D[h][t0 + 1], XA[h][k], b[2], b[3]);
        }
      }
      __syncwarp();
    };
    const HMul c1 = mk_mul(e1.re, -e1.im), c2 = mk_mul(e2.re, -e2.im), c4 = mk_mul(e4.re, -e4.im);
    const HMul c256 = mk_mul(e256.re, -e256.im), c512 = mk_mul(e512.re, -e512.im), c768 = mk_mul(e768.re, -e768.im);
    const HMul c1024 = mk_mul(e1024.re, -e1024.im);
    uint32_t W[8];
    W[0] = pack_f16(wr * sc, -wi * sc);
    W[1] = hcmul(W[0], c1); W[2] = hcmul(W[0], c2); W[3] = hcmul(W[1], c2);
    W[4] = hcmul(W[0], c4); W[5] = hcmul(W[1], c4); W[6] = hcmul(W[2], c4); W[7] = hcmul(W[3], c4);
#pragma unroll
    for (int i = 0; i < 8; ++i) put(i, W[i]);
#pragma unroll
    for (int i = 0; i < 4; ++i) put(8 + i, hcmul(W[2 * i], c256));
    put(12, hcmul(W[0], c512)); put(13, hcmul(W[4], c512)); put(14, hcmul(W[0], c768)); put(15, hcmul(W[4], c768));
    contract(0, 2);
    const uint32_t v0 = hcmul(W[0], c1024);
    put(0, v0); put(1, hcmul(v0, c256)); put(2, hcmul(v0, c512)); put(3, hcmul(v0, c768)); put(4, hcmul(v0, c1024));
    contract(2, 1);
    const uint32_t a = tb + (g * 24 + 2 * q) * 4;
#pragma unroll
    for (int t = 0; t < 6; ++t) {
      const float(&d)[4] = D[t / 3][t % 3];
      sts_f32x2(a + (t / 3) * 1536 + (t % 3) * 32, d[0] * inv, d[1] * inv);
      sts_f32x2(a + (t / 3) * 1536 + (t % 3) * 32 + 768, d[2] * inv, d[3] * inv);
    }
    if (mz > 0.f) {
      __syncwarp();
#pragma unroll 1
      for (int i = lane; i < 768; i += 32) {
        const int r = i / 24, y = i - 24 * r;
        sts_f32(tb + i * 4, lds_f32(tb + i * 4) * ex2(mz * 1.4426950408889634f * (koff(y) + 8 * r)));
      }
    }
  }
  if (tid == 0) TS(2);
  if (warp < 12) cluster_wait();
  if (tid == 0) TS(32);
  __syncthreads();
  if (tid == 0) TSD(33);

  if (warp < 4) {
    asm volatile("setmaxnreg.inc.sync.aligned.u32 152;");
    if (tid == 0) TS(34);
    const int d = cta * 4 + warp;
    const uint32_t vv = sb + SM_VV + warp * VV_BYTES;
    const uint32_t ub = sb + SM_U + warp * U_BYTES;
    const uint32_t pb = sb + SM_P + warp * P_BYTES;
    const float dskip = bf_lo(r_dskip);
#pragma unroll 1
    for (int pass = 0; pass < 2; ++pass) {
      if (pass == 1) {
        const uint32_t kf = vv;
#pragma unroll 2
        for (int i = 0; i < 6; ++i) {
          const uint32_t a = kf + (i * 32 + lane) * 16;
          const uint4 x0 = lds128(a), x1 = lds128(a + KG_BYTES), x2 = lds128(a + 2 * KG_BYTES), x3 = lds128(a + 3 * KG_BYTES);
          auto s4 = [](uint32_t a0, uint32_t a1, uint32_t a2, uint32_t a3) {
            return __float_as_uint((__uint_as_float(a0) + __uint_as_float(a1)) + (__uint_as_float(a2) + __uint_as_float(a3)));
          };
          sts128(a, s4(x0.x, x1.x, x2.x, x3.x), s4(x0.y, x1.y, x2.y, x3.y), s4(x0.z, x1.z, x2.z, x3.z), s4(x0.w, x1.w, x2.w, x3.w));
        }
        __syncwarp();
        if (lane == 0) {
          sts_f32(kf + SL_ZERO * 4, 0.f);
          sts_f32(kf + SL_510 * 4, lds_f32(kf + kidx_c(510) * 4) - lds_f32(kf + kidx_c(512) * 4));
          sts_f32(kf + SL_0 * 4, lds_f32(kf) + dskip);
        }
        __syncwarp();
        if (tid == 0) TS(36);
        mbar_wait_long(BAR(B_PFREE), 0);
        if (tid == 0) TS(37);
        {
          float prev = 0.f;
#pragma unroll 1
          for (int i0 = 0; i0 < 16; i0 += 4) {
            uint32_t e[4];
            float a[4], b[4];
#pragma unroll
            for (int i = 0; i < 4; ++i) e[i] = lds32(sb + SM_PTAB + ((i0 + i) * 32 + lane) * 4);
#pragma unroll
            for (int i = 0; i < 4; ++i) { a[i] = lds_f32(kf + (e[i] & 0xffff)); b[i] = lds_f32(kf + (e[i] >> 16)); }
#pragma unroll
            for (int i = 0; i < 4; ++i) {
              const uint32_t w = pb + (31 * lane + 2 * (i0 + i)) * 4;
              if (i0 + i > 0) sts32(w - 4, pack_bf16(a[i], prev));
              sts32(w, pack_bf16(b[i], a[i]));
              prev = b[i];
            }
          }
        }
        __syncwarp();
        if (lane == 0) TS(4);
        bar_arrive(5, 384);
        bar_sync(4, 512);
        mbar_wait_long(BAR(B_UCH + warp), 0);
        if (lane == 0) TS(7);
        conv_half<8>(ub, pb, vv, lane, (uint32_t)cta >> 20, warp, p.yT + (size_t)d * 2048);
        if (lane == 0) TS(8);
        if (lane < 2) mbar_arrive_cluster(BAR(B_CONVD), lane);
        bar_arrive(3, 512);
        if (elect_one()) {
          bulk_store(p.yT + (size_t)d * 2048 + 1024, pb + 2048, 2048);
          bulk_commit();
          bulk_wait0();
          red_relaxed_add(&g_cnt[(C_Y + (cta >> 4)) * 32], 1);
          TS(9);
        }
        bar_sync(2, 256);
        if (warp == 0 && elect_one()) {
          wait_counter(&g_cnt[(C_Y + tj) * 32], (epoch + 1) * 128);
          TS(28);
          mbar_expect_tx(BAR(B_TILE), 16384);
          tma_load_2d(sb + SM_U, &maps.yT, ti * 128, tj * 64, BAR(B_TILE));
          tma_load_2d(sb + SM_U + 8192, &maps.yT, ti * 128 + 64, tj * 64, BAR(B_TILE));
        }
        __syncwarp();
      }
      mbar_wait_long(BAR(B_TILE), pass);
      if (lane == 0) TS(26 + 3 * pass);
      {
        const int m = lane >> 3, r = lane & 7;
#pragma unroll 2
        for (int it = 0; it < 8; ++it) {
          const int tb = warp * 4 + (it >> 1), cb = (it & 1) * 4 + m;
          const uint32_t at = (tb * 8 + r) * 128 + ((cb ^ r) << 4);
          const uint32_t ac = (tb >> 3) * 8192 + (cb * 8 + r) * 128 + (((tb & 7) ^ (pass ? 0 : tb >> 3) ^ r) << 4);
          uint32_t v[4];
          ldsm_x4_t(v, sb + SM_U + (pass ? ac : at));
          stsm_x4(sb + SM_P + (pass ? at : ac), v[0], v[1], v[2], v[3]);
        }
      }
      if (pass == 0 && tid == 0) TS(35);
      fence_async_smem();
      if (pass == 0) {
        bar_arrive(6, 160);
      } else {
        bar_sync(7, 128);
        if (warp == 0 && elect_one()) {
          tma_store_2d(&maps.out, sb + SM_P, 64 * tj, 128 * ti);
          bulk_commit();
          bulk_wait_read0();
          TS(30);
        }
      }
    }
  } else if (warp < 12) {
    asm volatile("setmaxnreg.inc.sync.aligned.u32 160;");
    const int w8 = warp - 4;
    const int row = w8 * 16 + (lane & 7) + (((lane >> 3) & 1) << 3);
    {
      float acc[96];
#pragma unroll 1
      for (int ks = 0, s = 0, ph = 0; ks < 16; ++ks) {
        mbar_wait(BAR(B_FULL + s), ph);
        if (tid == 128 && !(ks & 1)) TSR(16, ks == 0 ? 16 : 9 + (ks >> 1) + (ks > 12 ? 43 : 0));
        const uint32_t st = sb + s * STG_BYTES;
        const uint32_t da = mkdesc(st + STG_X + (w8 >> 2) * 4096, 16);
        const uint32_t db = mkdesc(st + STG_W, 2048);
        wg_fence();
        wgmma_n192(acc, da, db, ks != 0);
        wgmma_n192(acc, da + 2, db + 384, 1);
        wg_commit();
        const uint32_t eprev = BAR(B_EMPTY + (s == 0 ? NSTG - 1 : s - 1));
        if (++s == NSTG) { s = 0; ph ^= 1; }
        if (ks > 0) {
          wg_wait<1>();
          if (lane < 2) mbar_arrive_cluster(eprev, lane);
        }
      }
      wg_wait<0>();
      if (tid == 128) TS(17);
      bar_sync(1, 256);
#pragma unroll
      for (int i = 0; i < 24; i += 2)
        stsm_x4(sb + SM_QS + row * 128 + (i >> 3) * 16384 + ((((i & 7) + (lane >> 4)) ^ (row & 7)) << 4),
                pack_bf16(acc[4 * i], acc[4 * i + 1]), pack_bf16(acc[4 * i + 2], acc[4 * i + 3]),
                pack_bf16(acc[4 * i + 4], acc[4 * i + 5]), pack_bf16(acc[4 * i + 6], acc[4 * i + 7]));
    }
    asm volatile("setmaxnreg.dec.sync.aligned.u32 112;");
    __syncwarp();
    float* kvg = &g_kv[epoch & 1][tj][0];
#pragma unroll 1
    for (int part = 1; part >= 0; --part) {
      const uint32_t pa = sb + SM_QS + part * 16384 + w8 * 2048 + lane * 16;
#pragma unroll 1
      for (int it = 0; it < 4; ++it) {
        uint4 t = lds128(pa + it * 512);
        uint32_t* tw = &t.x;
#pragma unroll
        for (int j = 0; j < 4; ++j) {
          const uint32_t x = tw[j];
          const __nv_bfloat162 xb = *reinterpret_cast<const __nv_bfloat162*>(&x);
          const uint32_t e = pack_bf16(ex2(bf_lo(x) * 1.4426950408889634f), ex2(bf_hi(x) * 1.4426950408889634f));
          const uint32_t m = __hgt2_mask(xb, __floats2bfloat162_rn(0.f, 0.f));
          tw[j] = badd((badd(x, 0x3f803f80u) & m) | (e & ~m), 0x35863586u);
        }
        sts128(pa + it * 512, t.x, t.y, t.z, t.w);
      }
      if (part == 1) {
        if (tid == 128) TS(53);
        bar_sync(1, 256);
        const int hh = w8 >> 1, dtile = w8 & 1;
        float kv[4] = {0.f, 0.f, 0.f, 0.f}, zz[4] = {0.f, 0.f, 0.f, 0.f};
        const int m = lane >> 3;
        const uint32_t aa = sb + SM_VS + ((lane & 7) + ((m >> 1) << 3)) * 128 + (((2 * hh + (m & 1)) ^ (lane & 7)) << 4);
        const uint32_t ab = sb + SM_PK + (lane & 15) * 128 + (((2 * hh + dtile) ^ (lane & 7)) << 4);
#pragma unroll 2
        for (int ks = 0; ks < 8; ++ks) {
          uint32_t a[4], b0, b1;
          ldsm_x4_t(a, aa + ks * 2048);
          ldsm_x2_t(b0, b1, ab + ks * 2048);
          mma_bf16(kv, a[0], a[1], a[2], a[3], b0, b1);
          mma_bf16(zz, 0x3f803f80u, 0x3f803f80u, 0x3f803f80u, 0x3f803f80u, b0, b1);
        }
        const uint32_t kp = sb + SM_KV + hh * 1088;
        sts128(kp + dtile * 512 + lane * 16, __float_as_uint(kv[0]), __float_as_uint(kv[1]), __float_as_uint(kv[2]),
               __float_as_uint(kv[3]));
        if (g == 0) sts_f32x2(kp + 1024 + dtile * 32 + q * 8, zz[0], zz[1]);
        fence_async_smem();
        __syncwarp();
        if (lane == 0) mbar_arrive(BAR(B_KVP));
        bar_arrive(4, 512);
        if (tid == 128) TS(55);
        if (warp == 4 && elect_one()) {
          mbar_wait(BAR(B_KVP), 0);
          bulk_reduce_add_f32(kvg, sb + SM_KV, 4352);
          bulk_commit();
        }
        __syncwarp();
      }
    }
    if (tid == 128) TS(56);
    if (warp == 4 && elect_one()) {
      bulk_wait0();
      red_relaxed_add(&g_cnt[(C_KV + tj) * 32], 1);
      TS(18);
    }
    __syncwarp();
    {
      const int ch = w8 >> 1;
      const uint32_t ub = sb + SM_U + ch * U_BYTES, vb = sb + SM_VV + ch * VV_BYTES;
      auto swz = [](int k, int pad) { const int r = (k >> 1) + pad; return (uint32_t)(r * 32 + (((k & 1) ^ ((r >> 2) & 1)) << 4)); };
      int k = -2 + (w8 & 1) * 32 + lane;
      uint32_t a0 = ub + swz(k - 1, 8), a1 = ub + swz(k, 8), a2 = ub + swz(k + 1, 8), aw = vb + swz(k, PADV);
      bar_sync(5, 384);
      mbar_wait_long(BAR(B_UCH + ch), 0);
      if (lane < 16 && !(w8 & 1)) {
        const uint32_t az = vb + swz(lane - 18, PADV);
        sts128(az + VV_U3, 0, 0, 0, 0); sts128(az + VV_U5, 0, 0, 0, 0); sts128(az + VV_U7, 0, 0, 0, 0); sts128(az + VV_U9, 0, 0, 0, 0);
      }
#pragma unroll 1
      for (; k - lane < 208; k += 64, a0 += 1024, a1 += 1024, a2 += 1024, aw += 1024) {
        const uint4 t0 = lds128(a0), t1 = lds128(a1), t2 = lds128(a2);
        const uint32_t E[12] = {t0.x, t0.y, t0.z, t0.w, t1.x, t1.y, t1.z, t1.w, t2.x, t2.y, t2.z, t2.w};
        uint32_t O[8];
#pragma unroll
        for (int j = 0; j < 8; ++j) O[j] = __byte_perm(E[j + 1], E[j + 2], 0x5432);
        uint32_t s3[6], s5[4], s7[4], s9[4];
#pragma unroll
        for (int j = 0; j < 6; ++j) s3[j] = badd(badd(O[j], O[j + 1]), E[j + 2]);
#pragma unroll
        for (int j = 0; j < 4; ++j) {
          s5[j] = badd(s3[j + 2], badd(E[j + 3], E[j + 5]));
          s7[j] = badd(s5[j], badd(O[j + 1], O[j + 4]));
          s9[j] = badd(s7[j], badd(E[j + 2], E[j + 6]));
        }
        if (k < 208) { sts128(aw + VV_U3, s3[0], s3[1], s3[2], s3[3]); sts128(aw + VV_U5, s5[0], s5[1], s5[2], s5[3]); }
        if (k < 144) { sts128(aw + VV_U7, s7[0], s7[1], s7[2], s7[3]); sts128(aw + VV_U9, s9[0], s9[1], s9[2], s9[3]); }
      }
      __syncwarp();
      bar_arrive(8 + ch, 128);
    }
    if (tid == 128) TS(6);
    if (warp == 4 && elect_one()) {
      wait_counter(&g_cnt[(C_KV + tj) * 32], (epoch + 1) * 16);
      mbar_expect_tx(BAR(B_KVF), 4352);
      bulk_load(sb + SM_KV, kvg, 4352, BAR(B_KVF));
    }
    __syncwarp();
    mbar_wait_long(BAR(B_KVF), 0);
    if (tid == 128) TS(19);
#pragma unroll 1
    for (int h = 0; h < 4; ++h) {
      uint32_t a[4];
      const uint32_t qa = sb + SM_QS + row * 128 + (((2 * h + (lane >> 4)) ^ (row & 7)) << 4);
      ldsm_x4(a, qa);
      const uint32_t kp = sb + SM_KV + h * 1088;
      const uint4 k0 = lds128(kp + lane * 16), k1 = lds128(kp + 512 + lane * 16);
      const uint32_t za = kp + 1024 + q * 8;
      auto pk2 = [](uint32_t x, uint32_t y) { return pack_bf16(__uint_as_float(x), __uint_as_float(y)); };
      float n0[4] = {0.f, 0.f, 0.f, 0.f}, n1[4] = {0.f, 0.f, 0.f, 0.f}, dn[4] = {0.f, 0.f, 0.f, 0.f};
      mma_bf16(n0, a[0], a[1], a[2], a[3], pk2(k0.x, k0.y), pk2(k1.x, k1.y));
      mma_bf16(n1, a[0], a[1], a[2], a[3], pk2(k0.z, k0.w), pk2(k1.z, k1.w));
      mma_bf16(dn, a[0], a[1], a[2], a[3], pack_bf16(lds_f32(za), lds_f32(za + 4)), pack_bf16(lds_f32(za + 32), lds_f32(za + 36)));
      const uint32_t dd = pack_bf16(dn[0], dn[2]);
      const uint32_t d2 = pack_bf16(bf_lo(dd) + 1e-6f, bf_hi(dd) + 1e-6f);
      const float r0 = rcp(bf_lo(d2)), r1 = rcp(bf_hi(d2));
      const uint32_t x0 = pack_bf16(n0[0], n0[1]), x1 = pack_bf16(n0[2], n0[3]);
      const uint32_t x2 = pack_bf16(n1[0], n1[1]), x3 = pack_bf16(n1[2], n1[3]);
      stsm_x4(qa, pack_bf16(bf_lo(x0) * r0, bf_hi(x0) * r0), pack_bf16(bf_lo(x1) * r1, bf_hi(x1) * r1),
              pack_bf16(bf_lo(x2) * r0, bf_hi(x2) * r0), pack_bf16(bf_lo(x3) * r1, bf_hi(x3) * r1));
    }
    fence_async_smem();
    bar_sync(1, 256);
    if (tid == 128) TS(57);
    if (warp == 4 && elect_one()) {
      tma_store_2d(&maps.o, sb + SM_QS, tj * 64, ti * 128);
      tma_store_2d(&maps.o, sb + SM_QS + 8192, tj * 64, ti * 128 + 64);
      bulk_commit();
      bulk_wait0();
      red_relaxed_add(&g_cnt[(C_O + ti) * 32], 1);
      TS(20);
      mbar_arrive_cluster(BAR(B_SLOT), 0);
      mbar_arrive_cluster(BAR(B_SLOT), 1);
      wait_counter(&g_cnt[(C_O + pi) * 32], (epoch + 1) * 8);
      if (cta == 0) g_epoch = epoch + 1;
      mbar_wait(BAR(B_SLOT), 0);
      TS(21);
#pragma unroll 1
      for (int c = 0; c < 4; ++c) {
        mbar_expect_tx(BAR(B_RF + c), 16384);
        tma_load_2d_mc(sb + SM_QS + c * 16384 + rank * 8192, &maps.o, c * 64, pi * 128 + rank * 64, BAR(B_RF + c), 3);
      }
      mbar_arrive(BAR(B_OST));
    }
    __syncwarp();
    mbar_wait_long(BAR(B_WO), 0);
    bar_sync(3, 512);
    {
      float o[32];
#pragma unroll 1
      for (int c = 0; c < 8; ++c) {
        mbar_wait_long(BAR(B_RF + c), 0);
        if (tid == 128) TSR(22, c == 0 ? 22 : 43 + c);
        const uint32_t slot = c < 4 ? SM_QS + c * 16384 : c < 7 ? SM_VV + (c - 4) * 16384 : SM_QS;
        const uint32_t da = mkdesc(sb + slot + (w8 >> 2) * 8192, 16);
        const uint32_t db = mkdesc(sb + SM_WO + c * 8192, 8192);
        wg_fence();
#pragma unroll
        for (int k = 0; k < 4; ++k) wgmma_n64(o, da + 2 * k, db + 128 * k, (c | k) != 0);
        wg_commit();
        if (c == 1) {
          wg_wait<1>();
          if (lane < 2) mbar_arrive_cluster(BAR(B_RE), lane);
        }
      }
      wg_wait<0>();
      if (tid == 128) TS(51);
      bar_sync(1, 256);
#pragma unroll
      for (int i = 0; i < 8; i += 2)
        stsm_x4(sb + SM_BOUT + row * 128 + (((i + (lane >> 4)) ^ (row & 7)) << 4), pack_bf16(o[4 * i], o[4 * i + 1]),
                pack_bf16(o[4 * i + 2], o[4 * i + 3]), pack_bf16(o[4 * i + 4], o[4 * i + 5]), pack_bf16(o[4 * i + 6], o[4 * i + 7]));
      fence_async_smem();
      bar_sync(1, 256);
      if (tid == 128) TS(52);
      if (warp == 4 && elect_one()) {
        tma_store_2d(&maps.out, sb + SM_BOUT, 512 + 64 * pj, 128 * pi);
        bulk_commit();
        bulk_wait_read0();
        TS(23);
      }
    }
  } else {
    asm volatile("setmaxnreg.dec.sync.aligned.u32 40;");
    if (warp == 12) {
      if (elect_one()) {
#pragma unroll 1
        for (int ks = NSTG, s = 0, ph = 0; ks < 16; ++ks) {
          mbar_wait(BAR(B_EMPTY + s), ph);
          issue_stage(ks, s);
          if (ks == NSTG) l2_prefetch((const char*)p.wo + (size_t)cta * 4096, 4096);
          if (++s == NSTG) { s = 0; ph ^= 1; }
        }
        mbar_wait(BAR(B_EMPTY + 6), 1);
        mbar_expect_tx(BAR(B_WO), 65536);
        tma_load_2d(sb + SM_WO, &maps.wo, pj * 64, 0, BAR(B_WO));
        tma_load_2d(sb + SM_WO + 32768, &maps.wo, pj * 64, 256, BAR(B_WO));
      }
    } else if (warp == 13) {
      bar_sync(6, 160);
      sts128(sb + SM_U + (lane >> 4) * U_BYTES + (lane & 15) * 16, 0, 0, 0, 0);
      sts128(sb + SM_U + (2 + (lane >> 4)) * U_BYTES + (lane & 15) * 16, 0, 0, 0, 0);
      __syncwarp();
      if (elect_one()) {
        tma_store_2d(&maps.uT, sb + SM_P, ti * 128, tj * 64);
        tma_store_2d(&maps.uT, sb + SM_P + 8192, ti * 128 + 64, tj * 64);
        bulk_commit();
        bulk_wait_read0();
        mbar_arrive(BAR(B_PFREE));
        bulk_wait0();
        red_relaxed_add(&g_cnt[(C_U + tj) * 32], 1);
        TS(27);
        wait_counter(&g_cnt[(C_U + (cta >> 4)) * 32], (epoch + 1) * 16);
#pragma unroll 1
        for (int c = 0; c < 4; ++c) {
          mbar_expect_tx(BAR(B_UCH + c), 4096);
          bulk_load(sb + SM_U + c * U_BYTES + 256, p.uT + (size_t)(cta * 4 + c) * 2048, 4096, BAR(B_UCH + c));
        }
        TS(3);
      }
      __syncwarp();
      if (ti == 0) {
        float4* z = (float4*)&g_kv[(epoch & 1) ^ 1][tj][0];
#pragma unroll 1
        for (int i = lane; i < 272; i += 32) z[i] = make_float4(0.f, 0.f, 0.f, 0.f);
      }
    }
    bar_sync(4, 512);
    asm volatile("setmaxnreg.inc.sync.aligned.u32 136;");
    {
      const int ch = warp - 12, d = cta * 4 + ch;
      const uint32_t ub = sb + SM_U + ch * U_BYTES, pb = sb + SM_P + ch * P_BYTES, vb = sb + SM_VV + ch * VV_BYTES;
      mbar_wait_long(BAR(B_UCH + ch), 0);
      conv_half<0>(ub, pb, vb, lane, (uint32_t)cta >> 20, ch, p.yT + (size_t)d * 2048);
      if (tid == 416) TS(40);
      if (lane < 2) mbar_arrive_cluster(BAR(B_CONVD), lane);
      bar_arrive(3, 512);
      if (elect_one()) {
        bulk_store(p.yT + (size_t)d * 2048, pb, 2048);
        bulk_commit();
        bulk_wait0();
        red_relaxed_add(&g_cnt[(C_Y + (cta >> 4)) * 32], 1);
      }
      __syncwarp();
      bar_arrive(2, 256);
      if (warp == 12 && elect_one()) {
        mbar_wait_long(BAR(B_OST), 0);
        mbar_wait_long(BAR(B_CONVD), 0);
#pragma unroll 1
        for (int c = 4; c < 8; ++c) {
          if (c == 7) mbar_wait(BAR(B_RE), 0);
          const uint32_t slot = c < 7 ? SM_VV + (c - 4) * 16384 : SM_QS;
          mbar_expect_tx(BAR(B_RF + c), 16384);
          tma_load_2d_mc(sb + slot + rank * 8192, &maps.o, c * 64, pi * 128 + rank * 64, BAR(B_RF + c), 3);
        }
      }
    }
  }
  __syncwarp();
  cluster_arrive();
  cluster_wait();
  if (tid == 0) TS(31);
#undef BAR
}

typedef CUresult (*EncodeFn)(CUtensorMap*, CUtensorMapDataType, cuuint32_t, void*, const cuuint64_t*, const cuuint64_t*,
                             const cuuint32_t*, const cuuint32_t*, CUtensorMapInterleave, CUtensorMapSwizzle,
                             CUtensorMapL2promotion, CUtensorMapFloatOOBfill);

static void make_map(EncodeFn enc, CUtensorMap* m, const void* base, uint64_t inner, uint64_t outer, uint32_t box_in,
                     uint32_t box_out, CUtensorMapSwizzle swz = CU_TENSOR_MAP_SWIZZLE_128B) {
  cuuint64_t gd[2] = {inner, outer};
  cuuint64_t gs[1] = {inner * 2};
  cuuint32_t bd[2] = {box_in, box_out};
  cuuint32_t es[2] = {1, 1};
  enc(m, CU_TENSOR_MAP_DATA_TYPE_BFLOAT16, 2, const_cast<void*>(base), gd, gs, bd, es, CU_TENSOR_MAP_INTERLEAVE_NONE,
      swz, CU_TENSOR_MAP_L2_PROMOTION_L2_128B, CU_TENSOR_MAP_FLOAT_OOB_FILL_NONE);
}

}

extern "C" void kernel_launch(void* const* d_in, const int* in_sizes, int n_in, void* d_out, int out_size) {
  using namespace s4la;
  (void)in_sizes; (void)n_in; (void)out_size;
  static EncodeFn enc = nullptr;
  static void *uT = nullptr, *yT = nullptr, *oS = nullptr;
  if (!enc) {
    void* fn = nullptr;
    cudaDriverEntryPointQueryResult qr;
    cudaGetDriverEntryPoint("cuTensorMapEncodeTiled", &fn, cudaEnableDefault, &qr);
    enc = (EncodeFn)fn;
    cudaGetSymbolAddress(&uT, g_uT);
    cudaGetSymbolAddress(&yT, g_yT);
    cudaGetSymbolAddress(&oS, g_o);
    cudaFuncSetAttribute(fused_kernel, cudaFuncAttributeMaxDynamicSharedMemorySize, SM_TOTAL);
  }
  const __nv_bfloat16* const* in = (const __nv_bfloat16* const*)d_in;
  Maps maps;
  make_map(enc, &maps.x, in[9], 512, 2048, 32, 128, CU_TENSOR_MAP_SWIZZLE_64B);
  {
    cuuint64_t gd[3] = {512, 512, 3};
    cuuint64_t gs[2] = {3072, 1024};
    cuuint32_t bd[3] = {64, 16, 3};
    cuuint32_t es[3] = {1, 1, 1};
    enc(&maps.w, CU_TENSOR_MAP_DATA_TYPE_BFLOAT16, 3, const_cast<__nv_bfloat16*>(in[10]), gd, gs, bd, es,
        CU_TENSOR_MAP_INTERLEAVE_NONE, CU_TENSOR_MAP_SWIZZLE_128B, CU_TENSOR_MAP_L2_PROMOTION_L2_128B,
        CU_TENSOR_MAP_FLOAT_OOB_FILL_NONE);
  }
  make_map(enc, &maps.wo, in[11], 512, 512, 64, 256);
  make_map(enc, &maps.u, in[0], 512, 2048, 64, 128);
  make_map(enc, &maps.uT, uT, 2048, 512, 64, 64);
  make_map(enc, &maps.yT, yT, 2048, 512, 64, 64);
  make_map(enc, &maps.o, oS, 512, 2048, 64, 64);
  make_map(enc, &maps.out, d_out, 1024, 2048, 64, 128);
  Ptrs p;
  p.A_re = in[1]; p.A_im = in[2]; p.B_re = in[3]; p.B_im = in[4]; p.C_re = in[5]; p.C_im = in[6];
  p.log_dt = in[7]; p.Dskip = in[8]; p.x = in[9]; p.wqkv = in[10]; p.wo = in[11];
  p.uT = (__nv_bfloat16*)uT; p.yT = (__nv_bfloat16*)yT;
  fused_kernel<<<NCTA, NTHREADS, SM_TOTAL, cudaStreamPerThread>>>(maps, p);
}
```

```cpp
#include <cuda_runtime.h>
#include <cuda_bf16.h>
#include <cuda_fp16.h>
#include <cuda.h>
#include <stdint.h>

#define DEVI __device__ __forceinline__

namespace s4la {

constexpr int NTHREADS = 512;
constexpr int NCTA = 128;

constexpr int NSTG = 7;
constexpr uint32_t STG_BYTES = 20480, STG_X = 0, STG_W = 8192;
constexpr uint32_t SM_QS = 0;
constexpr uint32_t SM_PK = SM_QS + 16384, SM_VS = SM_QS + 32768;
constexpr uint32_t SM_WO = 65536;
constexpr uint32_t SM_KV = 131072;
constexpr uint32_t SM_BOUT = 16384;
constexpr uint32_t SM_U = 143360, U_BYTES = 4352;
constexpr uint32_t SM_P = 160768, P_BYTES = 4096;
constexpr uint32_t SM_VV = 177152, VV_BYTES = 12800;
constexpr uint32_t VV_U5 = 0, VV_U3 = 3712, VV_U9 = 7424, VV_U7 = 10112;
constexpr uint32_t KG_BYTES = 3200;
constexpr uint32_t SM_BAR = SM_VV + 4 * VV_BYTES;
constexpr uint32_t SM_PTAB = SM_BAR + 320;
constexpr uint32_t SM_TOTAL = SM_PTAB + 2048;
static_assert(SM_TOTAL <= 232448, "shared memory");
constexpr int PADV = 12;

enum { B_FULL = 0, B_EMPTY = 7, B_TILE = 14, B_UCH = 15, B_KVP = 19, B_KVF = 20, B_OST = 21, B_RF = 22, B_WO = 30, B_RE = 31, B_PFREE = 32, B_CONVD = 33, B_SLOT = 34, B_COUNT = 35 };
__host__ __device__ constexpr int bar_count(int i) {
  return (i >= B_EMPTY && i < B_TILE) ? 16 : (i == B_KVP || i == B_OST || i == B_CONVD) ? 8 : i == B_RE ? 16 : i == B_SLOT ? 2 : 1;
}

constexpr int PD_OFF = 0, P2_OFF = 544, P3_OFF = 768;

constexpr int SL_K2048 = 20, SL_ZERO = 21, SL_510 = 22, SL_0 = 23;
__host__ __device__ constexpr int koff(int y) {
  return y < 8 ? y : y < 12 ? 256 + 2 * (y - 8) : y < 16 ? 512 + 256 * ((y - 12) >> 1) + 4 * (y & 1) : 1024 + 256 * (y - 16);
}
__host__ __device__ constexpr int kidx_c(int l) {
  const int y = l < 256 ? (l & 7) : l < 512 ? 8 + ((l & 7) >> 1) : l < 1024 ? 12 + (((l - 512) >> 8) << 1) + ((l >> 2) & 1)
                                                                            : 16 + ((l - 1024) >> 8);
  return ((l >> 3) & 31) * 24 + y;
}
constexpr int slot_direct(int l) {
  if (l < 0 || l > 510) return SL_ZERO;
  if (l == 510) return SL_510;
  if (l == 0) return SL_0;
  return kidx_c(l < 256 ? l : ((l + ((l >> 1) & 1)) & ~1));
}
constexpr int slot_seg2(int v, int k) { return (k >= 32 && k < 64) ? kidx_c(16 * k + 4 * v) : SL_ZERO; }
constexpr int slot_seg3(int pi, int k) {
  return (k >= 64 && k < 128) ? kidx_c(16 * k + 8 * pi) : ((k == 128 && pi == 0) ? SL_K2048 : SL_ZERO);
}
constexpr int slot_word(int w) {
  return w < 0 ? SL_ZERO : w < 544 ? slot_direct(w - 16) : w < 768 ? slot_seg2((w - 544) / 56, 16 + (w - 544) % 56)
       : w < 944 ? slot_seg3((w - 768) / 88, 48 + (w - 768) % 88) : SL_ZERO;
}
struct PTab { uint32_t v[512]; };
constexpr PTab make_ptab() {
  PTab t{};
  for (int lane = 0; lane < 32; ++lane)
    for (int i = 0; i < 16; ++i)
      t.v[i * 32 + lane] = (slot_word(31 * lane - 1 + 2 * i) * 4) | ((slot_word(31 * lane + 2 * i) * 4) << 16);
  return t;
}
__device__ const PTab g_ptab = make_ptab();

__device__ __nv_bfloat16 g_uT[512 * 2048];
__device__ __nv_bfloat16 g_yT[512 * 2048];
__device__ __nv_bfloat16 g_o[2048 * 512];
__device__ float g_kv[2][8][4 * 272];
__device__ unsigned g_cnt[64 * 32];
__device__ unsigned g_epoch;
#define TS(slot) do { } while (0)
#define TSR(on, slot) do { } while (0)
#define TSD(slot) do { } while (0)
enum { C_U = 0, C_KV = 8, C_O = 16, C_Y = 32 };

struct Maps {
  CUtensorMap x, w, wo, u, uT, yT, o, out;
};
struct Ptrs {
  const __nv_bfloat16 *A_re, *A_im, *B_re, *B_im, *C_re, *C_im, *log_dt, *Dskip;
  const __nv_bfloat16 *x, *wqkv, *wo;
  __nv_bfloat16 *uT, *yT;
};

DEVI uint32_t s2u(const void* p) { return (uint32_t)__cvta_generic_to_shared(p); }
DEVI void mbar_init(uint32_t b, uint32_t c) { asm volatile("mbarrier.init.shared::cta.b64 [%0], %1;" ::"r"(b), "r"(c) : "memory"); }
DEVI void mbar_expect_tx(uint32_t b, uint32_t bytes) {
  asm volatile("mbarrier.arrive.expect_tx.shared::cta.b64 _, [%0], %1;" ::"r"(b), "r"(bytes) : "memory");
}
DEVI void mbar_arrive(uint32_t b) { asm volatile("mbarrier.arrive.shared::cta.b64 _, [%0];" ::"r"(b) : "memory"); }
DEVI void mbar_arrive_cluster(uint32_t b, uint32_t cta) {
  asm volatile("{\n.reg .b32 r;\nmapa.shared::cluster.u32 r, %0, %1;\nmbarrier.arrive.shared::cluster.b64 _, [r];\n}"
               ::"r"(b), "r"(cta) : "memory");
}
DEVI void mbar_wait(uint32_t b, uint32_t parity) {
  asm volatile("{\n.reg .pred p;\nLAB_WAIT:\nmbarrier.try_wait.parity.shared::cta.b64 p, [%0], %1;\n@!p bra LAB_WAIT;\n}"
               ::"r"(b), "r"(parity) : "memory");
}
DEVI void mbar_wait_long(uint32_t b, uint32_t parity) {
  asm volatile("{\n.reg .pred p;\nLAB_WAIT:\nmbarrier.try_wait.parity.shared::cta.b64 p, [%0], %1, 0x989680;\n@!p bra LAB_WAIT;\n}"
               ::"r"(b), "r"(parity) : "memory");
}
DEVI void bar_sync(int id, int n) { asm volatile("bar.sync %0, %1;" ::"r"(id), "r"(n) : "memory"); }
DEVI void bar_arrive(int id, int n) { asm volatile("bar.arrive %0, %1;" ::"r"(id), "r"(n) : "memory"); }
DEVI void fence_async_smem() { asm volatile("fence.proxy.async.shared::cta;" ::: "memory"); }
DEVI void fence_async_all() { asm volatile("fence.proxy.async;" ::: "memory"); }
DEVI void cluster_arrive() { asm volatile("barrier.cluster.arrive.relaxed.aligned;" ::: "memory"); }
DEVI void cluster_wait() { asm volatile("barrier.cluster.wait.aligned;" ::: "memory"); }

DEVI void tma_load_2d(uint32_t dst, const CUtensorMap* m, int c0, int c1, uint32_t bar) {
  asm volatile("cp.async.bulk.tensor.2d.shared::cluster.global.mbarrier::complete_tx::bytes [%0], [%1, {%3, %4}], [%2];"
               ::"r"(dst), "l"(m), "r"(bar), "r"(c0), "r"(c1) : "memory");
}
DEVI void tma_load_2d_mc(uint32_t dst, const CUtensorMap* m, int c0, int c1, uint32_t bar, uint16_t mask) {
  asm volatile("cp.async.bulk.tensor.2d.shared::cluster.global.mbarrier::complete_tx::bytes.multicast::cluster [%0], [%1, {%3, %4}], [%2], %5;"
               ::"r"(dst), "l"(m), "r"(bar), "r"(c0), "r"(c1), "h"(mask) : "memory");
}
DEVI void tma_load_3d_mc(uint32_t dst, const CUtensorMap* m, int c0, int c1, int c2, uint32_t bar, uint16_t mask) {
  asm volatile("cp.async.bulk.tensor.3d.shared::cluster.global.mbarrier::complete_tx::bytes.multicast::cluster [%0], [%1, {%3, %4, %5}], [%2], %6;"
               ::"r"(dst), "l"(m), "r"(bar), "r"(c0), "r"(c1), "r"(c2), "h"(mask) : "memory");
}
DEVI void tma_store_2d(const CUtensorMap* m, uint32_t src, int c0, int c1) {
  asm volatile("cp.async.bulk.tensor.2d.global.shared::cta.bulk_group [%0, {%2, %3}], [%1];"
               ::"l"(m), "r"(src), "r"(c0), "r"(c1) : "memory");
}
DEVI void bulk_load(uint32_t dst, const void* src, uint32_t bytes, uint32_t bar) {
  asm volatile("cp.async.bulk.shared::cluster.global.mbarrier::complete_tx::bytes [%0], [%1], %2, [%3];"
               ::"r"(dst), "l"(src), "r"(bytes), "r"(bar) : "memory");
}
DEVI void bulk_store(void* dst, uint32_t src, uint32_t bytes) {
  asm volatile("cp.async.bulk.global.shared::cta.bulk_group [%0], [%1], %2;" ::"l"(dst), "r"(src), "r"(bytes) : "memory");
}
DEVI void bulk_reduce_add_f32(void* dst, uint32_t src, uint32_t bytes) {
  asm volatile("cp.reduce.async.bulk.global.shared::cta.bulk_group.add.f32 [%0], [%1], %2;" ::"l"(dst), "r"(src), "r"(bytes) : "memory");
}
DEVI void bulk_commit() { asm volatile("cp.async.bulk.commit_group;" ::: "memory"); }
DEVI void bulk_wait0() { asm volatile("cp.async.bulk.wait_group 0;" ::: "memory"); }
DEVI void bulk_wait_read0() { asm volatile("cp.async.bulk.wait_group.read 0;" ::: "memory"); }
DEVI void l2_prefetch(const void* p, uint32_t bytes) {
  asm volatile("cp.async.bulk.prefetch.L2.global [%0], %1;" ::"l"(p), "r"(bytes) : "memory");
}
DEVI void prefetch_tmap(const CUtensorMap* m) { asm volatile("prefetch.tensormap [%0];" ::"l"(m) : "memory"); }

DEVI void red_release_add(unsigned* p, unsigned v) {
  asm volatile("red.release.gpu.global.add.u32 [%0], %1;" ::"l"(p), "r"(v) : "memory");
}
DEVI void red_relaxed_add(unsigned* p, unsigned v) {
  asm volatile("red.relaxed.gpu.global.add.u32 [%0], %1;" ::"l"(p), "r"(v) : "memory");
}
DEVI unsigned ld_relaxed(const unsigned* p) {
  unsigned v;
  asm volatile("ld.relaxed.gpu.global.u32 %0, [%1];" : "=r"(v) : "l"(p) : "memory");
  return v;
}
DEVI void wait_counter(const unsigned* p, unsigned target) {
#pragma unroll 1
  for (int it = 0; (int)(ld_relaxed(p) - target) < 0; ++it)
    if (it > (1 << 22)) __trap();
}

DEVI void ldsm_x4(uint32_t (&r)[4], uint32_t a) {
  asm volatile("ldmatrix.sync.aligned.m8n8.x4.shared.b16 {%0,%1,%2,%3}, [%4];"
               : "=r"(r[0]), "=r"(r[1]), "=r"(r[2]), "=r"(r[3]) : "r"(a) : "memory");
}
DEVI void ldsm_x4_t(uint32_t (&r)[4], uint32_t a) {
  asm volatile("ldmatrix.sync.aligned.m8n8.x4.trans.shared.b16 {%0,%1,%2,%3}, [%4];"
               : "=r"(r[0]), "=r"(r[1]), "=r"(r[2]), "=r"(r[3]) : "r"(a) : "memory");
}
DEVI void ldsm_x2_t(uint32_t& r0, uint32_t& r1, uint32_t a) {
  asm volatile("ldmatrix.sync.aligned.m8n8.x2.trans.shared.b16 {%0,%1}, [%2];" : "=r"(r0), "=r"(r1) : "r"(a) : "memory");
}
DEVI void stsm_x4(uint32_t a, uint32_t r0, uint32_t r1, uint32_t r2, uint32_t r3) {
  asm volatile("stmatrix.sync.aligned.m8n8.x4.shared.b16 [%0], {%1,%2,%3,%4};"
               ::"r"(a), "r"(r0), "r"(r1), "r"(r2), "r"(r3) : "memory");
}
DEVI void stsm_x4_t(uint32_t a, uint32_t r0, uint32_t r1, uint32_t r2, uint32_t r3) {
  asm volatile("stmatrix.sync.aligned.m8n8.x4.trans.shared.b16 [%0], {%1,%2,%3,%4};"
               ::"r"(a), "r"(r0), "r"(r1), "r"(r2), "r"(r3) : "memory");
}
DEVI uint32_t lds32(uint32_t a) { uint32_t v; asm volatile("ld.shared.b32 %0, [%1];" : "=r"(v) : "r"(a) : "memory"); return v; }
DEVI float lds_f32(uint32_t a) { float v; asm volatile("ld.shared.f32 %0, [%1];" : "=f"(v) : "r"(a) : "memory"); return v; }
DEVI void sts32(uint32_t a, uint32_t v) { asm volatile("st.shared.b32 [%0], %1;" ::"r"(a), "r"(v) : "memory"); }
DEVI void sts_f32(uint32_t a, float v) { asm volatile("st.shared.f32 [%0], %1;" ::"r"(a), "f"(v) : "memory"); }
DEVI void sts_f32x2(uint32_t a, float x, float y) { asm volatile("st.shared.v2.f32 [%0], {%1,%2};" ::"r"(a), "f"(x), "f"(y) : "memory"); }
DEVI uint4 lds128(uint32_t a) {
  uint4 v;
  asm volatile("ld.shared.v4.b32 {%0,%1,%2,%3}, [%4];" : "=r"(v.x), "=r"(v.y), "=r"(v.z), "=r"(v.w) : "r"(a) : "memory");
  return v;
}
DEVI void sts128(uint32_t a, uint32_t x, uint32_t y, uint32_t z, uint32_t w) {
  asm volatile("st.shared.v4.b32 [%0], {%1,%2,%3,%4};" ::"r"(a), "r"(x), "r"(y), "r"(z), "r"(w) : "memory");
}

DEVI void mma_bf16(float (&d)[4], uint32_t a0, uint32_t a1, uint32_t a2, uint32_t a3, uint32_t b0, uint32_t b1) {
  asm("mma.sync.aligned.m16n8k16.row.col.f32.bf16.bf16.f32 {%0,%1,%2,%3}, {%4,%5,%6,%7}, {%8,%9}, {%0,%1,%2,%3};"
      : "+f"(d[0]), "+f"(d[1]), "+f"(d[2]), "+f"(d[3])
      : "r"(a0), "r"(a1), "r"(a2), "r"(a3), "r"(b0), "r"(b1));
}
DEVI void mma_f16(float (&d)[4], const uint32_t (&a)[4], uint32_t b0, uint32_t b1) {
  asm("mma.sync.aligned.m16n8k16.row.col.f32.f16.f16.f32 {%0,%1,%2,%3}, {%4,%5,%6,%7}, {%8,%9}, {%0,%1,%2,%3};"
      : "+f"(d[0]), "+f"(d[1]), "+f"(d[2]), "+f"(d[3])
      : "r"(a[0]), "r"(a[1]), "r"(a[2]), "r"(a[3]), "r"(b0), "r"(b1));
}
DEVI void mma_bf16v(float (&d)[4], const uint32_t (&a)[4], uint32_t b0, uint32_t b1) {
  asm volatile("mma.sync.aligned.m16n8k16.row.col.f32.bf16.bf16.f32 {%0,%1,%2,%3}, {%4,%5,%6,%7}, {%8,%9}, {%0,%1,%2,%3};"
               : "+f"(d[0]), "+f"(d[1]), "+f"(d[2]), "+f"(d[3])
               : "r"(a[0]), "r"(a[1]), "r"(a[2]), "r"(a[3]), "r"(b0), "r"(b1));
}
DEVI uint32_t pack_bf16(float lo, float hi) {
  uint32_t r;
  asm("cvt.rn.bf16x2.f32 %0, %1, %2;" : "=r"(r) : "f"(hi), "f"(lo));
  return r;
}
DEVI uint32_t pack_f16(float lo, float hi) {
  uint32_t r;
  asm("cvt.rn.f16x2.f32 %0, %1, %2;" : "=r"(r) : "f"(hi), "f"(lo));
  return r;
}
DEVI uint32_t ldg16(const __nv_bfloat16* p) {
  uint32_t v;
  asm volatile("ld.global.nc.u16 %0, [%1];" : "=r"(v) : "l"(p));
  return v;
}
DEVI bool elect_one() {
  uint32_t pred;
  asm volatile("{\n.reg .pred p;\nelect.sync _|p, 0xffffffff;\nselp.u32 %0, 1, 0, p;\n}" : "=r"(pred));
  return pred != 0;
}
DEVI float bf_lo(uint32_t v) { return __uint_as_float(v << 16); }
DEVI float bf_hi(uint32_t v) { return __uint_as_float(v & 0xffff0000u); }
DEVI float bf2f(__nv_bfloat16 v) { return __bfloat162float(v); }
DEVI float round_bf16(float v) { return __bfloat162float(__float2bfloat16_rn(v)); }
DEVI float rcp(float x) { float r; asm("rcp.approx.ftz.f32 %0, %1;" : "=f"(r) : "f"(x)); return r; }
DEVI float ex2(float x) { float r; asm("ex2.approx.ftz.f32 %0, %1;" : "=f"(r) : "f"(x)); return r; }

DEVI void wg_fence() { asm volatile("wgmma.fence.sync.aligned;" ::: "memory"); }
DEVI void wg_commit() { asm volatile("wgmma.commit_group.sync.aligned;" ::: "memory"); }
template <int N> DEVI void wg_wait() { asm volatile("wgmma.wait_group.sync.aligned %0;" ::"n"(N) : "memory"); }
constexpr uint32_t DESC_HI = (1u << 30) | (1024 >> 4);
constexpr uint32_t DESC_HI64 = (2u << 30) | (512 >> 4);
DEVI uint32_t mkdesc(uint32_t saddr, uint32_t lbo) { return ((saddr & 0x3FFFF) >> 4) | ((lbo >> 4) << 16); }

#define R8(b) "%" #b
DEVI void wgmma_n192(float (&d)[96], uint32_t da, uint32_t db, int scale_d) {
  asm volatile(
      "{\n.reg .pred p;\n.reg .b64 da, db;\nsetp.ne.b32 p, %98, 0;\nmov.b64 da, {%96, %100};\nmov.b64 db, {%97, %99};\n"
      "wgmma.mma_async.sync.aligned.m64n192k16.f32.bf16.bf16 "
      "{%0,%1,%2,%3,%4,%5,%6,%7,%8,%9,%10,%11,%12,%13,%14,%15,"
      "%16,%17,%18,%19,%20,%21,%22,%23,%24,%25,%26,%27,%28,%29,%30,%31,"
      "%32,%33,%34,%35,%36,%37,%38,%39,%40,%41,%42,%43,%44,%45,%46,%47,"
      "%48,%49,%50,%51,%52,%53,%54,%55,%56,%57,%58,%59,%60,%61,%62,%63,"
      "%64,%65,%66,%67,%68,%69,%70,%71,%72,%73,%74,%75,%76,%77,%78,%79,"
      "%80,%81,%82,%83,%84,%85,%86,%87,%88,%89,%90,%91,%92,%93,%94,%95}, "
      "da, db, p, 1, 1, 0, 1;\n}"
      : "+f"(d[0]), "+f"(d[1]), "+f"(d[2]), "+f"(d[3]), "+f"(d[4]), "+f"(d[5]), "+f"(d[6]), "+f"(d[7]),
        "+f"(d[8]), "+f"(d[9]), "+f"(d[10]), "+f"(d[11]), "+f"(d[12]), "+f"(d[13]), "+f"(d[14]), "+f"(d[15]),
        "+f"(d[16]), "+f"(d[17]), "+f"(d[18]), "+f"(d[19]), "+f"(d[20]), "+f"(d[21]), "+f"(d[22]), "+f"(d[23]),
        "+f"(d[24]), "+f"(d[25]), "+f"(d[26]), "+f"(d[27]), "+f"(d[28]), "+f"(d[29]), "+f"(d[30]), "+f"(d[31]),
        "+f"(d[32]), "+f"(d[33]), "+f"(d[34]), "+f"(d[35]), "+f"(d[36]), "+f"(d[37]), "+f"(d[38]), "+f"(d[39]),
        "+f"(d[40]), "+f"(d[41]), "+f"(d[42]), "+f"(d[43]), "+f"(d[44]), "+f"(d[45]), "+f"(d[46]), "+f"(d[47]),
        "+f"(d[48]), "+f"(d[49]), "+f"(d[50]), "+f"(d[51]), "+f"(d[52]), "+f"(d[53]), "+f"(d[54]), "+f"(d[55]),
        "+f"(d[56]), "+f"(d[57]), "+f"(d[58]), "+f"(d[59]), "+f"(d[60]), "+f"(d[61]), "+f"(d[62]), "+f"(d[63]),
        "+f"(d[64]), "+f"(d[65]), "+f"(d[66]), "+f"(d[67]), "+f"(d[68]), "+f"(d[69]), "+f"(d[70]), "+f"(d[71]),
        "+f"(d[72]), "+f"(d[73]), "+f"(d[74]), "+f"(d[75]), "+f"(d[76]), "+f"(d[77]), "+f"(d[78]), "+f"(d[79]),
        "+f"(d[80]), "+f"(d[81]), "+f"(d[82]), "+f"(d[83]), "+f"(d[84]), "+f"(d[85]), "+f"(d[86]), "+f"(d[87]),
        "+f"(d[88]), "+f"(d[89]), "+f"(d[90]), "+f"(d[91]), "+f"(d[92]), "+f"(d[93]), "+f"(d[94]), "+f"(d[95])
      : "r"(da), "r"(db), "r"(scale_d), "n"(DESC_HI), "n"(DESC_HI64));
}
DEVI void wgmma_n64(float (&d)[32], uint32_t da, uint32_t db, int scale_d) {
  asm volatile(
      "{\n.reg .pred p;\n.reg .b64 da, db;\nsetp.ne.b32 p, %34, 0;\nmov.b64 da, {%32, %35};\nmov.b64 db, {%33, %35};\n"
      "wgmma.mma_async.sync.aligned.m64n64k16.f32.bf16.bf16 "
      "{%0,%1,%2,%3,%4,%5,%6,%7,%8,%9,%10,%11,%12,%13,%14,%15,"
      "%16,%17,%18,%19,%20,%21,%22,%23,%24,%25,%26,%27,%28,%29,%30,%31}, "
      "da, db, p, 1, 1, 0, 1;\n}"
      : "+f"(d[0]), "+f"(d[1]), "+f"(d[2]), "+f"(d[3]), "+f"(d[4]), "+f"(d[5]), "+f"(d[6]), "+f"(d[7]),
        "+f"(d[8]), "+f"(d[9]), "+f"(d[10]), "+f"(d[11]), "+f"(d[12]), "+f"(d[13]), "+f"(d[14]), "+f"(d[15]),
        "+f"(d[16]), "+f"(d[17]), "+f"(d[18]), "+f"(d[19]), "+f"(d[20]), "+f"(d[21]), "+f"(d[22]), "+f"(d[23]),
        "+f"(d[24]), "+f"(d[25]), "+f"(d[26]), "+f"(d[27]), "+f"(d[28]), "+f"(d[29]), "+f"(d[30]), "+f"(d[31])
      : "r"(da), "r"(db), "r"(scale_d), "n"(DESC_HI));
}

struct C32 { float re, im; };
DEVI C32 csq(C32 a) { return {a.re * a.re - a.im * a.im, 2.f * a.re * a.im}; }
DEVI C32 cmul(C32 a, C32 b) { return {a.re * b.re - a.im * b.im, a.re * b.im + a.im * b.re}; }
DEVI C32 cfresh(float zl, float zi, float m) {
  float mag = ex2(zl * m), ph = zi * m;
  return {mag * __cosf(ph), mag * __sinf(ph)};
}
struct HMul { uint32_t b, bp; };
DEVI HMul mk_mul(float re, float im) { return {pack_f16(re, im), pack_f16(-im, re)}; }
DEVI uint32_t hcmul(uint32_t a, const HMul& m) {
  __half2 ah = *reinterpret_cast<__half2*>(&a);
  __half2 b = *reinterpret_cast<const __half2*>(&m.b), bp = *reinterpret_cast<const __half2*>(&m.bp);
  __half2 r = __hfma2(__high2half2(ah), bp, __hmul2(__low2half2(ah), b));
  return *reinterpret_cast<uint32_t*>(&r);
}
DEVI uint32_t badd(uint32_t a, uint32_t b) {
  __nv_bfloat162 r = __hadd2(*reinterpret_cast<__nv_bfloat162*>(&a), *reinterpret_cast<__nv_bfloat162*>(&b));
  return *reinterpret_cast<uint32_t*>(&r);
}
template <int MU0, int NMU, int DMAX>
DEVI void conv_tail(float (&acc)[16][4], uint32_t p_lane, uint32_t v_base, int back, bool edge, int lane) {
  const int hsel = (lane >> 3) & 1;
  const int row = (lane & 7) + ((lane >> 4) << 3) + PADV - 8 - (back & (hsel ^ 1));
  const uint32_t la = v_base + row * 32 + (((hsel ^ back) ^ ((row >> 2) & 1)) << 4);
  uint32_t M[3][4];
  ldsm_x4_t(M[0], la);
  ldsm_x4_t(M[1], la + 256);
  uint32_t H[2 * NMU];
#pragma unroll
  for (int i = 0; i < 2 * NMU; ++i) H[i ^ 1] = lds32(p_lane + (uint32_t)(MU0 - 1 + i) * 32);
  if (edge) {
    const uint32_t a[4] = {0u, 0u, M[0][0], M[0][1]};
#pragma unroll
    for (int k = 1; k < NMU; ++k) mma_bf16v(acc[MU0 - 2 + 2 * k], a, H[2 * k], H[2 * k + 1]);
  }
#pragma unroll
  for (int delta = -1; delta <= DMAX; ++delta) {
    if (delta + 2 <= DMAX) ldsm_x4_t(M[(delta + 3) % 3], la + (delta + 3) * 256);
#pragma unroll
    for (int k = 0; k < NMU; ++k)
      if (delta + MU0 + 2 * k < 16) mma_bf16v(acc[delta + MU0 + 2 * k], M[(delta + 1) % 3], H[2 * k], H[2 * k + 1]);
  }
}

__global__ void __cluster_dims__(2, 1, 1) __launch_bounds__(NTHREADS, 1)
fused_kernel(const __grid_constant__ Maps maps, const Ptrs p) {
  extern __shared__ __align__(1024) uint8_t smem[];
  const uint32_t sb = s2u(smem);
  const int tid = threadIdx.x, lane = tid & 31;
  const int warp = __shfl_sync(0xffffffffu, tid >> 5, 0);
  const int cta = blockIdx.x;
  const uint32_t rank = cta & 1;
  const int ti = 2 * (cta >> 4) + rank;
  const int tj = (cta >> 1) & 7;
  const int pi = cta >> 3, pj = cta & 7;
  const uint32_t bars = sb + SM_BAR;
#define BAR(i) (bars + 8 * (i))
  const int g = lane >> 2, q = lane & 3;

  auto issue_stage = [&](int ks, int s) {
    const uint32_t st = sb + s * STG_BYTES, fb = BAR(B_FULL + s);
    mbar_expect_tx(fb, STG_BYTES);
    tma_load_2d(st + STG_X, &maps.x, ks * 32, ti * 128, fb);
    tma_load_3d_mc(st + STG_W + rank * 6144, &maps.w, tj * 64, ks * 32 + rank * 16, 0, fb, 3);
  };

  const int kch = warp & 3, krd = warp >> 2;
  float zr, zi, wr, wi;
  unsigned epoch;
  uint32_t r_dskip;
  {
    const size_t po = (size_t)(cta * 4 + kch) * 128 + krd * 32 + lane;
    const uint32_t r_ar = ldg16(p.A_re + po), r_ai = ldg16(p.A_im + po), r_br = ldg16(p.B_re + po), r_bi = ldg16(p.B_im + po);
    const uint32_t r_cr = ldg16(p.C_re + po), r_ci = ldg16(p.C_im + po), r_ldt = ldg16(p.log_dt + cta * 4 + kch);
    epoch = __ldcg(&g_epoch);
    r_dskip = ldg16(p.Dskip + cta * 4 + kch);
    uint4 pt;
    if (tid < 128) pt = __ldg((const uint4*)g_ptab.v + tid);
    if (tid == 384) {
      TS(0);
#pragma unroll
      for (int i = 0; i < B_COUNT; ++i) mbar_init(BAR(i), bar_count(i));
      asm volatile("fence.mbarrier_init.release.cluster;" ::: "memory");
      prefetch_tmap(&maps.x); prefetch_tmap(&maps.w); prefetch_tmap(&maps.u);
    }
    __syncthreads();
    cluster_arrive();
    if (warp >= 12) {
      cluster_wait();
      if (elect_one()) {
        if (warp == 13) {
          mbar_expect_tx(BAR(B_TILE), 16384);
          tma_load_2d(sb + SM_U, &maps.u, tj * 64, ti * 128, BAR(B_TILE));
          prefetch_tmap(&maps.uT); prefetch_tmap(&maps.wo); prefetch_tmap(&maps.o); prefetch_tmap(&maps.yT);
          prefetch_tmap(&maps.out);
        } else {
          if (warp == 12) TS(61);
          { const int ks = warp == 12 ? 0 : warp - 13; issue_stage(ks, ks); }
        }
      }
      __syncwarp();
    }
    if (tid < 128) sts128(sb + SM_PTAB + tid * 16, pt.x, pt.y, pt.z, pt.w);
    const float dt = round_bf16(expf(bf_lo(r_ldt)));
    zr = dt * bf_lo(r_ar); zi = dt * bf_lo(r_ai);
    const float dbr = dt * bf_lo(r_br), dbi = dt * bf_lo(r_bi), cr = bf_lo(r_cr), ci = bf_lo(r_ci);
    wr = cr * dbr - ci * dbi; wi = cr * dbi + ci * dbr;
  }
  {
    const float mz = __uint_as_float(__reduce_max_sync(0xffffffffu, __float_as_uint(fmaxf(zr, 0.f))));
    const int E = min(max((int)(__reduce_max_sync(0xffffffffu, __float_as_uint(fmaxf(fabsf(wr), fabsf(wi)))) >> 23), 1), 252);
    const float sc = __int_as_float((253 - E) << 23), inv = __int_as_float((E + 1) << 23);
    const float zl = (zr - mz) * 1.4426950408889634f;
    const uint32_t tb = sb + SM_VV + kch * VV_BYTES + krd * KG_BYTES;
    const uint32_t sta = tb + (((lane >> 2) << 4) | ((lane & 3) << 2));
    auto put = [&](int r, uint32_t v) { sts32((sta ^ ((r & 7) << 4)) + r * 128, v); };
    const uint32_t lda = tb + ((lane & 7) + (((lane >> 3) & 1) << 3)) * 128;
    const uint32_t ldb = tb + ((lane & 7) + ((lane >> 4) << 3)) * 128;
    C32 e1 = cfresh(zl, zi, 1.f), e2 = csq(e1), e4 = csq(e2), e8 = csq(e4);
    C32 e16 = cfresh(zl, zi, 16.f), e32 = csq(e16), e64 = csq(e32), e128 = csq(e64);
    C32 e256 = cfresh(zl, zi, 256.f), e512 = csq(e256), e1024 = csq(e512), e768 = cmul(e512, e256);
    uint32_t XA[2][4][4];
    {
      const HMul m16 = mk_mul(e16.re, e16.im), m32 = mk_mul(e32.re, e32.im), m64 = mk_mul(e64.re, e64.im);
      const HMul m128 = mk_mul(e128.re, e128.im);
      uint32_t X[16];
      X[0] = 0x00003c00u; X[1] = pack_f16(e8.re, e8.im); X[2] = m16.b; X[4] = m32.b; X[8] = m64.b;
      X[3] = hcmul(X[1], m16); X[5] = hcmul(X[1], m32); X[6] = hcmul(X[2], m32); X[7] = hcmul(X[3], m32);
#pragma unroll
      for (int r = 1; r < 8; ++r) X[8 + r] = hcmul(X[r], m64);
#pragma unroll
      for (int h = 0; h < 2; ++h) {
#pragma unroll
        for (int r = 0; r < 16; ++r) put(r, h == 0 ? X[r] : r == 0 ? m128.b : hcmul(X[r], m128));
        __syncwarp();
#pragma unroll
        for (int k = 0; k < 4; ++k) ldsm_x4(XA[h][k], lda + (((2 * k + (lane >> 4)) ^ (lane & 7)) << 4));
        __syncwarp();
      }
    }
    if (warp >= 14 && elect_one()) {
      issue_stage(warp - 11, warp - 11);
      issue_stage(warp - 9, warp - 9);
      if (warp == 14) l2_prefetch((const char*)p.wqkv + 224 * 3072 + cta * 6912, 6912);
      else l2_prefetch((const char*)p.x + (size_t)cta * 16384, 16384);
    }
    __syncwarp();
    float D[2][3][4];
#pragma unroll
    for (int t = 0; t < 6; ++t) D[t / 3][t % 3][0] = D[t / 3][t % 3][1] = D[t / 3][t % 3][2] = D[t / 3][t % 3][3] = 0.f;
    auto contract = [&](int t0, int nt) {
      __syncwarp();
#pragma unroll
      for (int k = 0; k < 4; ++k) {
        uint32_t b[4];
        ldsm_x4(b, ldb + (((2 * k + ((lane >> 3) & 1)) ^ (lane & 7)) << 4));
#pragma unroll
        for (int h = 0; h < 2; ++h) {
          mma_f16(D[h][t0], XA[h][k], b[0], b[1]);
          if (nt == 2) mma_f16(D[h][t0 + 1], XA[h][k], b[2], b[3]);
        }
      }
      __syncwarp();
    };
    const HMul c1 = mk_mul(e1.re, -e1.im), c2 = mk_mul(e2.re, -e2.im), c4 = mk_mul(e4.re, -e4.im);
    const HMul c256 = mk_mul(e256.re, -e256.im), c512 = mk_mul(e512.re, -e512.im), c768 = mk_mul(e768.re, -e768.im);
    const HMul c1024 = mk_mul(e1024.re, -e1024.im);
    uint32_t W[8];
    W[0] = pack_f16(wr * sc, -wi * sc);
    W[1] = hcmul(W[0], c1); W[2] = hcmul(W[0], c2); W[3] = hcmul(W[1], c2);
    W[4] = hcmul(W[0], c4); W[5] = hcmul(W[1], c4); W[6] = hcmul(W[2], c4); W[7] = hcmul(W[3], c4);
#pragma unroll
    for (int i = 0; i < 8; ++i) put(i, W[i]);
#pragma unroll
    for (int i = 0; i < 4; ++i) put(8 + i, hcmul(W[2 * i], c256));
    put(12, hcmul(W[0], c512)); put(13, hcmul(W[4], c512)); put(14, hcmul(W[0], c768)); put(15, hcmul(W[4], c768));
    contract(0, 2);
    const uint32_t v0 = hcmul(W[0], c1024);
    put(0, v0); put(1, hcmul(v0, c256)); put(2, hcmul(v0, c512)); put(3, hcmul(v0, c768)); put(4, hcmul(v0, c1024));
    contract(2, 1);
    const uint32_t a = tb + (g * 24 + 2 * q) * 4;
#pragma unroll
    for (int t = 0; t < 6; ++t) {
      const float(&d)[4] = D[t / 3][t % 3];
      sts_f32x2(a + (t / 3) * 1536 + (t % 3) * 32, d[0] * inv, d[1] * inv);
      sts_f32x2(a + (t / 3) * 1536 + (t % 3) * 32 + 768, d[2] * inv, d[3] * inv);
    }
    if (mz > 0.f) {
      __syncwarp();
#pragma unroll 1
      for (int i = lane; i < 768; i += 32) {
        const int r = i / 24, y = i - 24 * r;
        sts_f32(tb + i * 4, lds_f32(tb + i * 4) * ex2(mz * 1.4426950408889634f * (koff(y) + 8 * r)));
      }
    }
  }
  if (tid == 0) TS(2);
  if (warp < 12) cluster_wait();
  if (tid == 0) TS(32);
  __syncthreads();
  if (tid == 0) TSD(33);

  if (warp < 4) {
    asm volatile("setmaxnreg.inc.sync.aligned.u32 152;");
    if (tid == 0) TS(34);
    const int d = cta * 4 + warp;
    const uint32_t vv = sb + SM_VV + warp * VV_BYTES;
    const uint32_t ub = sb + SM_U + warp * U_BYTES;
    const uint32_t pb = sb + SM_P + warp * P_BYTES;
    const float dskip = bf_lo(r_dskip);
#pragma unroll 1
    for (int pass = 0; pass < 2; ++pass) {
      if (pass == 1) {
        const uint32_t kf = vv;
#pragma unroll 2
        for (int i = 0; i < 6; ++i) {
          const uint32_t a = kf + (i * 32 + lane) * 16;
          const uint4 x0 = lds128(a), x1 = lds128(a + KG_BYTES), x2 = lds128(a + 2 * KG_BYTES), x3 = lds128(a + 3 * KG_BYTES);
          auto s4 = [](uint32_t a0, uint32_t a1, uint32_t a2, uint32_t a3) {
            return __float_as_uint((__uint_as_float(a0) + __uint_as_float(a1)) + (__uint_as_float(a2) + __uint_as_float(a3)));
          };
          sts128(a, s4(x0.x, x1.x, x2.x, x3.x), s4(x0.y, x1.y, x2.y, x3.y), s4(x0.z, x1.z, x2.z, x3.z), s4(x0.w, x1.w, x2.w, x3.w));
        }
        __syncwarp();
        const float k1024 = lds_f32(kf + kidx_c(1024) * 4);
        if (lane == 0) {
          sts_f32(kf + SL_ZERO * 4, 0.f);
          sts_f32(kf + SL_510 * 4, lds_f32(kf + kidx_c(510) * 4) - lds_f32(kf + kidx_c(512) * 4));
          sts_f32(kf + SL_0 * 4, lds_f32(kf) + dskip);
        }
        __syncwarp();
        if (tid == 0) TS(36);
        mbar_wait_long(BAR(B_PFREE), 0);
        if (tid == 0) TS(37);
        {
          float prev = 0.f;
#pragma unroll 1
          for (int i0 = 0; i0 < 16; i0 += 4) {
            uint32_t e[4];
            float a[4], b[4];
#pragma unroll
            for (int i = 0; i < 4; ++i) e[i] = lds32(sb + SM_PTAB + ((i0 + i) * 32 + lane) * 4);
#pragma unroll
            for (int i = 0; i < 4; ++i) { a[i] = lds_f32(kf + (e[i] & 0xffff)); b[i] = lds_f32(kf + (e[i] >> 16)); }
#pragma unroll
            for (int i = 0; i < 4; ++i) {
              const uint32_t w = pb + (31 * lane + 2 * (i0 + i)) * 4;
              if (i0 + i > 0) sts32(w - 4, pack_bf16(a[i], prev));
              sts32(w, pack_bf16(b[i], a[i]));
              prev = b[i];
            }
          }
        }
        __syncwarp();
        if (lane == 0) TS(4);
        const int gq = g - 2 * q;
        uint32_t h127, h128;
        {
          const uint32_t kf2 = pack_bf16(k1024, k1024) ^ 0x80008000u;
          h127 = (gq == 4 ? 0x0000ffffu : gq == 5 ? 0xffffffffu : gq == 6 ? 0xffff0000u : 0u) & kf2;
          h128 = (gq == -4 ? 0x0000ffffu : gq == -3 ? 0xffffffffu : gq == -2 ? 0xffff0000u : 0u) & kf2;
        }
        bar_sync(4, 480);
        mbar_wait_long(BAR(B_UCH + warp), 0);
        if (lane == 0) TS(7);
        float acc[16][4];
#pragma unroll
        for (int i = 0; i < 16; ++i) { acc[i][0] = acc[i][1] = acc[i][2] = acc[i][3] = 0.f; }
        {
          const uint32_t pd_lane = pb + (PD_OFF + 16 + gq) * 4;
          const int prow0 = 8 + (lane & 7) + ((lane >> 4) << 3), hs = (lane >> 3) & 1;
          const uint32_t zero = (uint32_t)cta >> 20;
          uint32_t B[2][4][4];
          uint32_t A[4][4];
          const uint32_t la0 = ub + prow0 * 32 + ((hs ^ ((prow0 >> 2) & 1)) << 4);
#pragma unroll
          for (int m2 = 0; m2 < 4; ++m2) ldsm_x4(B[0][m2], la0 + m2 * 512);
#pragma unroll
          for (int i = 0; i < 4; ++i) {
            const uint32_t a = pd_lane + i * 512;
            A[i][0] = lds32(a); A[i][1] = lds32(a + 32); A[i][2] = lds32(a - 32); A[i][3] = lds32(a + zero);
          }
          uint32_t la = la0;
#pragma unroll 1
          for (int rho = 0; rho < 8; ++rho) {
#pragma unroll
            for (int m2 = 0; m2 < 4; ++m2) ldsm_x4(B[1][m2], la + (4 + m2) * 512);
#pragma unroll
            for (int i = 0; i < 4; ++i)
#pragma unroll
              for (int m = 0; m < 8; ++m) mma_bf16v(acc[m + i], A[i], B[0][m >> 1][2 * (m & 1)], B[0][m >> 1][2 * (m & 1) + 1]);
            const int prow = prow0 - min(rho + 1, 7);
            la = ub + prow * 32 + ((hs ^ ((prow >> 2) & 1)) << 4);
#pragma unroll
            for (int m2 = 0; m2 < 4; ++m2) ldsm_x4(B[0][m2], la + m2 * 512);
            const uint32_t pa = pd_lane + (rho + 1) * 64;
#pragma unroll
            for (int i = 0; i < 4; ++i) {
#pragma unroll
              for (int m = 0; m < 8 - i; ++m)
                mma_bf16v(acc[8 + m + i], A[i], B[1][m >> 1][2 * (m & 1)], B[1][m >> 1][2 * (m & 1) + 1]);
              A[i][0] = lds32(pa + i * 512); A[i][1] = lds32(pa + i * 512 + 32); A[i][2] = lds32(pa + i * 512 - 32);
              A[i][3] = lds32(pa + i * 512 + zero);
            }
          }
          if (lane == 0) TS(40);
          {
            uint32_t b8[4];
            ldsm_x4(b8, la + 4 * 512);
            const uint32_t h63 = lds32(pd_lane + 63 * 32), h64 = lds32(pd_lane + 64 * 32);
            const uint32_t a63[4] = {0u, h127, 0u, 0u}, a32[4] = {h64, 0u, h63, h64}, a64[4] = {h128, 0u, h127, h128};
#pragma unroll
            for (int m2 = 0; m2 < 4; ++m2) ldsm_x4(B[1][m2], la0 + m2 * 512);
#pragma unroll
            for (int m = 0; m < 8; ++m) mma_bf16v(acc[m + 7], a63, B[0][m >> 1][2 * (m & 1)], B[0][m >> 1][2 * (m & 1) + 1]);
#pragma unroll
            for (int m2 = 0; m2 < 2; ++m2) ldsm_x4(B[0][m2], la0 + (4 + m2) * 512);
#pragma unroll
            for (int m = 0; m < 8; ++m) mma_bf16v(acc[m + 4], a32, B[1][m >> 1][2 * (m & 1)], B[1][m >> 1][2 * (m & 1) + 1]);
            mma_bf16v(acc[15], a63, b8[0], b8[1]);
#pragma unroll
            for (int m = 0; m < 8; ++m) mma_bf16v(acc[m + 8], a64, B[1][m >> 1][2 * (m & 1)], B[1][m >> 1][2 * (m & 1) + 1]);
#pragma unroll
            for (int m = 0; m < 4; ++m) mma_bf16v(acc[m + 12], a32, B[0][m >> 1][2 * (m & 1)], B[0][m >> 1][2 * (m & 1) + 1]);
          }
          if (lane == 0) TS(41);
          bar_sync(5, 224);
#pragma unroll 1
          for (int v = 0; v < 4; ++v)
            conv_tail<4, 3, 11>(acc, pb + (P2_OFF + 56 * v + gq - 16) * 4, vv + ((v & 1) ? VV_U3 : VV_U5), v >> 1, v == 0, lane);
          if (lane == 0) TS(42);
#pragma unroll 1
          for (int pi = 0; pi < 2; ++pi)
            conv_tail<8, 5, 7>(acc, pb + (P3_OFF + 88 * pi + gq - 48) * 4, vv + (pi ? VV_U7 : VV_U9), pi, pi == 0, lane);
        }
        if (lane == 0) TS(8);
        __syncwarp();
        {
          const int mt = lane >> 3;
          const uint32_t a = pb + (128 * (mt >> 1) + 16 * (lane & 7) + 8 * (mt & 1)) * 2;
#pragma unroll
          for (int ab = 0; ab < 16; ab += 2)
            stsm_x4_t(a + ab * 256, pack_bf16(acc[ab][0], acc[ab][1]), pack_bf16(acc[ab][2], acc[ab][3]),
                      pack_bf16(acc[ab + 1][0], acc[ab + 1][1]), pack_bf16(acc[ab + 1][2], acc[ab + 1][3]));
        }
        fence_async_smem();
        __syncwarp();
        if (lane < 2) mbar_arrive_cluster(BAR(B_CONVD), lane);
        bar_arrive(3, 384);
        if (elect_one()) {
          bulk_store(p.yT + (size_t)d * 2048, pb, 4096);
          bulk_commit();
          bulk_wait0();
          red_relaxed_add(&g_cnt[(C_Y + (cta >> 4)) * 32], 1);
          TS(9);
        }
        bar_sync(2, 128);
        if (warp == 0 && elect_one()) {
          wait_counter(&g_cnt[(C_Y + tj) * 32], (epoch + 1) * 64);
          TS(28);
          mbar_expect_tx(BAR(B_TILE), 16384);
          tma_load_2d(sb + SM_U, &maps.yT, ti * 128, tj * 64, BAR(B_TILE));
          tma_load_2d(sb + SM_U + 8192, &maps.yT, ti * 128 + 64, tj * 64, BAR(B_TILE));
        }
        __syncwarp();
      }
      mbar_wait_long(BAR(B_TILE), pass);
      if (lane == 0) TS(26 + 3 * pass);
      {
        const int m = lane >> 3, r = lane & 7;
#pragma unroll 2
        for (int it = 0; it < 8; ++it) {
          const int tb = warp * 4 + (it >> 1), cb = (it & 1) * 4 + m;
          const uint32_t at = (tb * 8 + r) * 128 + ((cb ^ r) << 4);
          const uint32_t ac = (tb >> 3) * 8192 + (cb * 8 + r) * 128 + (((tb & 7) ^ (pass ? 0 : tb >> 3) ^ r) << 4);
          uint32_t v[4];
          ldsm_x4_t(v, sb + SM_U + (pass ? ac : at));
          stsm_x4(sb + SM_P + (pass ? at : ac), v[0], v[1], v[2], v[3]);
        }
      }
      if (pass == 0 && tid == 0) TS(35);
      fence_async_smem();
      if (pass == 0) {
        bar_arrive(6, 160);
      } else {
        bar_sync(2, 128);
        if (warp == 0 && elect_one()) {
          tma_store_2d(&maps.out, sb + SM_P, 64 * tj, 128 * ti);
          bulk_commit();
          bulk_wait_read0();
          TS(30);
        }
      }
    }
  } else if (warp < 12) {
    asm volatile("setmaxnreg.inc.sync.aligned.u32 160;");
    const int w8 = warp - 4;
    const int row = w8 * 16 + (lane & 7) + (((lane >> 3) & 1) << 3);
    {
      float acc[96];
#pragma unroll 1
      for (int ks = 0, s = 0, ph = 0; ks < 16; ++ks) {
        mbar_wait(BAR(B_FULL + s), ph);
        if (tid == 128 && !(ks & 1)) TSR(16, ks == 0 ? 16 : 9 + (ks >> 1) + (ks > 12 ? 43 : 0));
        const uint32_t st = sb + s * STG_BYTES;
        const uint32_t da = mkdesc(st + STG_X + (w8 >> 2) * 4096, 16);
        const uint32_t db = mkdesc(st + STG_W, 2048);
        wg_fence();
        wgmma_n192(acc, da, db, ks != 0);
        wgmma_n192(acc, da + 2, db + 384, 1);
        wg_commit();
        const uint32_t eprev = BAR(B_EMPTY + (s == 0 ? NSTG - 1 : s - 1));
        if (++s == NSTG) { s = 0; ph ^= 1; }
        if (ks > 0) {
          wg_wait<1>();
          if (lane < 2) mbar_arrive_cluster(eprev, lane);
        }
      }
      wg_wait<0>();
      if (tid == 128) TS(17);
      bar_sync(1, 256);
#pragma unroll
      for (int i = 0; i < 24; i += 2)
        stsm_x4(sb + SM_QS + row * 128 + (i >> 3) * 16384 + ((((i & 7) + (lane >> 4)) ^ (row & 7)) << 4),
                pack_bf16(acc[4 * i], acc[4 * i + 1]), pack_bf16(acc[4 * i + 2], acc[4 * i + 3]),
                pack_bf16(acc[4 * i + 4], acc[4 * i + 5]), pack_bf16(acc[4 * i + 6], acc[4 * i + 7]));
    }
    __syncwarp();
#pragma unroll 1
    for (int part = 1; part >= 0; --part) {
      const uint32_t pa = sb + SM_QS + part * 16384 + w8 * 2048 + lane * 16;
#pragma unroll 1
      for (int it = 0; it < 4; ++it) {
        uint4 t = lds128(pa + it * 512);
        uint32_t* tw = &t.x;
#pragma unroll
        for (int j = 0; j < 4; ++j) {
          const uint32_t x = tw[j];
          const __nv_bfloat162 xb = *reinterpret_cast<const __nv_bfloat162*>(&x);
          const uint32_t e = pack_bf16(ex2(bf_lo(x) * 1.4426950408889634f), ex2(bf_hi(x) * 1.4426950408889634f));
          const uint32_t m = __hgt2_mask(xb, __floats2bfloat162_rn(0.f, 0.f));
          tw[j] = badd((badd(x, 0x3f803f80u) & m) | (e & ~m), 0x35863586u);
        }
        sts128(pa + it * 512, t.x, t.y, t.z, t.w);
      }
      if (part == 1) {
        if (tid == 128) TS(53);
        bar_sync(1, 256);
        const int hh = w8 >> 1, dtile = w8 & 1;
        float kv[4] = {0.f, 0.f, 0.f, 0.f}, zz[4] = {0.f, 0.f, 0.f, 0.f};
        const int m = lane >> 3;
        const uint32_t aa = sb + SM_VS + ((lane & 7) + ((m >> 1) << 3)) * 128 + (((2 * hh + (m & 1)) ^ (lane & 7)) << 4);
        const uint32_t ab = sb + SM_PK + (lane & 15) * 128 + (((2 * hh + dtile) ^ (lane & 7)) << 4);
#pragma unroll 2
        for (int ks = 0; ks < 8; ++ks) {
          uint32_t a[4], b0, b1;
          ldsm_x4_t(a, aa + ks * 2048);
          ldsm_x2_t(b0, b1, ab + ks * 2048);
          mma_bf16(kv, a[0], a[1], a[2], a[3], b0, b1);
          mma_bf16(zz, 0x3f803f80u, 0x3f803f80u, 0x3f803f80u, 0x3f803f80u, b0, b1);
        }
        const uint32_t kp = sb + SM_KV + hh * 1088;
        sts128(kp + dtile * 512 + lane * 16, __float_as_uint(kv[0]), __float_as_uint(kv[1]), __float_as_uint(kv[2]),
               __float_as_uint(kv[3]));
        if (g == 0) sts_f32x2(kp + 1024 + dtile * 32 + q * 8, zz[0], zz[1]);
        fence_async_smem();
        __syncwarp();
        if (lane == 0) mbar_arrive(BAR(B_KVP));
        bar_arrive(4, 480);
        if (tid == 128) TS(55);
      }
    }
    if (tid == 128) TS(56);
    mbar_wait_long(BAR(B_KVF), 0);
    if (tid == 128) TS(19);
#pragma unroll 1
    for (int h = 0; h < 4; ++h) {
      uint32_t a[4];
      const uint32_t qa = sb + SM_QS + row * 128 + (((2 * h + (lane >> 4)) ^ (row & 7)) << 4);
      ldsm_x4(a, qa);
      const uint32_t kp = sb + SM_KV + h * 1088;
      const uint4 k0 = lds128(kp + lane * 16), k1 = lds128(kp + 512 + lane * 16);
      const uint32_t za = kp + 1024 + q * 8;
      auto pk2 = [](uint32_t x, uint32_t y) { return pack_bf16(__uint_as_float(x), __uint_as_float(y)); };
      float n0[4] = {0.f, 0.f, 0.f, 0.f}, n1[4] = {0.f, 0.f, 0.f, 0.f}, dn[4] = {0.f, 0.f, 0.f, 0.f};
      mma_bf16(n0, a[0], a[1], a[2], a[3], pk2(k0.x, k0.y), pk2(k1.x, k1.y));
      mma_bf16(n1, a[0], a[1], a[2], a[3], pk2(k0.z, k0.w), pk2(k1.z, k1.w));
      mma_bf16(dn, a[0], a[1], a[2], a[3], pack_bf16(lds_f32(za), lds_f32(za + 4)), pack_bf16(lds_f32(za + 32), lds_f32(za + 36)));
      const uint32_t dd = pack_bf16(dn[0], dn[2]);
      const uint32_t d2 = pack_bf16(bf_lo(dd) + 1e-6f, bf_hi(dd) + 1e-6f);
      const float r0 = rcp(bf_lo(d2)), r1 = rcp(bf_hi(d2));
      const uint32_t x0 = pack_bf16(n0[0], n0[1]), x1 = pack_bf16(n0[2], n0[3]);
      const uint32_t x2 = pack_bf16(n1[0], n1[1]), x3 = pack_bf16(n1[2], n1[3]);
      stsm_x4(qa, pack_bf16(bf_lo(x0) * r0, bf_hi(x0) * r0), pack_bf16(bf_lo(x1) * r1, bf_hi(x1) * r1),
              pack_bf16(bf_lo(x2) * r0, bf_hi(x2) * r0), pack_bf16(bf_lo(x3) * r1, bf_hi(x3) * r1));
    }
    fence_async_smem();
    __syncwarp();
    if (lane == 0) mbar_arrive(BAR(B_OST));
    if (tid == 128) TS(57);
    mbar_wait_long(BAR(B_WO), 0);
    bar_sync(3, 384);
    {
      float o[32];
#pragma unroll 1
      for (int c = 0; c < 8; ++c) {
        mbar_wait_long(BAR(B_RF + c), 0);
        if (tid == 128) TSR(22, c == 0 ? 22 : 43 + c);
        const uint32_t slot = c < 4 ? SM_QS + c * 16384 : c < 7 ? SM_VV + (c - 4) * 16384 : SM_QS;
        const uint32_t da = mkdesc(sb + slot + (w8 >> 2) * 8192, 16);
        const uint32_t db = mkdesc(sb + SM_WO + c * 8192, 8192);
        wg_fence();
#pragma unroll
        for (int k = 0; k < 4; ++k) wgmma_n64(o, da + 2 * k, db + 128 * k, (c | k) != 0);
        wg_commit();
        if (c == 1) {
          wg_wait<1>();
          if (lane < 2) mbar_arrive_cluster(BAR(B_RE), lane);
        }
      }
      wg_wait<0>();
      if (tid == 128) TS(51);
      bar_sync(1, 256);
#pragma unroll
      for (int i = 0; i < 8; i += 2)
        stsm_x4(sb + SM_BOUT + row * 128 + (((i + (lane >> 4)) ^ (row & 7)) << 4), pack_bf16(o[4 * i], o[4 * i + 1]),
                pack_bf16(o[4 * i + 2], o[4 * i + 3]), pack_bf16(o[4 * i + 4], o[4 * i + 5]), pack_bf16(o[4 * i + 6], o[4 * i + 7]));
      fence_async_smem();
      bar_sync(1, 256);
      if (tid == 128) TS(52);
      if (warp == 4 && elect_one()) {
        tma_store_2d(&maps.out, sb + SM_BOUT, 512 + 64 * pj, 128 * pi);
        bulk_commit();
        bulk_wait_read0();
        TS(23);
      }
    }
  } else {
    asm volatile("setmaxnreg.dec.sync.aligned.u32 40;");
    if (warp == 12) {
      if (elect_one()) {
#pragma unroll 1
        for (int ks = NSTG, s = 0, ph = 0; ks < 16; ++ks) {
          mbar_wait(BAR(B_EMPTY + s), ph);
          issue_stage(ks, s);
          if (ks == NSTG) l2_prefetch((const char*)p.wo + (size_t)cta * 4096, 4096);
          if (++s == NSTG) { s = 0; ph ^= 1; }
        }
        mbar_wait(BAR(B_EMPTY + 6), 1);
        mbar_expect_tx(BAR(B_WO), 65536);
        tma_load_2d(sb + SM_WO, &maps.wo, pj * 64, 0, BAR(B_WO));
        tma_load_2d(sb + SM_WO + 32768, &maps.wo, pj * 64, 256, BAR(B_WO));
        float* kvg = &g_kv[epoch & 1][tj][0];
        mbar_wait_long(BAR(B_KVP), 0);
        bulk_reduce_add_f32(kvg, sb + SM_KV, 4352);
        bulk_commit();
        bulk_wait0();
        red_relaxed_add(&g_cnt[(C_KV + tj) * 32], 1);
        TS(18);
        wait_counter(&g_cnt[(C_KV + tj) * 32], (epoch + 1) * 16);
        mbar_expect_tx(BAR(B_KVF), 4352);
        bulk_load(sb + SM_KV, kvg, 4352, BAR(B_KVF));
        mbar_wait_long(BAR(B_OST), 0);
        tma_store_2d(&maps.o, sb + SM_QS, tj * 64, ti * 128);
        tma_store_2d(&maps.o, sb + SM_QS + 8192, tj * 64, ti * 128 + 64);
        bulk_commit();
        bulk_wait0();
        red_relaxed_add(&g_cnt[(C_O + ti) * 32], 1);
        TS(20);
        mbar_arrive_cluster(BAR(B_SLOT), 0);
        mbar_arrive_cluster(BAR(B_SLOT), 1);
        wait_counter(&g_cnt[(C_O + pi) * 32], (epoch + 1) * 8);
        if (cta == 0) g_epoch = epoch + 1;
        mbar_wait(BAR(B_SLOT), 0);
        TS(21);
#pragma unroll 1
        for (int c = 0; c < 8; ++c) {
          if (c == 4) mbar_wait_long(BAR(B_CONVD), 0);
          if (c == 7) mbar_wait(BAR(B_RE), 0);
          const uint32_t slot = c < 4 ? SM_QS + c * 16384 : c < 7 ? SM_VV + (c - 4) * 16384 : SM_QS;
          mbar_expect_tx(BAR(B_RF + c), 16384);
          tma_load_2d_mc(sb + slot + rank * 8192, &maps.o, c * 64, pi * 128 + rank * 64, BAR(B_RF + c), 3);
        }
      }
    } else if (warp == 13) {
      bar_sync(6, 160);
      sts128(sb + SM_U + (lane >> 4) * U_BYTES + (lane & 15) * 16, 0, 0, 0, 0);
      sts128(sb + SM_U + (2 + (lane >> 4)) * U_BYTES + (lane & 15) * 16, 0, 0, 0, 0);
      __syncwarp();
      if (elect_one()) {
        tma_store_2d(&maps.uT, sb + SM_P, ti * 128, tj * 64);
        tma_store_2d(&maps.uT, sb + SM_P + 8192, ti * 128 + 64, tj * 64);
        bulk_commit();
        bulk_wait_read0();
        mbar_arrive(BAR(B_PFREE));
        bulk_wait0();
        red_relaxed_add(&g_cnt[(C_U + tj) * 32], 1);
        TS(27);
        wait_counter(&g_cnt[(C_U + (cta >> 4)) * 32], (epoch + 1) * 16);
#pragma unroll 1
        for (int c = 0; c < 4; ++c) {
          mbar_expect_tx(BAR(B_UCH + c), 4096);
          bulk_load(sb + SM_U + c * U_BYTES + 256, p.uT + (size_t)(cta * 4 + c) * 2048, 4096, BAR(B_UCH + c));
        }
        TS(3);
      }
      __syncwarp();
      if (ti == 0) {
        float4* z = (float4*)&g_kv[(epoch & 1) ^ 1][tj][0];
#pragma unroll 1
        for (int i = lane; i < 272; i += 32) z[i] = make_float4(0.f, 0.f, 0.f, 0.f);
      }
    }
    if (warp >= 13) {
      bar_sync(4, 480);
      auto swz = [](int k, int pad) { const int r = (k >> 1) + pad; return (uint32_t)(r * 32 + (((k & 1) ^ ((r >> 2) & 1)) << 4)); };
      const uint32_t o0 = swz(lane - 3, 8), o1 = swz(lane - 2, 8), o2 = swz(lane - 1, 8), ow = swz(lane - 2, PADV);
      const uint32_t oz = swz(lane - 18, PADV);
#pragma unroll 1
      for (int item = warp - 13; item < 28; item += 3) {
        const int ch = item / 7, it = item - 7 * ch;
        const int k = -2 + 32 * it + lane;
        const uint32_t ua = sb + SM_U + ch * U_BYTES + it * 512, vb = sb + SM_VV + ch * VV_BYTES;
        const uint32_t a0 = ua + o0, a1 = ua + o1, a2 = ua + o2, aw = vb + it * 512 + ow;
        mbar_wait_long(BAR(B_UCH + ch), 0);
        if (it == 0 && lane < 16) {
          sts128(vb + oz + VV_U3, 0, 0, 0, 0); sts128(vb + oz + VV_U5, 0, 0, 0, 0);
          sts128(vb + oz + VV_U7, 0, 0, 0, 0); sts128(vb + oz + VV_U9, 0, 0, 0, 0);
        }
        const uint4 t0 = lds128(a0), t1 = lds128(a1), t2 = lds128(a2);
        const uint32_t E[12] = {t0.x, t0.y, t0.z, t0.w, t1.x, t1.y, t1.z, t1.w, t2.x, t2.y, t2.z, t2.w};
        uint32_t O[8];
#pragma unroll
        for (int j = 0; j < 8; ++j) O[j] = __byte_perm(E[j + 1], E[j + 2], 0x5432);
        uint32_t s3[6], s5[4], s7[4], s9[4];
#pragma unroll
        for (int j = 0; j < 6; ++j) s3[j] = badd(badd(O[j], O[j + 1]), E[j + 2]);
#pragma unroll
        for (int j = 0; j < 4; ++j) {
          s5[j] = badd(s3[j + 2], badd(E[j + 3], E[j + 5]));
          s7[j] = badd(s5[j], badd(O[j + 1], O[j + 4]));
          s9[j] = badd(s7[j], badd(E[j + 2], E[j + 6]));
        }
        if (k < 208) { sts128(aw + VV_U3, s3[0], s3[1], s3[2], s3[3]); sts128(aw + VV_U5, s5[0], s5[1], s5[2], s5[3]); }
        if (k < 144) { sts128(aw + VV_U7, s7[0], s7[1], s7[2], s7[3]); sts128(aw + VV_U9, s9[0], s9[1], s9[2], s9[3]); }
      }
      if (tid == 416) TS(6);
      bar_arrive(5, 224);
    }
  }
  __syncwarp();
  cluster_arrive();
  cluster_wait();
  if (tid == 0) TS(31);
#undef BAR
}

typedef CUresult (*EncodeFn)(CUtensorMap*, CUtensorMapDataType, cuuint32_t, void*, const cuuint64_t*, const cuuint64_t*,
                             const cuuint32_t*, const cuuint32_t*, CUtensorMapInterleave, CUtensorMapSwizzle,
                             CUtensorMapL2promotion, CUtensorMapFloatOOBfill);

static void make_map(EncodeFn enc, CUtensorMap* m, const void* base, uint64_t inner, uint64_t outer, uint32_t box_in,
                     uint32_t box_out, CUtensorMapSwizzle swz = CU_TENSOR_MAP_SWIZZLE_128B) {
  cuuint64_t gd[2] = {inner, outer};
  cuuint64_t gs[1] = {inner * 2};
  cuuint32_t bd[2] = {box_in, box_out};
  cuuint32_t es[2] = {1, 1};
  enc(m, CU_TENSOR_MAP_DATA_TYPE_BFLOAT16, 2, const_cast<void*>(base), gd, gs, bd, es, CU_TENSOR_MAP_INTERLEAVE_NONE,
      swz, CU_TENSOR_MAP_L2_PROMOTION_L2_128B, CU_TENSOR_MAP_FLOAT_OOB_FILL_NONE);
}

}

extern "C" void kernel_launch(void* const* d_in, const int* in_sizes, int n_in, void* d_out, int out_size) {
  using namespace s4la;
  (void)in_sizes; (void)n_in; (void)out_size;
  static EncodeFn enc = nullptr;
  static void *uT = nullptr, *yT = nullptr, *oS = nullptr;
  if (!enc) {
    void* fn = nullptr;
    cudaDriverEntryPointQueryResult qr;
    cudaGetDriverEntryPoint("cuTensorMapEncodeTiled", &fn, cudaEnableDefault, &qr);
    enc = (EncodeFn)fn;
    cudaGetSymbolAddress(&uT, g_uT);
    cudaGetSymbolAddress(&yT, g_yT);
    cudaGetSymbolAddress(&oS, g_o);
    cudaFuncSetAttribute(fused_kernel, cudaFuncAttributeMaxDynamicSharedMemorySize, SM_TOTAL);
  }
  const __nv_bfloat16* const* in = (const __nv_bfloat16* const*)d_in;
  Maps maps;
  make_map(enc, &maps.x, in[9], 512, 2048, 32, 128, CU_TENSOR_MAP_SWIZZLE_64B);
  {
    cuuint64_t gd[3] = {512, 512, 3};
    cuuint64_t gs[2] = {3072, 1024};
    cuuint32_t bd[3] = {64, 16, 3};
    cuuint32_t es[3] = {1, 1, 1};
    enc(&maps.w, CU_TENSOR_MAP_DATA_TYPE_BFLOAT16, 3, const_cast<__nv_bfloat16*>(in[10]), gd, gs, bd, es,
        CU_TENSOR_MAP_INTERLEAVE_NONE, CU_TENSOR_MAP_SWIZZLE_128B, CU_TENSOR_MAP_L2_PROMOTION_L2_128B,
        CU_TENSOR_MAP_FLOAT_OOB_FILL_NONE);
  }
  make_map(enc, &maps.wo, in[11], 512, 512, 64, 256);
  make_map(enc, &maps.u, in[0], 512, 2048, 64, 128);
  make_map(enc, &maps.uT, uT, 2048, 512, 64, 64);
  make_map(enc, &maps.yT, yT, 2048, 512, 64, 64);
  make_map(enc, &maps.o, oS, 512, 2048, 64, 64);
  make_map(enc, &maps.out, d_out, 1024, 2048, 64, 128);
  Ptrs p;
  p.A_re = in[1]; p.A_im = in[2]; p.B_re = in[3]; p.B_im = in[4]; p.C_re = in[5]; p.C_im = in[6];
  p.log_dt = in[7]; p.Dskip = in[8]; p.x = in[9]; p.wqkv = in[10]; p.wo = in[11];
  p.uT = (__nv_bfloat16*)uT; p.yT = (__nv_bfloat16*)yT;
  fused_kernel<<<NCTA, NTHREADS, SM_TOTAL, cudaStreamPerThread>>>(maps, p);
}
```

```cpp
#include <cuda_runtime.h>
#include <cuda_bf16.h>
#include <cuda_fp16.h>
#include <cuda.h>
#include <stdint.h>

#define DEVI __device__ __forceinline__

namespace s4la {

constexpr int NTHREADS = 512;
constexpr int NCTA = 128;

constexpr int NSTG = 7;
constexpr uint32_t STG_BYTES = 20480, STG_X = 0, STG_W = 8192;
constexpr uint32_t SM_QS = 0;
constexpr uint32_t SM_PK = SM_QS + 16384, SM_VS = SM_QS + 32768;
constexpr uint32_t SM_WO = 65536;
constexpr uint32_t SM_KV = 131072;
constexpr uint32_t SM_BOUT = 16384;
constexpr uint32_t SM_U = 143360, U_BYTES = 4352;
constexpr uint32_t SM_P = 160768, P_BYTES = 4096;
constexpr uint32_t SM_VV = 177152, VV_BYTES = 12800;
constexpr uint32_t VV_U5 = 0, VV_U3 = 3712, VV_U9 = 7424, VV_U7 = 10112;
constexpr uint32_t KG_BYTES = 3200;
constexpr uint32_t SM_BAR = SM_VV + 4 * VV_BYTES;
constexpr uint32_t SM_PTAB = SM_BAR + 320;
constexpr uint32_t SM_TOTAL = SM_PTAB + 2048;
static_assert(SM_TOTAL <= 232448, "shared memory");
constexpr int PADV = 12;

enum { B_FULL = 0, B_EMPTY = 7, B_TILE = 14, B_UCH = 15, B_KVP = 19, B_KVF = 20, B_OST = 21, B_RF = 22, B_WO = 30, B_RE = 31, B_PFREE = 32, B_CONVD = 33, B_SLOT = 34, B_COUNT = 35 };
__host__ __device__ constexpr int bar_count(int i) {
  return (i >= B_EMPTY && i < B_TILE) ? 16 : (i == B_KVP || i == B_OST || i == B_CONVD) ? 8 : i == B_RE ? 16 : i == B_SLOT ? 2 : 1;
}

constexpr int PD_OFF = 0, P2_OFF = 544, P3_OFF = 768;

constexpr int SL_K2048 = 20, SL_ZERO = 21, SL_510 = 22, SL_0 = 23;
__host__ __device__ constexpr int koff(int y) {
  return y < 8 ? y : y < 12 ? 256 + 2 * (y - 8) : y < 16 ? 512 + 256 * ((y - 12) >> 1) + 4 * (y & 1) : 1024 + 256 * (y - 16);
}
__host__ __device__ constexpr int kidx_c(int l) {
  const int y = l < 256 ? (l & 7) : l < 512 ? 8 + ((l & 7) >> 1) : l < 1024 ? 12 + (((l - 512) >> 8) << 1) + ((l >> 2) & 1)
                                                                            : 16 + ((l - 1024) >> 8);
  return ((l >> 3) & 31) * 24 + y;
}
constexpr int slot_direct(int l) {
  if (l < 0 || l > 510) return SL_ZERO;
  if (l == 510) return SL_510;
  if (l == 0) return SL_0;
  return kidx_c(l < 256 ? l : ((l + ((l >> 1) & 1)) & ~1));
}
constexpr int slot_seg2(int v, int k) { return (k >= 32 && k < 64) ? kidx_c(16 * k + 4 * v) : SL_ZERO; }
constexpr int slot_seg3(int pi, int k) {
  return (k >= 64 && k < 128) ? kidx_c(16 * k + 8 * pi) : ((k == 128 && pi == 0) ? SL_K2048 : SL_ZERO);
}
constexpr int slot_word(int w) {
  return w < 0 ? SL_ZERO : w < 544 ? slot_direct(w - 16) : w < 768 ? slot_seg2((w - 544) / 56, 16 + (w - 544) % 56)
       : w < 944 ? slot_seg3((w - 768) / 88, 48 + (w - 768) % 88) : SL_ZERO;
}
struct PTab { uint32_t v[512]; };
constexpr PTab make_ptab() {
  PTab t{};
  for (int lane = 0; lane < 32; ++lane)
    for (int i = 0; i < 16; ++i)
      t.v[i * 32 + lane] = (slot_word(31 * lane - 1 + 2 * i) * 4) | ((slot_word(31 * lane + 2 * i) * 4) << 16);
  return t;
}
__device__ const PTab g_ptab = make_ptab();

__device__ __nv_bfloat16 g_uT[512 * 2048];
__device__ __nv_bfloat16 g_yT[512 * 2048];
__device__ __nv_bfloat16 g_o[2048 * 512];
__device__ float g_kv[2][8][4 * 272];
__device__ unsigned g_cnt[64 * 32];
__device__ unsigned g_epoch;
#define TS(slot) do { } while (0)
#define TSR(on, slot) do { } while (0)
#define TSD(slot) do { } while (0)
enum { C_U = 0, C_KV = 8, C_O = 16, C_Y = 32 };

struct Maps {
  CUtensorMap x, w, wo, u, uT, yT, o, out;
};
struct Ptrs {
  const __nv_bfloat16 *A_re, *A_im, *B_re, *B_im, *C_re, *C_im, *log_dt, *Dskip;
  const __nv_bfloat16 *x, *wqkv, *wo;
  __nv_bfloat16 *uT, *yT;
};

DEVI uint32_t s2u(const void* p) { return (uint32_t)__cvta_generic_to_shared(p); }
DEVI void mbar_init(uint32_t b, uint32_t c) { asm volatile("mbarrier.init.shared::cta.b64 [%0], %1;" ::"r"(b), "r"(c) : "memory"); }
DEVI void mbar_expect_tx(uint32_t b, uint32_t bytes) {
  asm volatile("mbarrier.arrive.expect_tx.shared::cta.b64 _, [%0], %1;" ::"r"(b), "r"(bytes) : "memory");
}
DEVI void mbar_arrive(uint32_t b) { asm volatile("mbarrier.arrive.shared::cta.b64 _, [%0];" ::"r"(b) : "memory"); }
DEVI void mbar_arrive_cluster(uint32_t b, uint32_t cta) {
  asm volatile("{\n.reg .b32 r;\nmapa.shared::cluster.u32 r, %0, %1;\nmbarrier.arrive.shared::cluster.b64 _, [r];\n}"
               ::"r"(b), "r"(cta) : "memory");
}
DEVI void mbar_wait(uint32_t b, uint32_t parity) {
  asm volatile("{\n.reg .pred p;\nLAB_WAIT:\nmbarrier.try_wait.parity.shared::cta.b64 p, [%0], %1;\n@!p bra LAB_WAIT;\n}"
               ::"r"(b), "r"(parity) : "memory");
}
DEVI void mbar_wait_long(uint32_t b, uint32_t parity) {
  asm volatile("{\n.reg .pred p;\nLAB_WAIT:\nmbarrier.try_wait.parity.shared::cta.b64 p, [%0], %1, 0x989680;\n@!p bra LAB_WAIT;\n}"
               ::"r"(b), "r"(parity) : "memory");
}
DEVI void bar_sync(int id, int n) { asm volatile("bar.sync %0, %1;" ::"r"(id), "r"(n) : "memory"); }
DEVI void bar_arrive(int id, int n) { asm volatile("bar.arrive %0, %1;" ::"r"(id), "r"(n) : "memory"); }
DEVI void fence_async_smem() { asm volatile("fence.proxy.async.shared::cta;" ::: "memory"); }
DEVI void fence_async_all() { asm volatile("fence.proxy.async;" ::: "memory"); }
DEVI void cluster_arrive() { asm volatile("barrier.cluster.arrive.relaxed.aligned;" ::: "memory"); }
DEVI void cluster_wait() { asm volatile("barrier.cluster.wait.aligned;" ::: "memory"); }

DEVI void tma_load_2d(uint32_t dst, const CUtensorMap* m, int c0, int c1, uint32_t bar) {
  asm volatile("cp.async.bulk.tensor.2d.shared::cluster.global.mbarrier::complete_tx::bytes [%0], [%1, {%3, %4}], [%2];"
               ::"r"(dst), "l"(m), "r"(bar), "r"(c0), "r"(c1) : "memory");
}
DEVI void tma_load_2d_mc(uint32_t dst, const CUtensorMap* m, int c0, int c1, uint32_t bar, uint16_t mask) {
  asm volatile("cp.async.bulk.tensor.2d.shared::cluster.global.mbarrier::complete_tx::bytes.multicast::cluster [%0], [%1, {%3, %4}], [%2], %5;"
               ::"r"(dst), "l"(m), "r"(bar), "r"(c0), "r"(c1), "h"(mask) : "memory");
}
DEVI void tma_load_3d_mc(uint32_t dst, const CUtensorMap* m, int c0, int c1, int c2, uint32_t bar, uint16_t mask) {
  asm volatile("cp.async.bulk.tensor.3d.shared::cluster.global.mbarrier::complete_tx::bytes.multicast::cluster [%0], [%1, {%3, %4, %5}], [%2], %6;"
               ::"r"(dst), "l"(m), "r"(bar), "r"(c0), "r"(c1), "r"(c2), "h"(mask) : "memory");
}
DEVI void tma_store_2d(const CUtensorMap* m, uint32_t src, int c0, int c1) {
  asm volatile("cp.async.bulk.tensor.2d.global.shared::cta.bulk_group [%0, {%2, %3}], [%1];"
               ::"l"(m), "r"(src), "r"(c0), "r"(c1) : "memory");
}
DEVI void bulk_load(uint32_t dst, const void* src, uint32_t bytes, uint32_t bar) {
  asm volatile("cp.async.bulk.shared::cluster.global.mbarrier::complete_tx::bytes [%0], [%1], %2, [%3];"
               ::"r"(dst), "l"(src), "r"(bytes), "r"(bar) : "memory");
}
DEVI void bulk_store(void* dst, uint32_t src, uint32_t bytes) {
  asm volatile("cp.async.bulk.global.shared::cta.bulk_group [%0], [%1], %2;" ::"l"(dst), "r"(src), "r"(bytes) : "memory");
}
DEVI void bulk_reduce_add_f32(void* dst, uint32_t src, uint32_t bytes) {
  asm volatile("cp.reduce.async.bulk.global.shared::cta.bulk_group.add.f32 [%0], [%1], %2;" ::"l"(dst), "r"(src), "r"(bytes) : "memory");
}
DEVI void bulk_commit() { asm volatile("cp.async.bulk.commit_group;" ::: "memory"); }
DEVI void bulk_wait0() { asm volatile("cp.async.bulk.wait_group 0;" ::: "memory"); }
DEVI void bulk_wait_read0() { asm volatile("cp.async.bulk.wait_group.read 0;" ::: "memory"); }
DEVI void l2_prefetch(const void* p, uint32_t bytes) {
  asm volatile("cp.async.bulk.prefetch.L2.global [%0], %1;" ::"l"(p), "r"(bytes) : "memory");
}
DEVI void prefetch_tmap(const CUtensorMap* m) { asm volatile("prefetch.tensormap [%0];" ::"l"(m) : "memory"); }

DEVI void red_release_add(unsigned* p, unsigned v) {
  asm volatile("red.release.gpu.global.add.u32 [%0], %1;" ::"l"(p), "r"(v) : "memory");
}
DEVI void red_relaxed_add(unsigned* p, unsigned v) {
  asm volatile("red.relaxed.gpu.global.add.u32 [%0], %1;" ::"l"(p), "r"(v) : "memory");
}
DEVI unsigned ld_relaxed(const unsigned* p) {
  unsigned v;
  asm volatile("ld.relaxed.gpu.global.u32 %0, [%1];" : "=r"(v) : "l"(p) : "memory");
  return v;
}
DEVI void wait_counter(const unsigned* p, unsigned target) {
#pragma unroll 1
  for (int it = 0; (int)(ld_relaxed(p) - target) < 0; ++it)
    if (it > (1 << 22)) __trap();
}

DEVI void ldsm_x4(uint32_t (&r)[4], uint32_t a) {
  asm volatile("ldmatrix.sync.aligned.m8n8.x4.shared.b16 {%0,%1,%2,%3}, [%4];"
               : "=r"(r[0]), "=r"(r[1]), "=r"(r[2]), "=r"(r[3]) : "r"(a) : "memory");
}
DEVI void ldsm_x4_t(uint32_t (&r)[4], uint32_t a) {
  asm volatile("ldmatrix.sync.aligned.m8n8.x4.trans.shared.b16 {%0,%1,%2,%3}, [%4];"
               : "=r"(r[0]), "=r"(r[1]), "=r"(r[2]), "=r"(r[3]) : "r"(a) : "memory");
}
DEVI void ldsm_x2_t(uint32_t& r0, uint32_t& r1, uint32_t a) {
  asm volatile("ldmatrix.sync.aligned.m8n8.x2.trans.shared.b16 {%0,%1}, [%2];" : "=r"(r0), "=r"(r1) : "r"(a) : "memory");
}
DEVI void stsm_x4(uint32_t a, uint32_t r0, uint32_t r1, uint32_t r2, uint32_t r3) {
  asm volatile("stmatrix.sync.aligned.m8n8.x4.shared.b16 [%0], {%1,%2,%3,%4};"
               ::"r"(a), "r"(r0), "r"(r1), "r"(r2), "r"(r3) : "memory");
}
DEVI void stsm_x4_t(uint32_t a, uint32_t r0, uint32_t r1, uint32_t r2, uint32_t r3) {
  asm volatile("stmatrix.sync.aligned.m8n8.x4.trans.shared.b16 [%0], {%1,%2,%3,%4};"
               ::"r"(a), "r"(r0), "r"(r1), "r"(r2), "r"(r3) : "memory");
}
DEVI uint32_t lds32(uint32_t a) { uint32_t v; asm volatile("ld.shared.b32 %0, [%1];" : "=r"(v) : "r"(a) : "memory"); return v; }
DEVI float lds_f32(uint32_t a) { float v; asm volatile("ld.shared.f32 %0, [%1];" : "=f"(v) : "r"(a) : "memory"); return v; }
DEVI void sts32(uint32_t a, uint32_t v) { asm volatile("st.shared.b32 [%0], %1;" ::"r"(a), "r"(v) : "memory"); }
DEVI void sts_f32(uint32_t a, float v) { asm volatile("st.shared.f32 [%0], %1;" ::"r"(a), "f"(v) : "memory"); }
DEVI void sts_f32x2(uint32_t a, float x, float y) { asm volatile("st.shared.v2.f32 [%0], {%1,%2};" ::"r"(a), "f"(x), "f"(y) : "memory"); }
DEVI uint4 lds128(uint32_t a) {
  uint4 v;
  asm volatile("ld.shared.v4.b32 {%0,%1,%2,%3}, [%4];" : "=r"(v.x), "=r"(v.y), "=r"(v.z), "=r"(v.w) : "r"(a) : "memory");
  return v;
}
DEVI void sts128(uint32_t a, uint32_t x, uint32_t y, uint32_t z, uint32_t w) {
  asm volatile("st.shared.v4.b32 [%0], {%1,%2,%3,%4};" ::"r"(a), "r"(x), "r"(y), "r"(z), "r"(w) : "memory");
}

DEVI void mma_bf16(float (&d)[4], uint32_t a0, uint32_t a1, uint32_t a2, uint32_t a3, uint32_t b0, uint32_t b1) {
  asm("mma.sync.aligned.m16n8k16.row.col.f32.bf16.bf16.f32 {%0,%1,%2,%3}, {%4,%5,%6,%7}, {%8,%9}, {%0,%1,%2,%3};"
      : "+f"(d[0]), "+f"(d[1]), "+f"(d[2]), "+f"(d[3])
      : "r"(a0), "r"(a1), "r"(a2), "r"(a3), "r"(b0), "r"(b1));
}
DEVI void mma_f16(float (&d)[4], const uint32_t (&a)[4], uint32_t b0, uint32_t b1) {
  asm("mma.sync.aligned.m16n8k16.row.col.f32.f16.f16.f32 {%0,%1,%2,%3}, {%4,%5,%6,%7}, {%8,%9}, {%0,%1,%2,%3};"
      : "+f"(d[0]), "+f"(d[1]), "+f"(d[2]), "+f"(d[3])
      : "r"(a[0]), "r"(a[1]), "r"(a[2]), "r"(a[3]), "r"(b0), "r"(b1));
}
DEVI void mma_bf16v(float (&d)[4], const uint32_t (&a)[4], uint32_t b0, uint32_t b1) {
  asm volatile("mma.sync.aligned.m16n8k16.row.col.f32.bf16.bf16.f32 {%0,%1,%2,%3}, {%4,%5,%6,%7}, {%8,%9}, {%0,%1,%2,%3};"
               : "+f"(d[0]), "+f"(d[1]), "+f"(d[2]), "+f"(d[3])
               : "r"(a[0]), "r"(a[1]), "r"(a[2]), "r"(a[3]), "r"(b0), "r"(b1));
}
DEVI uint32_t pack_bf16(float lo, float hi) {
  uint32_t r;
  asm("cvt.rn.bf16x2.f32 %0, %1, %2;" : "=r"(r) : "f"(hi), "f"(lo));
  return r;
}
DEVI uint32_t pack_f16(float lo, float hi) {
  uint32_t r;
  asm("cvt.rn.f16x2.f32 %0, %1, %2;" : "=r"(r) : "f"(hi), "f"(lo));
  return r;
}
DEVI uint32_t ldg16(const __nv_bfloat16* p) {
  uint32_t v;
  asm volatile("ld.global.nc.u16 %0, [%1];" : "=r"(v) : "l"(p));
  return v;
}
DEVI bool elect_one() {
  uint32_t pred;
  asm volatile("{\n.reg .pred p;\nelect.sync _|p, 0xffffffff;\nselp.u32 %0, 1, 0, p;\n}" : "=r"(pred));
  return pred != 0;
}
DEVI float bf_lo(uint32_t v) { return __uint_as_float(v << 16); }
DEVI float bf_hi(uint32_t v) { return __uint_as_float(v & 0xffff0000u); }
DEVI float bf2f(__nv_bfloat16 v) { return __bfloat162float(v); }
DEVI float round_bf16(float v) { return __bfloat162float(__float2bfloat16_rn(v)); }
DEVI float rcp(float x) { float r; asm("rcp.approx.ftz.f32 %0, %1;" : "=f"(r) : "f"(x)); return r; }
DEVI float ex2(float x) { float r; asm("ex2.approx.ftz.f32 %0, %1;" : "=f"(r) : "f"(x)); return r; }

DEVI void wg_fence() { asm volatile("wgmma.fence.sync.aligned;" ::: "memory"); }
DEVI void wg_commit() { asm volatile("wgmma.commit_group.sync.aligned;" ::: "memory"); }
template <int N> DEVI void wg_wait() { asm volatile("wgmma.wait_group.sync.aligned %0;" ::"n"(N) : "memory"); }
constexpr uint32_t DESC_HI = (1u << 30) | (1024 >> 4);
constexpr uint32_t DESC_HI64 = (2u << 30) | (512 >> 4);
DEVI uint32_t mkdesc(uint32_t saddr, uint32_t lbo) { return ((saddr & 0x3FFFF) >> 4) | ((lbo >> 4) << 16); }

#define R8(b) "%" #b
DEVI void wgmma_n192(float (&d)[96], uint32_t da, uint32_t db, int scale_d) {
  asm volatile(
      "{\n.reg .pred p;\n.reg .b64 da, db;\nsetp.ne.b32 p, %98, 0;\nmov.b64 da, {%96, %100};\nmov.b64 db, {%97, %99};\n"
      "wgmma.mma_async.sync.aligned.m64n192k16.f32.bf16.bf16 "
      "{%0,%1,%2,%3,%4,%5,%6,%7,%8,%9,%10,%11,%12,%13,%14,%15,"
      "%16,%17,%18,%19,%20,%21,%22,%23,%24,%25,%26,%27,%28,%29,%30,%31,"
      "%32,%33,%34,%35,%36,%37,%38,%39,%40,%41,%42,%43,%44,%45,%46,%47,"
      "%48,%49,%50,%51,%52,%53,%54,%55,%56,%57,%58,%59,%60,%61,%62,%63,"
      "%64,%65,%66,%67,%68,%69,%70,%71,%72,%73,%74,%75,%76,%77,%78,%79,"
      "%80,%81,%82,%83,%84,%85,%86,%87,%88,%89,%90,%91,%92,%93,%94,%95}, "
      "da, db, p, 1, 1, 0, 1;\n}"
      : "+f"(d[0]), "+f"(d[1]), "+f"(d[2]), "+f"(d[3]), "+f"(d[4]), "+f"(d[5]), "+f"(d[6]), "+f"(d[7]),
        "+f"(d[8]), "+f"(d[9]), "+f"(d[10]), "+f"(d[11]), "+f"(d[12]), "+f"(d[13]), "+f"(d[14]), "+f"(d[15]),
        "+f"(d[16]), "+f"(d[17]), "+f"(d[18]), "+f"(d[19]), "+f"(d[20]), "+f"(d[21]), "+f"(d[22]), "+f"(d[23]),
        "+f"(d[24]), "+f"(d[25]), "+f"(d[26]), "+f"(d[27]), "+f"(d[28]), "+f"(d[29]), "+f"(d[30]), "+f"(d[31]),
        "+f"(d[32]), "+f"(d[33]), "+f"(d[34]), "+f"(d[35]), "+f"(d[36]), "+f"(d[37]), "+f"(d[38]), "+f"(d[39]),
        "+f"(d[40]), "+f"(d[41]), "+f"(d[42]), "+f"(d[43]), "+f"(d[44]), "+f"(d[45]), "+f"(d[46]), "+f"(d[47]),
        "+f"(d[48]), "+f"(d[49]), "+f"(d[50]), "+f"(d[51]), "+f"(d[52]), "+f"(d[53]), "+f"(d[54]), "+f"(d[55]),
        "+f"(d[56]), "+f"(d[57]), "+f"(d[58]), "+f"(d[59]), "+f"(d[60]), "+f"(d[61]), "+f"(d[62]), "+f"(d[63]),
        "+f"(d[64]), "+f"(d[65]), "+f"(d[66]), "+f"(d[67]), "+f"(d[68]), "+f"(d[69]), "+f"(d[70]), "+f"(d[71]),
        "+f"(d[72]), "+f"(d[73]), "+f"(d[74]), "+f"(d[75]), "+f"(d[76]), "+f"(d[77]), "+f"(d[78]), "+f"(d[79]),
        "+f"(d[80]), "+f"(d[81]), "+f"(d[82]), "+f"(d[83]), "+f"(d[84]), "+f"(d[85]), "+f"(d[86]), "+f"(d[87]),
        "+f"(d[88]), "+f"(d[89]), "+f"(d[90]), "+f"(d[91]), "+f"(d[92]), "+f"(d[93]), "+f"(d[94]), "+f"(d[95])
      : "r"(da), "r"(db), "r"(scale_d), "n"(DESC_HI), "n"(DESC_HI64));
}
DEVI void wgmma_n64(float (&d)[32], uint32_t da, uint32_t db, int scale_d) {
  asm volatile(
      "{\n.reg .pred p;\n.reg .b64 da, db;\nsetp.ne.b32 p, %34, 0;\nmov.b64 da, {%32, %35};\nmov.b64 db, {%33, %35};\n"
      "wgmma.mma_async.sync.aligned.m64n64k16.f32.bf16.bf16 "
      "{%0,%1,%2,%3,%4,%5,%6,%7,%8,%9,%10,%11,%12,%13,%14,%15,"
      "%16,%17,%18,%19,%20,%21,%22,%23,%24,%25,%26,%27,%28,%29,%30,%31}, "
      "da, db, p, 1, 1, 0, 1;\n}"
      : "+f"(d[0]), "+f"(d[1]), "+f"(d[2]), "+f"(d[3]), "+f"(d[4]), "+f"(d[5]), "+f"(d[6]), "+f"(d[7]),
        "+f"(d[8]), "+f"(d[9]), "+f"(d[10]), "+f"(d[11]), "+f"(d[12]), "+f"(d[13]), "+f"(d[14]), "+f"(d[15]),
        "+f"(d[16]), "+f"(d[17]), "+f"(d[18]), "+f"(d[19]), "+f"(d[20]), "+f"(d[21]), "+f"(d[22]), "+f"(d[23]),
        "+f"(d[24]), "+f"(d[25]), "+f"(d[26]), "+f"(d[27]), "+f"(d[28]), "+f"(d[29]), "+f"(d[30]), "+f"(d[31])
      : "r"(da), "r"(db), "r"(scale_d), "n"(DESC_HI));
}

struct C32 { float re, im; };
DEVI C32 csq(C32 a) { return {a.re * a.re - a.im * a.im, 2.f * a.re * a.im}; }
DEVI C32 cmul(C32 a, C32 b) { return {a.re * b.re - a.im * b.im, a.re * b.im + a.im * b.re}; }
DEVI C32 cfresh(float zl, float zi, float m) {
  float mag = ex2(zl * m), ph = zi * m;
  return {mag * __cosf(ph), mag * __sinf(ph)};
}
struct HMul { uint32_t b, bp; };
DEVI HMul mk_mul(float re, float im) { return {pack_f16(re, im), pack_f16(-im, re)}; }
DEVI uint32_t hcmul(uint32_t a, const HMul& m) {
  __half2 ah = *reinterpret_cast<__half2*>(&a);
  __half2 b = *reinterpret_cast<const __half2*>(&m.b), bp = *reinterpret_cast<const __half2*>(&m.bp);
  __half2 r = __hfma2(__high2half2(ah), bp, __hmul2(__low2half2(ah), b));
  return *reinterpret_cast<uint32_t*>(&r);
}
DEVI uint32_t badd(uint32_t a, uint32_t b) {
  __nv_bfloat162 r = __hadd2(*reinterpret_cast<__nv_bfloat162*>(&a), *reinterpret_cast<__nv_bfloat162*>(&b));
  return *reinterpret_cast<uint32_t*>(&r);
}
template <int MU0, int NMU, int DMAX>
DEVI void conv_tail(float (&acc)[16][4], uint32_t p_lane, uint32_t v_base, int back, bool edge, int lane) {
  const int hsel = (lane >> 3) & 1;
  const int row = (lane & 7) + ((lane >> 4) << 3) + PADV - 8 - (back & (hsel ^ 1));
  const uint32_t la = v_base + row * 32 + (((hsel ^ back) ^ ((row >> 2) & 1)) << 4);
  uint32_t M[3][4];
  ldsm_x4_t(M[0], la);
  ldsm_x4_t(M[1], la + 256);
  uint32_t H[2 * NMU];
#pragma unroll
  for (int i = 0; i < 2 * NMU; ++i) H[i ^ 1] = lds32(p_lane + (uint32_t)(MU0 - 1 + i) * 32);
  if (edge) {
    const uint32_t a[4] = {0u, 0u, M[0][0], M[0][1]};
#pragma unroll
    for (int k = 1; k < NMU; ++k) mma_bf16v(acc[MU0 - 2 + 2 * k], a, H[2 * k], H[2 * k + 1]);
  }
#pragma unroll
  for (int delta = -1; delta <= DMAX; ++delta) {
    if (delta + 2 <= DMAX) ldsm_x4_t(M[(delta + 3) % 3], la + (delta + 3) * 256);
#pragma unroll
    for (int k = 0; k < NMU; ++k)
      if (delta + MU0 + 2 * k < 16) mma_bf16v(acc[delta + MU0 + 2 * k], M[(delta + 1) % 3], H[2 * k], H[2 * k + 1]);
  }
}

__global__ void __cluster_dims__(2, 1, 1) __launch_bounds__(NTHREADS, 1)
fused_kernel(const __grid_constant__ Maps maps, const Ptrs p) {
  extern __shared__ __align__(1024) uint8_t smem[];
  const uint32_t sb = s2u(smem);
  const int tid = threadIdx.x, lane = tid & 31;
  const int warp = __shfl_sync(0xffffffffu, tid >> 5, 0);
  const int cta = blockIdx.x;
  const uint32_t rank = cta & 1;
  const int ti = 2 * (cta >> 4) + rank;
  const int tj = (cta >> 1) & 7;
  const int pi = cta >> 3, pj = cta & 7;
  const uint32_t bars = sb + SM_BAR;
#define BAR(i) (bars + 8 * (i))
  const int g = lane >> 2, q = lane & 3;

  auto issue_stage = [&](int ks, int s) {
    const uint32_t st = sb + s * STG_BYTES, fb = BAR(B_FULL + s);
    mbar_expect_tx(fb, STG_BYTES);
    tma_load_2d(st + STG_X, &maps.x, ks * 32, ti * 128, fb);
    tma_load_3d_mc(st + STG_W + rank * 6144, &maps.w, tj * 64, ks * 32 + rank * 16, 0, fb, 3);
  };

  const int kch = warp & 3, krd = warp >> 2;
  float zr, zi, wr, wi;
  unsigned epoch;
  uint32_t r_dskip;
  {
    const size_t po = (size_t)(cta * 4 + kch) * 128 + krd * 32 + lane;
    const uint32_t r_ar = ldg16(p.A_re + po), r_ai = ldg16(p.A_im + po), r_br = ldg16(p.B_re + po), r_bi = ldg16(p.B_im + po);
    const uint32_t r_cr = ldg16(p.C_re + po), r_ci = ldg16(p.C_im + po), r_ldt = ldg16(p.log_dt + cta * 4 + kch);
    epoch = __ldcg(&g_epoch);
    r_dskip = ldg16(p.Dskip + cta * 4 + kch);
    uint4 pt;
    if (tid < 128) pt = __ldg((const uint4*)g_ptab.v + tid);
    if (tid == 384) {
      TS(0);
#pragma unroll
      for (int i = 0; i < B_COUNT; ++i) mbar_init(BAR(i), bar_count(i));
      asm volatile("fence.mbarrier_init.release.cluster;" ::: "memory");
      prefetch_tmap(&maps.x); prefetch_tmap(&maps.w); prefetch_tmap(&maps.u);
    }
    __syncthreads();
    cluster_arrive();
    if (warp >= 12) {
      cluster_wait();
      if (elect_one()) {
        if (warp == 13) {
          mbar_expect_tx(BAR(B_TILE), 16384);
          tma_load_2d(sb + SM_U, &maps.u, tj * 64, ti * 128, BAR(B_TILE));
          prefetch_tmap(&maps.uT); prefetch_tmap(&maps.wo); prefetch_tmap(&maps.o); prefetch_tmap(&maps.yT);
          prefetch_tmap(&maps.out);
        } else {
          if (warp == 12) TS(61);
          { const int ks = warp == 12 ? 0 : warp - 13; issue_stage(ks, ks); }
        }
      }
      __syncwarp();
    }
    if (tid < 128) sts128(sb + SM_PTAB + tid * 16, pt.x, pt.y, pt.z, pt.w);
    const float dt = round_bf16(expf(bf_lo(r_ldt)));
    zr = dt * bf_lo(r_ar); zi = dt * bf_lo(r_ai);
    const float dbr = dt * bf_lo(r_br), dbi = dt * bf_lo(r_bi), cr = bf_lo(r_cr), ci = bf_lo(r_ci);
    wr = cr * dbr - ci * dbi; wi = cr * dbi + ci * dbr;
  }
  {
    const float mz = __uint_as_float(__reduce_max_sync(0xffffffffu, __float_as_uint(fmaxf(zr, 0.f))));
    const int E = min(max((int)(__reduce_max_sync(0xffffffffu, __float_as_uint(fmaxf(fabsf(wr), fabsf(wi)))) >> 23), 1), 252);
    const float sc = __int_as_float((253 - E) << 23), inv = __int_as_float((E + 1) << 23);
    const float zl = (zr - mz) * 1.4426950408889634f;
    const uint32_t tb = sb + SM_VV + kch * VV_BYTES + krd * KG_BYTES;
    const uint32_t sta = tb + (((lane >> 2) << 4) | ((lane & 3) << 2));
    auto put = [&](int r, uint32_t v) { sts32((sta ^ ((r & 7) << 4)) + r * 128, v); };
    const uint32_t lda = tb + ((lane & 7) + (((lane >> 3) & 1) << 3)) * 128;
    const uint32_t ldb = tb + ((lane & 7) + ((lane >> 4) << 3)) * 128;
    C32 e1 = cfresh(zl, zi, 1.f), e2 = csq(e1), e4 = csq(e2), e8 = csq(e4);
    C32 e16 = cfresh(zl, zi, 16.f), e32 = csq(e16), e64 = csq(e32), e128 = csq(e64);
    C32 e256 = cfresh(zl, zi, 256.f), e512 = csq(e256), e1024 = csq(e512), e768 = cmul(e512, e256);
    uint32_t XA[2][4][4];
    {
      const HMul m16 = mk_mul(e16.re, e16.im), m32 = mk_mul(e32.re, e32.im), m64 = mk_mul(e64.re, e64.im);
      const HMul m128 = mk_mul(e128.re, e128.im);
      uint32_t X[16];
      X[0] = 0x00003c00u; X[1] = pack_f16(e8.re, e8.im); X[2] = m16.b; X[4] = m32.b; X[8] = m64.b;
      X[3] = hcmul(X[1], m16); X[5] = hcmul(X[1], m32); X[6] = hcmul(X[2], m32); X[7] = hcmul(X[3], m32);
#pragma unroll
      for (int r = 1; r < 8; ++r) X[8 + r] = hcmul(X[r], m64);
#pragma unroll
      for (int h = 0; h < 2; ++h) {
#pragma unroll
        for (int r = 0; r < 16; ++r) put(r, h == 0 ? X[r] : r == 0 ? m128.b : hcmul(X[r], m128));
        __syncwarp();
#pragma unroll
        for (int k = 0; k < 4; ++k) ldsm_x4(XA[h][k], lda + (((2 * k + (lane >> 4)) ^ (lane & 7)) << 4));
        __syncwarp();
      }
    }
    if (warp >= 14 && elect_one()) {
      issue_stage(warp - 11, warp - 11);
      issue_stage(warp - 9, warp - 9);
      if (warp == 14) l2_prefetch((const char*)p.wqkv + 224 * 3072 + cta * 6912, 6912);
      else l2_prefetch((const char*)p.x + (size_t)cta * 16384, 16384);
    }
    __syncwarp();
    float D[2][3][4];
#pragma unroll
    for (int t = 0; t < 6; ++t) D[t / 3][t % 3][0] = D[t / 3][t % 3][1] = D[t / 3][t % 3][2] = D[t / 3][t % 3][3] = 0.f;
    auto contract = [&](int t0, int nt) {
      __syncwarp();
#pragma unroll
      for (int k = 0; k < 4; ++k) {
        uint32_t b[4];
        ldsm_x4(b, ldb + (((2 * k + ((lane >> 3) & 1)) ^ (lane & 7)) << 4));
#pragma unroll
        for (int h = 0; h < 2; ++h) {
          mma_f16(D[h][t0], XA[h][k], b[0], b[1]);
          if (nt == 2) mma_f16(D[h][t0 + 1], XA[h][k], b[2], b[3]);
        }
      }
      __syncwarp();
    };
    const HMul c1 = mk_mul(e1.re, -e1.im), c2 = mk_mul(e2.re, -e2.im), c4 = mk_mul(e4.re, -e4.im);
    const HMul c256 = mk_mul(e256.re, -e256.im), c512 = mk_mul(e512.re, -e512.im), c768 = mk_mul(e768.re, -e768.im);
    const HMul c1024 = mk_mul(e1024.re, -e1024.im);
    uint32_t W[8];
    W[0] = pack_f16(wr * sc, -wi * sc);
    W[1] = hcmul(W[0], c1); W[2] = hcmul(W[0], c2); W[3] = hcmul(W[1], c2);
    W[4] = hcmul(W[0], c4); W[5] = hcmul(W[1], c4); W[6] = hcmul(W[2], c4); W[7] = hcmul(W[3], c4);
#pragma unroll
    for (int i = 0; i < 8; ++i) put(i, W[i]);
#pragma unroll
    for (int i = 0; i < 4; ++i) put(8 + i, hcmul(W[2 * i], c256));
    put(12, hcmul(W[0], c512)); put(13, hcmul(W[4], c512)); put(14, hcmul(W[0], c768)); put(15, hcmul(W[4], c768));
    contract(0, 2);
    const uint32_t v0 = hcmul(W[0], c1024);
    put(0, v0); put(1, hcmul(v0, c256)); put(2, hcmul(v0, c512)); put(3, hcmul(v0, c768)); put(4, hcmul(v0, c1024));
    contract(2, 1);
    const uint32_t a = tb + (g * 24 + 2 * q) * 4;
#pragma unroll
    for (int t = 0; t < 6; ++t) {
      const float(&d)[4] = D[t / 3][t % 3];
      sts_f32x2(a + (t / 3) * 1536 + (t % 3) * 32, d[0] * inv, d[1] * inv);
      sts_f32x2(a + (t / 3) * 1536 + (t % 3) * 32 + 768, d[2] * inv, d[3] * inv);
    }
    if (mz > 0.f) {
      __syncwarp();
#pragma unroll 1
      for (int i = lane; i < 768; i += 32) {
        const int r = i / 24, y = i - 24 * r;
        sts_f32(tb + i * 4, lds_f32(tb + i * 4) * ex2(mz * 1.4426950408889634f * (koff(y) + 8 * r)));
      }
    }
  }
  if (tid == 0) TS(2);
  if (warp < 12) cluster_wait();
  if (tid == 0) TS(32);
  __syncthreads();
  if (tid == 0) TSD(33);

  if (warp < 4) {
    asm volatile("setmaxnreg.inc.sync.aligned.u32 152;");
    if (tid == 0) TS(34);
    const int d = cta * 4 + warp;
    const uint32_t vv = sb + SM_VV + warp * VV_BYTES;
    const uint32_t ub = sb + SM_U + warp * U_BYTES;
    const uint32_t pb = sb + SM_P + warp * P_BYTES;
    const float dskip = bf_lo(r_dskip);
#pragma unroll 1
    for (int pass = 0; pass < 2; ++pass) {
      if (pass == 1) {
        const uint32_t kf = vv;
#pragma unroll 2
        for (int i = 0; i < 6; ++i) {
          const uint32_t a = kf + (i * 32 + lane) * 16;
          const uint4 x0 = lds128(a), x1 = lds128(a + KG_BYTES), x2 = lds128(a + 2 * KG_BYTES), x3 = lds128(a + 3 * KG_BYTES);
          auto s4 = [](uint32_t a0, uint32_t a1, uint32_t a2, uint32_t a3) {
            return __float_as_uint((__uint_as_float(a0) + __uint_as_float(a1)) + (__uint_as_float(a2) + __uint_as_float(a3)));
          };
          sts128(a, s4(x0.x, x1.x, x2.x, x3.x), s4(x0.y, x1.y, x2.y, x3.y), s4(x0.z, x1.z, x2.z, x3.z), s4(x0.w, x1.w, x2.w, x3.w));
        }
        __syncwarp();
        const float k1024 = lds_f32(kf + kidx_c(1024) * 4);
        if (lane == 0) {
          sts_f32(kf + SL_ZERO * 4, 0.f);
          sts_f32(kf + SL_510 * 4, lds_f32(kf + kidx_c(510) * 4) - lds_f32(kf + kidx_c(512) * 4));
          sts_f32(kf + SL_0 * 4, lds_f32(kf) + dskip);
        }
        __syncwarp();
        if (tid == 0) TS(36);
        mbar_wait_long(BAR(B_PFREE), 0);
        if (tid == 0) TS(37);
        {
          float prev = 0.f;
#pragma unroll 1
          for (int i0 = 0; i0 < 16; i0 += 4) {
            uint32_t e[4];
            float a[4], b[4];
#pragma unroll
            for (int i = 0; i < 4; ++i) e[i] = lds32(sb + SM_PTAB + ((i0 + i) * 32 + lane) * 4);
#pragma unroll
            for (int i = 0; i < 4; ++i) { a[i] = lds_f32(kf + (e[i] & 0xffff)); b[i] = lds_f32(kf + (e[i] >> 16)); }
#pragma unroll
            for (int i = 0; i < 4; ++i) {
              const uint32_t w = pb + (31 * lane + 2 * (i0 + i)) * 4;
              if (i0 + i > 0) sts32(w - 4, pack_bf16(a[i], prev));
              sts32(w, pack_bf16(b[i], a[i]));
              prev = b[i];
            }
          }
        }
        __syncwarp();
        if (lane == 0) TS(4);
        const int gq = g - 2 * q;
        uint32_t h127, h128;
        {
          const uint32_t kf2 = pack_bf16(k1024, k1024) ^ 0x80008000u;
          h127 = (gq == 4 ? 0x0000ffffu : gq == 5 ? 0xffffffffu : gq == 6 ? 0xffff0000u : 0u) & kf2;
          h128 = (gq == -4 ? 0x0000ffffu : gq == -3 ? 0xffffffffu : gq == -2 ? 0xffff0000u : 0u) & kf2;
        }
        bar_sync(4, 480);
        mbar_wait_long(BAR(B_UCH + warp), 0);
        if (lane == 0) TS(7);
        float acc[16][4];
#pragma unroll
        for (int i = 0; i < 16; ++i) { acc[i][0] = acc[i][1] = acc[i][2] = acc[i][3] = 0.f; }
        {
          const uint32_t pd_lane = pb + (PD_OFF + 16 + gq) * 4;
          const int prow0 = 8 + (lane & 7) + ((lane >> 4) << 3), hs = (lane >> 3) & 1;
          const uint32_t zero = (uint32_t)cta >> 20;
          uint32_t B[2][4][4];
          uint32_t A[4][4];
          const uint32_t la0 = ub + prow0 * 32 + ((hs ^ ((prow0 >> 2) & 1)) << 4);
#pragma unroll
          for (int m2 = 0; m2 < 4; ++m2) ldsm_x4(B[0][m2], la0 + m2 * 512);
#pragma unroll
          for (int i = 0; i < 4; ++i) {
            const uint32_t a = pd_lane + i * 512;
            A[i][0] = lds32(a); A[i][1] = lds32(a + 32); A[i][2] = lds32(a - 32); A[i][3] = lds32(a + zero);
          }
          uint32_t la = la0;
#define UNR_RHO 4
#define UNR_TAIL 2
          constexpr int unr_rho = UNR_RHO, unr_tail = UNR_TAIL;
#pragma unroll unr_rho
          for (int rho = 0; rho < 8; ++rho) {
#pragma unroll
            for (int m2 = 0; m2 < 4; ++m2) ldsm_x4(B[1][m2], la + (4 + m2) * 512);
#pragma unroll
            for (int i = 0; i < 4; ++i)
#pragma unroll
              for (int m = 0; m < 8; ++m) mma_bf16v(acc[m + i], A[i], B[0][m >> 1][2 * (m & 1)], B[0][m >> 1][2 * (m & 1) + 1]);
            const int prow = prow0 - min(rho + 1, 7);
            la = ub + prow * 32 + ((hs ^ ((prow >> 2) & 1)) << 4);
#pragma unroll
            for (int m2 = 0; m2 < 4; ++m2) ldsm_x4(B[0][m2], la + m2 * 512);
            const uint32_t pa = pd_lane + (rho + 1) * 64;
#pragma unroll
            for (int i = 0; i < 4; ++i) {
#pragma unroll
              for (int m = 0; m < 8 - i; ++m)
                mma_bf16v(acc[8 + m + i], A[i], B[1][m >> 1][2 * (m & 1)], B[1][m >> 1][2 * (m & 1) + 1]);
              A[i][0] = lds32(pa + i * 512); A[i][1] = lds32(pa + i * 512 + 32); A[i][2] = lds32(pa + i * 512 - 32);
              A[i][3] = lds32(pa + i * 512 + zero);
            }
          }
          if (lane == 0) TS(40);
          {
            uint32_t b8[4];
            ldsm_x4(b8, la + 4 * 512);
            const uint32_t h63 = lds32(pd_lane + 63 * 32), h64 = lds32(pd_lane + 64 * 32);
            const uint32_t a63[4] = {0u, h127, 0u, 0u}, a32[4] = {h64, 0u, h63, h64}, a64[4] = {h128, 0u, h127, h128};
#pragma unroll
            for (int m2 = 0; m2 < 4; ++m2) ldsm_x4(B[1][m2], la0 + m2 * 512);
#pragma unroll
            for (int m = 0; m < 8; ++m) mma_bf16v(acc[m + 7], a63, B[0][m >> 1][2 * (m & 1)], B[0][m >> 1][2 * (m & 1) + 1]);
#pragma unroll
            for (int m2 = 0; m2 < 2; ++m2) ldsm_x4(B[0][m2], la0 + (4 + m2) * 512);
#pragma unroll
            for (int m = 0; m < 8; ++m) mma_bf16v(acc[m + 4], a32, B[1][m >> 1][2 * (m & 1)], B[1][m >> 1][2 * (m & 1) + 1]);
            mma_bf16v(acc[15], a63, b8[0], b8[1]);
#pragma unroll
            for (int m = 0; m < 8; ++m) mma_bf16v(acc[m + 8], a64, B[1][m >> 1][2 * (m & 1)], B[1][m >> 1][2 * (m & 1) + 1]);
#pragma unroll
            for (int m = 0; m < 4; ++m) mma_bf16v(acc[m + 12], a32, B[0][m >> 1][2 * (m & 1)], B[0][m >> 1][2 * (m & 1) + 1]);
          }
          if (lane == 0) TS(41);
          bar_sync(5, 224);
#pragma unroll unr_tail
          for (int v = 0; v < 4; ++v)
            conv_tail<4, 3, 11>(acc, pb + (P2_OFF + 56 * v + gq - 16) * 4, vv + ((v & 1) ? VV_U3 : VV_U5), v >> 1, v == 0, lane);
          if (lane == 0) TS(42);
#pragma unroll unr_tail
          for (int pi = 0; pi < 2; ++pi)
            conv_tail<8, 5, 7>(acc, pb + (P3_OFF + 88 * pi + gq - 48) * 4, vv + (pi ? VV_U7 : VV_U9), pi, pi == 0, lane);
        }
        if (lane == 0) TS(8);
        __syncwarp();
        {
          const int mt = lane >> 3;
          const uint32_t a = pb + (128 * (mt >> 1) + 16 * (lane & 7) + 8 * (mt & 1)) * 2;
#pragma unroll
          for (int ab = 0; ab < 16; ab += 2)
            stsm_x4_t(a + ab * 256, pack_bf16(acc[ab][0], acc[ab][1]), pack_bf16(acc[ab][2], acc[ab][3]),
                      pack_bf16(acc[ab + 1][0], acc[ab + 1][1]), pack_bf16(acc[ab + 1][2], acc[ab + 1][3]));
        }
        fence_async_smem();
        __syncwarp();
        if (lane < 2) mbar_arrive_cluster(BAR(B_CONVD), lane);
        bar_arrive(3, 384);
        if (elect_one()) {
          bulk_store(p.yT + (size_t)d * 2048, pb, 4096);
          bulk_commit();
          bulk_wait0();
          red_relaxed_add(&g_cnt[(C_Y + (cta >> 4)) * 32], 1);
          TS(9);
        }
        bar_sync(2, 128);
        if (warp == 0 && elect_one()) {
          wait_counter(&g_cnt[(C_Y + tj) * 32], (epoch + 1) * 64);
          TS(28);
          mbar_expect_tx(BAR(B_TILE), 16384);
          tma_load_2d(sb + SM_U, &maps.yT, ti * 128, tj * 64, BAR(B_TILE));
          tma_load_2d(sb + SM_U + 8192, &maps.yT, ti * 128 + 64, tj * 64, BAR(B_TILE));
        }
        __syncwarp();
      }
      mbar_wait_long(BAR(B_TILE), pass);
      if (lane == 0) TS(26 + 3 * pass);
      {
        const int m = lane >> 3, r = lane & 7;
#pragma unroll 2
        for (int it = 0; it < 8; ++it) {
          const int tb = warp * 4 + (it >> 1), cb = (it & 1) * 4 + m;
          const uint32_t at = (tb * 8 + r) * 128 + ((cb ^ r) << 4);
          const uint32_t ac = (tb >> 3) * 8192 + (cb * 8 + r) * 128 + (((tb & 7) ^ (pass ? 0 : tb >> 3) ^ r) << 4);
          uint32_t v[4];
          ldsm_x4_t(v, sb + SM_U + (pass ? ac : at));
          stsm_x4(sb + SM_P + (pass ? at : ac), v[0], v[1], v[2], v[3]);
        }
      }
      if (pass == 0 && tid == 0) TS(35);
      fence_async_smem();
      if (pass == 0) {
        bar_arrive(6, 160);
      } else {
        bar_sync(2, 128);
        if (warp == 0 && elect_one()) {
          tma_store_2d(&maps.out, sb + SM_P, 64 * tj, 128 * ti);
          bulk_commit();
          bulk_wait_read0();
          TS(30);
        }
      }
    }
  } else if (warp < 12) {
    asm volatile("setmaxnreg.inc.sync.aligned.u32 160;");
    const int w8 = warp - 4;
    const int row = w8 * 16 + (lane & 7) + (((lane >> 3) & 1) << 3);
    {
      float acc[96];
#pragma unroll 1
      for (int ks = 0, s = 0, ph = 0; ks < 16; ++ks) {
        mbar_wait(BAR(B_FULL + s), ph);
        if (tid == 128 && !(ks & 1)) TSR(16, ks == 0 ? 16 : 9 + (ks >> 1) + (ks > 12 ? 43 : 0));
        const uint32_t st = sb + s * STG_BYTES;
        const uint32_t da = mkdesc(st + STG_X + (w8 >> 2) * 4096, 16);
        const uint32_t db = mkdesc(st + STG_W, 2048);
        wg_fence();
        wgmma_n192(acc, da, db, ks != 0);
        wgmma_n192(acc, da + 2, db + 384, 1);
        wg_commit();
        const uint32_t eprev = BAR(B_EMPTY + (s == 0 ? NSTG - 1 : s - 1));
        if (++s == NSTG) { s = 0; ph ^= 1; }
        if (ks > 0) {
          wg_wait<1>();
          if (lane < 2) mbar_arrive_cluster(eprev, lane);
        }
      }
      wg_wait<0>();
      bar_arrive(4, 480);
      if (tid == 128) TS(17);
      bar_sync(1, 256);
#pragma unroll
      for (int i = 0; i < 24; i += 2)
        stsm_x4(sb + SM_QS + row * 128 + (i >> 3) * 16384 + ((((i & 7) + (lane >> 4)) ^ (row & 7)) << 4),
                pack_bf16(acc[4 * i], acc[4 * i + 1]), pack_bf16(acc[4 * i + 2], acc[4 * i + 3]),
                pack_bf16(acc[4 * i + 4], acc[4 * i + 5]), pack_bf16(acc[4 * i + 6], acc[4 * i + 7]));
    }
    __syncwarp();
#pragma unroll 1
    for (int part = 1; part >= 0; --part) {
      const uint32_t pa = sb + SM_QS + part * 16384 + w8 * 2048 + lane * 16;
#pragma unroll 1
      for (int it = 0; it < 4; ++it) {
        uint4 t = lds128(pa + it * 512);
        uint32_t* tw = &t.x;
#pragma unroll
        for (int j = 0; j < 4; ++j) {
          const uint32_t x = tw[j];
          const __nv_bfloat162 xb = *reinterpret_cast<const __nv_bfloat162*>(&x);
          const uint32_t e = pack_bf16(ex2(bf_lo(x) * 1.4426950408889634f), ex2(bf_hi(x) * 1.4426950408889634f));
          const uint32_t m = __hgt2_mask(xb, __floats2bfloat162_rn(0.f, 0.f));
          tw[j] = badd((badd(x, 0x3f803f80u) & m) | (e & ~m), 0x35863586u);
        }
        sts128(pa + it * 512, t.x, t.y, t.z, t.w);
      }
      if (part == 1) {
        if (tid == 128) TS(53);
        bar_sync(1, 256);
        const int hh = w8 >> 1, dtile = w8 & 1;
        float kv[4] = {0.f, 0.f, 0.f, 0.f}, zz[4] = {0.f, 0.f, 0.f, 0.f};
        const int m = lane >> 3;
        const uint32_t aa = sb + SM_VS + ((lane & 7) + ((m >> 1) << 3)) * 128 + (((2 * hh + (m & 1)) ^ (lane & 7)) << 4);
        const uint32_t ab = sb + SM_PK + (lane & 15) * 128 + (((2 * hh + dtile) ^ (lane & 7)) << 4);
#pragma unroll 2
        for (int ks = 0; ks < 8; ++ks) {
          uint32_t a[4], b0, b1;
          ldsm_x4_t(a, aa + ks * 2048);
          ldsm_x2_t(b0, b1, ab + ks * 2048);
          mma_bf16(kv, a[0], a[1], a[2], a[3], b0, b1);
          mma_bf16(zz, 0x3f803f80u, 0x3f803f80u, 0x3f803f80u, 0x3f803f80u, b0, b1);
        }
        const uint32_t kp = sb + SM_KV + hh * 1088;
        sts128(kp + dtile * 512 + lane * 16, __float_as_uint(kv[0]), __float_as_uint(kv[1]), __float_as_uint(kv[2]),
               __float_as_uint(kv[3]));
        if (g == 0) sts_f32x2(kp + 1024 + dtile * 32 + q * 8, zz[0], zz[1]);
        fence_async_smem();
        __syncwarp();
        if (lane == 0) mbar_arrive(BAR(B_KVP));
        if (tid == 128) TS(55);
      }
    }
    if (tid == 128) TS(56);
    mbar_wait_long(BAR(B_KVF), 0);
    if (tid == 128) TS(19);
#pragma unroll 1
    for (int h = 0; h < 4; ++h) {
      uint32_t a[4];
      const uint32_t qa = sb + SM_QS + row * 128 + (((2 * h + (lane >> 4)) ^ (row & 7)) << 4);
      ldsm_x4(a, qa);
      const uint32_t kp = sb + SM_KV + h * 1088;
      const uint4 k0 = lds128(kp + lane * 16), k1 = lds128(kp + 512 + lane * 16);
      const uint32_t za = kp + 1024 + q * 8;
      auto pk2 = [](uint32_t x, uint32_t y) { return pack_bf16(__uint_as_float(x), __uint_as_float(y)); };
      float n0[4] = {0.f, 0.f, 0.f, 0.f}, n1[4] = {0.f, 0.f, 0.f, 0.f}, dn[4] = {0.f, 0.f, 0.f, 0.f};
      mma_bf16(n0, a[0], a[1], a[2], a[3], pk2(k0.x, k0.y), pk2(k1.x, k1.y));
      mma_bf16(n1, a[0], a[1], a[2], a[3], pk2(k0.z, k0.w), pk2(k1.z, k1.w));
      mma_bf16(dn, a[0], a[1], a[2], a[3], pack_bf16(lds_f32(za), lds_f32(za + 4)), pack_bf16(lds_f32(za + 32), lds_f32(za + 36)));
      const uint32_t dd = pack_bf16(dn[0], dn[2]);
      const uint32_t d2 = pack_bf16(bf_lo(dd) + 1e-6f, bf_hi(dd) + 1e-6f);
      const float r0 = rcp(bf_lo(d2)), r1 = rcp(bf_hi(d2));
      const uint32_t x0 = pack_bf16(n0[0], n0[1]), x1 = pack_bf16(n0[2], n0[3]);
      const uint32_t x2 = pack_bf16(n1[0], n1[1]), x3 = pack_bf16(n1[2], n1[3]);
      stsm_x4(qa, pack_bf16(bf_lo(x0) * r0, bf_hi(x0) * r0), pack_bf16(bf_lo(x1) * r1, bf_hi(x1) * r1),
              pack_bf16(bf_lo(x2) * r0, bf_hi(x2) * r0), pack_bf16(bf_lo(x3) * r1, bf_hi(x3) * r1));
    }
    fence_async_smem();
    __syncwarp();
    if (lane == 0) mbar_arrive(BAR(B_OST));
    if (tid == 128) TS(57);
    mbar_wait_long(BAR(B_WO), 0);
    bar_sync(3, 384);
    {
      float o[32];
#pragma unroll 1
      for (int c = 0; c < 8; ++c) {
        mbar_wait_long(BAR(B_RF + c), 0);
        if (tid == 128) TSR(22, c == 0 ? 22 : 43 + c);
        const uint32_t slot = c < 4 ? SM_QS + c * 16384 : c < 7 ? SM_VV + (c - 4) * 16384 : SM_QS;
        const uint32_t da = mkdesc(sb + slot + (w8 >> 2) * 8192, 16);
        const uint32_t db = mkdesc(sb + SM_WO + c * 8192, 8192);
        wg_fence();
#pragma unroll
        for (int k = 0; k < 4; ++k) wgmma_n64(o, da + 2 * k, db + 128 * k, (c | k) != 0);
        wg_commit();
        if (c == 1) {
          wg_wait<1>();
          if (lane < 2) mbar_arrive_cluster(BAR(B_RE), lane);
        }
      }
      wg_wait<0>();
      if (tid == 128) TS(51);
      bar_sync(1, 256);
#pragma unroll
      for (int i = 0; i < 8; i += 2)
        stsm_x4(sb + SM_BOUT + row * 128 + (((i + (lane >> 4)) ^ (row & 7)) << 4), pack_bf16(o[4 * i], o[4 * i + 1]),
                pack_bf16(o[4 * i + 2], o[4 * i + 3]), pack_bf16(o[4 * i + 4], o[4 * i + 5]), pack_bf16(o[4 * i + 6], o[4 * i + 7]));
      fence_async_smem();
      bar_sync(1, 256);
      if (tid == 128) TS(52);
      if (warp == 4 && elect_one()) {
        tma_store_2d(&maps.out, sb + SM_BOUT, 512 + 64 * pj, 128 * pi);
        bulk_commit();
        bulk_wait_read0();
        TS(23);
      }
    }
  } else {
    asm volatile("setmaxnreg.dec.sync.aligned.u32 40;");
    if (warp == 12) {
      if (elect_one()) {
#pragma unroll 1
        for (int ks = NSTG, s = 0, ph = 0; ks < 16; ++ks) {
          mbar_wait(BAR(B_EMPTY + s), ph);
          issue_stage(ks, s);
          if (ks == NSTG) l2_prefetch((const char*)p.wo + (size_t)cta * 4096, 4096);
          if (++s == NSTG) { s = 0; ph ^= 1; }
        }
        mbar_wait(BAR(B_EMPTY + 6), 1);
        mbar_expect_tx(BAR(B_WO), 65536);
        tma_load_2d(sb + SM_WO, &maps.wo, pj * 64, 0, BAR(B_WO));
        tma_load_2d(sb + SM_WO + 32768, &maps.wo, pj * 64, 256, BAR(B_WO));
        float* kvg = &g_kv[epoch & 1][tj][0];
        mbar_wait_long(BAR(B_KVP), 0);
        bulk_reduce_add_f32(kvg, sb + SM_KV, 4352);
        bulk_commit();
        bulk_wait0();
        red_relaxed_add(&g_cnt[(C_KV + tj) * 32], 1);
        TS(18);
        wait_counter(&g_cnt[(C_KV + tj) * 32], (epoch + 1) * 16);
        mbar_expect_tx(BAR(B_KVF), 4352);
        bulk_load(sb + SM_KV, kvg, 4352, BAR(B_KVF));
        mbar_wait_long(BAR(B_OST), 0);
        tma_store_2d(&maps.o, sb + SM_QS, tj * 64, ti * 128);
        tma_store_2d(&maps.o, sb + SM_QS + 8192, tj * 64, ti * 128 + 64);
        bulk_commit();
        bulk_wait0();
        red_relaxed_add(&g_cnt[(C_O + ti) * 32], 1);
        TS(20);
        mbar_arrive_cluster(BAR(B_SLOT), 0);
        mbar_arrive_cluster(BAR(B_SLOT), 1);
        wait_counter(&g_cnt[(C_O + pi) * 32], (epoch + 1) * 8);
        if (cta == 0) g_epoch = epoch + 1;
        mbar_wait(BAR(B_SLOT), 0);
        TS(21);
#pragma unroll 1
        for (int c = 0; c < 8; ++c) {
          if (c == 4) mbar_wait_long(BAR(B_CONVD), 0);
          if (c == 7) mbar_wait(BAR(B_RE), 0);
          const uint32_t slot = c < 4 ? SM_QS + c * 16384 : c < 7 ? SM_VV + (c - 4) * 16384 : SM_QS;
          mbar_expect_tx(BAR(B_RF + c), 16384);
          tma_load_2d_mc(sb + slot + rank * 8192, &maps.o, c * 64, pi * 128 + rank * 64, BAR(B_RF + c), 3);
        }
      }
    } else if (warp == 13) {
      bar_sync(6, 160);
      sts128(sb + SM_U + (lane >> 4) * U_BYTES + (lane & 15) * 16, 0, 0, 0, 0);
      sts128(sb + SM_U + (2 + (lane >> 4)) * U_BYTES + (lane & 15) * 16, 0, 0, 0, 0);
      __syncwarp();
      if (elect_one()) {
        tma_store_2d(&maps.uT, sb + SM_P, ti * 128, tj * 64);
        tma_store_2d(&maps.uT, sb + SM_P + 8192, ti * 128 + 64, tj * 64);
        bulk_commit();
        bulk_wait_read0();
        mbar_arrive(BAR(B_PFREE));
        bulk_wait0();
        red_relaxed_add(&g_cnt[(C_U + tj) * 32], 1);
        TS(27);
        wait_counter(&g_cnt[(C_U + (cta >> 4)) * 32], (epoch + 1) * 16);
#pragma unroll 1
        for (int c = 0; c < 4; ++c) {
          mbar_expect_tx(BAR(B_UCH + c), 4096);
          bulk_load(sb + SM_U + c * U_BYTES + 256, p.uT + (size_t)(cta * 4 + c) * 2048, 4096, BAR(B_UCH + c));
        }
        TS(3);
      }
      __syncwarp();
      if (ti == 0) {
        float4* z = (float4*)&g_kv[(epoch & 1) ^ 1][tj][0];
#pragma unroll 1
        for (int i = lane; i < 272; i += 32) z[i] = make_float4(0.f, 0.f, 0.f, 0.f);
      }
    }
    if (warp >= 13) {
      bar_sync(4, 480);
      auto swz = [](int k, int pad) { const int r = (k >> 1) + pad; return (uint32_t)(r * 32 + (((k & 1) ^ ((r >> 2) & 1)) << 4)); };
      const uint32_t o0 = swz(lane - 3, 8), o1 = swz(lane - 2, 8), o2 = swz(lane - 1, 8), ow = swz(lane - 2, PADV);
      const uint32_t oz = swz(lane - 18, PADV);
#pragma unroll 1
      for (int item = warp - 13; item < 28; item += 3) {
        const int ch = item / 7, it = item - 7 * ch;
        const int k = -2 + 32 * it + lane;
        const uint32_t ua = sb + SM_U + ch * U_BYTES + it * 512, vb = sb + SM_VV + ch * VV_BYTES;
        const uint32_t a0 = ua + o0, a1 = ua + o1, a2 = ua + o2, aw = vb + it * 512 + ow;
        mbar_wait_long(BAR(B_UCH + ch), 0);
        if (it == 0 && lane < 16) {
          sts128(vb + oz + VV_U3, 0, 0, 0, 0); sts128(vb + oz + VV_U5, 0, 0, 0, 0);
          sts128(vb + oz + VV_U7, 0, 0, 0, 0); sts128(vb + oz + VV_U9, 0, 0, 0, 0);
        }
        const uint4 t0 = lds128(a0), t1 = lds128(a1), t2 = lds128(a2);
        const uint32_t E[12] = {t0.x, t0.y, t0.z, t0.w, t1.x, t1.y, t1.z, t1.w, t2.x, t2.y, t2.z, t2.w};
        uint32_t O[8];
#pragma unroll
        for (int j = 0; j < 8; ++j) O[j] = __byte_perm(E[j + 1], E[j + 2], 0x5432);
        uint32_t s3[6], s5[4], s7[4], s9[4];
#pragma unroll
        for (int j = 0; j < 6; ++j) s3[j] = badd(badd(O[j], O[j + 1]), E[j + 2]);
#pragma unroll
        for (int j = 0; j < 4; ++j) {
          s5[j] = badd(s3[j + 2], badd(E[j + 3], E[j + 5]));
          s7[j] = badd(s5[j], badd(O[j + 1], O[j + 4]));
          s9[j] = badd(s7[j], badd(E[j + 2], E[j + 6]));
        }
        if (k < 208) { sts128(aw + VV_U3, s3[0], s3[1], s3[2], s3[3]); sts128(aw + VV_U5, s5[0], s5[1], s5[2], s5[3]); }
        if (k < 144) { sts128(aw + VV_U7, s7[0], s7[1], s7[2], s7[3]); sts128(aw + VV_U9, s9[0], s9[1], s9[2], s9[3]); }
      }
      if (tid == 416) TS(6);
      bar_arrive(5, 224);
    }
  }
  __syncwarp();
  cluster_arrive();
  cluster_wait();
  if (tid == 0) TS(31);
#undef BAR
}

typedef CUresult (*EncodeFn)(CUtensorMap*, CUtensorMapDataType, cuuint32_t, void*, const cuuint64_t*, const cuuint64_t*,
                             const cuuint32_t*, const cuuint32_t*, CUtensorMapInterleave, CUtensorMapSwizzle,
                             CUtensorMapL2promotion, CUtensorMapFloatOOBfill);

static void make_map(EncodeFn enc, CUtensorMap* m, const void* base, uint64_t inner, uint64_t outer, uint32_t box_in,
                     uint32_t box_out, CUtensorMapSwizzle swz = CU_TENSOR_MAP_SWIZZLE_128B) {
  cuuint64_t gd[2] = {inner, outer};
  cuuint64_t gs[1] = {inner * 2};
  cuuint32_t bd[2] = {box_in, box_out};
  cuuint32_t es[2] = {1, 1};
  enc(m, CU_TENSOR_MAP_DATA_TYPE_BFLOAT16, 2, const_cast<void*>(base), gd, gs, bd, es, CU_TENSOR_MAP_INTERLEAVE_NONE,
      swz, CU_TENSOR_MAP_L2_PROMOTION_L2_128B, CU_TENSOR_MAP_FLOAT_OOB_FILL_NONE);
}

}

extern "C" void kernel_launch(void* const* d_in, const int* in_sizes, int n_in, void* d_out, int out_size) {
  using namespace s4la;
  (void)in_sizes; (void)n_in; (void)out_size;
  static EncodeFn enc = nullptr;
  static void *uT = nullptr, *yT = nullptr, *oS = nullptr;
  if (!enc) {
    void* fn = nullptr;
    cudaDriverEntryPointQueryResult qr;
    cudaGetDriverEntryPoint("cuTensorMapEncodeTiled", &fn, cudaEnableDefault, &qr);
    enc = (EncodeFn)fn;
    cudaGetSymbolAddress(&uT, g_uT);
    cudaGetSymbolAddress(&yT, g_yT);
    cudaGetSymbolAddress(&oS, g_o);
    cudaFuncSetAttribute(fused_kernel, cudaFuncAttributeMaxDynamicSharedMemorySize, SM_TOTAL);
  }
  const __nv_bfloat16* const* in = (const __nv_bfloat16* const*)d_in;
  Maps maps;
  make_map(enc, &maps.x, in[9], 512, 2048, 32, 128, CU_TENSOR_MAP_SWIZZLE_64B);
  {
    cuuint64_t gd[3] = {512, 512, 3};
    cuuint64_t gs[2] = {3072, 1024};
    cuuint32_t bd[3] = {64, 16, 3};
    cuuint32_t es[3] = {1, 1, 1};
    enc(&maps.w, CU_TENSOR_MAP_DATA_TYPE_BFLOAT16, 3, const_cast<__nv_bfloat16*>(in[10]), gd, gs, bd, es,
        CU_TENSOR_MAP_INTERLEAVE_NONE, CU_TENSOR_MAP_SWIZZLE_128B, CU_TENSOR_MAP_L2_PROMOTION_L2_128B,
        CU_TENSOR_MAP_FLOAT_OOB_FILL_NONE);
  }
  make_map(enc, &maps.wo, in[11], 512, 512, 64, 256);
  make_map(enc, &maps.u, in[0], 512, 2048, 64, 128);
  make_map(enc, &maps.uT, uT, 2048, 512, 64, 64);
  make_map(enc, &maps.yT, yT, 2048, 512, 64, 64);
  make_map(enc, &maps.o, oS, 512, 2048, 64, 64);
  make_map(enc, &maps.out, d_out, 1024, 2048, 64, 128);
  Ptrs p;
  p.A_re = in[1]; p.A_im = in[2]; p.B_re = in[3]; p.B_im = in[4]; p.C_re = in[5]; p.C_im = in[6];
  p.log_dt = in[7]; p.Dskip = in[8]; p.x = in[9]; p.wqkv = in[10]; p.wo = in[11];
  p.uT = (__nv_bfloat16*)uT; p.yT = (__nv_bfloat16*)yT;
  fused_kernel<<<NCTA, NTHREADS, SM_TOTAL, cudaStreamPerThread>>>(maps, p);
}
```

```cpp
#include <cuda_runtime.h>
#include <cuda_bf16.h>
#include <cuda_fp16.h>
#include <cuda.h>
#include <stdint.h>

#define DEVI __device__ __forceinline__

namespace s4la {

constexpr int NTHREADS = 512;
constexpr int NCTA = 128;

constexpr int NSTG = 7;
constexpr uint32_t STG_BYTES = 20480, STG_X = 0, STG_W = 8192;
constexpr uint32_t SM_QS = 0;
constexpr uint32_t SM_PK = SM_QS + 16384, SM_VS = SM_QS + 32768;
constexpr uint32_t SM_WO = 65536;
constexpr uint32_t SM_KV = 131072;
constexpr uint32_t SM_BOUT = 16384;
constexpr uint32_t SM_U = 143360, U_BYTES = 4352;
constexpr uint32_t SM_P = 160768, P_BYTES = 4096;
constexpr uint32_t SM_VV = 177152, VV_BYTES = 12800;
constexpr uint32_t VV_U5 = 0, VV_U3 = 3712, VV_U9 = 7424, VV_U7 = 10112;
constexpr uint32_t KG_BYTES = 3200;
constexpr uint32_t SM_BAR = SM_VV + 4 * VV_BYTES;
constexpr uint32_t SM_PTAB = SM_BAR + 320;
constexpr uint32_t SM_TOTAL = SM_PTAB + 2048;
static_assert(SM_TOTAL <= 232448, "shared memory");
constexpr int PADV = 12;

enum { B_FULL = 0, B_EMPTY = 7, B_TILE = 14, B_UCH = 15, B_KVP = 19, B_KVF = 20, B_OST = 21, B_RF = 22, B_WO = 30, B_RE = 31, B_PFREE = 32, B_CONVD = 33, B_SLOT = 34, B_COUNT = 35 };
__host__ __device__ constexpr int bar_count(int i) {
  return (i >= B_EMPTY && i < B_TILE) ? 16 : (i == B_KVP || i == B_OST || i == B_CONVD) ? 8 : i == B_RE ? 16 : i == B_SLOT ? 2 : 1;
}

constexpr int PD_OFF = 0, P2_OFF = 544, P3_OFF = 768;

constexpr int SL_K2048 = 20, SL_ZERO = 21, SL_510 = 22, SL_0 = 23;
__host__ __device__ constexpr int koff(int y) {
  return y < 8 ? y : y < 12 ? 256 + 2 * (y - 8) : y < 16 ? 512 + 256 * ((y - 12) >> 1) + 4 * (y & 1) : 1024 + 256 * (y - 16);
}
__host__ __device__ constexpr int kidx_c(int l) {
  const int y = l < 256 ? (l & 7) : l < 512 ? 8 + ((l & 7) >> 1) : l < 1024 ? 12 + (((l - 512) >> 8) << 1) + ((l >> 2) & 1)
                                                                            : 16 + ((l - 1024) >> 8);
  return ((l >> 3) & 31) * 24 + y;
}
constexpr int slot_direct(int l) {
  if (l < 0 || l > 510) return SL_ZERO;
  if (l == 510) return SL_510;
  if (l == 0) return SL_0;
  return kidx_c(l < 256 ? l : ((l + ((l >> 1) & 1)) & ~1));
}
constexpr int slot_seg2(int v, int k) { return (k >= 32 && k < 64) ? kidx_c(16 * k + 4 * v) : SL_ZERO; }
constexpr int slot_seg3(int pi, int k) {
  return (k >= 64 && k < 128) ? kidx_c(16 * k + 8 * pi) : ((k == 128 && pi == 0) ? SL_K2048 : SL_ZERO);
}
constexpr int slot_word(int w) {
  return w < 0 ? SL_ZERO : w < 544 ? slot_direct(w - 16) : w < 768 ? slot_seg2((w - 544) / 56, 16 + (w - 544) % 56)
       : w < 944 ? slot_seg3((w - 768) / 88, 48 + (w - 768) % 88) : SL_ZERO;
}
struct PTab { uint32_t v[512]; };
constexpr PTab make_ptab() {
  PTab t{};
  for (int lane = 0; lane < 32; ++lane)
    for (int i = 0; i < 16; ++i)
      t.v[i * 32 + lane] = (slot_word(31 * lane - 1 + 2 * i) * 4) | ((slot_word(31 * lane + 2 * i) * 4) << 16);
  return t;
}
__device__ const PTab g_ptab = make_ptab();

__device__ __nv_bfloat16 g_uT[512 * 2048];
__device__ __nv_bfloat16 g_yT[512 * 2048];
__device__ __nv_bfloat16 g_o[2048 * 512];
__device__ float g_kv[2][8][4 * 272];
__device__ unsigned g_cnt[64 * 32];
__device__ unsigned g_epoch;
#define TS(slot) do { } while (0)
#define TSR(on, slot) do { } while (0)
#define TSD(slot) do { } while (0)
enum { C_U = 0, C_KV = 8, C_O = 16, C_Y = 32 };

struct Maps {
  CUtensorMap x, w, wo, u, uT, yT, o, out;
};
struct Ptrs {
  const __nv_bfloat16 *A_re, *A_im, *B_re, *B_im, *C_re, *C_im, *log_dt, *Dskip;
  const __nv_bfloat16 *x, *wqkv, *wo;
  __nv_bfloat16 *uT, *yT;
};

DEVI uint32_t s2u(const void* p) { return (uint32_t)__cvta_generic_to_shared(p); }
DEVI void mbar_init(uint32_t b, uint32_t c) { asm volatile("mbarrier.init.shared::cta.b64 [%0], %1;" ::"r"(b), "r"(c) : "memory"); }
DEVI void mbar_expect_tx(uint32_t b, uint32_t bytes) {
  asm volatile("mbarrier.arrive.expect_tx.shared::cta.b64 _, [%0], %1;" ::"r"(b), "r"(bytes) : "memory");
}
DEVI void mbar_arrive(uint32_t b) { asm volatile("mbarrier.arrive.shared::cta.b64 _, [%0];" ::"r"(b) : "memory"); }
DEVI void mbar_arrive_cluster(uint32_t b, uint32_t cta) {
  asm volatile("{\n.reg .b32 r;\nmapa.shared::cluster.u32 r, %0, %1;\nmbarrier.arrive.shared::cluster.b64 _, [r];\n}"
               ::"r"(b), "r"(cta) : "memory");
}
DEVI void mbar_wait(uint32_t b, uint32_t parity) {
  asm volatile("{\n.reg .pred p;\nLAB_WAIT:\nmbarrier.try_wait.parity.shared::cta.b64 p, [%0], %1;\n@!p bra LAB_WAIT;\n}"
               ::"r"(b), "r"(parity) : "memory");
}
DEVI void mbar_wait_long(uint32_t b, uint32_t parity) {
  asm volatile("{\n.reg .pred p;\nLAB_WAIT:\nmbarrier.try_wait.parity.shared::cta.b64 p, [%0], %1, 0x989680;\n@!p bra LAB_WAIT;\n}"
               ::"r"(b), "r"(parity) : "memory");
}
DEVI void bar_sync(int id, int n) { asm volatile("bar.sync %0, %1;" ::"r"(id), "r"(n) : "memory"); }
DEVI void bar_arrive(int id, int n) { asm volatile("bar.arrive %0, %1;" ::"r"(id), "r"(n) : "memory"); }
DEVI void fence_async_smem() { asm volatile("fence.proxy.async.shared::cta;" ::: "memory"); }
DEVI void fence_async_all() { asm volatile("fence.proxy.async;" ::: "memory"); }
DEVI void cluster_arrive() { asm volatile("barrier.cluster.arrive.relaxed.aligned;" ::: "memory"); }
DEVI void cluster_wait() { asm volatile("barrier.cluster.wait.aligned;" ::: "memory"); }

DEVI void tma_load_2d(uint32_t dst, const CUtensorMap* m, int c0, int c1, uint32_t bar) {
  asm volatile("cp.async.bulk.tensor.2d.shared::cluster.global.mbarrier::complete_tx::bytes [%0], [%1, {%3, %4}], [%2];"
               ::"r"(dst), "l"(m), "r"(bar), "r"(c0), "r"(c1) : "memory");
}
DEVI void tma_load_2d_mc(uint32_t dst, const CUtensorMap* m, int c0, int c1, uint32_t bar, uint16_t mask) {
  asm volatile("cp.async.bulk.tensor.2d.shared::cluster.global.mbarrier::complete_tx::bytes.multicast::cluster [%0], [%1, {%3, %4}], [%2], %5;"
               ::"r"(dst), "l"(m), "r"(bar), "r"(c0), "r"(c1), "h"(mask) : "memory");
}
DEVI void tma_load_3d_mc(uint32_t dst, const CUtensorMap* m, int c0, int c1, int c2, uint32_t bar, uint16_t mask) {
  asm volatile("cp.async.bulk.tensor.3d.shared::cluster.global.mbarrier::complete_tx::bytes.multicast::cluster [%0], [%1, {%3, %4, %5}], [%2], %6;"
               ::"r"(dst), "l"(m), "r"(bar), "r"(c0), "r"(c1), "r"(c2), "h"(mask) : "memory");
}
DEVI void tma_store_2d(const CUtensorMap* m, uint32_t src, int c0, int c1) {
  asm volatile("cp.async.bulk.tensor.2d.global.shared::cta.bulk_group [%0, {%2, %3}], [%1];"
               ::"l"(m), "r"(src), "r"(c0), "r"(c1) : "memory");
}
DEVI void bulk_load(uint32_t dst, const void* src, uint32_t bytes, uint32_t bar) {
  asm volatile("cp.async.bulk.shared::cluster.global.mbarrier::complete_tx::bytes [%0], [%1], %2, [%3];"
               ::"r"(dst), "l"(src), "r"(bytes), "r"(bar) : "memory");
}
DEVI void bulk_store(void* dst, uint32_t src, uint32_t bytes) {
  asm volatile("cp.async.bulk.global.shared::cta.bulk_group [%0], [%1], %2;" ::"l"(dst), "r"(src), "r"(bytes) : "memory");
}
DEVI void bulk_reduce_add_f32(void* dst, uint32_t src, uint32_t bytes) {
  asm volatile("cp.reduce.async.bulk.global.shared::cta.bulk_group.add.f32 [%0], [%1], %2;" ::"l"(dst), "r"(src), "r"(bytes) : "memory");
}
DEVI void bulk_commit() { asm volatile("cp.async.bulk.commit_group;" ::: "memory"); }
DEVI void bulk_wait0() { asm volatile("cp.async.bulk.wait_group 0;" ::: "memory"); }
DEVI void bulk_wait_read0() { asm volatile("cp.async.bulk.wait_group.read 0;" ::: "memory"); }
DEVI void l2_prefetch(const void* p, uint32_t bytes) {
  asm volatile("cp.async.bulk.prefetch.L2.global [%0], %1;" ::"l"(p), "r"(bytes) : "memory");
}
DEVI void prefetch_tmap(const CUtensorMap* m) { asm volatile("prefetch.tensormap [%0];" ::"l"(m) : "memory"); }

DEVI void red_release_add(unsigned* p, unsigned v) {
  asm volatile("red.release.gpu.global.add.u32 [%0], %1;" ::"l"(p), "r"(v) : "memory");
}
DEVI void red_relaxed_add(unsigned* p, unsigned v) {
  asm volatile("red.relaxed.gpu.global.add.u32 [%0], %1;" ::"l"(p), "r"(v) : "memory");
}
DEVI unsigned ld_relaxed(const unsigned* p) {
  unsigned v;
  asm volatile("ld.relaxed.gpu.global.u32 %0, [%1];" : "=r"(v) : "l"(p) : "memory");
  return v;
}
DEVI void wait_counter(const unsigned* p, unsigned target) {
#pragma unroll 1
  for (int it = 0; (int)(ld_relaxed(p) - target) < 0; ++it)
    if (it > (1 << 22)) __trap();
}

DEVI void ldsm_x4(uint32_t (&r)[4], uint32_t a) {
  asm volatile("ldmatrix.sync.aligned.m8n8.x4.shared.b16 {%0,%1,%2,%3}, [%4];"
               : "=r"(r[0]), "=r"(r[1]), "=r"(r[2]), "=r"(r[3]) : "r"(a) : "memory");
}
DEVI void ldsm_x4_t(uint32_t (&r)[4], uint32_t a) {
  asm volatile("ldmatrix.sync.aligned.m8n8.x4.trans.shared.b16 {%0,%1,%2,%3}, [%4];"
               : "=r"(r[0]), "=r"(r[1]), "=r"(r[2]), "=r"(r[3]) : "r"(a) : "memory");
}
DEVI void ldsm_x2_t(uint32_t& r0, uint32_t& r1, uint32_t a) {
  asm volatile("ldmatrix.sync.aligned.m8n8.x2.trans.shared.b16 {%0,%1}, [%2];" : "=r"(r0), "=r"(r1) : "r"(a) : "memory");
}
DEVI void stsm_x4(uint32_t a, uint32_t r0, uint32_t r1, uint32_t r2, uint32_t r3) {
  asm volatile("stmatrix.sync.aligned.m8n8.x4.shared.b16 [%0], {%1,%2,%3,%4};"
               ::"r"(a), "r"(r0), "r"(r1), "r"(r2), "r"(r3) : "memory");
}
DEVI void stsm_x4_t(uint32_t a, uint32_t r0, uint32_t r1, uint32_t r2, uint32_t r3) {
  asm volatile("stmatrix.sync.aligned.m8n8.x4.trans.shared.b16 [%0], {%1,%2,%3,%4};"
               ::"r"(a), "r"(r0), "r"(r1), "r"(r2), "r"(r3) : "memory");
}
DEVI uint32_t lds32(uint32_t a) { uint32_t v; asm volatile("ld.shared.b32 %0, [%1];" : "=r"(v) : "r"(a) : "memory"); return v; }
DEVI float lds_f32(uint32_t a) { float v; asm volatile("ld.shared.f32 %0, [%1];" : "=f"(v) : "r"(a) : "memory"); return v; }
DEVI void sts32(uint32_t a, uint32_t v) { asm volatile("st.shared.b32 [%0], %1;" ::"r"(a), "r"(v) : "memory"); }
DEVI void sts_f32(uint32_t a, float v) { asm volatile("st.shared.f32 [%0], %1;" ::"r"(a), "f"(v) : "memory"); }
DEVI void sts_f32x2(uint32_t a, float x, float y) { asm volatile("st.shared.v2.f32 [%0], {%1,%2};" ::"r"(a), "f"(x), "f"(y) : "memory"); }
DEVI uint4 lds128(uint32_t a) {
  uint4 v;
  asm volatile("ld.shared.v4.b32 {%0,%1,%2,%3}, [%4];" : "=r"(v.x), "=r"(v.y), "=r"(v.z), "=r"(v.w) : "r"(a) : "memory");
  return v;
}
DEVI void sts128(uint32_t a, uint32_t x, uint32_t y, uint32_t z, uint32_t w) {
  asm volatile("st.shared.v4.b32 [%0], {%1,%2,%3,%4};" ::"r"(a), "r"(x), "r"(y), "r"(z), "r"(w) : "memory");
}

DEVI void mma_bf16(float (&d)[4], uint32_t a0, uint32_t a1, uint32_t a2, uint32_t a3, uint32_t b0, uint32_t b1) {
  asm("mma.sync.aligned.m16n8k16.row.col.f32.bf16.bf16.f32 {%0,%1,%2,%3}, {%4,%5,%6,%7}, {%8,%9}, {%0,%1,%2,%3};"
      : "+f"(d[0]), "+f"(d[1]), "+f"(d[2]), "+f"(d[3])
      : "r"(a0), "r"(a1), "r"(a2), "r"(a3), "r"(b0), "r"(b1));
}
DEVI void mma_f16(float (&d)[4], const uint32_t (&a)[4], uint32_t b0, uint32_t b1) {
  asm("mma.sync.aligned.m16n8k16.row.col.f32.f16.f16.f32 {%0,%1,%2,%3}, {%4,%5,%6,%7}, {%8,%9}, {%0,%1,%2,%3};"
      : "+f"(d[0]), "+f"(d[1]), "+f"(d[2]), "+f"(d[3])
      : "r"(a[0]), "r"(a[1]), "r"(a[2]), "r"(a[3]), "r"(b0), "r"(b1));
}
DEVI void mma_bf16v(float (&d)[4], const uint32_t (&a)[4], uint32_t b0, uint32_t b1) {
  asm volatile("mma.sync.aligned.m16n8k16.row.col.f32.bf16.bf16.f32 {%0,%1,%2,%3}, {%4,%5,%6,%7}, {%8,%9}, {%0,%1,%2,%3};"
               : "+f"(d[0]), "+f"(d[1]), "+f"(d[2]), "+f"(d[3])
               : "r"(a[0]), "r"(a[1]), "r"(a[2]), "r"(a[3]), "r"(b0), "r"(b1));
}
DEVI uint32_t pack_bf16(float lo, float hi) {
  uint32_t r;
  asm("cvt.rn.bf16x2.f32 %0, %1, %2;" : "=r"(r) : "f"(hi), "f"(lo));
  return r;
}
DEVI uint32_t pack_f16(float lo, float hi) {
  uint32_t r;
  asm("cvt.rn.f16x2.f32 %0, %1, %2;" : "=r"(r) : "f"(hi), "f"(lo));
  return r;
}
DEVI uint32_t ldg16(const __nv_bfloat16* p) {
  uint32_t v;
  asm volatile("ld.global.nc.u16 %0, [%1];" : "=r"(v) : "l"(p));
  return v;
}
DEVI bool elect_one() {
  uint32_t pred;
  asm volatile("{\n.reg .pred p;\nelect.sync _|p, 0xffffffff;\nselp.u32 %0, 1, 0, p;\n}" : "=r"(pred));
  return pred != 0;
}
DEVI float bf_lo(uint32_t v) { return __uint_as_float(v << 16); }
DEVI float bf_hi(uint32_t v) { return __uint_as_float(v & 0xffff0000u); }
DEVI float bf2f(__nv_bfloat16 v) { return __bfloat162float(v); }
DEVI float round_bf16(float v) { return __bfloat162float(__float2bfloat16_rn(v)); }
DEVI float rcp(float x) { float r; asm("rcp.approx.ftz.f32 %0, %1;" : "=f"(r) : "f"(x)); return r; }
DEVI float ex2(float x) { float r; asm("ex2.approx.ftz.f32 %0, %1;" : "=f"(r) : "f"(x)); return r; }

DEVI void wg_fence() { asm volatile("wgmma.fence.sync.aligned;" ::: "memory"); }
DEVI void wg_commit() { asm volatile("wgmma.commit_group.sync.aligned;" ::: "memory"); }
template <int N> DEVI void wg_wait() { asm volatile("wgmma.wait_group.sync.aligned %0;" ::"n"(N) : "memory"); }
constexpr uint32_t DESC_HI = (1u << 30) | (1024 >> 4);
constexpr uint32_t DESC_HI64 = (2u << 30) | (512 >> 4);
DEVI uint32_t mkdesc(uint32_t saddr, uint32_t lbo) { return ((saddr & 0x3FFFF) >> 4) | ((lbo >> 4) << 16); }

#define R8(b) "%" #b
DEVI void wgmma_n192(float (&d)[96], uint32_t da, uint32_t db, int scale_d) {
  asm volatile(
      "{\n.reg .pred p;\n.reg .b64 da, db;\nsetp.ne.b32 p, %98, 0;\nmov.b64 da, {%96, %100};\nmov.b64 db, {%97, %99};\n"
      "wgmma.mma_async.sync.aligned.m64n192k16.f32.bf16.bf16 "
      "{%0,%1,%2,%3,%4,%5,%6,%7,%8,%9,%10,%11,%12,%13,%14,%15,"
      "%16,%17,%18,%19,%20,%21,%22,%23,%24,%25,%26,%27,%28,%29,%30,%31,"
      "%32,%33,%34,%35,%36,%37,%38,%39,%40,%41,%42,%43,%44,%45,%46,%47,"
      "%48,%49,%50,%51,%52,%53,%54,%55,%56,%57,%58,%59,%60,%61,%62,%63,"
      "%64,%65,%66,%67,%68,%69,%70,%71,%72,%73,%74,%75,%76,%77,%78,%79,"
      "%80,%81,%82,%83,%84,%85,%86,%87,%88,%89,%90,%91,%92,%93,%94,%95}, "
      "da, db, p, 1, 1, 0, 1;\n}"
      : "+f"(d[0]), "+f"(d[1]), "+f"(d[2]), "+f"(d[3]), "+f"(d[4]), "+f"(d[5]), "+f"(d[6]), "+f"(d[7]),
        "+f"(d[8]), "+f"(d[9]), "+f"(d[10]), "+f"(d[11]), "+f"(d[12]), "+f"(d[13]), "+f"(d[14]), "+f"(d[15]),
        "+f"(d[16]), "+f"(d[17]), "+f"(d[18]), "+f"(d[19]), "+f"(d[20]), "+f"(d[21]), "+f"(d[22]), "+f"(d[23]),
        "+f"(d[24]), "+f"(d[25]), "+f"(d[26]), "+f"(d[27]), "+f"(d[28]), "+f"(d[29]), "+f"(d[30]), "+f"(d[31]),
        "+f"(d[32]), "+f"(d[33]), "+f"(d[34]), "+f"(d[35]), "+f"(d[36]), "+f"(d[37]), "+f"(d[38]), "+f"(d[39]),
        "+f"(d[40]), "+f"(d[41]), "+f"(d[42]), "+f"(d[43]), "+f"(d[44]), "+f"(d[45]), "+f"(d[46]), "+f"(d[47]),
        "+f"(d[48]), "+f"(d[49]), "+f"(d[50]), "+f"(d[51]), "+f"(d[52]), "+f"(d[53]), "+f"(d[54]), "+f"(d[55]),
        "+f"(d[56]), "+f"(d[57]), "+f"(d[58]), "+f"(d[59]), "+f"(d[60]), "+f"(d[61]), "+f"(d[62]), "+f"(d[63]),
        "+f"(d[64]), "+f"(d[65]), "+f"(d[66]), "+f"(d[67]), "+f"(d[68]), "+f"(d[69]), "+f"(d[70]), "+f"(d[71]),
        "+f"(d[72]), "+f"(d[73]), "+f"(d[74]), "+f"(d[75]), "+f"(d[76]), "+f"(d[77]), "+f"(d[78]), "+f"(d[79]),
        "+f"(d[80]), "+f"(d[81]), "+f"(d[82]), "+f"(d[83]), "+f"(d[84]), "+f"(d[85]), "+f"(d[86]), "+f"(d[87]),
        "+f"(d[88]), "+f"(d[89]), "+f"(d[90]), "+f"(d[91]), "+f"(d[92]), "+f"(d[93]), "+f"(d[94]), "+f"(d[95])
      : "r"(da), "r"(db), "r"(scale_d), "n"(DESC_HI), "n"(DESC_HI64));
}
DEVI void wgmma_n64(float (&d)[32], uint32_t da, uint32_t db, int scale_d) {
  asm volatile(
      "{\n.reg .pred p;\n.reg .b64 da, db;\nsetp.ne.b32 p, %34, 0;\nmov.b64 da, {%32, %35};\nmov.b64 db, {%33, %35};\n"
      "wgmma.mma_async.sync.aligned.m64n64k16.f32.bf16.bf16 "
      "{%0,%1,%2,%3,%4,%5,%6,%7,%8,%9,%10,%11,%12,%13,%14,%15,"
      "%16,%17,%18,%19,%20,%21,%22,%23,%24,%25,%26,%27,%28,%29,%30,%31}, "
      "da, db, p, 1, 1, 0, 1;\n}"
      : "+f"(d[0]), "+f"(d[1]), "+f"(d[2]), "+f"(d[3]), "+f"(d[4]), "+f"(d[5]), "+f"(d[6]), "+f"(d[7]),
        "+f"(d[8]), "+f"(d[9]), "+f"(d[10]), "+f"(d[11]), "+f"(d[12]), "+f"(d[13]), "+f"(d[14]), "+f"(d[15]),
        "+f"(d[16]), "+f"(d[17]), "+f"(d[18]), "+f"(d[19]), "+f"(d[20]), "+f"(d[21]), "+f"(d[22]), "+f"(d[23]),
        "+f"(d[24]), "+f"(d[25]), "+f"(d[26]), "+f"(d[27]), "+f"(d[28]), "+f"(d[29]), "+f"(d[30]), "+f"(d[31])
      : "r"(da), "r"(db), "r"(scale_d), "n"(DESC_HI));
}

struct C32 { float re, im; };
DEVI C32 csq(C32 a) { return {a.re * a.re - a.im * a.im, 2.f * a.re * a.im}; }
DEVI C32 cmul(C32 a, C32 b) { return {a.re * b.re - a.im * b.im, a.re * b.im + a.im * b.re}; }
DEVI C32 cfresh(float zl, float zi, float m) {
  float mag = ex2(zl * m), ph = zi * m;
  return {mag * __cosf(ph), mag * __sinf(ph)};
}
struct HMul { uint32_t b, bp; };
DEVI HMul mk_mul(float re, float im) { return {pack_f16(re, im), pack_f16(-im, re)}; }
DEVI uint32_t hcmul(uint32_t a, const HMul& m) {
  __half2 ah = *reinterpret_cast<__half2*>(&a);
  __half2 b = *reinterpret_cast<const __half2*>(&m.b), bp = *reinterpret_cast<const __half2*>(&m.bp);
  __half2 r = __hfma2(__high2half2(ah), bp, __hmul2(__low2half2(ah), b));
  return *reinterpret_cast<uint32_t*>(&r);
}
DEVI uint32_t badd(uint32_t a, uint32_t b) {
  __nv_bfloat162 r = __hadd2(*reinterpret_cast<__nv_bfloat162*>(&a), *reinterpret_cast<__nv_bfloat162*>(&b));
  return *reinterpret_cast<uint32_t*>(&r);
}
template <int MU0, int NMU, int DMAX>
DEVI void conv_tail(float (&acc)[16][4], uint32_t p_lane, uint32_t v_base, int back, bool edge, int lane) {
  const int hsel = (lane >> 3) & 1;
  const int row = (lane & 7) + ((lane >> 4) << 3) + PADV - 8 - (back & (hsel ^ 1));
  const uint32_t la = v_base + row * 32 + (((hsel ^ back) ^ ((row >> 2) & 1)) << 4);
  uint32_t M[3][4];
  ldsm_x4_t(M[0], la);
  ldsm_x4_t(M[1], la + 256);
  uint32_t H[2 * NMU];
#pragma unroll
  for (int i = 0; i < 2 * NMU; ++i) H[i ^ 1] = lds32(p_lane + (uint32_t)(MU0 - 1 + i) * 32);
  if (edge) {
    const uint32_t a[4] = {0u, 0u, M[0][0], M[0][1]};
#pragma unroll
    for (int k = 1; k < NMU; ++k) mma_bf16v(acc[MU0 - 2 + 2 * k], a, H[2 * k], H[2 * k + 1]);
  }
#pragma unroll
  for (int delta = -1; delta <= DMAX; ++delta) {
    if (delta + 2 <= DMAX) ldsm_x4_t(M[(delta + 3) % 3], la + (delta + 3) * 256);
#pragma unroll
    for (int k = 0; k < NMU; ++k)
      if (delta + MU0 + 2 * k < 16) mma_bf16v(acc[delta + MU0 + 2 * k], M[(delta + 1) % 3], H[2 * k], H[2 * k + 1]);
  }
}

__global__ void __cluster_dims__(2, 1, 1) __launch_bounds__(NTHREADS, 1)
fused_kernel(const __grid_constant__ Maps maps, const Ptrs p) {
  extern __shared__ __align__(1024) uint8_t smem[];
  const uint32_t sb = s2u(smem);
  const int tid = threadIdx.x, lane = tid & 31;
  const int warp = __shfl_sync(0xffffffffu, tid >> 5, 0);
  const int cta = blockIdx.x;
  const uint32_t rank = cta & 1;
  const int ti = 2 * (cta >> 4) + rank;
  const int tj = (cta >> 1) & 7;
  const int pi = cta >> 3, pj = cta & 7;
  const uint32_t bars = sb + SM_BAR;
#define BAR(i) (bars + 8 * (i))
  const int g = lane >> 2, q = lane & 3;

  auto issue_stage = [&](int ks, int s) {
    const uint32_t st = sb + s * STG_BYTES, fb = BAR(B_FULL + s);
    mbar_expect_tx(fb, STG_BYTES);
    tma_load_2d(st + STG_X, &maps.x, ks * 32, ti * 128, fb);
    tma_load_3d_mc(st + STG_W + rank * 6144, &maps.w, tj * 64, ks * 32 + rank * 16, 0, fb, 3);
  };

  const int kch = warp & 3, krd = warp >> 2;
  float zr, zi, wr, wi;
  unsigned epoch;
  uint32_t r_dskip;
  {
    const size_t po = (size_t)(cta * 4 + kch) * 128 + krd * 32 + lane;
    const uint32_t r_ar = ldg16(p.A_re + po), r_ai = ldg16(p.A_im + po), r_br = ldg16(p.B_re + po), r_bi = ldg16(p.B_im + po);
    const uint32_t r_cr = ldg16(p.C_re + po), r_ci = ldg16(p.C_im + po), r_ldt = ldg16(p.log_dt + cta * 4 + kch);
    epoch = __ldcg(&g_epoch);
    r_dskip = ldg16(p.Dskip + cta * 4 + kch);
    uint4 pt;
    if (tid < 128) pt = __ldg((const uint4*)g_ptab.v + tid);
    if (tid == 384) {
      TS(0);
#pragma unroll
      for (int i = 0; i < B_COUNT; ++i) mbar_init(BAR(i), bar_count(i));
      asm volatile("fence.mbarrier_init.release.cluster;" ::: "memory");
      prefetch_tmap(&maps.x); prefetch_tmap(&maps.w); prefetch_tmap(&maps.u);
    }
    __syncthreads();
    cluster_arrive();
    if (warp >= 12) {
      cluster_wait();
      if (elect_one()) {
        if (warp == 13) {
          mbar_expect_tx(BAR(B_TILE), 16384);
          tma_load_2d(sb + SM_U, &maps.u, tj * 64, ti * 128, BAR(B_TILE));
          prefetch_tmap(&maps.uT); prefetch_tmap(&maps.wo); prefetch_tmap(&maps.o); prefetch_tmap(&maps.yT);
          prefetch_tmap(&maps.out);
        } else {
          if (warp == 12) TS(61);
          { const int ks = warp == 12 ? 0 : warp - 13; issue_stage(ks, ks); }
        }
      }
      __syncwarp();
    }
    if (tid < 128) sts128(sb + SM_PTAB + tid * 16, pt.x, pt.y, pt.z, pt.w);
    const float dt = round_bf16(expf(bf_lo(r_ldt)));
    zr = dt * bf_lo(r_ar); zi = dt * bf_lo(r_ai);
    const float dbr = dt * bf_lo(r_br), dbi = dt * bf_lo(r_bi), cr = bf_lo(r_cr), ci = bf_lo(r_ci);
    wr = cr * dbr - ci * dbi; wi = cr * dbi + ci * dbr;
  }
  {
    const float mz = __uint_as_float(__reduce_max_sync(0xffffffffu, __float_as_uint(fmaxf(zr, 0.f))));
    const int E = min(max((int)(__reduce_max_sync(0xffffffffu, __float_as_uint(fmaxf(fabsf(wr), fabsf(wi)))) >> 23), 1), 252);
    const float sc = __int_as_float((253 - E) << 23), inv = __int_as_float((E + 1) << 23);
    const float zl = (zr - mz) * 1.4426950408889634f;
    const uint32_t tb = sb + SM_VV + kch * VV_BYTES + krd * KG_BYTES;
    const uint32_t sta = tb + (((lane >> 2) << 4) | ((lane & 3) << 2));
    auto put = [&](int r, uint32_t v) { sts32((sta ^ ((r & 7) << 4)) + r * 128, v); };
    const uint32_t lda = tb + ((lane & 7) + (((lane >> 3) & 1) << 3)) * 128;
    const uint32_t ldb = tb + ((lane & 7) + ((lane >> 4) << 3)) * 128;
    C32 e1 = cfresh(zl, zi, 1.f), e2 = csq(e1), e4 = csq(e2), e8 = csq(e4);
    C32 e16 = cfresh(zl, zi, 16.f), e32 = csq(e16), e64 = csq(e32), e128 = csq(e64);
    C32 e256 = cfresh(zl, zi, 256.f), e512 = csq(e256), e1024 = csq(e512), e768 = cmul(e512, e256);
    uint32_t XA[2][4][4];
    {
      const HMul m16 = mk_mul(e16.re, e16.im), m32 = mk_mul(e32.re, e32.im), m64 = mk_mul(e64.re, e64.im);
      const HMul m128 = mk_mul(e128.re, e128.im);
      uint32_t X[16];
      X[0] = 0x00003c00u; X[1] = pack_f16(e8.re, e8.im); X[2] = m16.b; X[4] = m32.b; X[8] = m64.b;
      X[3] = hcmul(X[1], m16); X[5] = hcmul(X[1], m32); X[6] = hcmul(X[2], m32); X[7] = hcmul(X[3], m32);
#pragma unroll
      for (int r = 1; r < 8; ++r) X[8 + r] = hcmul(X[r], m64);
#pragma unroll
      for (int h = 0; h < 2; ++h) {
#pragma unroll
        for (int r = 0; r < 16; ++r) put(r, h == 0 ? X[r] : r == 0 ? m128.b : hcmul(X[r], m128));
        __syncwarp();
#pragma unroll
        for (int k = 0; k < 4; ++k) ldsm_x4(XA[h][k], lda + (((2 * k + (lane >> 4)) ^ (lane & 7)) << 4));
        __syncwarp();
      }
    }
    if (warp >= 14 && elect_one()) {
      issue_stage(warp - 11, warp - 11);
      issue_stage(warp - 9, warp - 9);
      if (warp == 14) l2_prefetch((const char*)p.wqkv + 224 * 3072 + cta * 6912, 6912);
      else l2_prefetch((const char*)p.x + (size_t)cta * 16384, 16384);
    }
    __syncwarp();
    float D[2][3][4];
#pragma unroll
    for (int t = 0; t < 6; ++t) D[t / 3][t % 3][0] = D[t / 3][t % 3][1] = D[t / 3][t % 3][2] = D[t / 3][t % 3][3] = 0.f;
    auto contract = [&](int t0, int nt) {
      __syncwarp();
#pragma unroll
      for (int k = 0; k < 4; ++k) {
        uint32_t b[4];
        ldsm_x4(b, ldb + (((2 * k + ((lane >> 3) & 1)) ^ (lane & 7)) << 4));
#pragma unroll
        for (int h = 0; h < 2; ++h) {
          mma_f16(D[h][t0], XA[h][k], b[0], b[1]);
          if (nt == 2) mma_f16(D[h][t0 + 1], XA[h][k], b[2], b[3]);
        }
      }
      __syncwarp();
    };
    const HMul c1 = mk_mul(e1.re, -e1.im), c2 = mk_mul(e2.re, -e2.im), c4 = mk_mul(e4.re, -e4.im);
    const HMul c256 = mk_mul(e256.re, -e256.im), c512 = mk_mul(e512.re, -e512.im), c768 = mk_mul(e768.re, -e768.im);
    const HMul c1024 = mk_mul(e1024.re, -e1024.im);
    uint32_t W[8];
    W[0] = pack_f16(wr * sc, -wi * sc);
    W[1] = hcmul(W[0], c1); W[2] = hcmul(W[0], c2); W[3] = hcmul(W[1], c2);
    W[4] = hcmul(W[0], c4); W[5] = hcmul(W[1], c4); W[6] = hcmul(W[2], c4); W[7] = hcmul(W[3], c4);
#pragma unroll
    for (int i = 0; i < 8; ++i) put(i, W[i]);
#pragma unroll
    for (int i = 0; i < 4; ++i) put(8 + i, hcmul(W[2 * i], c256));
    put(12, hcmul(W[0], c512)); put(13, hcmul(W[4], c512)); put(14, hcmul(W[0], c768)); put(15, hcmul(W[4], c768));
    contract(0, 2);
    const uint32_t v0 = hcmul(W[0], c1024);
    put(0, v0); put(1, hcmul(v0, c256)); put(2, hcmul(v0, c512)); put(3, hcmul(v0, c768)); put(4, hcmul(v0, c1024));
    contract(2, 1);
    const uint32_t a = tb + (g * 24 + 2 * q) * 4;
#pragma unroll
    for (int t = 0; t < 6; ++t) {
      const float(&d)[4] = D[t / 3][t % 3];
      sts_f32x2(a + (t / 3) * 1536 + (t % 3) * 32, d[0] * inv, d[1] * inv);
      sts_f32x2(a + (t / 3) * 1536 + (t % 3) * 32 + 768, d[2] * inv, d[3] * inv);
    }
    if (mz > 0.f) {
      __syncwarp();
#pragma unroll 1
      for (int i = lane; i < 768; i += 32) {
        const int r = i / 24, y = i - 24 * r;
        sts_f32(tb + i * 4, lds_f32(tb + i * 4) * ex2(mz * 1.4426950408889634f * (koff(y) + 8 * r)));
      }
    }
  }
  if (tid == 0) TS(2);
  if (warp < 12) cluster_wait();
  if (tid == 0) TS(32);
  __syncthreads();
  if (tid == 0) TSD(33);

  if (warp < 4) {
    asm volatile("setmaxnreg.inc.sync.aligned.u32 152;");
    if (tid == 0) TS(34);
    const int d = cta * 4 + warp;
    const uint32_t vv = sb + SM_VV + warp * VV_BYTES;
    const uint32_t ub = sb + SM_U + warp * U_BYTES;
    const uint32_t pb = sb + SM_P + warp * P_BYTES;
    const float dskip = bf_lo(r_dskip);
#pragma unroll 1
    for (int pass = 0; pass < 2; ++pass) {
      if (pass == 1) {
        const uint32_t kf = vv;
#pragma unroll 2
        for (int i = 0; i < 6; ++i) {
          const uint32_t a = kf + (i * 32 + lane) * 16;
          const uint4 x0 = lds128(a), x1 = lds128(a + KG_BYTES), x2 = lds128(a + 2 * KG_BYTES), x3 = lds128(a + 3 * KG_BYTES);
          auto s4 = [](uint32_t a0, uint32_t a1, uint32_t a2, uint32_t a3) {
            return __float_as_uint((__uint_as_float(a0) + __uint_as_float(a1)) + (__uint_as_float(a2) + __uint_as_float(a3)));
          };
          sts128(a, s4(x0.x, x1.x, x2.x, x3.x), s4(x0.y, x1.y, x2.y, x3.y), s4(x0.z, x1.z, x2.z, x3.z), s4(x0.w, x1.w, x2.w, x3.w));
        }
        __syncwarp();
        const float k1024 = lds_f32(kf + kidx_c(1024) * 4);
        if (lane == 0) {
          sts_f32(kf + SL_ZERO * 4, 0.f);
          sts_f32(kf + SL_510 * 4, lds_f32(kf + kidx_c(510) * 4) - lds_f32(kf + kidx_c(512) * 4));
          sts_f32(kf + SL_0 * 4, lds_f32(kf) + dskip);
        }
        __syncwarp();
        if (tid == 0) TS(36);
        mbar_wait_long(BAR(B_PFREE), 0);
        if (tid == 0) TS(37);
        {
          float prev = 0.f;
#pragma unroll 1
          for (int i0 = 0; i0 < 16; i0 += 4) {
            uint32_t e[4];
            float a[4], b[4];
#pragma unroll
            for (int i = 0; i < 4; ++i) e[i] = lds32(sb + SM_PTAB + ((i0 + i) * 32 + lane) * 4);
#pragma unroll
            for (int i = 0; i < 4; ++i) { a[i] = lds_f32(kf + (e[i] & 0xffff)); b[i] = lds_f32(kf + (e[i] >> 16)); }
#pragma unroll
            for (int i = 0; i < 4; ++i) {
              const uint32_t w = pb + (31 * lane + 2 * (i0 + i)) * 4;
              if (i0 + i > 0) sts32(w - 4, pack_bf16(a[i], prev));
              sts32(w, pack_bf16(b[i], a[i]));
              prev = b[i];
            }
          }
        }
        __syncwarp();
        if (lane == 0) TS(4);
        const int gq = g - 2 * q;
        uint32_t h127, h128;
        {
          const uint32_t kf2 = pack_bf16(k1024, k1024) ^ 0x80008000u;
          h127 = (gq == 4 ? 0x0000ffffu : gq == 5 ? 0xffffffffu : gq == 6 ? 0xffff0000u : 0u) & kf2;
          h128 = (gq == -4 ? 0x0000ffffu : gq == -3 ? 0xffffffffu : gq == -2 ? 0xffff0000u : 0u) & kf2;
        }
        bar_sync(4, 480);
        mbar_wait_long(BAR(B_UCH + warp), 0);
        if (lane == 0) TS(7);
        float acc[16][4];
#pragma unroll
        for (int i = 0; i < 16; ++i) { acc[i][0] = acc[i][1] = acc[i][2] = acc[i][3] = 0.f; }
        {
          const uint32_t pd_lane = pb + (PD_OFF + 16 + gq) * 4;
          const int prow0 = 8 + (lane & 7) + ((lane >> 4) << 3), hs = (lane >> 3) & 1;
          const uint32_t zero = (uint32_t)cta >> 20;
          uint32_t B[2][4][4];
          uint32_t A[4][4];
          const uint32_t la0 = ub + prow0 * 32 + ((hs ^ ((prow0 >> 2) & 1)) << 4);
#pragma unroll
          for (int m2 = 0; m2 < 4; ++m2) ldsm_x4(B[0][m2], la0 + m2 * 512);
#pragma unroll
          for (int i = 0; i < 4; ++i) {
            const uint32_t a = pd_lane + i * 512;
            A[i][0] = lds32(a); A[i][1] = lds32(a + 32); A[i][2] = lds32(a - 32); A[i][3] = lds32(a + zero);
          }
          uint32_t la = la0;
#define UNR_RHO 1
#define UNR_TAIL 1
          constexpr int unr_rho = UNR_RHO, unr_tail = UNR_TAIL;
#pragma unroll unr_rho
          for (int rho = 0; rho < 8; ++rho) {
#pragma unroll
            for (int m2 = 0; m2 < 4; ++m2) ldsm_x4(B[1][m2], la + (4 + m2) * 512);
#pragma unroll
            for (int i = 0; i < 4; ++i)
#pragma unroll
              for (int m = 0; m < 8; ++m) mma_bf16v(acc[m + i], A[i], B[0][m >> 1][2 * (m & 1)], B[0][m >> 1][2 * (m & 1) + 1]);
            const int prow = prow0 - min(rho + 1, 7);
            la = ub + prow * 32 + ((hs ^ ((prow >> 2) & 1)) << 4);
#pragma unroll
            for (int m2 = 0; m2 < 4; ++m2) ldsm_x4(B[0][m2], la + m2 * 512);
            const uint32_t pa = pd_lane + (rho + 1) * 64;
#pragma unroll
            for (int i = 0; i < 4; ++i) {
#pragma unroll
              for (int m = 0; m < 8 - i; ++m)
                mma_bf16v(acc[8 + m + i], A[i], B[1][m >> 1][2 * (m & 1)], B[1][m >> 1][2 * (m & 1) + 1]);
              A[i][0] = lds32(pa + i * 512); A[i][1] = lds32(pa + i * 512 + 32); A[i][2] = lds32(pa + i * 512 - 32);
              A[i][3] = lds32(pa + i * 512 + zero);
            }
          }
          if (lane == 0) TS(40);
          {
            uint32_t b8[4];
            ldsm_x4(b8, la + 4 * 512);
            const uint32_t h63 = lds32(pd_lane + 63 * 32), h64 = lds32(pd_lane + 64 * 32);
            const uint32_t a63[4] = {0u, h127, 0u, 0u}, a32[4] = {h64, 0u, h63, h64}, a64[4] = {h128, 0u, h127, h128};
#pragma unroll
            for (int m2 = 0; m2 < 4; ++m2) ldsm_x4(B[1][m2], la0 + m2 * 512);
#pragma unroll
            for (int m = 0; m < 8; ++m) mma_bf16v(acc[m + 7], a63, B[0][m >> 1][2 * (m & 1)], B[0][m >> 1][2 * (m & 1) + 1]);
#pragma unroll
            for (int m2 = 0; m2 < 2; ++m2) ldsm_x4(B[0][m2], la0 + (4 + m2) * 512);
#pragma unroll
            for (int m = 0; m < 8; ++m) mma_bf16v(acc[m + 4], a32, B[1][m >> 1][2 * (m & 1)], B[1][m >> 1][2 * (m & 1) + 1]);
            mma_bf16v(acc[15], a63, b8[0], b8[1]);
#pragma unroll
            for (int m = 0; m < 8; ++m) mma_bf16v(acc[m + 8], a64, B[1][m >> 1][2 * (m & 1)], B[1][m >> 1][2 * (m & 1) + 1]);
#pragma unroll
            for (int m = 0; m < 4; ++m) mma_bf16v(acc[m + 12], a32, B[0][m >> 1][2 * (m & 1)], B[0][m >> 1][2 * (m & 1) + 1]);
          }
          if (lane == 0) TS(41);
          bar_sync(5, 224);
#pragma unroll unr_tail
          for (int v = 0; v < 4; ++v)
            conv_tail<4, 3, 11>(acc, pb + (P2_OFF + 56 * v + gq - 16) * 4, vv + ((v & 1) ? VV_U3 : VV_U5), v >> 1, v == 0, lane);
          if (lane == 0) TS(42);
#pragma unroll unr_tail
          for (int pi = 0; pi < 2; ++pi)
            conv_tail<8, 5, 7>(acc, pb + (P3_OFF + 88 * pi + gq - 48) * 4, vv + (pi ? VV_U7 : VV_U9), pi, pi == 0, lane);
        }
        if (lane == 0) TS(8);
        __syncwarp();
        {
          const int mt = lane >> 3;
          const uint32_t a = pb + (128 * (mt >> 1) + 16 * (lane & 7) + 8 * (mt & 1)) * 2;
#pragma unroll
          for (int ab = 0; ab < 16; ab += 2)
            stsm_x4_t(a + ab * 256, pack_bf16(acc[ab][0], acc[ab][1]), pack_bf16(acc[ab][2], acc[ab][3]),
                      pack_bf16(acc[ab + 1][0], acc[ab + 1][1]), pack_bf16(acc[ab + 1][2], acc[ab + 1][3]));
        }
        fence_async_smem();
        __syncwarp();
        if (lane < 2) mbar_arrive_cluster(BAR(B_CONVD), lane);
        bar_arrive(3, 384);
        if (elect_one()) {
          bulk_store(p.yT + (size_t)d * 2048, pb, 4096);
          bulk_commit();
          bulk_wait0();
          red_relaxed_add(&g_cnt[(C_Y + (cta >> 4)) * 32], 1);
          TS(9);
        }
        bar_sync(2, 128);
        if (warp == 0 && elect_one()) {
          wait_counter(&g_cnt[(C_Y + tj) * 32], (epoch + 1) * 64);
          TS(28);
          mbar_expect_tx(BAR(B_TILE), 16384);
          tma_load_2d(sb + SM_U, &maps.yT, ti * 128, tj * 64, BAR(B_TILE));
          tma_load_2d(sb + SM_U + 8192, &maps.yT, ti * 128 + 64, tj * 64, BAR(B_TILE));
        }
        __syncwarp();
      }
      mbar_wait_long(BAR(B_TILE), pass);
      if (lane == 0) TS(26 + 3 * pass);
      {
        const int m = lane >> 3, r = lane & 7;
#pragma unroll 2
        for (int it = 0; it < 8; ++it) {
          const int tb = warp * 4 + (it >> 1), cb = (it & 1) * 4 + m;
          const uint32_t at = (tb * 8 + r) * 128 + ((cb ^ r) << 4);
          const uint32_t ac = (tb >> 3) * 8192 + (cb * 8 + r) * 128 + (((tb & 7) ^ (pass ? 0 : tb >> 3) ^ r) << 4);
          uint32_t v[4];
          ldsm_x4_t(v, sb + SM_U + (pass ? ac : at));
          stsm_x4(sb + SM_P + (pass ? at : ac), v[0], v[1], v[2], v[3]);
        }
      }
      if (pass == 0 && tid == 0) TS(35);
      fence_async_smem();
      if (pass == 0) {
        bar_arrive(6, 160);
      } else {
        bar_sync(2, 128);
        if (warp == 0 && elect_one()) {
          tma_store_2d(&maps.out, sb + SM_P, 64 * tj, 128 * ti);
          bulk_commit();
          bulk_wait_read0();
          TS(30);
        }
      }
    }
  } else if (warp < 12) {
    asm volatile("setmaxnreg.inc.sync.aligned.u32 160;");
    const int w8 = warp - 4;
    const int row = w8 * 16 + (lane & 7) + (((lane >> 3) & 1) << 3);
    {
      float acc[96];
#pragma unroll 1
      for (int ks = 0, s = 0, ph = 0; ks < 16; ++ks) {
        mbar_wait(BAR(B_FULL + s), ph);
        if (tid == 128 && !(ks & 1)) TSR(16, ks == 0 ? 16 : 9 + (ks >> 1) + (ks > 12 ? 43 : 0));
        const uint32_t st = sb + s * STG_BYTES;
        const uint32_t da = mkdesc(st + STG_X + (w8 >> 2) * 4096, 16);
        const uint32_t db = mkdesc(st + STG_W, 2048);
        wg_fence();
        wgmma_n192(acc, da, db, ks != 0);
        wgmma_n192(acc, da + 2, db + 384, 1);
        wg_commit();
        const uint32_t eprev = BAR(B_EMPTY + (s == 0 ? NSTG - 1 : s - 1));
        if (++s == NSTG) { s = 0; ph ^= 1; }
        if (ks > 0) {
          wg_wait<1>();
          if (lane < 2) mbar_arrive_cluster(eprev, lane);
        }
      }
      wg_wait<0>();
      bar_arrive(4, 480);
      if (tid == 128) TS(17);
      bar_sync(1, 256);
#pragma unroll
      for (int i = 0; i < 24; i += 2)
        stsm_x4(sb + SM_QS + row * 128 + (i >> 3) * 16384 + ((((i & 7) + (lane >> 4)) ^ (row & 7)) << 4),
                pack_bf16(acc[4 * i], acc[4 * i + 1]), pack_bf16(acc[4 * i + 2], acc[4 * i + 3]),
                pack_bf16(acc[4 * i + 4], acc[4 * i + 5]), pack_bf16(acc[4 * i + 6], acc[4 * i + 7]));
    }
    __syncwarp();
#pragma unroll 1
    for (int part = 1; part >= 0; --part) {
      const uint32_t pa = sb + SM_QS + part * 16384 + w8 * 2048 + lane * 16;
#pragma unroll 1
      for (int it = 0; it < 4; ++it) {
        uint4 t = lds128(pa + it * 512);
        uint32_t* tw = &t.x;
#pragma unroll
        for (int j = 0; j < 4; ++j) {
          const uint32_t x = tw[j];
          const __nv_bfloat162 xb = *reinterpret_cast<const __nv_bfloat162*>(&x);
          const uint32_t e = pack_bf16(ex2(bf_lo(x) * 1.4426950408889634f), ex2(bf_hi(x) * 1.4426950408889634f));
          const uint32_t m = __hgt2_mask(xb, __floats2bfloat162_rn(0.f, 0.f));
          tw[j] = badd((badd(x, 0x3f803f80u) & m) | (e & ~m), 0x35863586u);
        }
        sts128(pa + it * 512, t.x, t.y, t.z, t.w);
      }
      if (part == 1) {
        if (tid == 128) TS(53);
        bar_sync(1, 256);
        const int hh = w8 >> 1, dtile = w8 & 1;
        float kv[4] = {0.f, 0.f, 0.f, 0.f}, zz[4] = {0.f, 0.f, 0.f, 0.f};
        const int m = lane >> 3;
        const uint32_t aa = sb + SM_VS + ((lane & 7) + ((m >> 1) << 3)) * 128 + (((2 * hh + (m & 1)) ^ (lane & 7)) << 4);
        const uint32_t ab = sb + SM_PK + (lane & 15) * 128 + (((2 * hh + dtile) ^ (lane & 7)) << 4);
#pragma unroll 2
        for (int ks = 0; ks < 8; ++ks) {
          uint32_t a[4], b0, b1;
          ldsm_x4_t(a, aa + ks * 2048);
          ldsm_x2_t(b0, b1, ab + ks * 2048);
          mma_bf16(kv, a[0], a[1], a[2], a[3], b0, b1);
          mma_bf16(zz, 0x3f803f80u, 0x3f803f80u, 0x3f803f80u, 0x3f803f80u, b0, b1);
        }
        const uint32_t kp = sb + SM_KV + hh * 1088;
        sts128(kp + dtile * 512 + lane * 16, __float_as_uint(kv[0]), __float_as_uint(kv[1]), __float_as_uint(kv[2]),
               __float_as_uint(kv[3]));
        if (g == 0) sts_f32x2(kp + 1024 + dtile * 32 + q * 8, zz[0], zz[1]);
        fence_async_smem();
        __syncwarp();
        if (lane == 0) mbar_arrive(BAR(B_KVP));
        if (tid == 128) TS(55);
      }
    }
    if (tid == 128) TS(56);
    if (warp == 4) mbar_wait_long(BAR(B_KVF), 0);
    bar_sync(1, 256);
    if (tid == 128) TS(19);
#pragma unroll 1
    for (int h = 0; h < 4; ++h) {
      uint32_t a[4];
      const uint32_t qa = sb + SM_QS + row * 128 + (((2 * h + (lane >> 4)) ^ (row & 7)) << 4);
      ldsm_x4(a, qa);
      const uint32_t kp = sb + SM_KV + h * 1088;
      const uint4 k0 = lds128(kp + lane * 16), k1 = lds128(kp + 512 + lane * 16);
      const uint32_t za = kp + 1024 + q * 8;
      auto pk2 = [](uint32_t x, uint32_t y) { return pack_bf16(__uint_as_float(x), __uint_as_float(y)); };
      float n0[4] = {0.f, 0.f, 0.f, 0.f}, n1[4] = {0.f, 0.f, 0.f, 0.f}, dn[4] = {0.f, 0.f, 0.f, 0.f};
      mma_bf16(n0, a[0], a[1], a[2], a[3], pk2(k0.x, k0.y), pk2(k1.x, k1.y));
      mma_bf16(n1, a[0], a[1], a[2], a[3], pk2(k0.z, k0.w), pk2(k1.z, k1.w));
      mma_bf16(dn, a[0], a[1], a[2], a[3], pack_bf16(lds_f32(za), lds_f32(za + 4)), pack_bf16(lds_f32(za + 32), lds_f32(za + 36)));
      const uint32_t dd = pack_bf16(dn[0], dn[2]);
      const uint32_t d2 = pack_bf16(bf_lo(dd) + 1e-6f, bf_hi(dd) + 1e-6f);
      const float r0 = rcp(bf_lo(d2)), r1 = rcp(bf_hi(d2));
      const uint32_t x0 = pack_bf16(n0[0], n0[1]), x1 = pack_bf16(n0[2], n0[3]);
      const uint32_t x2 = pack_bf16(n1[0], n1[1]), x3 = pack_bf16(n1[2], n1[3]);
      stsm_x4(qa, pack_bf16(bf_lo(x0) * r0, bf_hi(x0) * r0), pack_bf16(bf_lo(x1) * r1, bf_hi(x1) * r1),
              pack_bf16(bf_lo(x2) * r0, bf_hi(x2) * r0), pack_bf16(bf_lo(x3) * r1, bf_hi(x3) * r1));
    }
    fence_async_smem();
    __syncwarp();
    if (lane == 0) mbar_arrive(BAR(B_OST));
    if (tid == 128) TS(57);
    if (warp == 4) mbar_wait_long(BAR(B_WO), 0);
    bar_sync(3, 384);
    {
      float o[32];
#pragma unroll 1
      for (int c = 0; c < 8; ++c) {
        mbar_wait_long(BAR(B_RF + c), 0);
        if (tid == 128) TSR(22, c == 0 ? 22 : 43 + c);
        const uint32_t slot = c < 4 ? SM_QS + c * 16384 : c < 7 ? SM_VV + (c - 4) * 16384 : SM_QS;
        const uint32_t da = mkdesc(sb + slot + (w8 >> 2) * 8192, 16);
        const uint32_t db = mkdesc(sb + SM_WO + c * 8192, 8192);
        wg_fence();
#pragma unroll
        for (int k = 0; k < 4; ++k) wgmma_n64(o, da + 2 * k, db + 128 * k, (c | k) != 0);
        wg_commit();
        if (c == 1) {
          wg_wait<1>();
          if (lane < 2) mbar_arrive_cluster(BAR(B_RE), lane);
        }
      }
      wg_wait<0>();
      if (tid == 128) TS(51);
      bar_sync(1, 256);
#pragma unroll
      for (int i = 0; i < 8; i += 2)
        stsm_x4(sb + SM_BOUT + row * 128 + (((i + (lane >> 4)) ^ (row & 7)) << 4), pack_bf16(o[4 * i], o[4 * i + 1]),
                pack_bf16(o[4 * i + 2], o[4 * i + 3]), pack_bf16(o[4 * i + 4], o[4 * i + 5]), pack_bf16(o[4 * i + 6], o[4 * i + 7]));
      fence_async_smem();
      bar_sync(1, 256);
      if (tid == 128) TS(52);
      if (warp == 4 && elect_one()) {
        tma_store_2d(&maps.out, sb + SM_BOUT, 512 + 64 * pj, 128 * pi);
        bulk_commit();
        bulk_wait_read0();
        TS(23);
      }
    }
  } else {
    asm volatile("setmaxnreg.dec.sync.aligned.u32 40;");
    if (warp == 12) {
      if (elect_one()) {
#pragma unroll 1
        for (int ks = NSTG, s = 0, ph = 0; ks < 16; ++ks) {
          mbar_wait(BAR(B_EMPTY + s), ph);
          issue_stage(ks, s);
          if (ks == NSTG) l2_prefetch((const char*)p.wo + (size_t)cta * 4096, 4096);
          if (++s == NSTG) { s = 0; ph ^= 1; }
        }
        mbar_wait(BAR(B_EMPTY + 6), 1);
        mbar_expect_tx(BAR(B_WO), 65536);
        tma_load_2d(sb + SM_WO, &maps.wo, pj * 64, 0, BAR(B_WO));
        tma_load_2d(sb + SM_WO + 32768, &maps.wo, pj * 64, 256, BAR(B_WO));
        float* kvg = &g_kv[epoch & 1][tj][0];
        mbar_wait_long(BAR(B_KVP), 0);
        bulk_reduce_add_f32(kvg, sb + SM_KV, 4352);
        bulk_commit();
        bulk_wait0();
        red_relaxed_add(&g_cnt[(C_KV + tj) * 32], 1);
        TS(18);
        wait_counter(&g_cnt[(C_KV + tj) * 32], (epoch + 1) * 16);
        mbar_expect_tx(BAR(B_KVF), 4352);
        bulk_load(sb + SM_KV, kvg, 4352, BAR(B_KVF));
        mbar_wait_long(BAR(B_OST), 0);
        tma_store_2d(&maps.o, sb + SM_QS, tj * 64, ti * 128);
        tma_store_2d(&maps.o, sb + SM_QS + 8192, tj * 64, ti * 128 + 64);
        bulk_commit();
        bulk_wait0();
        red_relaxed_add(&g_cnt[(C_O + ti) * 32], 1);
        TS(20);
        mbar_arrive_cluster(BAR(B_SLOT), 0);
        mbar_arrive_cluster(BAR(B_SLOT), 1);
        wait_counter(&g_cnt[(C_O + pi) * 32], (epoch + 1) * 8);
        if (cta == 0) g_epoch = epoch + 1;
        mbar_wait(BAR(B_SLOT), 0);
        TS(21);
#pragma unroll 1
        for (int c = 0; c < 8; ++c) {
          if (c == 4) mbar_wait_long(BAR(B_CONVD), 0);
          if (c == 7) mbar_wait(BAR(B_RE), 0);
          const uint32_t slot = c < 4 ? SM_QS + c * 16384 : c < 7 ? SM_VV + (c - 4) * 16384 : SM_QS;
          mbar_expect_tx(BAR(B_RF + c), 16384);
          tma_load_2d_mc(sb + slot + rank * 8192, &maps.o, c * 64, pi * 128 + rank * 64, BAR(B_RF + c), 3);
        }
      }
    } else if (warp == 13) {
      bar_sync(6, 160);
      sts128(sb + SM_U + (lane >> 4) * U_BYTES + (lane & 15) * 16, 0, 0, 0, 0);
      sts128(sb + SM_U + (2 + (lane >> 4)) * U_BYTES + (lane & 15) * 16, 0, 0, 0, 0);
      __syncwarp();
      if (elect_one()) {
        tma_store_2d(&maps.uT, sb + SM_P, ti * 128, tj * 64);
        tma_store_2d(&maps.uT, sb + SM_P + 8192, ti * 128 + 64, tj * 64);
        bulk_commit();
        bulk_wait_read0();
        mbar_arrive(BAR(B_PFREE));
        bulk_wait0();
        red_relaxed_add(&g_cnt[(C_U + tj) * 32], 1);
        TS(27);
        wait_counter(&g_cnt[(C_U + (cta >> 4)) * 32], (epoch + 1) * 16);
#pragma unroll 1
        for (int c = 0; c < 4; ++c) {
          mbar_expect_tx(BAR(B_UCH + c), 4096);
          bulk_load(sb + SM_U + c * U_BYTES + 256, p.uT + (size_t)(cta * 4 + c) * 2048, 4096, BAR(B_UCH + c));
        }
        TS(3);
      }
      __syncwarp();
      if (ti == 0) {
        float4* z = (float4*)&g_kv[(epoch & 1) ^ 1][tj][0];
#pragma unroll 1
        for (int i = lane; i < 272; i += 32) z[i] = make_float4(0.f, 0.f, 0.f, 0.f);
      }
    }
    if (warp >= 13) {
      bar_sync(4, 480);
      auto swz = [](int k, int pad) { const int r = (k >> 1) + pad; return (uint32_t)(r * 32 + (((k & 1) ^ ((r >> 2) & 1)) << 4)); };
      const uint32_t o0 = swz(lane - 3, 8), o1 = swz(lane - 2, 8), o2 = swz(lane - 1, 8), ow = swz(lane - 2, PADV);
      const uint32_t oz = swz(lane - 18, PADV);
#pragma unroll 1
      for (int item = warp - 13; item < 28; item += 3) {
        const int ch = item / 7, it = item - 7 * ch;
        const int k = -2 + 32 * it + lane;
        const uint32_t ua = sb + SM_U + ch * U_BYTES + it * 512, vb = sb + SM_VV + ch * VV_BYTES;
        const uint32_t a0 = ua + o0, a1 = ua + o1, a2 = ua + o2, aw = vb + it * 512 + ow;
        mbar_wait_long(BAR(B_UCH + ch), 0);
        if (it == 0 && lane < 16) {
          sts128(vb + oz + VV_U3, 0, 0, 0, 0); sts128(vb + oz + VV_U5, 0, 0, 0, 0);
          sts128(vb + oz + VV_U7, 0, 0, 0, 0); sts128(vb + oz + VV_U9, 0, 0, 0, 0);
        }
        const uint4 t0 = lds128(a0), t1 = lds128(a1), t2 = lds128(a2);
        const uint32_t E[12] = {t0.x, t0.y, t0.z, t0.w, t1.x, t1.y, t1.z, t1.w, t2.x, t2.y, t2.z, t2.w};
        uint32_t O[8];
#pragma unroll
        for (int j = 0; j < 8; ++j) O[j] = __byte_perm(E[j + 1], E[j + 2], 0x5432);
        uint32_t s3[6], s5[4], s7[4], s9[4];
#pragma unroll
        for (int j = 0; j < 6; ++j) s3[j] = badd(badd(O[j], O[j + 1]), E[j + 2]);
#pragma unroll
        for (int j = 0; j < 4; ++j) {
          s5[j] = badd(s3[j + 2], badd(E[j + 3], E[j + 5]));
          s7[j] = badd(s5[j], badd(O[j + 1], O[j + 4]));
          s9[j] = badd(s7[j], badd(E[j + 2], E[j + 6]));
        }
        if (k < 208) { sts128(aw + VV_U3, s3[0], s3[1], s3[2], s3[3]); sts128(aw + VV_U5, s5[0], s5[1], s5[2], s5[3]); }
        if (k < 144) { sts128(aw + VV_U7, s7[0], s7[1], s7[2], s7[3]); sts128(aw + VV_U9, s9[0], s9[1], s9[2], s9[3]); }
      }
      if (tid == 416) TS(6);
      bar_arrive(5, 224);
    }
  }
  __syncwarp();
  cluster_arrive();
  cluster_wait();
  if (tid == 0) TS(31);
#undef BAR
}

typedef CUresult (*EncodeFn)(CUtensorMap*, CUtensorMapDataType, cuuint32_t, void*, const cuuint64_t*, const cuuint64_t*,
                             const cuuint32_t*, const cuuint32_t*, CUtensorMapInterleave, CUtensorMapSwizzle,
                             CUtensorMapL2promotion, CUtensorMapFloatOOBfill);

static void make_map(EncodeFn enc, CUtensorMap* m, const void* base, uint64_t inner, uint64_t outer, uint32_t box_in,
                     uint32_t box_out, CUtensorMapSwizzle swz = CU_TENSOR_MAP_SWIZZLE_128B) {
  cuuint64_t gd[2] = {inner, outer};
  cuuint64_t gs[1] = {inner * 2};
  cuuint32_t bd[2] = {box_in, box_out};
  cuuint32_t es[2] = {1, 1};
  enc(m, CU_TENSOR_MAP_DATA_TYPE_BFLOAT16, 2, const_cast<void*>(base), gd, gs, bd, es, CU_TENSOR_MAP_INTERLEAVE_NONE,
      swz, CU_TENSOR_MAP_L2_PROMOTION_L2_128B, CU_TENSOR_MAP_FLOAT_OOB_FILL_NONE);
}

}

extern "C" void kernel_launch(void* const* d_in, const int* in_sizes, int n_in, void* d_out, int out_size) {
  using namespace s4la;
  (void)in_sizes; (void)n_in; (void)out_size;
  static EncodeFn enc = nullptr;
  static void *uT = nullptr, *yT = nullptr, *oS = nullptr;
  if (!enc) {
    void* fn = nullptr;
    cudaDriverEntryPointQueryResult qr;
    cudaGetDriverEntryPoint("cuTensorMapEncodeTiled", &fn, cudaEnableDefault, &qr);
    enc = (EncodeFn)fn;
    cudaGetSymbolAddress(&uT, g_uT);
    cudaGetSymbolAddress(&yT, g_yT);
    cudaGetSymbolAddress(&oS, g_o);
    cudaFuncSetAttribute(fused_kernel, cudaFuncAttributeMaxDynamicSharedMemorySize, SM_TOTAL);
  }
  const __nv_bfloat16* const* in = (const __nv_bfloat16* const*)d_in;
  Maps maps;
  make_map(enc, &maps.x, in[9], 512, 2048, 32, 128, CU_TENSOR_MAP_SWIZZLE_64B);
  {
    cuuint64_t gd[3] = {512, 512, 3};
    cuuint64_t gs[2] = {3072, 1024};
    cuuint32_t bd[3] = {64, 16, 3};
    cuuint32_t es[3] = {1, 1, 1};
    enc(&maps.w, CU_TENSOR_MAP_DATA_TYPE_BFLOAT16, 3, const_cast<__nv_bfloat16*>(in[10]), gd, gs, bd, es,
        CU_TENSOR_MAP_INTERLEAVE_NONE, CU_TENSOR_MAP_SWIZZLE_128B, CU_TENSOR_MAP_L2_PROMOTION_L2_128B,
        CU_TENSOR_MAP_FLOAT_OOB_FILL_NONE);
  }
  make_map(enc, &maps.wo, in[11], 512, 512, 64, 256);
  make_map(enc, &maps.u, in[0], 512, 2048, 64, 128);
  make_map(enc, &maps.uT, uT, 2048, 512, 64, 64);
  make_map(enc, &maps.yT, yT, 2048, 512, 64, 64);
  make_map(enc, &maps.o, oS, 512, 2048, 64, 64);
  make_map(enc, &maps.out, d_out, 1024, 2048, 64, 128);
  Ptrs p;
  p.A_re = in[1]; p.A_im = in[2]; p.B_re = in[3]; p.B_im = in[4]; p.C_re = in[5]; p.C_im = in[6];
  p.log_dt = in[7]; p.Dskip = in[8]; p.x = in[9]; p.wqkv = in[10]; p.wo = in[11];
  p.uT = (__nv_bfloat16*)uT; p.yT = (__nv_bfloat16*)yT;
  fused_kernel<<<NCTA, NTHREADS, SM_TOTAL, cudaStreamPerThread>>>(maps, p);
}
```

```cpp
#include <cuda_runtime.h>
#include <cuda_bf16.h>
#include <cuda_fp16.h>
#include <cuda.h>
#include <stdint.h>

#define DEVI __device__ __forceinline__

namespace s4la {

constexpr int NTHREADS = 512;
constexpr int NCTA = 128;

constexpr int NSTG = 7;
constexpr uint32_t STG_BYTES = 20480, STG_X = 0, STG_W = 8192;
constexpr uint32_t SM_QS = 0;
constexpr uint32_t SM_PK = SM_QS + 16384, SM_VS = SM_QS + 32768;
constexpr uint32_t SM_WO = 65536;
constexpr uint32_t SM_KV = 131072;
constexpr uint32_t SM_BOUT = 16384;
constexpr uint32_t SM_U = 143360, U_BYTES = 4352;
constexpr uint32_t SM_P = 160768, P_BYTES = 4096;
constexpr uint32_t SM_VV = 177152, VV_BYTES = 12800;
constexpr uint32_t VV_U5 = 0, VV_U3 = 3712, VV_U9 = 7424, VV_U7 = 10112;
constexpr uint32_t KG_BYTES = 3200;
constexpr uint32_t SM_BAR = SM_VV + 4 * VV_BYTES;
constexpr uint32_t SM_PTAB = SM_BAR + 320;
constexpr uint32_t SM_TOTAL = SM_PTAB + 2048;
static_assert(SM_TOTAL <= 232448, "shared memory");
constexpr int PADV = 12;

enum { B_FULL = 0, B_EMPTY = 7, B_TILE = 14, B_UCH = 15, B_KVP = 19, B_KVF = 20, B_OST = 21, B_RF = 22, B_WO = 30, B_RE = 31, B_PFREE = 32, B_CONVD = 33, B_SLOT = 34, B_COUNT = 35 };
__host__ __device__ constexpr int bar_count(int i) {
  return (i >= B_EMPTY && i < B_TILE) ? 16 : (i == B_KVP || i == B_OST || i == B_CONVD) ? 8 : i == B_RE ? 16 : i == B_SLOT ? 2 : 1;
}

constexpr int PD_OFF = 0, P2_OFF = 544, P3_OFF = 768;

constexpr int SL_K2048 = 20, SL_ZERO = 21, SL_510 = 22, SL_0 = 23;
__host__ __device__ constexpr int koff(int y) {
  return y < 8 ? y : y < 12 ? 256 + 2 * (y - 8) : y < 16 ? 512 + 256 * ((y - 12) >> 1) + 4 * (y & 1) : 1024 + 256 * (y - 16);
}
__host__ __device__ constexpr int kidx_c(int l) {
  const int y = l < 256 ? (l & 7) : l < 512 ? 8 + ((l & 7) >> 1) : l < 1024 ? 12 + (((l - 512) >> 8) << 1) + ((l >> 2) & 1)
                                                                            : 16 + ((l - 1024) >> 8);
  return ((l >> 3) & 31) * 24 + y;
}
constexpr int slot_direct(int l) {
  if (l < 0 || l > 510) return SL_ZERO;
  if (l == 510) return SL_510;
  if (l == 0) return SL_0;
  return kidx_c(l < 256 ? l : ((l + ((l >> 1) & 1)) & ~1));
}
constexpr int slot_seg2(int v, int k) { return (k >= 32 && k < 64) ? kidx_c(16 * k + 4 * v) : SL_ZERO; }
constexpr int slot_seg3(int pi, int k) {
  return (k >= 64 && k < 128) ? kidx_c(16 * k + 8 * pi) : ((k == 128 && pi == 0) ? SL_K2048 : SL_ZERO);
}
constexpr int slot_word(int w) {
  return w < 0 ? SL_ZERO : w < 544 ? slot_direct(w - 16) : w < 768 ? slot_seg2((w - 544) / 56, 16 + (w - 544) % 56)
       : w < 944 ? slot_seg3((w - 768) / 88, 48 + (w - 768) % 88) : SL_ZERO;
}
struct PTab { uint32_t v[512]; };
constexpr PTab make_ptab() {
  PTab t{};
  for (int lane = 0; lane < 32; ++lane)
    for (int i = 0; i < 16; ++i)
      t.v[i * 32 + lane] = (slot_word(31 * lane - 1 + 2 * i) * 4) | ((slot_word(31 * lane + 2 * i) * 4) << 16);
  return t;
}
__device__ const PTab g_ptab = make_ptab();

__device__ __nv_bfloat16 g_uT[512 * 2048];
__device__ __nv_bfloat16 g_yT[512 * 2048];
__device__ __nv_bfloat16 g_o[2048 * 512];
__device__ float g_kv[2][8][4 * 272];
__device__ unsigned g_cnt[64 * 32];
__device__ unsigned g_epoch;
#define TS(slot) do { } while (0)
#define TSR(on, slot) do { } while (0)
#define TSD(slot) do { } while (0)
enum { C_U = 0, C_KV = 8, C_O = 16, C_Y = 32 };

struct Maps {
  CUtensorMap x, w, wo, u, uT, o, out;
};
struct Ptrs {
  const __nv_bfloat16 *A_re, *A_im, *B_re, *B_im, *C_re, *C_im, *log_dt, *Dskip;
  const __nv_bfloat16 *x, *wqkv, *wo;
  __nv_bfloat16 *uT, *yT, *out;
};

DEVI uint32_t s2u(const void* p) { return (uint32_t)__cvta_generic_to_shared(p); }
DEVI void mbar_init(uint32_t b, uint32_t c) { asm volatile("mbarrier.init.shared::cta.b64 [%0], %1;" ::"r"(b), "r"(c) : "memory"); }
DEVI void mbar_expect_tx(uint32_t b, uint32_t bytes) {
  asm volatile("mbarrier.arrive.expect_tx.shared::cta.b64 _, [%0], %1;" ::"r"(b), "r"(bytes) : "memory");
}
DEVI void mbar_arrive(uint32_t b) { asm volatile("mbarrier.arrive.shared::cta.b64 _, [%0];" ::"r"(b) : "memory"); }
DEVI void mbar_arrive_cluster(uint32_t b, uint32_t cta) {
  asm volatile("{\n.reg .b32 r;\nmapa.shared::cluster.u32 r, %0, %1;\nmbarrier.arrive.shared::cluster.b64 _, [r];\n}"
               ::"r"(b), "r"(cta) : "memory");
}
DEVI void mbar_wait(uint32_t b, uint32_t parity) {
  asm volatile("{\n.reg .pred p;\nLAB_WAIT:\nmbarrier.try_wait.parity.shared::cta.b64 p, [%0], %1;\n@!p bra LAB_WAIT;\n}"
               ::"r"(b), "r"(parity) : "memory");
}
DEVI void mbar_wait_long(uint32_t b, uint32_t parity) {
  asm volatile("{\n.reg .pred p;\nLAB_WAIT:\nmbarrier.try_wait.parity.shared::cta.b64 p, [%0], %1, 0x989680;\n@!p bra LAB_WAIT;\n}"
               ::"r"(b), "r"(parity) : "memory");
}
DEVI void bar_sync(int id, int n) { asm volatile("bar.sync %0, %1;" ::"r"(id), "r"(n) : "memory"); }
DEVI void bar_arrive(int id, int n) { asm volatile("bar.arrive %0, %1;" ::"r"(id), "r"(n) : "memory"); }
DEVI void fence_async_smem() { asm volatile("fence.proxy.async.shared::cta;" ::: "memory"); }
DEVI void fence_async_all() { asm volatile("fence.proxy.async;" ::: "memory"); }
DEVI void cluster_arrive() { asm volatile("barrier.cluster.arrive.relaxed.aligned;" ::: "memory"); }
DEVI void cluster_wait() { asm volatile("barrier.cluster.wait.aligned;" ::: "memory"); }

DEVI void tma_load_2d(uint32_t dst, const CUtensorMap* m, int c0, int c1, uint32_t bar) {
  asm volatile("cp.async.bulk.tensor.2d.shared::cluster.global.mbarrier::complete_tx::bytes [%0], [%1, {%3, %4}], [%2];"
               ::"r"(dst), "l"(m), "r"(bar), "r"(c0), "r"(c1) : "memory");
}
DEVI void tma_load_2d_mc(uint32_t dst, const CUtensorMap* m, int c0, int c1, uint32_t bar, uint16_t mask) {
  asm volatile("cp.async.bulk.tensor.2d.shared::cluster.global.mbarrier::complete_tx::bytes.multicast::cluster [%0], [%1, {%3, %4}], [%2], %5;"
               ::"r"(dst), "l"(m), "r"(bar), "r"(c0), "r"(c1), "h"(mask) : "memory");
}
DEVI void tma_load_3d_mc(uint32_t dst, const CUtensorMap* m, int c0, int c1, int c2, uint32_t bar, uint16_t mask) {
  asm volatile("cp.async.bulk.tensor.3d.shared::cluster.global.mbarrier::complete_tx::bytes.multicast::cluster [%0], [%1, {%3, %4, %5}], [%2], %6;"
               ::"r"(dst), "l"(m), "r"(bar), "r"(c0), "r"(c1), "r"(c2), "h"(mask) : "memory");
}
DEVI void tma_store_2d(const CUtensorMap* m, uint32_t src, int c0, int c1) {
  asm volatile("cp.async.bulk.tensor.2d.global.shared::cta.bulk_group [%0, {%2, %3}], [%1];"
               ::"l"(m), "r"(src), "r"(c0), "r"(c1) : "memory");
}
DEVI void bulk_load(uint32_t dst, const void* src, uint32_t bytes, uint32_t bar) {
  asm volatile("cp.async.bulk.shared::cluster.global.mbarrier::complete_tx::bytes [%0], [%1], %2, [%3];"
               ::"r"(dst), "l"(src), "r"(bytes), "r"(bar) : "memory");
}
DEVI void bulk_store(void* dst, uint32_t src, uint32_t bytes) {
  asm volatile("cp.async.bulk.global.shared::cta.bulk_group [%0], [%1], %2;" ::"l"(dst), "r"(src), "r"(bytes) : "memory");
}
DEVI void bulk_reduce_add_f32(void* dst, uint32_t src, uint32_t bytes) {
  asm volatile("cp.reduce.async.bulk.global.shared::cta.bulk_group.add.f32 [%0], [%1], %2;" ::"l"(dst), "r"(src), "r"(bytes) : "memory");
}
DEVI void bulk_commit() { asm volatile("cp.async.bulk.commit_group;" ::: "memory"); }
DEVI void bulk_wait0() { asm volatile("cp.async.bulk.wait_group 0;" ::: "memory"); }
DEVI void bulk_wait_read0() { asm volatile("cp.async.bulk.wait_group.read 0;" ::: "memory"); }
DEVI void l2_prefetch(const void* p, uint32_t bytes) {
  asm volatile("cp.async.bulk.prefetch.L2.global [%0], %1;" ::"l"(p), "r"(bytes) : "memory");
}
DEVI void prefetch_tmap(const CUtensorMap* m) { asm volatile("prefetch.tensormap [%0];" ::"l"(m) : "memory"); }

DEVI void red_release_add(unsigned* p, unsigned v) {
  asm volatile("red.release.gpu.global.add.u32 [%0], %1;" ::"l"(p), "r"(v) : "memory");
}
DEVI void red_relaxed_add(unsigned* p, unsigned v) {
  asm volatile("red.relaxed.gpu.global.add.u32 [%0], %1;" ::"l"(p), "r"(v) : "memory");
}
DEVI unsigned ld_relaxed(const unsigned* p) {
  unsigned v;
  asm volatile("ld.relaxed.gpu.global.u32 %0, [%1];" : "=r"(v) : "l"(p) : "memory");
  return v;
}
DEVI void wait_counter(const unsigned* p, unsigned target) {
#pragma unroll 1
  for (int it = 0; (int)(ld_relaxed(p) - target) < 0; ++it)
    if (it > (1 << 22)) __trap();
}

DEVI void ldsm_x4(uint32_t (&r)[4], uint32_t a) {
  asm volatile("ldmatrix.sync.aligned.m8n8.x4.shared.b16 {%0,%1,%2,%3}, [%4];"
               : "=r"(r[0]), "=r"(r[1]), "=r"(r[2]), "=r"(r[3]) : "r"(a) : "memory");
}
DEVI void ldsm_x4_t(uint32_t (&r)[4], uint32_t a) {
  asm volatile("ldmatrix.sync.aligned.m8n8.x4.trans.shared.b16 {%0,%1,%2,%3}, [%4];"
               : "=r"(r[0]), "=r"(r[1]), "=r"(r[2]), "=r"(r[3]) : "r"(a) : "memory");
}
DEVI void ldsm_x2_t(uint32_t& r0, uint32_t& r1, uint32_t a) {
  asm volatile("ldmatrix.sync.aligned.m8n8.x2.trans.shared.b16 {%0,%1}, [%2];" : "=r"(r0), "=r"(r1) : "r"(a) : "memory");
}
DEVI void stsm_x4(uint32_t a, uint32_t r0, uint32_t r1, uint32_t r2, uint32_t r3) {
  asm volatile("stmatrix.sync.aligned.m8n8.x4.shared.b16 [%0], {%1,%2,%3,%4};"
               ::"r"(a), "r"(r0), "r"(r1), "r"(r2), "r"(r3) : "memory");
}
DEVI void stsm_x4_t(uint32_t a, uint32_t r0, uint32_t r1, uint32_t r2, uint32_t r3) {
  asm volatile("stmatrix.sync.aligned.m8n8.x4.trans.shared.b16 [%0], {%1,%2,%3,%4};"
               ::"r"(a), "r"(r0), "r"(r1), "r"(r2), "r"(r3) : "memory");
}
DEVI uint32_t lds32(uint32_t a) { uint32_t v; asm volatile("ld.shared.b32 %0, [%1];" : "=r"(v) : "r"(a) : "memory"); return v; }
DEVI float lds_f32(uint32_t a) { float v; asm volatile("ld.shared.f32 %0, [%1];" : "=f"(v) : "r"(a) : "memory"); return v; }
DEVI void sts32(uint32_t a, uint32_t v) { asm volatile("st.shared.b32 [%0], %1;" ::"r"(a), "r"(v) : "memory"); }
DEVI void sts_f32(uint32_t a, float v) { asm volatile("st.shared.f32 [%0], %1;" ::"r"(a), "f"(v) : "memory"); }
DEVI void sts_f32x2(uint32_t a, float x, float y) { asm volatile("st.shared.v2.f32 [%0], {%1,%2};" ::"r"(a), "f"(x), "f"(y) : "memory"); }
DEVI uint4 lds128(uint32_t a) {
  uint4 v;
  asm volatile("ld.shared.v4.b32 {%0,%1,%2,%3}, [%4];" : "=r"(v.x), "=r"(v.y), "=r"(v.z), "=r"(v.w) : "r"(a) : "memory");
  return v;
}
DEVI void sts128(uint32_t a, uint32_t x, uint32_t y, uint32_t z, uint32_t w) {
  asm volatile("st.shared.v4.b32 [%0], {%1,%2,%3,%4};" ::"r"(a), "r"(x), "r"(y), "r"(z), "r"(w) : "memory");
}

DEVI void mma_bf16(float (&d)[4], uint32_t a0, uint32_t a1, uint32_t a2, uint32_t a3, uint32_t b0, uint32_t b1) {
  asm("mma.sync.aligned.m16n8k16.row.col.f32.bf16.bf16.f32 {%0,%1,%2,%3}, {%4,%5,%6,%7}, {%8,%9}, {%0,%1,%2,%3};"
      : "+f"(d[0]), "+f"(d[1]), "+f"(d[2]), "+f"(d[3])
      : "r"(a0), "r"(a1), "r"(a2), "r"(a3), "r"(b0), "r"(b1));
}
DEVI void mma_f16(float (&d)[4], const uint32_t (&a)[4], uint32_t b0, uint32_t b1) {
  asm("mma.sync.aligned.m16n8k16.row.col.f32.f16.f16.f32 {%0,%1,%2,%3}, {%4,%5,%6,%7}, {%8,%9}, {%0,%1,%2,%3};"
      : "+f"(d[0]), "+f"(d[1]), "+f"(d[2]), "+f"(d[3])
      : "r"(a[0]), "r"(a[1]), "r"(a[2]), "r"(a[3]), "r"(b0), "r"(b1));
}
DEVI void mma_bf16v(float (&d)[4], const uint32_t (&a)[4], uint32_t b0, uint32_t b1) {
  asm volatile("mma.sync.aligned.m16n8k16.row.col.f32.bf16.bf16.f32 {%0,%1,%2,%3}, {%4,%5,%6,%7}, {%8,%9}, {%0,%1,%2,%3};"
               : "+f"(d[0]), "+f"(d[1]), "+f"(d[2]), "+f"(d[3])
               : "r"(a[0]), "r"(a[1]), "r"(a[2]), "r"(a[3]), "r"(b0), "r"(b1));
}
DEVI uint32_t pack_bf16(float lo, float hi) {
  uint32_t r;
  asm("cvt.rn.bf16x2.f32 %0, %1, %2;" : "=r"(r) : "f"(hi), "f"(lo));
  return r;
}
DEVI uint32_t pack_f16(float lo, float hi) {
  uint32_t r;
  asm("cvt.rn.f16x2.f32 %0, %1, %2;" : "=r"(r) : "f"(hi), "f"(lo));
  return r;
}
DEVI uint32_t ldg16(const __nv_bfloat16* p) {
  uint32_t v;
  asm volatile("ld.global.nc.u16 %0, [%1];" : "=r"(v) : "l"(p));
  return v;
}
DEVI bool elect_one() {
  uint32_t pred;
  asm volatile("{\n.reg .pred p;\nelect.sync _|p, 0xffffffff;\nselp.u32 %0, 1, 0, p;\n}" : "=r"(pred));
  return pred != 0;
}
DEVI float bf_lo(uint32_t v) { return __uint_as_float(v << 16); }
DEVI float bf_hi(uint32_t v) { return __uint_as_float(v & 0xffff0000u); }
DEVI float bf2f(__nv_bfloat16 v) { return __bfloat162float(v); }
DEVI float round_bf16(float v) { return __bfloat162float(__float2bfloat16_rn(v)); }
DEVI float rcp(float x) { float r; asm("rcp.approx.ftz.f32 %0, %1;" : "=f"(r) : "f"(x)); return r; }
DEVI float ex2(float x) { float r; asm("ex2.approx.ftz.f32 %0, %1;" : "=f"(r) : "f"(x)); return r; }

DEVI void wg_fence() { asm volatile("wgmma.fence.sync.aligned;" ::: "memory"); }
DEVI void wg_commit() { asm volatile("wgmma.commit_group.sync.aligned;" ::: "memory"); }
template <int N> DEVI void wg_wait() { asm volatile("wgmma.wait_group.sync.aligned %0;" ::"n"(N) : "memory"); }
constexpr uint32_t DESC_HI = (1u << 30) | (1024 >> 4);
constexpr uint32_t DESC_HI64 = (2u << 30) | (512 >> 4);
DEVI uint32_t mkdesc(uint32_t saddr, uint32_t lbo) { return ((saddr & 0x3FFFF) >> 4) | ((lbo >> 4) << 16); }

#define R8(b) "%" #b
DEVI void wgmma_n192(float (&d)[96], uint32_t da, uint32_t db, int scale_d) {
  asm volatile(
      "{\n.reg .pred p;\n.reg .b64 da, db;\nsetp.ne.b32 p, %98, 0;\nmov.b64 da, {%96, %100};\nmov.b64 db, {%97, %99};\n"
      "wgmma.mma_async.sync.aligned.m64n192k16.f32.bf16.bf16 "
      "{%0,%1,%2,%3,%4,%5,%6,%7,%8,%9,%10,%11,%12,%13,%14,%15,"
      "%16,%17,%18,%19,%20,%21,%22,%23,%24,%25,%26,%27,%28,%29,%30,%31,"
      "%32,%33,%34,%35,%36,%37,%38,%39,%40,%41,%42,%43,%44,%45,%46,%47,"
      "%48,%49,%50,%51,%52,%53,%54,%55,%56,%57,%58,%59,%60,%61,%62,%63,"
      "%64,%65,%66,%67,%68,%69,%70,%71,%72,%73,%74,%75,%76,%77,%78,%79,"
      "%80,%81,%82,%83,%84,%85,%86,%87,%88,%89,%90,%91,%92,%93,%94,%95}, "
      "da, db, p, 1, 1, 0, 1;\n}"
      : "+f"(d[0]), "+f"(d[1]), "+f"(d[2]), "+f"(d[3]), "+f"(d[4]), "+f"(d[5]), "+f"(d[6]), "+f"(d[7]),
        "+f"(d[8]), "+f"(d[9]), "+f"(d[10]), "+f"(d[11]), "+f"(d[12]), "+f"(d[13]), "+f"(d[14]), "+f"(d[15]),
        "+f"(d[16]), "+f"(d[17]), "+f"(d[18]), "+f"(d[19]), "+f"(d[20]), "+f"(d[21]), "+f"(d[22]), "+f"(d[23]),
        "+f"(d[24]), "+f"(d[25]), "+f"(d[26]), "+f"(d[27]), "+f"(d[28]), "+f"(d[29]), "+f"(d[30]), "+f"(d[31]),
        "+f"(d[32]), "+f"(d[33]), "+f"(d[34]), "+f"(d[35]), "+f"(d[36]), "+f"(d[37]), "+f"(d[38]), "+f"(d[39]),
        "+f"(d[40]), "+f"(d[41]), "+f"(d[42]), "+f"(d[43]), "+f"(d[44]), "+f"(d[45]), "+f"(d[46]), "+f"(d[47]),
        "+f"(d[48]), "+f"(d[49]), "+f"(d[50]), "+f"(d[51]), "+f"(d[52]), "+f"(d[53]), "+f"(d[54]), "+f"(d[55]),
        "+f"(d[56]), "+f"(d[57]), "+f"(d[58]), "+f"(d[59]), "+f"(d[60]), "+f"(d[61]), "+f"(d[62]), "+f"(d[63]),
        "+f"(d[64]), "+f"(d[65]), "+f"(d[66]), "+f"(d[67]), "+f"(d[68]), "+f"(d[69]), "+f"(d[70]), "+f"(d[71]),
        "+f"(d[72]), "+f"(d[73]), "+f"(d[74]), "+f"(d[75]), "+f"(d[76]), "+f"(d[77]), "+f"(d[78]), "+f"(d[79]),
        "+f"(d[80]), "+f"(d[81]), "+f"(d[82]), "+f"(d[83]), "+f"(d[84]), "+f"(d[85]), "+f"(d[86]), "+f"(d[87]),
        "+f"(d[88]), "+f"(d[89]), "+f"(d[90]), "+f"(d[91]), "+f"(d[92]), "+f"(d[93]), "+f"(d[94]), "+f"(d[95])
      : "r"(da), "r"(db), "r"(scale_d), "n"(DESC_HI), "n"(DESC_HI64));
}
DEVI void wgmma_n64(float (&d)[32], uint32_t da, uint32_t db, int scale_d) {
  asm volatile(
      "{\n.reg .pred p;\n.reg .b64 da, db;\nsetp.ne.b32 p, %34, 0;\nmov.b64 da, {%32, %35};\nmov.b64 db, {%33, %35};\n"
      "wgmma.mma_async.sync.aligned.m64n64k16.f32.bf16.bf16 "
      "{%0,%1,%2,%3,%4,%5,%6,%7,%8,%9,%10,%11,%12,%13,%14,%15,"
      "%16,%17,%18,%19,%20,%21,%22,%23,%24,%25,%26,%27,%28,%29,%30,%31}, "
      "da, db, p, 1, 1, 0, 1;\n}"
      : "+f"(d[0]), "+f"(d[1]), "+f"(d[2]), "+f"(d[3]), "+f"(d[4]), "+f"(d[5]), "+f"(d[6]), "+f"(d[7]),
        "+f"(d[8]), "+f"(d[9]), "+f"(d[10]), "+f"(d[11]), "+f"(d[12]), "+f"(d[13]), "+f"(d[14]), "+f"(d[15]),
        "+f"(d[16]), "+f"(d[17]), "+f"(d[18]), "+f"(d[19]), "+f"(d[20]), "+f"(d[21]), "+f"(d[22]), "+f"(d[23]),
        "+f"(d[24]), "+f"(d[25]), "+f"(d[26]), "+f"(d[27]), "+f"(d[28]), "+f"(d[29]), "+f"(d[30]), "+f"(d[31])
      : "r"(da), "r"(db), "r"(scale_d), "n"(DESC_HI));
}

struct C32 { float re, im; };
DEVI C32 csq(C32 a) { return {a.re * a.re - a.im * a.im, 2.f * a.re * a.im}; }
DEVI C32 cmul(C32 a, C32 b) { return {a.re * b.re - a.im * b.im, a.re * b.im + a.im * b.re}; }
DEVI C32 cfresh(float zl, float zi, float m) {
  float mag = ex2(zl * m), ph = zi * m;
  return {mag * __cosf(ph), mag * __sinf(ph)};
}
struct HMul { uint32_t b, bp; };
DEVI HMul mk_mul(float re, float im) { return {pack_f16(re, im), pack_f16(-im, re)}; }
DEVI uint32_t hcmul(uint32_t a, const HMul& m) {
  __half2 ah = *reinterpret_cast<__half2*>(&a);
  __half2 b = *reinterpret_cast<const __half2*>(&m.b), bp = *reinterpret_cast<const __half2*>(&m.bp);
  __half2 r = __hfma2(__high2half2(ah), bp, __hmul2(__low2half2(ah), b));
  return *reinterpret_cast<uint32_t*>(&r);
}
DEVI uint32_t badd(uint32_t a, uint32_t b) {
  __nv_bfloat162 r = __hadd2(*reinterpret_cast<__nv_bfloat162*>(&a), *reinterpret_cast<__nv_bfloat162*>(&b));
  return *reinterpret_cast<uint32_t*>(&r);
}
template <int MU0, int NMU, int DMAX>
DEVI void conv_tail(float (&acc)[16][4], uint32_t p_lane, uint32_t v_base, int back, bool edge, int lane) {
  const int hsel = (lane >> 3) & 1;
  const int row = (lane & 7) + ((lane >> 4) << 3) + PADV - 8 - (back & (hsel ^ 1));
  const uint32_t la = v_base + row * 32 + (((hsel ^ back) ^ ((row >> 2) & 1)) << 4);
  uint32_t M[3][4];
  ldsm_x4_t(M[0], la);
  ldsm_x4_t(M[1], la + 256);
  uint32_t H[2 * NMU];
#pragma unroll
  for (int i = 0; i < 2 * NMU; ++i) H[i ^ 1] = lds32(p_lane + (uint32_t)(MU0 - 1 + i) * 32);
  if (edge) {
    const uint32_t a[4] = {0u, 0u, M[0][0], M[0][1]};
#pragma unroll
    for (int k = 1; k < NMU; ++k) mma_bf16v(acc[MU0 - 2 + 2 * k], a, H[2 * k], H[2 * k + 1]);
  }
#pragma unroll
  for (int delta = -1; delta <= DMAX; ++delta) {
    if (delta + 2 <= DMAX) ldsm_x4_t(M[(delta + 3) % 3], la + (delta + 3) * 256);
#pragma unroll
    for (int k = 0; k < NMU; ++k)
      if (delta + MU0 + 2 * k < 16) mma_bf16v(acc[delta + MU0 + 2 * k], M[(delta + 1) % 3], H[2 * k], H[2 * k + 1]);
  }
}

__global__ void __cluster_dims__(2, 1, 1) __launch_bounds__(NTHREADS, 1)
fused_kernel(const __grid_constant__ Maps maps, const Ptrs p) {
  extern __shared__ __align__(1024) uint8_t smem[];
  const uint32_t sb = s2u(smem);
  const int tid = threadIdx.x, lane = tid & 31;
  const int warp = __shfl_sync(0xffffffffu, tid >> 5, 0);
  const int cta = blockIdx.x;
  const uint32_t rank = cta & 1;
  const int ti = 2 * (cta >> 4) + rank;
  const int tj = (cta >> 1) & 7;
  const int pi = cta >> 3, pj = cta & 7;
  const uint32_t bars = sb + SM_BAR;
#define BAR(i) (bars + 8 * (i))
  const int g = lane >> 2, q = lane & 3;

  auto issue_stage = [&](int ks, int s) {
    const uint32_t st = sb + s * STG_BYTES, fb = BAR(B_FULL + s);
    mbar_expect_tx(fb, STG_BYTES);
    tma_load_2d(st + STG_X, &maps.x, ks * 32, ti * 128, fb);
    tma_load_3d_mc(st + STG_W + rank * 6144, &maps.w, tj * 64, ks * 32 + rank * 16, 0, fb, 3);
  };

  const int kch = warp & 3, krd = warp >> 2;
  float zr, zi, wr, wi;
  unsigned epoch;
  uint32_t r_dskip;
  {
    const size_t po = (size_t)(cta * 4 + kch) * 128 + krd * 32 + lane;
    const uint32_t r_ar = ldg16(p.A_re + po), r_ai = ldg16(p.A_im + po), r_br = ldg16(p.B_re + po), r_bi = ldg16(p.B_im + po);
    const uint32_t r_cr = ldg16(p.C_re + po), r_ci = ldg16(p.C_im + po), r_ldt = ldg16(p.log_dt + cta * 4 + kch);
    epoch = __ldcg(&g_epoch);
    r_dskip = ldg16(p.Dskip + cta * 4 + kch);
    uint4 pt;
    if (tid < 128) pt = __ldg((const uint4*)g_ptab.v + tid);
    if (tid == 384) {
      TS(0);
#pragma unroll
      for (int i = 0; i < B_COUNT; ++i) mbar_init(BAR(i), bar_count(i));
      asm volatile("fence.mbarrier_init.release.cluster;" ::: "memory");
      prefetch_tmap(&maps.x); prefetch_tmap(&maps.w); prefetch_tmap(&maps.u);
    }
    __syncthreads();
    cluster_arrive();
    if (warp >= 12) {
      cluster_wait();
      if (elect_one()) {
        if (warp == 13) {
          mbar_expect_tx(BAR(B_TILE), 16384);
          tma_load_2d(sb + SM_U, &maps.u, tj * 64, ti * 128, BAR(B_TILE));
          prefetch_tmap(&maps.uT); prefetch_tmap(&maps.wo); prefetch_tmap(&maps.o);
          prefetch_tmap(&maps.out);
        } else {
          if (warp == 12) TS(61);
          { const int ks = warp == 12 ? 0 : warp - 13; issue_stage(ks, ks); }
        }
      }
      __syncwarp();
    }
    if (tid < 128) sts128(sb + SM_PTAB + tid * 16, pt.x, pt.y, pt.z, pt.w);
    const float dt = round_bf16(expf(bf_lo(r_ldt)));
    zr = dt * bf_lo(r_ar); zi = dt * bf_lo(r_ai);
    const float dbr = dt * bf_lo(r_br), dbi = dt * bf_lo(r_bi), cr = bf_lo(r_cr), ci = bf_lo(r_ci);
    wr = cr * dbr - ci * dbi; wi = cr * dbi + ci * dbr;
  }
  {
    const float mz = __uint_as_float(__reduce_max_sync(0xffffffffu, __float_as_uint(fmaxf(zr, 0.f))));
    const int E = min(max((int)(__reduce_max_sync(0xffffffffu, __float_as_uint(fmaxf(fabsf(wr), fabsf(wi)))) >> 23), 1), 252);
    const float sc = __int_as_float((253 - E) << 23), inv = __int_as_float((E + 1) << 23);
    const float zl = (zr - mz) * 1.4426950408889634f;
    const uint32_t tb = sb + SM_VV + kch * VV_BYTES + krd * KG_BYTES;
    const uint32_t sta = tb + (((lane >> 2) << 4) | ((lane & 3) << 2));
    auto put = [&](int r, uint32_t v) { sts32((sta ^ ((r & 7) << 4)) + r * 128, v); };
    const uint32_t lda = tb + ((lane & 7) + (((lane >> 3) & 1) << 3)) * 128;
    const uint32_t ldb = tb + ((lane & 7) + ((lane >> 4) << 3)) * 128;
    C32 e1 = cfresh(zl, zi, 1.f), e2 = csq(e1), e4 = csq(e2), e8 = csq(e4);
    C32 e16 = cfresh(zl, zi, 16.f), e32 = csq(e16), e64 = csq(e32), e128 = csq(e64);
    C32 e256 = cfresh(zl, zi, 256.f), e512 = csq(e256), e1024 = csq(e512), e768 = cmul(e512, e256);
    uint32_t XA[2][4][4];
    {
      const HMul m16 = mk_mul(e16.re, e16.im), m32 = mk_mul(e32.re, e32.im), m64 = mk_mul(e64.re, e64.im);
      const HMul m128 = mk_mul(e128.re, e128.im);
      uint32_t X[16];
      X[0] = 0x00003c00u; X[1] = pack_f16(e8.re, e8.im); X[2] = m16.b; X[4] = m32.b; X[8] = m64.b;
      X[3] = hcmul(X[1], m16); X[5] = hcmul(X[1], m32); X[6] = hcmul(X[2], m32); X[7] = hcmul(X[3], m32);
#pragma unroll
      for (int r = 1; r < 8; ++r) X[8 + r] = hcmul(X[r], m64);
#pragma unroll
      for (int h = 0; h < 2; ++h) {
#pragma unroll
        for (int r = 0; r < 16; ++r) put(r, h == 0 ? X[r] : r == 0 ? m128.b : hcmul(X[r], m128));
        __syncwarp();
#pragma unroll
        for (int k = 0; k < 4; ++k) ldsm_x4(XA[h][k], lda + (((2 * k + (lane >> 4)) ^ (lane & 7)) << 4));
        __syncwarp();
      }
    }
    if (warp >= 14 && elect_one()) {
      issue_stage(warp - 11, warp - 11);
      issue_stage(warp - 9, warp - 9);
      if (warp == 14) l2_prefetch((const char*)p.wqkv + 224 * 3072 + cta * 6912, 6912);
      else l2_prefetch((const char*)p.x + (size_t)cta * 16384, 16384);
    }
    __syncwarp();
    float D[2][3][4];
#pragma unroll
    for (int t = 0; t < 6; ++t) D[t / 3][t % 3][0] = D[t / 3][t % 3][1] = D[t / 3][t % 3][2] = D[t / 3][t % 3][3] = 0.f;
    auto contract = [&](int t0, int nt) {
      __syncwarp();
#pragma unroll
      for (int k = 0; k < 4; ++k) {
        uint32_t b[4];
        ldsm_x4(b, ldb + (((2 * k + ((lane >> 3) & 1)) ^ (lane & 7)) << 4));
#pragma unroll
        for (int h = 0; h < 2; ++h) {
          mma_f16(D[h][t0], XA[h][k], b[0], b[1]);
          if (nt == 2) mma_f16(D[h][t0 + 1], XA[h][k], b[2], b[3]);
        }
      }
      __syncwarp();
    };
    const HMul c1 = mk_mul(e1.re, -e1.im), c2 = mk_mul(e2.re, -e2.im), c4 = mk_mul(e4.re, -e4.im);
    const HMul c256 = mk_mul(e256.re, -e256.im), c512 = mk_mul(e512.re, -e512.im), c768 = mk_mul(e768.re, -e768.im);
    const HMul c1024 = mk_mul(e1024.re, -e1024.im);
    uint32_t W[8];
    W[0] = pack_f16(wr * sc, -wi * sc);
    W[1] = hcmul(W[0], c1); W[2] = hcmul(W[0], c2); W[3] = hcmul(W[1], c2);
    W[4] = hcmul(W[0], c4); W[5] = hcmul(W[1], c4); W[6] = hcmul(W[2], c4); W[7] = hcmul(W[3], c4);
#pragma unroll
    for (int i = 0; i < 8; ++i) put(i, W[i]);
#pragma unroll
    for (int i = 0; i < 4; ++i) put(8 + i, hcmul(W[2 * i], c256));
    put(12, hcmul(W[0], c512)); put(13, hcmul(W[4], c512)); put(14, hcmul(W[0], c768)); put(15, hcmul(W[4], c768));
    contract(0, 2);
    const uint32_t v0 = hcmul(W[0], c1024);
    put(0, v0); put(1, hcmul(v0, c256)); put(2, hcmul(v0, c512)); put(3, hcmul(v0, c768)); put(4, hcmul(v0, c1024));
    contract(2, 1);
    const uint32_t a = tb + (g * 24 + 2 * q) * 4;
#pragma unroll
    for (int t = 0; t < 6; ++t) {
      const float(&d)[4] = D[t / 3][t % 3];
      sts_f32x2(a + (t / 3) * 1536 + (t % 3) * 32, d[0] * inv, d[1] * inv);
      sts_f32x2(a + (t / 3) * 1536 + (t % 3) * 32 + 768, d[2] * inv, d[3] * inv);
    }
    if (mz > 0.f) {
      __syncwarp();
#pragma unroll 1
      for (int i = lane; i < 768; i += 32) {
        const int r = i / 24, y = i - 24 * r;
        sts_f32(tb + i * 4, lds_f32(tb + i * 4) * ex2(mz * 1.4426950408889634f * (koff(y) + 8 * r)));
      }
    }
  }
  if (tid == 0) TS(2);
  if (warp < 12) cluster_wait();
  if (tid == 0) TS(32);
  __syncthreads();
  if (tid == 0) TSD(33);

  if (warp < 4) {
    asm volatile("setmaxnreg.inc.sync.aligned.u32 152;");
    if (tid == 0) TS(34);
    const int d = cta * 4 + warp;
    const uint32_t vv = sb + SM_VV + warp * VV_BYTES;
    const uint32_t ub = sb + SM_U + warp * U_BYTES;
    const uint32_t pb = sb + SM_P + warp * P_BYTES;
    const float dskip = bf_lo(r_dskip);
    mbar_wait_long(BAR(B_TILE), 0);
    if (lane == 0) TS(26);
    {
      const int m = lane >> 3, r = lane & 7;
#pragma unroll 2
      for (int it = 0; it < 8; ++it) {
        const int tb = warp * 4 + (it >> 1), cb = (it & 1) * 4 + m;
        uint32_t v[4];
        ldsm_x4_t(v, sb + SM_U + (tb * 8 + r) * 128 + ((cb ^ r) << 4));
        stsm_x4(sb + SM_P + (tb >> 3) * 8192 + (cb * 8 + r) * 128 + (((tb & 7) ^ (tb >> 3) ^ r) << 4), v[0], v[1], v[2], v[3]);
      }
    }
    if (tid == 0) TS(35);
    fence_async_smem();
    bar_arrive(6, 160);
    {
      {
        const uint32_t kf = vv;
#pragma unroll 2
        for (int i = 0; i < 6; ++i) {
          const uint32_t a = kf + (i * 32 + lane) * 16;
          const uint4 x0 = lds128(a), x1 = lds128(a + KG_BYTES), x2 = lds128(a + 2 * KG_BYTES), x3 = lds128(a + 3 * KG_BYTES);
          auto s4 = [](uint32_t a0, uint32_t a1, uint32_t a2, uint32_t a3) {
            return __float_as_uint((__uint_as_float(a0) + __uint_as_float(a1)) + (__uint_as_float(a2) + __uint_as_float(a3)));
          };
          sts128(a, s4(x0.x, x1.x, x2.x, x3.x), s4(x0.y, x1.y, x2.y, x3.y), s4(x0.z, x1.z, x2.z, x3.z), s4(x0.w, x1.w, x2.w, x3.w));
        }
        __syncwarp();
        const float k1024 = lds_f32(kf + kidx_c(1024) * 4);
        if (lane == 0) {
          sts_f32(kf + SL_ZERO * 4, 0.f);
          sts_f32(kf + SL_510 * 4, lds_f32(kf + kidx_c(510) * 4) - lds_f32(kf + kidx_c(512) * 4));
          sts_f32(kf + SL_0 * 4, lds_f32(kf) + dskip);
        }
        __syncwarp();
        if (tid == 0) TS(36);
        mbar_wait_long(BAR(B_PFREE), 0);
        if (tid == 0) TS(37);
        {
          float prev = 0.f;
#pragma unroll 1
          for (int i0 = 0; i0 < 16; i0 += 4) {
            uint32_t e[4];
            float a[4], b[4];
#pragma unroll
            for (int i = 0; i < 4; ++i) e[i] = lds32(sb + SM_PTAB + ((i0 + i) * 32 + lane) * 4);
#pragma unroll
            for (int i = 0; i < 4; ++i) { a[i] = lds_f32(kf + (e[i] & 0xffff)); b[i] = lds_f32(kf + (e[i] >> 16)); }
#pragma unroll
            for (int i = 0; i < 4; ++i) {
              const uint32_t w = pb + (31 * lane + 2 * (i0 + i)) * 4;
              if (i0 + i > 0) sts32(w - 4, pack_bf16(a[i], prev));
              sts32(w, pack_bf16(b[i], a[i]));
              prev = b[i];
            }
          }
        }
        __syncwarp();
        if (lane == 0) TS(4);
        const int gq = g - 2 * q;
        uint32_t h127, h128;
        {
          const uint32_t kf2 = pack_bf16(k1024, k1024) ^ 0x80008000u;
          h127 = (gq == 4 ? 0x0000ffffu : gq == 5 ? 0xffffffffu : gq == 6 ? 0xffff0000u : 0u) & kf2;
          h128 = (gq == -4 ? 0x0000ffffu : gq == -3 ? 0xffffffffu : gq == -2 ? 0xffff0000u : 0u) & kf2;
        }
        bar_sync(4, 480);
        mbar_wait_long(BAR(B_UCH + warp), 0);
        if (lane == 0) TS(7);
        float acc[16][4];
#pragma unroll
        for (int i = 0; i < 16; ++i) { acc[i][0] = acc[i][1] = acc[i][2] = acc[i][3] = 0.f; }
        {
          const uint32_t pd_lane = pb + (PD_OFF + 16 + gq) * 4;
          const int prow0 = 8 + (lane & 7) + ((lane >> 4) << 3), hs = (lane >> 3) & 1;
          const uint32_t zero = (uint32_t)cta >> 20;
          uint32_t B[2][4][4];
          uint32_t A[4][4];
          const uint32_t la0 = ub + prow0 * 32 + ((hs ^ ((prow0 >> 2) & 1)) << 4);
#pragma unroll
          for (int m2 = 0; m2 < 4; ++m2) ldsm_x4(B[0][m2], la0 + m2 * 512);
#pragma unroll
          for (int i = 0; i < 4; ++i) {
            const uint32_t a = pd_lane + i * 512;
            A[i][0] = lds32(a); A[i][1] = lds32(a + 32); A[i][2] = lds32(a - 32); A[i][3] = lds32(a + zero);
          }
          uint32_t la = la0;
#define UNR_RHO 1
#define UNR_TAIL 1
          constexpr int unr_rho = UNR_RHO, unr_tail = UNR_TAIL;
#pragma unroll unr_rho
          for (int rho = 0; rho < 8; ++rho) {
#pragma unroll
            for (int m2 = 0; m2 < 4; ++m2) ldsm_x4(B[1][m2], la + (4 + m2) * 512);
#pragma unroll
            for (int i = 0; i < 4; ++i)
#pragma unroll
              for (int m = 0; m < 8; ++m) mma_bf16v(acc[m + i], A[i], B[0][m >> 1][2 * (m & 1)], B[0][m >> 1][2 * (m & 1) + 1]);
            const int prow = prow0 - min(rho + 1, 7);
            la = ub + prow * 32 + ((hs ^ ((prow >> 2) & 1)) << 4);
#pragma unroll
            for (int m2 = 0; m2 < 4; ++m2) ldsm_x4(B[0][m2], la + m2 * 512);
            const uint32_t pa = pd_lane + (rho + 1) * 64;
#pragma unroll
            for (int i = 0; i < 4; ++i) {
#pragma unroll
              for (int m = 0; m < 8 - i; ++m)
                mma_bf16v(acc[8 + m + i], A[i], B[1][m >> 1][2 * (m & 1)], B[1][m >> 1][2 * (m & 1) + 1]);
              A[i][0] = lds32(pa + i * 512); A[i][1] = lds32(pa + i * 512 + 32); A[i][2] = lds32(pa + i * 512 - 32);
              A[i][3] = lds32(pa + i * 512 + zero);
            }
          }
          if (lane == 0) TS(40);
          {
            uint32_t b8[4];
            ldsm_x4(b8, la + 4 * 512);
            const uint32_t h63 = lds32(pd_lane + 63 * 32), h64 = lds32(pd_lane + 64 * 32);
            const uint32_t a63[4] = {0u, h127, 0u, 0u}, a32[4] = {h64, 0u, h63, h64}, a64[4] = {h128, 0u, h127, h128};
#pragma unroll
            for (int m2 = 0; m2 < 4; ++m2) ldsm_x4(B[1][m2], la0 + m2 * 512);
#pragma unroll
            for (int m = 0; m < 8; ++m) mma_bf16v(acc[m + 7], a63, B[0][m >> 1][2 * (m & 1)], B[0][m >> 1][2 * (m & 1) + 1]);
#pragma unroll
            for (int m2 = 0; m2 < 2; ++m2) ldsm_x4(B[0][m2], la0 + (4 + m2) * 512);
#pragma unroll
            for (int m = 0; m < 8; ++m) mma_bf16v(acc[m + 4], a32, B[1][m >> 1][2 * (m & 1)], B[1][m >> 1][2 * (m & 1) + 1]);
            mma_bf16v(acc[15], a63, b8[0], b8[1]);
#pragma unroll
            for (int m = 0; m < 8; ++m) mma_bf16v(acc[m + 8], a64, B[1][m >> 1][2 * (m & 1)], B[1][m >> 1][2 * (m & 1) + 1]);
#pragma unroll
            for (int m = 0; m < 4; ++m) mma_bf16v(acc[m + 12], a32, B[0][m >> 1][2 * (m & 1)], B[0][m >> 1][2 * (m & 1) + 1]);
          }
          if (lane == 0) TS(41);
          bar_sync(5, 224);
#pragma unroll unr_tail
          for (int v = 0; v < 4; ++v)
            conv_tail<4, 3, 11>(acc, pb + (P2_OFF + 56 * v + gq - 16) * 4, vv + ((v & 1) ? VV_U3 : VV_U5), v >> 1, v == 0, lane);
          if (lane == 0) TS(42);
#pragma unroll unr_tail
          for (int pi = 0; pi < 2; ++pi)
            conv_tail<8, 5, 7>(acc, pb + (P3_OFF + 88 * pi + gq - 48) * 4, vv + (pi ? VV_U7 : VV_U9), pi, pi == 0, lane);
        }
        if (lane == 0) TS(8);
        __syncwarp();
        {
          const int mt = lane >> 3;
          const uint32_t a = pb + (128 * (mt >> 1) + 16 * (lane & 7) + 8 * (mt & 1)) * 2;
#pragma unroll
          for (int ab = 0; ab < 16; ab += 2)
            stsm_x4_t(a + ab * 256, pack_bf16(acc[ab][0], acc[ab][1]), pack_bf16(acc[ab][2], acc[ab][3]),
                      pack_bf16(acc[ab + 1][0], acc[ab + 1][1]), pack_bf16(acc[ab + 1][2], acc[ab + 1][3]));
        }
        fence_async_smem();
        __syncwarp();
        if (lane < 2) mbar_arrive_cluster(BAR(B_CONVD), lane);
        bar_arrive(3, 384);
        if (elect_one()) {
          bulk_store(p.yT + (size_t)d * 2048, pb, 4096);
          bulk_commit();
          bulk_wait0();
          red_relaxed_add(&g_cnt[(C_Y + (cta >> 4)) * 32], 1);
          TS(9);
        }
        __syncwarp();
        if (elect_one()) { wait_counter(&g_cnt[(C_Y + tj) * 32], (epoch + 1) * 64); TS(28); }
        __syncwarp();
        {
          const int cb = lane & 7, tb = warp * 4 + (lane >> 3);
          const uint4* src = (const uint4*)(p.yT + (size_t)(tj * 64 + cb * 8) * 2048 + ti * 128 + tb * 8);
          uint4 r[8];
#pragma unroll
          for (int j = 0; j < 8; ++j) r[j] = __ldcg(src + j * 256);
          uint4* dst = (uint4*)(p.out + (size_t)(ti * 128 + tb * 8) * 1024 + tj * 64 + cb * 8);
#pragma unroll
          for (int k = 0; k < 4; ++k) {
            auto el = [&](int j) { return k == 0 ? r[j].x : k == 1 ? r[j].y : k == 2 ? r[j].z : r[j].w; };
            dst[(2 * k) * 128] = make_uint4(__byte_perm(el(0), el(1), 0x5410), __byte_perm(el(2), el(3), 0x5410),
                                            __byte_perm(el(4), el(5), 0x5410), __byte_perm(el(6), el(7), 0x5410));
            dst[(2 * k + 1) * 128] = make_uint4(__byte_perm(el(0), el(1), 0x7632), __byte_perm(el(2), el(3), 0x7632),
                                                __byte_perm(el(4), el(5), 0x7632), __byte_perm(el(6), el(7), 0x7632));
          }
          if (lane == 0) TS(30);
        }
      }
    }
  } else if (warp < 12) {
    asm volatile("setmaxnreg.inc.sync.aligned.u32 160;");
    const int w8 = warp - 4;
    const int row = w8 * 16 + (lane & 7) + (((lane >> 3) & 1) << 3);
    {
      float acc[96];
#pragma unroll 1
      for (int ks = 0, s = 0, ph = 0; ks < 16; ++ks) {
        mbar_wait(BAR(B_FULL + s), ph);
        if (tid == 128 && !(ks & 1)) TSR(16, ks == 0 ? 16 : 9 + (ks >> 1) + (ks > 12 ? 43 : 0));
        const uint32_t st = sb + s * STG_BYTES;
        const uint32_t da = mkdesc(st + STG_X + (w8 >> 2) * 4096, 16);
        const uint32_t db = mkdesc(st + STG_W, 2048);
        wg_fence();
        wgmma_n192(acc, da, db, ks != 0);
        wgmma_n192(acc, da + 2, db + 384, 1);
        wg_commit();
        const uint32_t eprev = BAR(B_EMPTY + (s == 0 ? NSTG - 1 : s - 1));
        if (++s == NSTG) { s = 0; ph ^= 1; }
        if (ks > 0) {
          wg_wait<1>();
          if (lane < 2) mbar_arrive_cluster(eprev, lane);
        }
      }
      wg_wait<0>();
      bar_arrive(4, 480);
      if (tid == 128) TS(17);
      bar_sync(1, 256);
#pragma unroll
      for (int i = 0; i < 24; i += 2)
        stsm_x4(sb + SM_QS + row * 128 + (i >> 3) * 16384 + ((((i & 7) + (lane >> 4)) ^ (row & 7)) << 4),
                pack_bf16(acc[4 * i], acc[4 * i + 1]), pack_bf16(acc[4 * i + 2], acc[4 * i + 3]),
                pack_bf16(acc[4 * i + 4], acc[4 * i + 5]), pack_bf16(acc[4 * i + 6], acc[4 * i + 7]));
    }
    __syncwarp();
#pragma unroll 1
    for (int part = 1; part >= 0; --part) {
      const uint32_t pa = sb + SM_QS + part * 16384 + w8 * 2048 + lane * 16;
#pragma unroll 1
      for (int it = 0; it < 4; ++it) {
        uint4 t = lds128(pa + it * 512);
        uint32_t* tw = &t.x;
#pragma unroll
        for (int j = 0; j < 4; ++j) {
          const uint32_t x = tw[j];
          const __nv_bfloat162 xb = *reinterpret_cast<const __nv_bfloat162*>(&x);
          const uint32_t e = pack_bf16(ex2(bf_lo(x) * 1.4426950408889634f), ex2(bf_hi(x) * 1.4426950408889634f));
          const uint32_t m = __hgt2_mask(xb, __floats2bfloat162_rn(0.f, 0.f));
          tw[j] = badd((badd(x, 0x3f803f80u) & m) | (e & ~m), 0x35863586u);
        }
        sts128(pa + it * 512, t.x, t.y, t.z, t.w);
      }
      if (part == 1) {
        if (tid == 128) TS(53);
        bar_sync(1, 256);
        const int hh = w8 >> 1, dtile = w8 & 1;
        float kv[4] = {0.f, 0.f, 0.f, 0.f}, zz[4] = {0.f, 0.f, 0.f, 0.f};
        const int m = lane >> 3;
        const uint32_t aa = sb + SM_VS + ((lane & 7) + ((m >> 1) << 3)) * 128 + (((2 * hh + (m & 1)) ^ (lane & 7)) << 4);
        const uint32_t ab = sb + SM_PK + (lane & 15) * 128 + (((2 * hh + dtile) ^ (lane & 7)) << 4);
#pragma unroll 2
        for (int ks = 0; ks < 8; ++ks) {
          uint32_t a[4], b0, b1;
          ldsm_x4_t(a, aa + ks * 2048);
          ldsm_x2_t(b0, b1, ab + ks * 2048);
          mma_bf16(kv, a[0], a[1], a[2], a[3], b0, b1);
          mma_bf16(zz, 0x3f803f80u, 0x3f803f80u, 0x3f803f80u, 0x3f803f80u, b0, b1);
        }
        const uint32_t kp = sb + SM_KV + hh * 1088;
        sts128(kp + dtile * 512 + lane * 16, __float_as_uint(kv[0]), __float_as_uint(kv[1]), __float_as_uint(kv[2]),
               __float_as_uint(kv[3]));
        if (g == 0) sts_f32x2(kp + 1024 + dtile * 32 + q * 8, zz[0], zz[1]);
        fence_async_smem();
        __syncwarp();
        if (lane == 0) mbar_arrive(BAR(B_KVP));
        if (tid == 128) TS(55);
      }
    }
    if (tid == 128) TS(56);
    if (warp == 4) mbar_wait_long(BAR(B_KVF), 0);
    bar_sync(1, 256);
    if (tid == 128) TS(19);
#pragma unroll 1
    for (int h = 0; h < 4; ++h) {
      uint32_t a[4];
      const uint32_t qa = sb + SM_QS + row * 128 + (((2 * h + (lane >> 4)) ^ (row & 7)) << 4);
      ldsm_x4(a, qa);
      const uint32_t kp = sb + SM_KV + h * 1088;
      const uint4 k0 = lds128(kp + lane * 16), k1 = lds128(kp + 512 + lane * 16);
      const uint32_t za = kp + 1024 + q * 8;
      auto pk2 = [](uint32_t x, uint32_t y) { return pack_bf16(__uint_as_float(x), __uint_as_float(y)); };
      float n0[4] = {0.f, 0.f, 0.f, 0.f}, n1[4] = {0.f, 0.f, 0.f, 0.f}, dn[4] = {0.f, 0.f, 0.f, 0.f};
      mma_bf16(n0, a[0], a[1], a[2], a[3], pk2(k0.x, k0.y), pk2(k1.x, k1.y));
      mma_bf16(n1, a[0], a[1], a[2], a[3], pk2(k0.z, k0.w), pk2(k1.z, k1.w));
      mma_bf16(dn, a[0], a[1], a[2], a[3], pack_bf16(lds_f32(za), lds_f32(za + 4)), pack_bf16(lds_f32(za + 32), lds_f32(za + 36)));
      const uint32_t dd = pack_bf16(dn[0], dn[2]);
      const uint32_t d2 = pack_bf16(bf_lo(dd) + 1e-6f, bf_hi(dd) + 1e-6f);
      const float r0 = rcp(bf_lo(d2)), r1 = rcp(bf_hi(d2));
      const uint32_t x0 = pack_bf16(n0[0], n0[1]), x1 = pack_bf16(n0[2], n0[3]);
      const uint32_t x2 = pack_bf16(n1[0], n1[1]), x3 = pack_bf16(n1[2], n1[3]);
      stsm_x4(qa, pack_bf16(bf_lo(x0) * r0, bf_hi(x0) * r0), pack_bf16(bf_lo(x1) * r1, bf_hi(x1) * r1),
              pack_bf16(bf_lo(x2) * r0, bf_hi(x2) * r0), pack_bf16(bf_lo(x3) * r1, bf_hi(x3) * r1));
    }
    fence_async_smem();
    __syncwarp();
    if (lane == 0) mbar_arrive(BAR(B_OST));
    if (tid == 128) TS(57);
    if (warp == 4) mbar_wait_long(BAR(B_WO), 0);
    bar_sync(3, 384);
    {
      float o[32];
#pragma unroll 1
      for (int c = 0; c < 8; ++c) {
        mbar_wait_long(BAR(B_RF + c), 0);
        if (tid == 128) TSR(22, c == 0 ? 22 : 43 + c);
        const uint32_t slot = c < 4 ? SM_QS + c * 16384 : c < 7 ? SM_VV + (c - 4) * 16384 : SM_QS;
        const uint32_t da = mkdesc(sb + slot + (w8 >> 2) * 8192, 16);
        const uint32_t db = mkdesc(sb + SM_WO + c * 8192, 8192);
        wg_fence();
#pragma unroll
        for (int k = 0; k < 4; ++k) wgmma_n64(o, da + 2 * k, db + 128 * k, (c | k) != 0);
        wg_commit();
        if (c == 1) {
          wg_wait<1>();
          if (lane < 2) mbar_arrive_cluster(BAR(B_RE), lane);
        }
      }
      wg_wait<0>();
      if (tid == 128) TS(51);
      bar_sync(1, 256);
#pragma unroll
      for (int i = 0; i < 8; i += 2)
        stsm_x4(sb + SM_BOUT + row * 128 + (((i + (lane >> 4)) ^ (row & 7)) << 4), pack_bf16(o[4 * i], o[4 * i + 1]),
                pack_bf16(o[4 * i + 2], o[4 * i + 3]), pack_bf16(o[4 * i + 4], o[4 * i + 5]), pack_bf16(o[4 * i + 6], o[4 * i + 7]));
      fence_async_smem();
      bar_sync(1, 256);
      if (tid == 128) TS(52);
      if (warp == 4 && elect_one()) {
        tma_store_2d(&maps.out, sb + SM_BOUT, 512 + 64 * pj, 128 * pi);
        bulk_commit();
        bulk_wait_read0();
        TS(23);
      }
    }
  } else {
    asm volatile("setmaxnreg.dec.sync.aligned.u32 40;");
    if (warp == 12) {
      if (elect_one()) {
#pragma unroll 1
        for (int ks = NSTG, s = 0, ph = 0; ks < 16; ++ks) {
          mbar_wait(BAR(B_EMPTY + s), ph);
          issue_stage(ks, s);
          if (ks == NSTG) l2_prefetch((const char*)p.wo + (size_t)cta * 4096, 4096);
          if (++s == NSTG) { s = 0; ph ^= 1; }
        }
        mbar_wait(BAR(B_EMPTY + 6), 1);
        mbar_expect_tx(BAR(B_WO), 65536);
        tma_load_2d(sb + SM_WO, &maps.wo, pj * 64, 0, BAR(B_WO));
        tma_load_2d(sb + SM_WO + 32768, &maps.wo, pj * 64, 256, BAR(B_WO));
        float* kvg = &g_kv[epoch & 1][tj][0];
        mbar_wait_long(BAR(B_KVP), 0);
        bulk_reduce_add_f32(kvg, sb + SM_KV, 4352);
        bulk_commit();
        bulk_wait0();
        red_relaxed_add(&g_cnt[(C_KV + tj) * 32], 1);
        TS(18);
        wait_counter(&g_cnt[(C_KV + tj) * 32], (epoch + 1) * 16);
        mbar_expect_tx(BAR(B_KVF), 4352);
        bulk_load(sb + SM_KV, kvg, 4352, BAR(B_KVF));
        mbar_wait_long(BAR(B_OST), 0);
        tma_store_2d(&maps.o, sb + SM_QS, tj * 64, ti * 128);
        tma_store_2d(&maps.o, sb + SM_QS + 8192, tj * 64, ti * 128 + 64);
        bulk_commit();
        bulk_wait0();
        red_relaxed_add(&g_cnt[(C_O + ti) * 32], 1);
        TS(20);
        mbar_arrive_cluster(BAR(B_SLOT), 0);
        mbar_arrive_cluster(BAR(B_SLOT), 1);
        wait_counter(&g_cnt[(C_O + pi) * 32], (epoch + 1) * 8);
        if (cta == 0) g_epoch = epoch + 1;
        mbar_wait(BAR(B_SLOT), 0);
        TS(21);
#pragma unroll 1
        for (int c = 0; c < 8; ++c) {
          if (c == 4) mbar_wait_long(BAR(B_CONVD), 0);
          if (c == 7) mbar_wait(BAR(B_RE), 0);
          const uint32_t slot = c < 4 ? SM_QS + c * 16384 : c < 7 ? SM_VV + (c - 4) * 16384 : SM_QS;
          mbar_expect_tx(BAR(B_RF + c), 16384);
          tma_load_2d_mc(sb + slot + rank * 8192, &maps.o, c * 64, pi * 128 + rank * 64, BAR(B_RF + c), 3);
        }
      }
    } else if (warp == 13) {
      bar_sync(6, 160);
      sts128(sb + SM_U + (lane >> 4) * U_BYTES + (lane & 15) * 16, 0, 0, 0, 0);
      sts128(sb + SM_U + (2 + (lane >> 4)) * U_BYTES + (lane & 15) * 16, 0, 0, 0, 0);
      __syncwarp();
      if (elect_one()) {
        tma_store_2d(&maps.uT, sb + SM_P, ti * 128, tj * 64);
        tma_store_2d(&maps.uT, sb + SM_P + 8192, ti * 128 + 64, tj * 64);
        bulk_commit();
        bulk_wait_read0();
        mbar_arrive(BAR(B_PFREE));
        bulk_wait0();
        red_relaxed_add(&g_cnt[(C_U + tj) * 32], 1);
        TS(27);
        wait_counter(&g_cnt[(C_U + (cta >> 4)) * 32], (epoch + 1) * 16);
#pragma unroll 1
        for (int c = 0; c < 4; ++c) {
          mbar_expect_tx(BAR(B_UCH + c), 4096);
          bulk_load(sb + SM_U + c * U_BYTES + 256, p.uT + (size_t)(cta * 4 + c) * 2048, 4096, BAR(B_UCH + c));
        }
        TS(3);
      }
      __syncwarp();
      if (ti == 0) {
        float4* z = (float4*)&g_kv[(epoch & 1) ^ 1][tj][0];
#pragma unroll 1
        for (int i = lane; i < 272; i += 32) z[i] = make_float4(0.f, 0.f, 0.f, 0.f);
      }
    }
    if (warp >= 13) {
      bar_sync(4, 480);
      auto swz = [](int k, int pad) { const int r = (k >> 1) + pad; return (uint32_t)(r * 32 + (((k & 1) ^ ((r >> 2) & 1)) << 4)); };
      const uint32_t o0 = swz(lane - 3, 8), o1 = swz(lane - 2, 8), o2 = swz(lane - 1, 8), ow = swz(lane - 2, PADV);
      const uint32_t oz = swz(lane - 18, PADV);
#pragma unroll 1
      for (int item = warp - 13; item < 28; item += 3) {
        const int ch = item / 7, it = item - 7 * ch;
        const int k = -2 + 32 * it + lane;
        const uint32_t ua = sb + SM_U + ch * U_BYTES + it * 512, vb = sb + SM_VV + ch * VV_BYTES;
        const uint32_t a0 = ua + o0, a1 = ua + o1, a2 = ua + o2, aw = vb + it * 512 + ow;
        mbar_wait_long(BAR(B_UCH + ch), 0);
        if (it == 0 && lane < 16) {
          sts128(vb + oz + VV_U3, 0, 0, 0, 0); sts128(vb + oz + VV_U5, 0, 0, 0, 0);
          sts128(vb + oz + VV_U7, 0, 0, 0, 0); sts128(vb + oz + VV_U9, 0, 0, 0, 0);
        }
        const uint4 t0 = lds128(a0), t1 = lds128(a1), t2 = lds128(a2);
        const uint32_t E[12] = {t0.x, t0.y, t0.z, t0.w, t1.x, t1.y, t1.z, t1.w, t2.x, t2.y, t2.z, t2.w};
        uint32_t O[8];
#pragma unroll
        for (int j = 0; j < 8; ++j) O[j] = __byte_perm(E[j + 1], E[j + 2], 0x5432);
        uint32_t s3[6], s5[4], s7[4], s9[4];
#pragma unroll
        for (int j = 0; j < 6; ++j) s3[j] = badd(badd(O[j], O[j + 1]), E[j + 2]);
#pragma unroll
        for (int j = 0; j < 4; ++j) {
          s5[j] = badd(s3[j + 2], badd(E[j + 3], E[j + 5]));
          s7[j] = badd(s5[j], badd(O[j + 1], O[j + 4]));
          s9[j] = badd(s7[j], badd(E[j + 2], E[j + 6]));
        }
        if (k < 208) { sts128(aw + VV_U3, s3[0], s3[1], s3[2], s3[3]); sts128(aw + VV_U5, s5[0], s5[1], s5[2], s5[3]); }
        if (k < 144) { sts128(aw + VV_U7, s7[0], s7[1], s7[2], s7[3]); sts128(aw + VV_U9, s9[0], s9[1], s9[2], s9[3]); }
      }
      if (tid == 416) TS(6);
      bar_arrive(5, 224);
    }
  }
  __syncwarp();
  cluster_arrive();
  cluster_wait();
  if (tid == 0) TS(31);
#undef BAR
}

typedef CUresult (*EncodeFn)(CUtensorMap*, CUtensorMapDataType, cuuint32_t, void*, const cuuint64_t*, const cuuint64_t*,
                             const cuuint32_t*, const cuuint32_t*, CUtensorMapInterleave, CUtensorMapSwizzle,
                             CUtensorMapL2promotion, CUtensorMapFloatOOBfill);

static void make_map(EncodeFn enc, CUtensorMap* m, const void* base, uint64_t inner, uint64_t outer, uint32_t box_in,
                     uint32_t box_out, CUtensorMapSwizzle swz = CU_TENSOR_MAP_SWIZZLE_128B) {
  cuuint64_t gd[2] = {inner, outer};
  cuuint64_t gs[1] = {inner * 2};
  cuuint32_t bd[2] = {box_in, box_out};
  cuuint32_t es[2] = {1, 1};
  enc(m, CU_TENSOR_MAP_DATA_TYPE_BFLOAT16, 2, const_cast<void*>(base), gd, gs, bd, es, CU_TENSOR_MAP_INTERLEAVE_NONE,
      swz, CU_TENSOR_MAP_L2_PROMOTION_L2_128B, CU_TENSOR_MAP_FLOAT_OOB_FILL_NONE);
}

}

extern "C" void kernel_launch(void* const* d_in, const int* in_sizes, int n_in, void* d_out, int out_size) {
  using namespace s4la;
  (void)in_sizes; (void)n_in; (void)out_size;
  static EncodeFn enc = nullptr;
  static void *uT = nullptr, *yT = nullptr, *oS = nullptr;
  if (!enc) {
    void* fn = nullptr;
    cudaDriverEntryPointQueryResult qr;
    cudaGetDriverEntryPoint("cuTensorMapEncodeTiled", &fn, cudaEnableDefault, &qr);
    enc = (EncodeFn)fn;
    cudaGetSymbolAddress(&uT, g_uT);
    cudaGetSymbolAddress(&yT, g_yT);
    cudaGetSymbolAddress(&oS, g_o);
    cudaFuncSetAttribute(fused_kernel, cudaFuncAttributeMaxDynamicSharedMemorySize, SM_TOTAL);
  }
  const __nv_bfloat16* const* in = (const __nv_bfloat16* const*)d_in;
  Maps maps;
  make_map(enc, &maps.x, in[9], 512, 2048, 32, 128, CU_TENSOR_MAP_SWIZZLE_64B);
  {
    cuuint64_t gd[3] = {512, 512, 3};
    cuuint64_t gs[2] = {3072, 1024};
    cuuint32_t bd[3] = {64, 16, 3};
    cuuint32_t es[3] = {1, 1, 1};
    enc(&maps.w, CU_TENSOR_MAP_DATA_TYPE_BFLOAT16, 3, const_cast<__nv_bfloat16*>(in[10]), gd, gs, bd, es,
        CU_TENSOR_MAP_INTERLEAVE_NONE, CU_TENSOR_MAP_SWIZZLE_128B, CU_TENSOR_MAP_L2_PROMOTION_L2_128B,
        CU_TENSOR_MAP_FLOAT_OOB_FILL_NONE);
  }
  make_map(enc, &maps.wo, in[11], 512, 512, 64, 256);
  make_map(enc, &maps.u, in[0], 512, 2048, 64, 128);
  make_map(enc, &maps.uT, uT, 2048, 512, 64, 64);
  make_map(enc, &maps.o, oS, 512, 2048, 64, 64);
  make_map(enc, &maps.out, d_out, 1024, 2048, 64, 128);
  Ptrs p;
  p.A_re = in[1]; p.A_im = in[2]; p.B_re = in[3]; p.B_im = in[4]; p.C_re = in[5]; p.C_im = in[6];
  p.log_dt = in[7]; p.Dskip = in[8]; p.x = in[9]; p.wqkv = in[10]; p.wo = in[11];
  p.uT = (__nv_bfloat16*)uT; p.yT = (__nv_bfloat16*)yT; p.out = (__nv_bfloat16*)d_out;
  fused_kernel<<<NCTA, NTHREADS, SM_TOTAL, cudaStreamPerThread>>>(maps, p);
}
```

```cpp
#include <cuda_runtime.h>
#include <cuda_bf16.h>
#include <cuda_fp16.h>
#include <cuda.h>
#include <stdint.h>

#define DEVI __device__ __forceinline__

namespace s4la {

constexpr int NTHREADS = 512;
constexpr int NCTA = 128;

constexpr int NSTG = 7;
constexpr uint32_t STG_BYTES = 20480, STG_X = 0, STG_W = 8192;
constexpr uint32_t SM_QS = 0;
constexpr uint32_t SM_PK = SM_QS + 16384, SM_VS = SM_QS + 32768;
constexpr uint32_t SM_WO = 65536;
constexpr uint32_t SM_KV = 131072;
constexpr uint32_t SM_BOUT = 16384;
constexpr uint32_t SM_U = 143360, U_BYTES = 4352;
constexpr uint32_t SM_P = 160768, P_BYTES = 4096;
constexpr uint32_t SM_VV = 177152, VV_BYTES = 12800;
constexpr uint32_t VV_U5 = 0, VV_U3 = 3712, VV_U9 = 7424, VV_U7 = 10112;
constexpr uint32_t KG_BYTES = 3200;
constexpr uint32_t SM_BAR = SM_VV + 4 * VV_BYTES;
constexpr uint32_t SM_PTAB = SM_BAR + 320;
constexpr uint32_t SM_TOTAL = SM_PTAB + 2048;
static_assert(SM_TOTAL <= 232448, "shared memory");
constexpr int PADV = 12;

enum { B_FULL = 0, B_EMPTY = 7, B_TILE = 14, B_UCH = 15, B_KVP = 19, B_KVF = 20, B_OST = 21, B_RF = 22, B_WO = 30, B_RE = 31, B_PFREE = 32, B_CONVD = 33, B_SLOT = 34, B_COUNT = 35 };
__host__ __device__ constexpr int bar_count(int i) {
  return (i >= B_EMPTY && i < B_TILE) ? 16 : (i == B_KVP || i == B_OST || i == B_CONVD) ? 8 : i == B_RE ? 16 : i == B_SLOT ? 2 : 1;
}

constexpr int PD_OFF = 0, P2_OFF = 544, P3_OFF = 768;

constexpr int SL_K2048 = 20, SL_ZERO = 21, SL_510 = 22, SL_0 = 23;
__host__ __device__ constexpr int koff(int y) {
  return y < 8 ? y : y < 12 ? 256 + 2 * (y - 8) : y < 16 ? 512 + 256 * ((y - 12) >> 1) + 4 * (y & 1) : 1024 + 256 * (y - 16);
}
__host__ __device__ constexpr int kidx_c(int l) {
  const int y = l < 256 ? (l & 7) : l < 512 ? 8 + ((l & 7) >> 1) : l < 1024 ? 12 + (((l - 512) >> 8) << 1) + ((l >> 2) & 1)
                                                                            : 16 + ((l - 1024) >> 8);
  return ((l >> 3) & 31) * 24 + y;
}
constexpr int slot_direct(int l) {
  if (l < 0 || l > 510) return SL_ZERO;
  if (l == 510) return SL_510;
  if (l == 0) return SL_0;
  return kidx_c(l < 256 ? l : ((l + ((l >> 1) & 1)) & ~1));
}
constexpr int slot_seg2(int v, int k) { return (k >= 32 && k < 64) ? kidx_c(16 * k + 4 * v) : SL_ZERO; }
constexpr int slot_seg3(int pi, int k) {
  return (k >= 64 && k < 128) ? kidx_c(16 * k + 8 * pi) : ((k == 128 && pi == 0) ? SL_K2048 : SL_ZERO);
}
constexpr int slot_word(int w) {
  return w < 0 ? SL_ZERO : w < 544 ? slot_direct(w - 16) : w < 768 ? slot_seg2((w - 544) / 56, 16 + (w - 544) % 56)
       : w < 944 ? slot_seg3((w - 768) / 88, 48 + (w - 768) % 88) : SL_ZERO;
}
struct PTab { uint32_t v[512]; };
constexpr PTab make_ptab() {
  PTab t{};
  for (int lane = 0; lane < 32; ++lane)
    for (int i = 0; i < 16; ++i)
      t.v[i * 32 + lane] = (slot_word(31 * lane - 1 + 2 * i) * 4) | ((slot_word(31 * lane + 2 * i) * 4) << 16);
  return t;
}
__device__ const PTab g_ptab = make_ptab();

__device__ __nv_bfloat16 g_uT[512 * 2048];
__device__ __nv_bfloat16 g_yT[512 * 2048];
__device__ __nv_bfloat16 g_o[2048 * 512];
__device__ float g_kv[2][8][4 * 272];
__device__ unsigned g_cnt[64 * 32];
__device__ unsigned g_epoch;
#define TS(slot) do { } while (0)
#define TSR(on, slot) do { } while (0)
#define TSD(slot) do { } while (0)
enum { C_U = 0, C_KV = 8, C_O = 16, C_Y = 32 };

struct Maps {
  CUtensorMap x, w, wo, u, uT, yT, o, out;
};
struct Ptrs {
  const __nv_bfloat16 *A_re, *A_im, *B_re, *B_im, *C_re, *C_im, *log_dt, *Dskip;
  const __nv_bfloat16 *x, *wqkv, *wo;
  __nv_bfloat16 *uT, *yT;
};

DEVI uint32_t s2u(const void* p) { return (uint32_t)__cvta_generic_to_shared(p); }
DEVI void mbar_init(uint32_t b, uint32_t c) { asm volatile("mbarrier.init.shared::cta.b64 [%0], %1;" ::"r"(b), "r"(c) : "memory"); }
DEVI void mbar_expect_tx(uint32_t b, uint32_t bytes) {
  asm volatile("mbarrier.arrive.expect_tx.shared::cta.b64 _, [%0], %1;" ::"r"(b), "r"(bytes) : "memory");
}
DEVI void mbar_arrive(uint32_t b) { asm volatile("mbarrier.arrive.shared::cta.b64 _, [%0];" ::"r"(b) : "memory"); }
DEVI void mbar_arrive_cluster(uint32_t b, uint32_t cta) {
  asm volatile("{\n.reg .b32 r;\nmapa.shared::cluster.u32 r, %0, %1;\nmbarrier.arrive.shared::cluster.b64 _, [r];\n}"
               ::"r"(b), "r"(cta) : "memory");
}
DEVI void mbar_wait(uint32_t b, uint32_t parity) {
  asm volatile("{\n.reg .pred p;\nLAB_WAIT:\nmbarrier.try_wait.parity.shared::cta.b64 p, [%0], %1;\n@!p bra LAB_WAIT;\n}"
               ::"r"(b), "r"(parity) : "memory");
}
DEVI void mbar_wait_long(uint32_t b, uint32_t parity) {
  asm volatile("{\n.reg .pred p;\nLAB_WAIT:\nmbarrier.try_wait.parity.shared::cta.b64 p, [%0], %1, 0x989680;\n@!p bra LAB_WAIT;\n}"
               ::"r"(b), "r"(parity) : "memory");
}
DEVI void bar_sync(int id, int n) { asm volatile("bar.sync %0, %1;" ::"r"(id), "r"(n) : "memory"); }
DEVI void bar_arrive(int id, int n) { asm volatile("bar.arrive %0, %1;" ::"r"(id), "r"(n) : "memory"); }
DEVI void fence_async_smem() { asm volatile("fence.proxy.async.shared::cta;" ::: "memory"); }
DEVI void fence_async_all() { asm volatile("fence.proxy.async;" ::: "memory"); }
DEVI void cluster_arrive() { asm volatile("barrier.cluster.arrive.relaxed.aligned;" ::: "memory"); }
DEVI void cluster_wait() { asm volatile("barrier.cluster.wait.aligned;" ::: "memory"); }

DEVI void tma_load_2d(uint32_t dst, const CUtensorMap* m, int c0, int c1, uint32_t bar) {
  asm volatile("cp.async.bulk.tensor.2d.shared::cluster.global.mbarrier::complete_tx::bytes [%0], [%1, {%3, %4}], [%2];"
               ::"r"(dst), "l"(m), "r"(bar), "r"(c0), "r"(c1) : "memory");
}
DEVI void tma_load_2d_mc(uint32_t dst, const CUtensorMap* m, int c0, int c1, uint32_t bar, uint16_t mask) {
  asm volatile("cp.async.bulk.tensor.2d.shared::cluster.global.mbarrier::complete_tx::bytes.multicast::cluster [%0], [%1, {%3, %4}], [%2], %5;"
               ::"r"(dst), "l"(m), "r"(bar), "r"(c0), "r"(c1), "h"(mask) : "memory");
}
DEVI void tma_load_3d_mc(uint32_t dst, const CUtensorMap* m, int c0, int c1, int c2, uint32_t bar, uint16_t mask) {
  asm volatile("cp.async.bulk.tensor.3d.shared::cluster.global.mbarrier::complete_tx::bytes.multicast::cluster [%0], [%1, {%3, %4, %5}], [%2], %6;"
               ::"r"(dst), "l"(m), "r"(bar), "r"(c0), "r"(c1), "r"(c2), "h"(mask) : "memory");
}
DEVI void tma_store_2d(const CUtensorMap* m, uint32_t src, int c0, int c1) {
  asm volatile("cp.async.bulk.tensor.2d.global.shared::cta.bulk_group [%0, {%2, %3}], [%1];"
               ::"l"(m), "r"(src), "r"(c0), "r"(c1) : "memory");
}
DEVI void bulk_load(uint32_t dst, const void* src, uint32_t bytes, uint32_t bar) {
  asm volatile("cp.async.bulk.shared::cluster.global.mbarrier::complete_tx::bytes [%0], [%1], %2, [%3];"
               ::"r"(dst), "l"(src), "r"(bytes), "r"(bar) : "memory");
}
DEVI void bulk_store(void* dst, uint32_t src, uint32_t bytes) {
  asm volatile("cp.async.bulk.global.shared::cta.bulk_group [%0], [%1], %2;" ::"l"(dst), "r"(src), "r"(bytes) : "memory");
}
DEVI void bulk_reduce_add_f32(void* dst, uint32_t src, uint32_t bytes) {
  asm volatile("cp.reduce.async.bulk.global.shared::cta.bulk_group.add.f32 [%0], [%1], %2;" ::"l"(dst), "r"(src), "r"(bytes) : "memory");
}
DEVI void bulk_commit() { asm volatile("cp.async.bulk.commit_group;" ::: "memory"); }
DEVI void bulk_wait0() { asm volatile("cp.async.bulk.wait_group 0;" ::: "memory"); }
DEVI void bulk_wait_read0() { asm volatile("cp.async.bulk.wait_group.read 0;" ::: "memory"); }
DEVI void l2_prefetch(const void* p, uint32_t bytes) {
  asm volatile("cp.async.bulk.prefetch.L2.global [%0], %1;" ::"l"(p), "r"(bytes) : "memory");
}
DEVI void prefetch_tmap(const CUtensorMap* m) { asm volatile("prefetch.tensormap [%0];" ::"l"(m) : "memory"); }

DEVI void red_release_add(unsigned* p, unsigned v) {
  asm volatile("red.release.gpu.global.add.u32 [%0], %1;" ::"l"(p), "r"(v) : "memory");
}
DEVI void red_relaxed_add(unsigned* p, unsigned v) {
  asm volatile("red.relaxed.gpu.global.add.u32 [%0], %1;" ::"l"(p), "r"(v) : "memory");
}
DEVI unsigned ld_relaxed(const unsigned* p) {
  unsigned v;
  asm volatile("ld.relaxed.gpu.global.u32 %0, [%1];" : "=r"(v) : "l"(p) : "memory");
  return v;
}
DEVI void wait_counter(const unsigned* p, unsigned target) {
#pragma unroll 1
  for (int it = 0; (int)(ld_relaxed(p) - target) < 0; ++it)
    if (it > (1 << 22)) __trap();
}

DEVI void ldsm_x4(uint32_t (&r)[4], uint32_t a) {
  asm volatile("ldmatrix.sync.aligned.m8n8.x4.shared.b16 {%0,%1,%2,%3}, [%4];"
               : "=r"(r[0]), "=r"(r[1]), "=r"(r[2]), "=r"(r[3]) : "r"(a) : "memory");
}
DEVI void ldsm_x4_t(uint32_t (&r)[4], uint32_t a) {
  asm volatile("ldmatrix.sync.aligned.m8n8.x4.trans.shared.b16 {%0,%1,%2,%3}, [%4];"
               : "=r"(r[0]), "=r"(r[1]), "=r"(r[2]), "=r"(r[3]) : "r"(a) : "memory");
}
DEVI void ldsm_x2_t(uint32_t& r0, uint32_t& r1, uint32_t a) {
  asm volatile("ldmatrix.sync.aligned.m8n8.x2.trans.shared.b16 {%0,%1}, [%2];" : "=r"(r0), "=r"(r1) : "r"(a) : "memory");
}
DEVI void stsm_x4(uint32_t a, uint32_t r0, uint32_t r1, uint32_t r2, uint32_t r3) {
  asm volatile("stmatrix.sync.aligned.m8n8.x4.shared.b16 [%0], {%1,%2,%3,%4};"
               ::"r"(a), "r"(r0), "r"(r1), "r"(r2), "r"(r3) : "memory");
}
DEVI void stsm_x4_t(uint32_t a, uint32_t r0, uint32_t r1, uint32_t r2, uint32_t r3) {
  asm volatile("stmatrix.sync.aligned.m8n8.x4.trans.shared.b16 [%0], {%1,%2,%3,%4};"
               ::"r"(a), "r"(r0), "r"(r1), "r"(r2), "r"(r3) : "memory");
}
DEVI uint32_t lds32(uint32_t a) { uint32_t v; asm volatile("ld.shared.b32 %0, [%1];" : "=r"(v) : "r"(a) : "memory"); return v; }
DEVI float lds_f32(uint32_t a) { float v; asm volatile("ld.shared.f32 %0, [%1];" : "=f"(v) : "r"(a) : "memory"); return v; }
DEVI void sts32(uint32_t a, uint32_t v) { asm volatile("st.shared.b32 [%0], %1;" ::"r"(a), "r"(v) : "memory"); }
DEVI void sts_f32(uint32_t a, float v) { asm volatile("st.shared.f32 [%0], %1;" ::"r"(a), "f"(v) : "memory"); }
DEVI void sts_f32x2(uint32_t a, float x, float y) { asm volatile("st.shared.v2.f32 [%0], {%1,%2};" ::"r"(a), "f"(x), "f"(y) : "memory"); }
DEVI uint4 lds128(uint32_t a) {
  uint4 v;
  asm volatile("ld.shared.v4.b32 {%0,%1,%2,%3}, [%4];" : "=r"(v.x), "=r"(v.y), "=r"(v.z), "=r"(v.w) : "r"(a) : "memory");
  return v;
}
DEVI void sts128(uint32_t a, uint32_t x, uint32_t y, uint32_t z, uint32_t w) {
  asm volatile("st.shared.v4.b32 [%0], {%1,%2,%3,%4};" ::"r"(a), "r"(x), "r"(y), "r"(z), "r"(w) : "memory");
}

DEVI void mma_bf16(float (&d)[4], uint32_t a0, uint32_t a1, uint32_t a2, uint32_t a3, uint32_t b0, uint32_t b1) {
  asm("mma.sync.aligned.m16n8k16.row.col.f32.bf16.bf16.f32 {%0,%1,%2,%3}, {%4,%5,%6,%7}, {%8,%9}, {%0,%1,%2,%3};"
      : "+f"(d[0]), "+f"(d[1]), "+f"(d[2]), "+f"(d[3])
      : "r"(a0), "r"(a1), "r"(a2), "r"(a3), "r"(b0), "r"(b1));
}
DEVI void mma_f16(float (&d)[4], const uint32_t (&a)[4], uint32_t b0, uint32_t b1) {
  asm("mma.sync.aligned.m16n8k16.row.col.f32.f16.f16.f32 {%0,%1,%2,%3}, {%4,%5,%6,%7}, {%8,%9}, {%0,%1,%2,%3};"
      : "+f"(d[0]), "+f"(d[1]), "+f"(d[2]), "+f"(d[3])
      : "r"(a[0]), "r"(a[1]), "r"(a[2]), "r"(a[3]), "r"(b0), "r"(b1));
}
DEVI void mma_bf16v(float (&d)[4], const uint32_t (&a)[4], uint32_t b0, uint32_t b1) {
  asm volatile("mma.sync.aligned.m16n8k16.row.col.f32.bf16.bf16.f32 {%0,%1,%2,%3}, {%4,%5,%6,%7}, {%8,%9}, {%0,%1,%2,%3};"
               : "+f"(d[0]), "+f"(d[1]), "+f"(d[2]), "+f"(d[3])
               : "r"(a[0]), "r"(a[1]), "r"(a[2]), "r"(a[3]), "r"(b0), "r"(b1));
}
DEVI uint32_t pack_bf16(float lo, float hi) {
  uint32_t r;
  asm("cvt.rn.bf16x2.f32 %0, %1, %2;" : "=r"(r) : "f"(hi), "f"(lo));
  return r;
}
DEVI uint32_t pack_f16(float lo, float hi) {
  uint32_t r;
  asm("cvt.rn.f16x2.f32 %0, %1, %2;" : "=r"(r) : "f"(hi), "f"(lo));
  return r;
}
DEVI uint32_t ldg16(const __nv_bfloat16* p) {
  uint32_t v;
  asm volatile("ld.global.nc.u16 %0, [%1];" : "=r"(v) : "l"(p));
  return v;
}
DEVI bool elect_one() {
  uint32_t pred;
  asm volatile("{\n.reg .pred p;\nelect.sync _|p, 0xffffffff;\nselp.u32 %0, 1, 0, p;\n}" : "=r"(pred));
  return pred != 0;
}
DEVI float bf_lo(uint32_t v) { return __uint_as_float(v << 16); }
DEVI float bf_hi(uint32_t v) { return __uint_as_float(v & 0xffff0000u); }
DEVI float bf2f(__nv_bfloat16 v) { return __bfloat162float(v); }
DEVI float round_bf16(float v) { return __bfloat162float(__float2bfloat16_rn(v)); }
DEVI float rcp(float x) { float r; asm("rcp.approx.ftz.f32 %0, %1;" : "=f"(r) : "f"(x)); return r; }
DEVI float ex2(float x) { float r; asm("ex2.approx.ftz.f32 %0, %1;" : "=f"(r) : "f"(x)); return r; }

DEVI void wg_fence() { asm volatile("wgmma.fence.sync.aligned;" ::: "memory"); }
DEVI void wg_commit() { asm volatile("wgmma.commit_group.sync.aligned;" ::: "memory"); }
template <int N> DEVI void wg_wait() { asm volatile("wgmma.wait_group.sync.aligned %0;" ::"n"(N) : "memory"); }
constexpr uint32_t DESC_HI = (1u << 30) | (1024 >> 4);
constexpr uint32_t DESC_HI64 = (2u << 30) | (512 >> 4);
DEVI uint32_t mkdesc(uint32_t saddr, uint32_t lbo) { return ((saddr & 0x3FFFF) >> 4) | ((lbo >> 4) << 16); }

#define R8(b) "%" #b
DEVI void wgmma_n192(float (&d)[96], uint32_t da, uint32_t db, int scale_d) {
  asm volatile(
      "{\n.reg .pred p;\n.reg .b64 da, db;\nsetp.ne.b32 p, %98, 0;\nmov.b64 da, {%96, %100};\nmov.b64 db, {%97, %99};\n"
      "wgmma.mma_async.sync.aligned.m64n192k16.f32.bf16.bf16 "
      "{%0,%1,%2,%3,%4,%5,%6,%7,%8,%9,%10,%11,%12,%13,%14,%15,"
      "%16,%17,%18,%19,%20,%21,%22,%23,%24,%25,%26,%27,%28,%29,%30,%31,"
      "%32,%33,%34,%35,%36,%37,%38,%39,%40,%41,%42,%43,%44,%45,%46,%47,"
      "%48,%49,%50,%51,%52,%53,%54,%55,%56,%57,%58,%59,%60,%61,%62,%63,"
      "%64,%65,%66,%67,%68,%69,%70,%71,%72,%73,%74,%75,%76,%77,%78,%79,"
      "%80,%81,%82,%83,%84,%85,%86,%87,%88,%89,%90,%91,%92,%93,%94,%95}, "
      "da, db, p, 1, 1, 0, 1;\n}"
      : "+f"(d[0]), "+f"(d[1]), "+f"(d[2]), "+f"(d[3]), "+f"(d[4]), "+f"(d[5]), "+f"(d[6]), "+f"(d[7]),
        "+f"(d[8]), "+f"(d[9]), "+f"(d[10]), "+f"(d[11]), "+f"(d[12]), "+f"(d[13]), "+f"(d[14]), "+f"(d[15]),
        "+f"(d[16]), "+f"(d[17]), "+f"(d[18]), "+f"(d[19]), "+f"(d[20]), "+f"(d[21]), "+f"(d[22]), "+f"(d[23]),
        "+f"(d[24]), "+f"(d[25]), "+f"(d[26]), "+f"(d[27]), "+f"(d[28]), "+f"(d[29]), "+f"(d[30]), "+f"(d[31]),
        "+f"(d[32]), "+f"(d[33]), "+f"(d[34]), "+f"(d[35]), "+f"(d[36]), "+f"(d[37]), "+f"(d[38]), "+f"(d[39]),
        "+f"(d[40]), "+f"(d[41]), "+f"(d[42]), "+f"(d[43]), "+f"(d[44]), "+f"(d[45]), "+f"(d[46]), "+f"(d[47]),
        "+f"(d[48]), "+f"(d[49]), "+f"(d[50]), "+f"(d[51]), "+f"(d[52]), "+f"(d[53]), "+f"(d[54]), "+f"(d[55]),
        "+f"(d[56]), "+f"(d[57]), "+f"(d[58]), "+f"(d[59]), "+f"(d[60]), "+f"(d[61]), "+f"(d[62]), "+f"(d[63]),
        "+f"(d[64]), "+f"(d[65]), "+f"(d[66]), "+f"(d[67]), "+f"(d[68]), "+f"(d[69]), "+f"(d[70]), "+f"(d[71]),
        "+f"(d[72]), "+f"(d[73]), "+f"(d[74]), "+f"(d[75]), "+f"(d[76]), "+f"(d[77]), "+f"(d[78]), "+f"(d[79]),
        "+f"(d[80]), "+f"(d[81]), "+f"(d[82]), "+f"(d[83]), "+f"(d[84]), "+f"(d[85]), "+f"(d[86]), "+f"(d[87]),
        "+f"(d[88]), "+f"(d[89]), "+f"(d[90]), "+f"(d[91]), "+f"(d[92]), "+f"(d[93]), "+f"(d[94]), "+f"(d[95])
      : "r"(da), "r"(db), "r"(scale_d), "n"(DESC_HI), "n"(DESC_HI64));
}
DEVI void wgmma_n64(float (&d)[32], uint32_t da, uint32_t db, int scale_d) {
  asm volatile(
      "{\n.reg .pred p;\n.reg .b64 da, db;\nsetp.ne.b32 p, %34, 0;\nmov.b64 da, {%32, %35};\nmov.b64 db, {%33, %35};\n"
      "wgmma.mma_async.sync.aligned.m64n64k16.f32.bf16.bf16 "
      "{%0,%1,%2,%3,%4,%5,%6,%7,%8,%9,%10,%11,%12,%13,%14,%15,"
      "%16,%17,%18,%19,%20,%21,%22,%23,%24,%25,%26,%27,%28,%29,%30,%31}, "
      "da, db, p, 1, 1, 0, 1;\n}"
      : "+f"(d[0]), "+f"(d[1]), "+f"(d[2]), "+f"(d[3]), "+f"(d[4]), "+f"(d[5]), "+f"(d[6]), "+f"(d[7]),
        "+f"(d[8]), "+f"(d[9]), "+f"(d[10]), "+f"(d[11]), "+f"(d[12]), "+f"(d[13]), "+f"(d[14]), "+f"(d[15]),
        "+f"(d[16]), "+f"(d[17]), "+f"(d[18]), "+f"(d[19]), "+f"(d[20]), "+f"(d[21]), "+f"(d[22]), "+f"(d[23]),
        "+f"(d[24]), "+f"(d[25]), "+f"(d[26]), "+f"(d[27]), "+f"(d[28]), "+f"(d[29]), "+f"(d[30]), "+f"(d[31])
      : "r"(da), "r"(db), "r"(scale_d), "n"(DESC_HI));
}

struct C32 { float re, im; };
DEVI C32 csq(C32 a) { return {a.re * a.re - a.im * a.im, 2.f * a.re * a.im}; }
DEVI C32 cmul(C32 a, C32 b) { return {a.re * b.re - a.im * b.im, a.re * b.im + a.im * b.re}; }
DEVI C32 cfresh(float zl, float zi, float m) {
  float mag = ex2(zl * m), ph = zi * m;
  return {mag * __cosf(ph), mag * __sinf(ph)};
}
struct HMul { uint32_t b, bp; };
DEVI HMul mk_mul(float re, float im) { return {pack_f16(re, im), pack_f16(-im, re)}; }
DEVI uint32_t hcmul(uint32_t a, const HMul& m) {
  __half2 ah = *reinterpret_cast<__half2*>(&a);
  __half2 b = *reinterpret_cast<const __half2*>(&m.b), bp = *reinterpret_cast<const __half2*>(&m.bp);
  __half2 r = __hfma2(__high2half2(ah), bp, __hmul2(__low2half2(ah), b));
  return *reinterpret_cast<uint32_t*>(&r);
}
DEVI uint32_t badd(uint32_t a, uint32_t b) {
  __nv_bfloat162 r = __hadd2(*reinterpret_cast<__nv_bfloat162*>(&a), *reinterpret_cast<__nv_bfloat162*>(&b));
  return *reinterpret_cast<uint32_t*>(&r);
}
template <int MU0, int NMU, int DMAX>
DEVI void conv_tail(float (&acc)[16][4], uint32_t p_lane, uint32_t v_base, int back, bool edge, int lane) {
  const int hsel = (lane >> 3) & 1;
  const int row = (lane & 7) + ((lane >> 4) << 3) + PADV - 8 - (back & (hsel ^ 1));
  const uint32_t la = v_base + row * 32 + (((hsel ^ back) ^ ((row >> 2) & 1)) << 4);
  uint32_t M[3][4];
  ldsm_x4_t(M[0], la);
  ldsm_x4_t(M[1], la + 256);
  uint32_t H[2 * NMU];
#pragma unroll
  for (int i = 0; i < 2 * NMU; ++i) H[i ^ 1] = lds32(p_lane + (uint32_t)(MU0 - 1 + i) * 32);
  if (edge) {
    const uint32_t a[4] = {0u, 0u, M[0][0], M[0][1]};
#pragma unroll
    for (int k = 1; k < NMU; ++k) mma_bf16v(acc[MU0 - 2 + 2 * k], a, H[2 * k], H[2 * k + 1]);
  }
#pragma unroll
  for (int delta = -1; delta <= DMAX; ++delta) {
    if (delta + 2 <= DMAX) ldsm_x4_t(M[(delta + 3) % 3], la + (delta + 3) * 256);
#pragma unroll
    for (int k = 0; k < NMU; ++k)
      if (delta + MU0 + 2 * k < 16) mma_bf16v(acc[delta + MU0 + 2 * k], M[(delta + 1) % 3], H[2 * k], H[2 * k + 1]);
  }
}

__global__ void __cluster_dims__(2, 1, 1) __launch_bounds__(NTHREADS, 1)
fused_kernel(const __grid_constant__ Maps maps, const Ptrs p) {
  extern __shared__ __align__(1024) uint8_t smem[];
  const uint32_t sb = s2u(smem);
  const int tid = threadIdx.x, lane = tid & 31;
  const int warp = __shfl_sync(0xffffffffu, tid >> 5, 0);
  const int cta = blockIdx.x;
  const uint32_t rank = cta & 1;
  const int ti = 2 * (cta >> 4) + rank;
  const int tj = (cta >> 1) & 7;
  const int pi = cta >> 3, pj = cta & 7;
  const uint32_t bars = sb + SM_BAR;
#define BAR(i) (bars + 8 * (i))
  const int g = lane >> 2, q = lane & 3;

  auto issue_stage = [&](int ks, int s) {
    const uint32_t st = sb + s * STG_BYTES, fb = BAR(B_FULL + s);
    mbar_expect_tx(fb, STG_BYTES);
    tma_load_2d(st + STG_X, &maps.x, ks * 32, ti * 128, fb);
    tma_load_3d_mc(st + STG_W + rank * 6144, &maps.w, tj * 64, ks * 32 + rank * 16, 0, fb, 3);
  };

  const int kch = warp & 3, krd = warp >> 2;
  float zr, zi, wr, wi;
  unsigned epoch;
  uint32_t r_dskip;
  {
    const size_t po = (size_t)(cta * 4 + kch) * 128 + krd * 32 + lane;
    const uint32_t r_ar = ldg16(p.A_re + po), r_ai = ldg16(p.A_im + po), r_br = ldg16(p.B_re + po), r_bi = ldg16(p.B_im + po);
    const uint32_t r_cr = ldg16(p.C_re + po), r_ci = ldg16(p.C_im + po), r_ldt = ldg16(p.log_dt + cta * 4 + kch);
    epoch = __ldcg(&g_epoch);
    r_dskip = ldg16(p.Dskip + cta * 4 + kch);
    uint4 pt;
    if (tid < 128) pt = __ldg((const uint4*)g_ptab.v + tid);
    if (tid == 384) {
      TS(0);
#pragma unroll
      for (int i = 0; i < B_COUNT; ++i) mbar_init(BAR(i), bar_count(i));
      asm volatile("fence.mbarrier_init.release.cluster;" ::: "memory");
      prefetch_tmap(&maps.x); prefetch_tmap(&maps.w); prefetch_tmap(&maps.u);
    }
    __syncthreads();
    cluster_arrive();
    if (warp >= 12) {
      cluster_wait();
      if (elect_one()) {
        if (warp == 13) {
          mbar_expect_tx(BAR(B_TILE), 16384);
          tma_load_2d(sb + SM_U, &maps.u, tj * 64, ti * 128, BAR(B_TILE));
          prefetch_tmap(&maps.uT); prefetch_tmap(&maps.wo); prefetch_tmap(&maps.o); prefetch_tmap(&maps.yT);
          prefetch_tmap(&maps.out);
        } else {
          if (warp == 12) TS(61);
          { const int ks = warp == 12 ? 0 : warp - 13; issue_stage(ks, ks); }
        }
      }
      __syncwarp();
    }
    if (tid < 128) sts128(sb + SM_PTAB + tid * 16, pt.x, pt.y, pt.z, pt.w);
    const float dt = round_bf16(expf(bf_lo(r_ldt)));
    zr = dt * bf_lo(r_ar); zi = dt * bf_lo(r_ai);
    const float dbr = dt * bf_lo(r_br), dbi = dt * bf_lo(r_bi), cr = bf_lo(r_cr), ci = bf_lo(r_ci);
    wr = cr * dbr - ci * dbi; wi = cr * dbi + ci * dbr;
  }
  {
    const float mz = __uint_as_float(__reduce_max_sync(0xffffffffu, __float_as_uint(fmaxf(zr, 0.f))));
    const int E = min(max((int)(__reduce_max_sync(0xffffffffu, __float_as_uint(fmaxf(fabsf(wr), fabsf(wi)))) >> 23), 1), 252);
    const float sc = __int_as_float((253 - E) << 23), inv = __int_as_float((E + 1) << 23);
    const float zl = (zr - mz) * 1.4426950408889634f;
    const uint32_t tb = sb + SM_VV + kch * VV_BYTES + krd * KG_BYTES;
    const uint32_t sta = tb + (((lane >> 2) << 4) | ((lane & 3) << 2));
    auto put = [&](int r, uint32_t v) { sts32((sta ^ ((r & 7) << 4)) + r * 128, v); };
    const uint32_t lda = tb + ((lane & 7) + (((lane >> 3) & 1) << 3)) * 128;
    const uint32_t ldb = tb + ((lane & 7) + ((lane >> 4) << 3)) * 128;
    C32 e1 = cfresh(zl, zi, 1.f), e2 = csq(e1), e4 = csq(e2), e8 = csq(e4);
    C32 e16 = cfresh(zl, zi, 16.f), e32 = csq(e16), e64 = csq(e32), e128 = csq(e64);
    C32 e256 = cfresh(zl, zi, 256.f), e512 = csq(e256), e1024 = csq(e512), e768 = cmul(e512, e256);
    uint32_t XA[2][4][4];
    {
      const HMul m16 = mk_mul(e16.re, e16.im), m32 = mk_mul(e32.re, e32.im), m64 = mk_mul(e64.re, e64.im);
      const HMul m128 = mk_mul(e128.re, e128.im);
      uint32_t X[16];
      X[0] = 0x00003c00u; X[1] = pack_f16(e8.re, e8.im); X[2] = m16.b; X[4] = m32.b; X[8] = m64.b;
      X[3] = hcmul(X[1], m16); X[5] = hcmul(X[1], m32); X[6] = hcmul(X[2], m32); X[7] = hcmul(X[3], m32);
#pragma unroll
      for (int r = 1; r < 8; ++r) X[8 + r] = hcmul(X[r], m64);
#pragma unroll
      for (int h = 0; h < 2; ++h) {
#pragma unroll
        for (int r = 0; r < 16; ++r) put(r, h == 0 ? X[r] : r == 0 ? m128.b : hcmul(X[r], m128));
        __syncwarp();
#pragma unroll
        for (int k = 0; k < 4; ++k) ldsm_x4(XA[h][k], lda + (((2 * k + (lane >> 4)) ^ (lane & 7)) << 4));
        __syncwarp();
      }
    }
    if (warp >= 14 && elect_one()) {
      issue_stage(warp - 11, warp - 11);
      issue_stage(warp - 9, warp - 9);
      if (warp == 14) l2_prefetch((const char*)p.wqkv + 224 * 3072 + cta * 6912, 6912);
      else l2_prefetch((const char*)p.x + (size_t)cta * 16384, 16384);
    }
    __syncwarp();
    float D[2][3][4];
#pragma unroll
    for (int t = 0; t < 6; ++t) D[t / 3][t % 3][0] = D[t / 3][t % 3][1] = D[t / 3][t % 3][2] = D[t / 3][t % 3][3] = 0.f;
    auto contract = [&](int t0, int nt) {
      __syncwarp();
#pragma unroll
      for (int k = 0; k < 4; ++k) {
        uint32_t b[4];
        ldsm_x4(b, ldb + (((2 * k + ((lane >> 3) & 1)) ^ (lane & 7)) << 4));
#pragma unroll
        for (int h = 0; h < 2; ++h) {
          mma_f16(D[h][t0], XA[h][k], b[0], b[1]);
          if (nt == 2) mma_f16(D[h][t0 + 1], XA[h][k], b[2], b[3]);
        }
      }
      __syncwarp();
    };
    const HMul c1 = mk_mul(e1.re, -e1.im), c2 = mk_mul(e2.re, -e2.im), c4 = mk_mul(e4.re, -e4.im);
    const HMul c256 = mk_mul(e256.re, -e256.im), c512 = mk_mul(e512.re, -e512.im), c768 = mk_mul(e768.re, -e768.im);
    const HMul c1024 = mk_mul(e1024.re, -e1024.im);
    uint32_t W[8];
    W[0] = pack_f16(wr * sc, -wi * sc);
    W[1] = hcmul(W[0], c1); W[2] = hcmul(W[0], c2); W[3] = hcmul(W[1], c2);
    W[4] = hcmul(W[0], c4); W[5] = hcmul(W[1], c4); W[6] = hcmul(W[2], c4); W[7] = hcmul(W[3], c4);
#pragma unroll
    for (int i = 0; i < 8; ++i) put(i, W[i]);
#pragma unroll
    for (int i = 0; i < 4; ++i) put(8 + i, hcmul(W[2 * i], c256));
    put(12, hcmul(W[0], c512)); put(13, hcmul(W[4], c512)); put(14, hcmul(W[0], c768)); put(15, hcmul(W[4], c768));
    contract(0, 2);
    const uint32_t v0 = hcmul(W[0], c1024);
    put(0, v0); put(1, hcmul(v0, c256)); put(2, hcmul(v0, c512)); put(3, hcmul(v0, c768)); put(4, hcmul(v0, c1024));
    contract(2, 1);
    const uint32_t a = tb + (g * 24 + 2 * q) * 4;
#pragma unroll
    for (int t = 0; t < 6; ++t) {
      const float(&d)[4] = D[t / 3][t % 3];
      sts_f32x2(a + (t / 3) * 1536 + (t % 3) * 32, d[0] * inv, d[1] * inv);
      sts_f32x2(a + (t / 3) * 1536 + (t % 3) * 32 + 768, d[2] * inv, d[3] * inv);
    }
    if (mz > 0.f) {
      __syncwarp();
#pragma unroll 1
      for (int i = lane; i < 768; i += 32) {
        const int r = i / 24, y = i - 24 * r;
        sts_f32(tb + i * 4, lds_f32(tb + i * 4) * ex2(mz * 1.4426950408889634f * (koff(y) + 8 * r)));
      }
    }
  }
  if (tid == 0) TS(2);
  if (warp < 12) cluster_wait();
  if (warp < 4) bar_sync(7, 512); else bar_arrive(7, 512);

  if (warp < 4) {
#define A_REGS 152
    asm volatile("setmaxnreg.inc.sync.aligned.u32 %0;" ::"n"(A_REGS));
    if (tid == 0) TS(34);
    const int d = cta * 4 + warp;
    const uint32_t vv = sb + SM_VV + warp * VV_BYTES;
    const uint32_t ub = sb + SM_U + warp * U_BYTES;
    const uint32_t pb = sb + SM_P + warp * P_BYTES;
    const float dskip = bf_lo(r_dskip);
#pragma unroll 1
    for (int pass = 0; pass < 2; ++pass) {
      if (pass == 1) {
        const uint32_t kf = vv;
#pragma unroll 2
        for (int i = 0; i < 6; ++i) {
          const uint32_t a = kf + (i * 32 + lane) * 16;
          const uint4 x0 = lds128(a), x1 = lds128(a + KG_BYTES), x2 = lds128(a + 2 * KG_BYTES), x3 = lds128(a + 3 * KG_BYTES);
          auto s4 = [](uint32_t a0, uint32_t a1, uint32_t a2, uint32_t a3) {
            return __float_as_uint((__uint_as_float(a0) + __uint_as_float(a1)) + (__uint_as_float(a2) + __uint_as_float(a3)));
          };
          sts128(a, s4(x0.x, x1.x, x2.x, x3.x), s4(x0.y, x1.y, x2.y, x3.y), s4(x0.z, x1.z, x2.z, x3.z), s4(x0.w, x1.w, x2.w, x3.w));
        }
        __syncwarp();
        const float k1024 = lds_f32(kf + kidx_c(1024) * 4);
        if (lane == 0) {
          sts_f32(kf + SL_ZERO * 4, 0.f);
          sts_f32(kf + SL_510 * 4, lds_f32(kf + kidx_c(510) * 4) - lds_f32(kf + kidx_c(512) * 4));
          sts_f32(kf + SL_0 * 4, lds_f32(kf) + dskip);
        }
        __syncwarp();
        if (tid == 0) TS(36);
        mbar_wait_long(BAR(B_PFREE), 0);
        if (tid == 0) TS(37);
        {
          float prev = 0.f;
#pragma unroll 1
          for (int i0 = 0; i0 < 16; i0 += 4) {
            uint32_t e[4];
            float a[4], b[4];
#pragma unroll
            for (int i = 0; i < 4; ++i) e[i] = lds32(sb + SM_PTAB + ((i0 + i) * 32 + lane) * 4);
#pragma unroll
            for (int i = 0; i < 4; ++i) { a[i] = lds_f32(kf + (e[i] & 0xffff)); b[i] = lds_f32(kf + (e[i] >> 16)); }
#pragma unroll
            for (int i = 0; i < 4; ++i) {
              const uint32_t w = pb + (31 * lane + 2 * (i0 + i)) * 4;
              if (i0 + i > 0) sts32(w - 4, pack_bf16(a[i], prev));
              sts32(w, pack_bf16(b[i], a[i]));
              prev = b[i];
            }
          }
        }
        __syncwarp();
        if (lane == 0) TS(4);
        const int gq = g - 2 * q;
        uint32_t h127, h128;
        {
          const uint32_t kf2 = pack_bf16(k1024, k1024) ^ 0x80008000u;
          h127 = (gq == 4 ? 0x0000ffffu : gq == 5 ? 0xffffffffu : gq == 6 ? 0xffff0000u : 0u) & kf2;
          h128 = (gq == -4 ? 0x0000ffffu : gq == -3 ? 0xffffffffu : gq == -2 ? 0xffff0000u : 0u) & kf2;
        }
        bar_sync(4, 480);
        mbar_wait_long(BAR(B_UCH + warp), 0);
        if (lane == 0) TS(7);
        float acc[16][4];
#pragma unroll
        for (int i = 0; i < 16; ++i) { acc[i][0] = acc[i][1] = acc[i][2] = acc[i][3] = 0.f; }
        {
          const uint32_t pd_lane = pb + (PD_OFF + 16 + gq) * 4;
          const int prow0 = 8 + (lane & 7) + ((lane >> 4) << 3), hs = (lane >> 3) & 1;
          const uint32_t zero = (uint32_t)cta >> 20;
          uint32_t B[2][4][4];
          uint32_t A[4][4];
          const uint32_t la0 = ub + prow0 * 32 + ((hs ^ ((prow0 >> 2) & 1)) << 4);
#pragma unroll
          for (int m2 = 0; m2 < 4; ++m2) ldsm_x4(B[0][m2], la0 + m2 * 512);
#pragma unroll
          for (int i = 0; i < 4; ++i) {
            const uint32_t a = pd_lane + i * 512;
            A[i][0] = lds32(a); A[i][1] = lds32(a + 32); A[i][2] = lds32(a - 32); A[i][3] = lds32(a + zero);
          }
          uint32_t la = la0;
#define UNR_RHO 1
#define UNR_TAIL 1
          constexpr int unr_rho = UNR_RHO, unr_tail = UNR_TAIL;
#pragma unroll unr_rho
          for (int rho = 0; rho < 8; ++rho) {
#pragma unroll
            for (int m2 = 0; m2 < 4; ++m2) ldsm_x4(B[1][m2], la + (4 + m2) * 512);
#pragma unroll
            for (int i = 0; i < 4; ++i)
#pragma unroll
              for (int m = 0; m < 8; ++m) mma_bf16v(acc[m + i], A[i], B[0][m >> 1][2 * (m & 1)], B[0][m >> 1][2 * (m & 1) + 1]);
            const int prow = prow0 - min(rho + 1, 7);
            la = ub + prow * 32 + ((hs ^ ((prow >> 2) & 1)) << 4);
#pragma unroll
            for (int m2 = 0; m2 < 4; ++m2) ldsm_x4(B[0][m2], la + m2 * 512);
            const uint32_t pa = pd_lane + (rho + 1) * 64;
#pragma unroll
            for (int i = 0; i < 4; ++i) {
#pragma unroll
              for (int m = 0; m < 8 - i; ++m)
                mma_bf16v(acc[8 + m + i], A[i], B[1][m >> 1][2 * (m & 1)], B[1][m >> 1][2 * (m & 1) + 1]);
              A[i][0] = lds32(pa + i * 512); A[i][1] = lds32(pa + i * 512 + 32); A[i][2] = lds32(pa + i * 512 - 32);
              A[i][3] = lds32(pa + i * 512 + zero);
            }
          }
          if (lane == 0) TS(40);
          {
            uint32_t b8[4];
            ldsm_x4(b8, la + 4 * 512);
            const uint32_t h63 = lds32(pd_lane + 63 * 32), h64 = lds32(pd_lane + 64 * 32);
            const uint32_t a63[4] = {0u, h127, 0u, 0u}, a32[4] = {h64, 0u, h63, h64}, a64[4] = {h128, 0u, h127, h128};
#pragma unroll
            for (int m2 = 0; m2 < 4; ++m2) ldsm_x4(B[1][m2], la0 + m2 * 512);
#pragma unroll
            for (int m = 0; m < 8; ++m) mma_bf16v(acc[m + 7], a63, B[0][m >> 1][2 * (m & 1)], B[0][m >> 1][2 * (m & 1) + 1]);
#pragma unroll
            for (int m2 = 0; m2 < 2; ++m2) ldsm_x4(B[0][m2], la0 + (4 + m2) * 512);
#pragma unroll
            for (int m = 0; m < 8; ++m) mma_bf16v(acc[m + 4], a32, B[1][m >> 1][2 * (m & 1)], B[1][m >> 1][2 * (m & 1) + 1]);
            mma_bf16v(acc[15], a63, b8[0], b8[1]);
#pragma unroll
            for (int m = 0; m < 8; ++m) mma_bf16v(acc[m + 8], a64, B[1][m >> 1][2 * (m & 1)], B[1][m >> 1][2 * (m & 1) + 1]);
#pragma unroll
            for (int m = 0; m < 4; ++m) mma_bf16v(acc[m + 12], a32, B[0][m >> 1][2 * (m & 1)], B[0][m >> 1][2 * (m & 1) + 1]);
          }
          if (lane == 0) TS(41);
          bar_sync(5, 224);
#pragma unroll unr_tail
          for (int v = 0; v < 4; ++v)
            conv_tail<4, 3, 11>(acc, pb + (P2_OFF + 56 * v + gq - 16) * 4, vv + ((v & 1) ? VV_U3 : VV_U5), v >> 1, v == 0, lane);
          if (lane == 0) TS(42);
#pragma unroll unr_tail
          for (int pi = 0; pi < 2; ++pi)
            conv_tail<8, 5, 7>(acc, pb + (P3_OFF + 88 * pi + gq - 48) * 4, vv + (pi ? VV_U7 : VV_U9), pi, pi == 0, lane);
        }
        if (lane == 0) TS(8);
        __syncwarp();
        {
          const int mt = lane >> 3;
          const uint32_t a = pb + (128 * (mt >> 1) + 16 * (lane & 7) + 8 * (mt & 1)) * 2;
#pragma unroll
          for (int ab = 0; ab < 16; ab += 2)
            stsm_x4_t(a + ab * 256, pack_bf16(acc[ab][0], acc[ab][1]), pack_bf16(acc[ab][2], acc[ab][3]),
                      pack_bf16(acc[ab + 1][0], acc[ab + 1][1]), pack_bf16(acc[ab + 1][2], acc[ab + 1][3]));
        }
        fence_async_smem();
        __syncwarp();
        if (lane < 2) mbar_arrive_cluster(BAR(B_CONVD), lane);
        bar_arrive(3, 384);
        if (elect_one()) {
          bulk_store(p.yT + (size_t)d * 2048, pb, 4096);
          bulk_commit();
          bulk_wait0();
          red_relaxed_add(&g_cnt[(C_Y + (cta >> 4)) * 32], 1);
          TS(9);
        }
        bar_sync(2, 128);
        if (warp == 0 && elect_one()) {
          wait_counter(&g_cnt[(C_Y + tj) * 32], (epoch + 1) * 64);
          TS(28);
          mbar_expect_tx(BAR(B_TILE), 16384);
          tma_load_2d(sb + SM_U, &maps.yT, ti * 128, tj * 64, BAR(B_TILE));
          tma_load_2d(sb + SM_U + 8192, &maps.yT, ti * 128 + 64, tj * 64, BAR(B_TILE));
        }
        __syncwarp();
      }
      mbar_wait_long(BAR(B_TILE), pass);
      if (lane == 0) TS(26 + 3 * pass);
      {
        const int m = lane >> 3, r = lane & 7;
#pragma unroll 2
        for (int it = 0; it < 8; ++it) {
          const int tb = warp * 4 + (it >> 1), cb = (it & 1) * 4 + m;
          const uint32_t at = (tb * 8 + r) * 128 + ((cb ^ r) << 4);
          const uint32_t ac = (tb >> 3) * 8192 + (cb * 8 + r) * 128 + (((tb & 7) ^ (pass ? 0 : tb >> 3) ^ r) << 4);
          uint32_t v[4];
          ldsm_x4_t(v, sb + SM_U + (pass ? ac : at));
          stsm_x4(sb + SM_P + (pass ? at : ac), v[0], v[1], v[2], v[3]);
        }
      }
      if (pass == 0 && tid == 0) TS(35);
      fence_async_smem();
      if (pass == 0) {
        bar_arrive(6, 160);
      } else {
        bar_sync(2, 128);
        if (warp == 0 && elect_one()) {
          tma_store_2d(&maps.out, sb + SM_P, 64 * tj, 128 * ti);
          bulk_commit();
          bulk_wait_read0();
          TS(30);
        }
      }
    }
  } else if (warp < 12) {
    const int w8 = warp - 4;
    const int row = w8 * 16 + (lane & 7) + (((lane >> 3) & 1) << 3);
    {
      float acc[96];
#pragma unroll 1
      for (int ks = 0, s = 0, ph = 0; ks < 16; ++ks) {
        mbar_wait(BAR(B_FULL + s), ph);
        if (tid == 128 && !(ks & 1)) TSR(16, ks == 0 ? 16 : 9 + (ks >> 1) + (ks > 12 ? 43 : 0));
        const uint32_t st = sb + s * STG_BYTES;
        const uint32_t da = mkdesc(st + STG_X + (w8 >> 2) * 4096, 16);
        const uint32_t db = mkdesc(st + STG_W, 2048);
        wg_fence();
        wgmma_n192(acc, da, db, ks != 0);
        wgmma_n192(acc, da + 2, db + 384, 1);
        wg_commit();
        const uint32_t eprev = BAR(B_EMPTY + (s == 0 ? NSTG - 1 : s - 1));
        if (++s == NSTG) { s = 0; ph ^= 1; }
        if (ks > 0) {
          wg_wait<1>();
          if (lane < 2) mbar_arrive_cluster(eprev, lane);
        }
      }
      wg_wait<0>();
      bar_arrive(4, 480);
      if (tid == 128) TS(17);
      bar_sync(1, 256);
#pragma unroll
      for (int i = 0; i < 24; i += 2)
        stsm_x4(sb + SM_QS + row * 128 + (i >> 3) * 16384 + ((((i & 7) + (lane >> 4)) ^ (row & 7)) << 4),
                pack_bf16(acc[4 * i], acc[4 * i + 1]), pack_bf16(acc[4 * i + 2], acc[4 * i + 3]),
                pack_bf16(acc[4 * i + 4], acc[4 * i + 5]), pack_bf16(acc[4 * i + 6], acc[4 * i + 7]));
    }
    __syncwarp();
#pragma unroll 1
    for (int part = 1; part >= 0; --part) {
      const uint32_t pa = sb + SM_QS + part * 16384 + w8 * 2048 + lane * 16;
#pragma unroll 1
      for (int it = 0; it < 4; ++it) {
        uint4 t = lds128(pa + it * 512);
        uint32_t* tw = &t.x;
#pragma unroll
        for (int j = 0; j < 4; ++j) {
          const uint32_t x = tw[j];
          const __nv_bfloat162 xb = *reinterpret_cast<const __nv_bfloat162*>(&x);
          const uint32_t e = pack_bf16(ex2(bf_lo(x) * 1.4426950408889634f), ex2(bf_hi(x) * 1.4426950408889634f));
          const uint32_t m = __hgt2_mask(xb, __floats2bfloat162_rn(0.f, 0.f));
          tw[j] = badd((badd(x, 0x3f803f80u) & m) | (e & ~m), 0x35863586u);
        }
        sts128(pa + it * 512, t.x, t.y, t.z, t.w);
      }
      if (part == 1) {
        if (tid == 128) TS(53);
        bar_sync(1, 256);
        const int hh = w8 >> 1, dtile = w8 & 1;
        float kv[4] = {0.f, 0.f, 0.f, 0.f}, zz[4] = {0.f, 0.f, 0.f, 0.f};
        const int m = lane >> 3;
        const uint32_t aa = sb + SM_VS + ((lane & 7) + ((m >> 1) << 3)) * 128 + (((2 * hh + (m & 1)) ^ (lane & 7)) << 4);
        const uint32_t ab = sb + SM_PK + (lane & 15) * 128 + (((2 * hh + dtile) ^ (lane & 7)) << 4);
#pragma unroll 2
        for (int ks = 0; ks < 8; ++ks) {
          uint32_t a[4], b0, b1;
          ldsm_x4_t(a, aa + ks * 2048);
          ldsm_x2_t(b0, b1, ab + ks * 2048);
          mma_bf16(kv, a[0], a[1], a[2], a[3], b0, b1);
          mma_bf16(zz, 0x3f803f80u, 0x3f803f80u, 0x3f803f80u, 0x3f803f80u, b0, b1);
        }
        const uint32_t kp = sb + SM_KV + hh * 1088;
        sts128(kp + dtile * 512 + lane * 16, __float_as_uint(kv[0]), __float_as_uint(kv[1]), __float_as_uint(kv[2]),
               __float_as_uint(kv[3]));
        if (g == 0) sts_f32x2(kp + 1024 + dtile * 32 + q * 8, zz[0], zz[1]);
        fence_async_smem();
        __syncwarp();
        if (lane == 0) mbar_arrive(BAR(B_KVP));
        if (tid == 128) TS(55);
      }
    }
    if (tid == 128) TS(56);
    if (warp == 4) mbar_wait_long(BAR(B_KVF), 0);
    bar_sync(1, 256);
    if (tid == 128) TS(19);
#pragma unroll 1
    for (int h = 0; h < 4; ++h) {
      uint32_t a[4];
      const uint32_t qa = sb + SM_QS + row * 128 + (((2 * h + (lane >> 4)) ^ (row & 7)) << 4);
      ldsm_x4(a, qa);
      const uint32_t kp = sb + SM_KV + h * 1088;
      const uint4 k0 = lds128(kp + lane * 16), k1 = lds128(kp + 512 + lane * 16);
      const uint32_t za = kp + 1024 + q * 8;
      auto pk2 = [](uint32_t x, uint32_t y) { return pack_bf16(__uint_as_float(x), __uint_as_float(y)); };
      float n0[4] = {0.f, 0.f, 0.f, 0.f}, n1[4] = {0.f, 0.f, 0.f, 0.f}, dn[4] = {0.f, 0.f, 0.f, 0.f};
      mma_bf16(n0, a[0], a[1], a[2], a[3], pk2(k0.x, k0.y), pk2(k1.x, k1.y));
      mma_bf16(n1, a[0], a[1], a[2], a[3], pk2(k0.z, k0.w), pk2(k1.z, k1.w));
      mma_bf16(dn, a[0], a[1], a[2], a[3], pack_bf16(lds_f32(za), lds_f32(za + 4)), pack_bf16(lds_f32(za + 32), lds_f32(za + 36)));
      const uint32_t dd = pack_bf16(dn[0], dn[2]);
      const uint32_t d2 = pack_bf16(bf_lo(dd) + 1e-6f, bf_hi(dd) + 1e-6f);
      const float r0 = rcp(bf_lo(d2)), r1 = rcp(bf_hi(d2));
      const uint32_t x0 = pack_bf16(n0[0], n0[1]), x1 = pack_bf16(n0[2], n0[3]);
      const uint32_t x2 = pack_bf16(n1[0], n1[1]), x3 = pack_bf16(n1[2], n1[3]);
      stsm_x4(qa, pack_bf16(bf_lo(x0) * r0, bf_hi(x0) * r0), pack_bf16(bf_lo(x1) * r1, bf_hi(x1) * r1),
              pack_bf16(bf_lo(x2) * r0, bf_hi(x2) * r0), pack_bf16(bf_lo(x3) * r1, bf_hi(x3) * r1));
    }
    fence_async_smem();
    __syncwarp();
    if (lane == 0) mbar_arrive(BAR(B_OST));
    if (tid == 128) TS(57);
    if (warp == 4) mbar_wait_long(BAR(B_WO), 0);
    bar_sync(3, 384);
    {
      float o[32];
#pragma unroll 1
      for (int c = 0; c < 8; ++c) {
        mbar_wait_long(BAR(B_RF + c), 0);
        if (tid == 128) TSR(22, c == 0 ? 22 : 43 + c);
        const uint32_t slot = c < 4 ? SM_QS + c * 16384 : c < 7 ? SM_VV + (c - 4) * 16384 : SM_QS;
        const uint32_t da = mkdesc(sb + slot + (w8 >> 2) * 8192, 16);
        const uint32_t db = mkdesc(sb + SM_WO + c * 8192, 8192);
        wg_fence();
#pragma unroll
        for (int k = 0; k < 4; ++k) wgmma_n64(o, da + 2 * k, db + 128 * k, (c | k) != 0);
        wg_commit();
        if (c == 1) {
          wg_wait<1>();
          if (lane < 2) mbar_arrive_cluster(BAR(B_RE), lane);
        }
      }
      wg_wait<0>();
      if (tid == 128) TS(51);
      bar_sync(1, 256);
#pragma unroll
      for (int i = 0; i < 8; i += 2)
        stsm_x4(sb + SM_BOUT + row * 128 + (((i + (lane >> 4)) ^ (row & 7)) << 4), pack_bf16(o[4 * i], o[4 * i + 1]),
                pack_bf16(o[4 * i + 2], o[4 * i + 3]), pack_bf16(o[4 * i + 4], o[4 * i + 5]), pack_bf16(o[4 * i + 6], o[4 * i + 7]));
      fence_async_smem();
      bar_sync(1, 256);
      if (tid == 128) TS(52);
      if (warp == 4 && elect_one()) {
        tma_store_2d(&maps.out, sb + SM_BOUT, 512 + 64 * pj, 128 * pi);
        bulk_commit();
        bulk_wait_read0();
        TS(23);
      }
    }
  } else {
    asm volatile("setmaxnreg.dec.sync.aligned.u32 40;");
    if (warp == 12) {
      if (elect_one()) {
#pragma unroll 1
        for (int ks = NSTG, s = 0, ph = 0; ks < 16; ++ks) {
          mbar_wait(BAR(B_EMPTY + s), ph);
          issue_stage(ks, s);
          if (ks == NSTG) l2_prefetch((const char*)p.wo + (size_t)cta * 4096, 4096);
          if (++s == NSTG) { s = 0; ph ^= 1; }
        }
        mbar_wait(BAR(B_EMPTY + 6), 1);
        mbar_expect_tx(BAR(B_WO), 65536);
        tma_load_2d(sb + SM_WO, &maps.wo, pj * 64, 0, BAR(B_WO));
        tma_load_2d(sb + SM_WO + 32768, &maps.wo, pj * 64, 256, BAR(B_WO));
        float* kvg = &g_kv[epoch & 1][tj][0];
        mbar_wait_long(BAR(B_KVP), 0);
        bulk_reduce_add_f32(kvg, sb + SM_KV, 4352);
        bulk_commit();
        bulk_wait0();
        red_relaxed_add(&g_cnt[(C_KV + tj) * 32], 1);
        TS(18);
        wait_counter(&g_cnt[(C_KV + tj) * 32], (epoch + 1) * 16);
        mbar_expect_tx(BAR(B_KVF), 4352);
        bulk_load(sb + SM_KV, kvg, 4352, BAR(B_KVF));
        mbar_wait_long(BAR(B_OST), 0);
        tma_store_2d(&maps.o, sb + SM_QS, tj * 64, ti * 128);
        tma_store_2d(&maps.o, sb + SM_QS + 8192, tj * 64, ti * 128 + 64);
        bulk_commit();
        bulk_wait0();
        red_relaxed_add(&g_cnt[(C_O + ti) * 32], 1);
        TS(20);
        mbar_arrive_cluster(BAR(B_SLOT), 0);
        mbar_arrive_cluster(BAR(B_SLOT), 1);
        wait_counter(&g_cnt[(C_O + pi) * 32], (epoch + 1) * 8);
        if (cta == 0) g_epoch = epoch + 1;
        mbar_wait(BAR(B_SLOT), 0);
        TS(21);
#pragma unroll 1
        for (int c = 0; c < 8; ++c) {
          if (c == 4) mbar_wait_long(BAR(B_CONVD), 0);
          if (c == 7) mbar_wait(BAR(B_RE), 0);
          const uint32_t slot = c < 4 ? SM_QS + c * 16384 : c < 7 ? SM_VV + (c - 4) * 16384 : SM_QS;
          mbar_expect_tx(BAR(B_RF + c), 16384);
          tma_load_2d_mc(sb + slot + rank * 8192, &maps.o, c * 64, pi * 128 + rank * 64, BAR(B_RF + c), 3);
        }
      }
    } else if (warp == 13) {
      bar_sync(6, 160);
      sts128(sb + SM_U + (lane >> 4) * U_BYTES + (lane & 15) * 16, 0, 0, 0, 0);
      sts128(sb + SM_U + (2 + (lane >> 4)) * U_BYTES + (lane & 15) * 16, 0, 0, 0, 0);
      __syncwarp();
      if (elect_one()) {
        tma_store_2d(&maps.uT, sb + SM_P, ti * 128, tj * 64);
        tma_store_2d(&maps.uT, sb + SM_P + 8192, ti * 128 + 64, tj * 64);
        bulk_commit();
        bulk_wait_read0();
        mbar_arrive(BAR(B_PFREE));
        bulk_wait0();
        red_relaxed_add(&g_cnt[(C_U + tj) * 32], 1);
        TS(27);
        wait_counter(&g_cnt[(C_U + (cta >> 4)) * 32], (epoch + 1) * 16);
#pragma unroll 1
        for (int c = 0; c < 4; ++c) {
          mbar_expect_tx(BAR(B_UCH + c), 4096);
          bulk_load(sb + SM_U + c * U_BYTES + 256, p.uT + (size_t)(cta * 4 + c) * 2048, 4096, BAR(B_UCH + c));
        }
        TS(3);
      }
      __syncwarp();
      if (ti == 0) {
        float4* z = (float4*)&g_kv[(epoch & 1) ^ 1][tj][0];
#pragma unroll 1
        for (int i = lane; i < 272; i += 32) z[i] = make_float4(0.f, 0.f, 0.f, 0.f);
      }
    }
    if (warp >= 13) {
      bar_sync(4, 480);
      auto swz = [](int k, int pad) { const int r = (k >> 1) + pad; return (uint32_t)(r * 32 + (((k & 1) ^ ((r >> 2) & 1)) << 4)); };
      const uint32_t o0 = swz(lane - 3, 8), o1 = swz(lane - 2, 8), o2 = swz(lane - 1, 8), ow = swz(lane - 2, PADV);
      const uint32_t oz = swz(lane - 18, PADV);
#pragma unroll 1
      for (int item = warp - 13; item < 28; item += 3) {
        const int ch = item / 7, it = item - 7 * ch;
        const int k = -2 + 32 * it + lane;
        const uint32_t ua = sb + SM_U + ch * U_BYTES + it * 512, vb = sb + SM_VV + ch * VV_BYTES;
        const uint32_t a0 = ua + o0, a1 = ua + o1, a2 = ua + o2, aw = vb + it * 512 + ow;
        mbar_wait_long(BAR(B_UCH + ch), 0);
        if (it == 0 && lane < 16) {
          sts128(vb + oz + VV_U3, 0, 0, 0, 0); sts128(vb + oz + VV_U5, 0, 0, 0, 0);
          sts128(vb + oz + VV_U7, 0, 0, 0, 0); sts128(vb + oz + VV_U9, 0, 0, 0, 0);
        }
        const uint4 t0 = lds128(a0), t1 = lds128(a1), t2 = lds128(a2);
        const uint32_t E[12] = {t0.x, t0.y, t0.z, t0.w, t1.x, t1.y, t1.z, t1.w, t2.x, t2.y, t2.z, t2.w};
        uint32_t O[8];
#pragma unroll
        for (int j = 0; j < 8; ++j) O[j] = __byte_perm(E[j + 1], E[j + 2], 0x5432);
        uint32_t s3[6], s5[4], s7[4], s9[4];
#pragma unroll
        for (int j = 0; j < 6; ++j) s3[j] = badd(badd(O[j], O[j + 1]), E[j + 2]);
#pragma unroll
        for (int j = 0; j < 4; ++j) {
          s5[j] = badd(s3[j + 2], badd(E[j + 3], E[j + 5]));
          s7[j] = badd(s5[j], badd(O[j + 1], O[j + 4]));
          s9[j] = badd(s7[j], badd(E[j + 2], E[j + 6]));
        }
        if (k < 208) { sts128(aw + VV_U3, s3[0], s3[1], s3[2], s3[3]); sts128(aw + VV_U5, s5[0], s5[1], s5[2], s5[3]); }
        if (k < 144) { sts128(aw + VV_U7, s7[0], s7[1], s7[2], s7[3]); sts128(aw + VV_U9, s9[0], s9[1], s9[2], s9[3]); }
      }
      if (tid == 416) TS(6);
      bar_arrive(5, 224);
    }
  }
  __syncwarp();
  cluster_arrive();
  cluster_wait();
  if (tid == 0) TS(31);
#undef BAR
}

typedef CUresult (*EncodeFn)(CUtensorMap*, CUtensorMapDataType, cuuint32_t, void*, const cuuint64_t*, const cuuint64_t*,
                             const cuuint32_t*, const cuuint32_t*, CUtensorMapInterleave, CUtensorMapSwizzle,
                             CUtensorMapL2promotion, CUtensorMapFloatOOBfill);

static void make_map(EncodeFn enc, CUtensorMap* m, const void* base, uint64_t inner, uint64_t outer, uint32_t box_in,
                     uint32_t box_out, CUtensorMapSwizzle swz = CU_TENSOR_MAP_SWIZZLE_128B) {
  cuuint64_t gd[2] = {inner, outer};
  cuuint64_t gs[1] = {inner * 2};
  cuuint32_t bd[2] = {box_in, box_out};
  cuuint32_t es[2] = {1, 1};
  enc(m, CU_TENSOR_MAP_DATA_TYPE_BFLOAT16, 2, const_cast<void*>(base), gd, gs, bd, es, CU_TENSOR_MAP_INTERLEAVE_NONE,
      swz, CU_TENSOR_MAP_L2_PROMOTION_L2_128B, CU_TENSOR_MAP_FLOAT_OOB_FILL_NONE);
}

}

extern "C" void kernel_launch(void* const* d_in, const int* in_sizes, int n_in, void* d_out, int out_size) {
  using namespace s4la;
  (void)in_sizes; (void)n_in; (void)out_size;
  static EncodeFn enc = nullptr;
  static void *uT = nullptr, *yT = nullptr, *oS = nullptr;
  if (!enc) {
    void* fn = nullptr;
    cudaDriverEntryPointQueryResult qr;
    cudaGetDriverEntryPoint("cuTensorMapEncodeTiled", &fn, cudaEnableDefault, &qr);
    enc = (EncodeFn)fn;
    cudaGetSymbolAddress(&uT, g_uT);
    cudaGetSymbolAddress(&yT, g_yT);
    cudaGetSymbolAddress(&oS, g_o);
    cudaFuncSetAttribute(fused_kernel, cudaFuncAttributeMaxDynamicSharedMemorySize, SM_TOTAL);
  }
  const __nv_bfloat16* const* in = (const __nv_bfloat16* const*)d_in;
  Maps maps;
  make_map(enc, &maps.x, in[9], 512, 2048, 32, 128, CU_TENSOR_MAP_SWIZZLE_64B);
  {
    cuuint64_t gd[3] = {512, 512, 3};
    cuuint64_t gs[2] = {3072, 1024};
    cuuint32_t bd[3] = {64, 16, 3};
    cuuint32_t es[3] = {1, 1, 1};
    enc(&maps.w, CU_TENSOR_MAP_DATA_TYPE_BFLOAT16, 3, const_cast<__nv_bfloat16*>(in[10]), gd, gs, bd, es,
        CU_TENSOR_MAP_INTERLEAVE_NONE, CU_TENSOR_MAP_SWIZZLE_128B, CU_TENSOR_MAP_L2_PROMOTION_L2_128B,
        CU_TENSOR_MAP_FLOAT_OOB_FILL_NONE);
  }
  make_map(enc, &maps.wo, in[11], 512, 512, 64, 256);
  make_map(enc, &maps.u, in[0], 512, 2048, 64, 128);
  make_map(enc, &maps.uT, uT, 2048, 512, 64, 64);
  make_map(enc, &maps.yT, yT, 2048, 512, 64, 64);
  make_map(enc, &maps.o, oS, 512, 2048, 64, 64);
  make_map(enc, &maps.out, d_out, 1024, 2048, 64, 128);
  Ptrs p;
  p.A_re = in[1]; p.A_im = in[2]; p.B_re = in[3]; p.B_im = in[4]; p.C_re = in[5]; p.C_im = in[6];
  p.log_dt = in[7]; p.Dskip = in[8]; p.x = in[9]; p.wqkv = in[10]; p.wo = in[11];
  p.uT = (__nv_bfloat16*)uT; p.yT = (__nv_bfloat16*)yT;
  fused_kernel<<<NCTA, NTHREADS, SM_TOTAL, cudaStreamPerThread>>>(maps, p);
}
```

```cpp
#include <cuda_runtime.h>
#include <cuda_bf16.h>
#include <cuda_fp16.h>
#include <cuda.h>
#include <stdint.h>

#define DEVI __device__ __forceinline__

namespace s4la {

constexpr int NTHREADS = 512;
constexpr int NCTA = 128;

constexpr int NSTG = 7;
constexpr uint32_t STG_BYTES = 20480, STG_X = 0, STG_W = 8192;
constexpr uint32_t SM_QS = 0;
constexpr uint32_t SM_PK = SM_QS + 16384, SM_VS = SM_QS + 32768;
constexpr uint32_t SM_WO = 65536;
constexpr uint32_t SM_KV = 131072;
constexpr uint32_t SM_BOUT = 16384;
constexpr uint32_t SM_U = 143360, U_BYTES = 4352;
constexpr uint32_t SM_P = 160768, P_BYTES = 4096;
constexpr uint32_t SM_VV = 177152, VV_BYTES = 12800;
constexpr uint32_t VV_U5 = 0, VV_U3 = 3712, VV_U9 = 7424, VV_U7 = 10112;
constexpr uint32_t KG_BYTES = 3200;
constexpr uint32_t SM_BAR = SM_VV + 4 * VV_BYTES;
constexpr uint32_t SM_PTAB = SM_BAR + 320;
constexpr uint32_t SM_TOTAL = SM_PTAB + 2048;
static_assert(SM_TOTAL <= 232448, "shared memory");
constexpr int PADV = 12;

enum { B_FULL = 0, B_EMPTY = 7, B_TILE = 14, B_UCH = 15, B_KVP = 19, B_KVF = 20, B_OST = 21, B_RF = 22, B_WO = 30, B_RE = 31, B_PFREE = 32, B_CONVD = 33, B_SLOT = 34, B_COUNT = 35 };
__host__ __device__ constexpr int bar_count(int i) {
  return (i >= B_EMPTY && i < B_TILE) ? 16 : (i == B_KVP || i == B_OST || i == B_CONVD) ? 8 : i == B_RE ? 16 : i == B_SLOT ? 2 : 1;
}

constexpr int PD_OFF = 0, P2_OFF = 544, P3_OFF = 768;

constexpr int SL_K2048 = 20, SL_ZERO = 21, SL_510 = 22, SL_0 = 23;
__host__ __device__ constexpr int koff(int y) {
  return y < 8 ? y : y < 12 ? 256 + 2 * (y - 8) : y < 16 ? 512 + 256 * ((y - 12) >> 1) + 4 * (y & 1) : 1024 + 256 * (y - 16);
}
__host__ __device__ constexpr int kidx_c(int l) {
  const int y = l < 256 ? (l & 7) : l < 512 ? 8 + ((l & 7) >> 1) : l < 1024 ? 12 + (((l - 512) >> 8) << 1) + ((l >> 2) & 1)
                                                                            : 16 + ((l - 1024) >> 8);
  return ((l >> 3) & 31) * 24 + y;
}
constexpr int slot_direct(int l) {
  if (l < 0 || l > 510) return SL_ZERO;
  if (l == 510) return SL_510;
  if (l == 0) return SL_0;
  return kidx_c(l < 256 ? l : ((l + ((l >> 1) & 1)) & ~1));
}
constexpr int slot_seg2(int v, int k) { return (k >= 32 && k < 64) ? kidx_c(16 * k + 4 * v) : SL_ZERO; }
constexpr int slot_seg3(int pi, int k) {
  return (k >= 64 && k < 128) ? kidx_c(16 * k + 8 * pi) : ((k == 128 && pi == 0) ? SL_K2048 : SL_ZERO);
}
constexpr int slot_word(int w) {
  return w < 0 ? SL_ZERO : w < 544 ? slot_direct(w - 16) : w < 768 ? slot_seg2((w - 544) / 56, 16 + (w - 544) % 56)
       : w < 944 ? slot_seg3((w - 768) / 88, 48 + (w - 768) % 88) : SL_ZERO;
}
struct PTab { uint32_t v[512]; };
constexpr PTab make_ptab() {
  PTab t{};
  for (int lane = 0; lane < 32; ++lane)
    for (int i = 0; i < 16; ++i)
      t.v[i * 32 + lane] = (slot_word(31 * lane - 1 + 2 * i) * 4) | ((slot_word(31 * lane + 2 * i) * 4) << 16);
  return t;
}
__device__ const PTab g_ptab = make_ptab();

__device__ __nv_bfloat16 g_uT[512 * 2048];
__device__ __nv_bfloat16 g_yT[512 * 2048];
__device__ __nv_bfloat16 g_o[2048 * 512];
__device__ float g_kv[2][8][4 * 272];
__device__ unsigned g_cnt[64 * 32];
__device__ unsigned g_epoch;
#define TS(slot) do { } while (0)
#define TSR(on, slot) do { } while (0)
#define TSD(slot) do { } while (0)
enum { C_U = 0, C_KV = 8, C_O = 16, C_Y = 32 };

struct Maps {
  CUtensorMap x, w, wo, u, uT, yT, o, out;
};
struct Ptrs {
  const __nv_bfloat16 *A_re, *A_im, *B_re, *B_im, *C_re, *C_im, *log_dt, *Dskip;
  const __nv_bfloat16 *x, *wqkv, *wo;
  __nv_bfloat16 *uT, *yT;
};

DEVI uint32_t s2u(const void* p) { return (uint32_t)__cvta_generic_to_shared(p); }
DEVI void mbar_init(uint32_t b, uint32_t c) { asm volatile("mbarrier.init.shared::cta.b64 [%0], %1;" ::"r"(b), "r"(c) : "memory"); }
DEVI void mbar_expect_tx(uint32_t b, uint32_t bytes) {
  asm volatile("mbarrier.arrive.expect_tx.shared::cta.b64 _, [%0], %1;" ::"r"(b), "r"(bytes) : "memory");
}
DEVI void mbar_arrive(uint32_t b) { asm volatile("mbarrier.arrive.shared::cta.b64 _, [%0];" ::"r"(b) : "memory"); }
DEVI void mbar_arrive_cluster(uint32_t b, uint32_t cta) {
  asm volatile("{\n.reg .b32 r;\nmapa.shared::cluster.u32 r, %0, %1;\nmbarrier.arrive.shared::cluster.b64 _, [r];\n}"
               ::"r"(b), "r"(cta) : "memory");
}
DEVI void mbar_wait(uint32_t b, uint32_t parity) {
  asm volatile("{\n.reg .pred p;\nLAB_WAIT:\nmbarrier.try_wait.parity.shared::cta.b64 p, [%0], %1;\n@!p bra LAB_WAIT;\n}"
               ::"r"(b), "r"(parity) : "memory");
}
DEVI void mbar_wait_long(uint32_t b, uint32_t parity) {
  asm volatile("{\n.reg .pred p;\nLAB_WAIT:\nmbarrier.try_wait.parity.shared::cta.b64 p, [%0], %1, 0x989680;\n@!p bra LAB_WAIT;\n}"
               ::"r"(b), "r"(parity) : "memory");
}
DEVI void bar_sync(int id, int n) { asm volatile("bar.sync %0, %1;" ::"r"(id), "r"(n) : "memory"); }
DEVI void bar_arrive(int id, int n) { asm volatile("bar.arrive %0, %1;" ::"r"(id), "r"(n) : "memory"); }
DEVI void fence_async_smem() { asm volatile("fence.proxy.async.shared::cta;" ::: "memory"); }
DEVI void fence_async_all() { asm volatile("fence.proxy.async;" ::: "memory"); }
DEVI void cluster_arrive() { asm volatile("barrier.cluster.arrive.relaxed.aligned;" ::: "memory"); }
DEVI void cluster_wait() { asm volatile("barrier.cluster.wait.aligned;" ::: "memory"); }

DEVI void tma_load_2d(uint32_t dst, const CUtensorMap* m, int c0, int c1, uint32_t bar) {
  asm volatile("cp.async.bulk.tensor.2d.shared::cluster.global.mbarrier::complete_tx::bytes [%0], [%1, {%3, %4}], [%2];"
               ::"r"(dst), "l"(m), "r"(bar), "r"(c0), "r"(c1) : "memory");
}
DEVI void tma_load_2d_mc(uint32_t dst, const CUtensorMap* m, int c0, int c1, uint32_t bar, uint16_t mask) {
  asm volatile("cp.async.bulk.tensor.2d.shared::cluster.global.mbarrier::complete_tx::bytes.multicast::cluster [%0], [%1, {%3, %4}], [%2], %5;"
               ::"r"(dst), "l"(m), "r"(bar), "r"(c0), "r"(c1), "h"(mask) : "memory");
}
DEVI void tma_load_3d_mc(uint32_t dst, const CUtensorMap* m, int c0, int c1, int c2, uint32_t bar, uint16_t mask) {
  asm volatile("cp.async.bulk.tensor.3d.shared::cluster.global.mbarrier::complete_tx::bytes.multicast::cluster [%0], [%1, {%3, %4, %5}], [%2], %6;"
               ::"r"(dst), "l"(m), "r"(bar), "r"(c0), "r"(c1), "r"(c2), "h"(mask) : "memory");
}
DEVI void tma_store_2d(const CUtensorMap* m, uint32_t src, int c0, int c1) {
  asm volatile("cp.async.bulk.tensor.2d.global.shared::cta.bulk_group [%0, {%2, %3}], [%1];"
               ::"l"(m), "r"(src), "r"(c0), "r"(c1) : "memory");
}
DEVI void bulk_load(uint32_t dst, const void* src, uint32_t bytes, uint32_t bar) {
  asm volatile("cp.async.bulk.shared::cluster.global.mbarrier::complete_tx::bytes [%0], [%1], %2, [%3];"
               ::"r"(dst), "l"(src), "r"(bytes), "r"(bar) : "memory");
}
DEVI void bulk_store(void* dst, uint32_t src, uint32_t bytes) {
  asm volatile("cp.async.bulk.global.shared::cta.bulk_group [%0], [%1], %2;" ::"l"(dst), "r"(src), "r"(bytes) : "memory");
}
DEVI void bulk_reduce_add_f32(void* dst, uint32_t src, uint32_t bytes) {
  asm volatile("cp.reduce.async.bulk.global.shared::cta.bulk_group.add.f32 [%0], [%1], %2;" ::"l"(dst), "r"(src), "r"(bytes) : "memory");
}
DEVI void bulk_commit() { asm volatile("cp.async.bulk.commit_group;" ::: "memory"); }
DEVI void bulk_wait0() { asm volatile("cp.async.bulk.wait_group 0;" ::: "memory"); }
DEVI void bulk_wait_read0() { asm volatile("cp.async.bulk.wait_group.read 0;" ::: "memory"); }
DEVI void l2_prefetch(const void* p, uint32_t bytes) {
  asm volatile("cp.async.bulk.prefetch.L2.global [%0], %1;" ::"l"(p), "r"(bytes) : "memory");
}
DEVI void prefetch_tmap(const CUtensorMap* m) { asm volatile("prefetch.tensormap [%0];" ::"l"(m) : "memory"); }

DEVI void red_release_add(unsigned* p, unsigned v) {
  asm volatile("red.release.gpu.global.add.u32 [%0], %1;" ::"l"(p), "r"(v) : "memory");
}
DEVI void red_relaxed_add(unsigned* p, unsigned v) {
  asm volatile("red.relaxed.gpu.global.add.u32 [%0], %1;" ::"l"(p), "r"(v) : "memory");
}
DEVI unsigned ld_relaxed(const unsigned* p) {
  unsigned v;
  asm volatile("ld.relaxed.gpu.global.u32 %0, [%1];" : "=r"(v) : "l"(p) : "memory");
  return v;
}
DEVI void wait_counter(const unsigned* p, unsigned target) {
#pragma unroll 1
  for (int it = 0; (int)(ld_relaxed(p) - target) < 0; ++it)
    if (it > (1 << 22)) __trap();
}

DEVI void ldsm_x4(uint32_t (&r)[4], uint32_t a) {
  asm volatile("ldmatrix.sync.aligned.m8n8.x4.shared.b16 {%0,%1,%2,%3}, [%4];"
               : "=r"(r[0]), "=r"(r[1]), "=r"(r[2]), "=r"(r[3]) : "r"(a) : "memory");
}
DEVI void ldsm_x4_t(uint32_t (&r)[4], uint32_t a) {
  asm volatile("ldmatrix.sync.aligned.m8n8.x4.trans.shared.b16 {%0,%1,%2,%3}, [%4];"
               : "=r"(r[0]), "=r"(r[1]), "=r"(r[2]), "=r"(r[3]) : "r"(a) : "memory");
}
DEVI void ldsm_x2_t(uint32_t& r0, uint32_t& r1, uint32_t a) {
  asm volatile("ldmatrix.sync.aligned.m8n8.x2.trans.shared.b16 {%0,%1}, [%2];" : "=r"(r0), "=r"(r1) : "r"(a) : "memory");
}
DEVI void stsm_x4(uint32_t a, uint32_t r0, uint32_t r1, uint32_t r2, uint32_t r3) {
  asm volatile("stmatrix.sync.aligned.m8n8.x4.shared.b16 [%0], {%1,%2,%3,%4};"
               ::"r"(a), "r"(r0), "r"(r1), "r"(r2), "r"(r3) : "memory");
}
DEVI void stsm_x4_t(uint32_t a, uint32_t r0, uint32_t r1, uint32_t r2, uint32_t r3) {
  asm volatile("stmatrix.sync.aligned.m8n8.x4.trans.shared.b16 [%0], {%1,%2,%3,%4};"
               ::"r"(a), "r"(r0), "r"(r1), "r"(r2), "r"(r3) : "memory");
}
DEVI uint32_t lds32(uint32_t a) { uint32_t v; asm volatile("ld.shared.b32 %0, [%1];" : "=r"(v) : "r"(a) : "memory"); return v; }
DEVI float lds_f32(uint32_t a) { float v; asm volatile("ld.shared.f32 %0, [%1];" : "=f"(v) : "r"(a) : "memory"); return v; }
DEVI void sts32(uint32_t a, uint32_t v) { asm volatile("st.shared.b32 [%0], %1;" ::"r"(a), "r"(v) : "memory"); }
DEVI void sts_f32(uint32_t a, float v) { asm volatile("st.shared.f32 [%0], %1;" ::"r"(a), "f"(v) : "memory"); }
DEVI void sts_f32x2(uint32_t a, float x, float y) { asm volatile("st.shared.v2.f32 [%0], {%1,%2};" ::"r"(a), "f"(x), "f"(y) : "memory"); }
DEVI uint4 lds128(uint32_t a) {
  uint4 v;
  asm volatile("ld.shared.v4.b32 {%0,%1,%2,%3}, [%4];" : "=r"(v.x), "=r"(v.y), "=r"(v.z), "=r"(v.w) : "r"(a) : "memory");
  return v;
}
DEVI void sts128(uint32_t a, uint32_t x, uint32_t y, uint32_t z, uint32_t w) {
  asm volatile("st.shared.v4.b32 [%0], {%1,%2,%3,%4};" ::"r"(a), "r"(x), "r"(y), "r"(z), "r"(w) : "memory");
}

DEVI void mma_bf16(float (&d)[4], uint32_t a0, uint32_t a1, uint32_t a2, uint32_t a3, uint32_t b0, uint32_t b1) {
  asm("mma.sync.aligned.m16n8k16.row.col.f32.bf16.bf16.f32 {%0,%1,%2,%3}, {%4,%5,%6,%7}, {%8,%9}, {%0,%1,%2,%3};"
      : "+f"(d[0]), "+f"(d[1]), "+f"(d[2]), "+f"(d[3])
      : "r"(a0), "r"(a1), "r"(a2), "r"(a3), "r"(b0), "r"(b1));
}
DEVI void mma_f16(float (&d)[4], const uint32_t (&a)[4], uint32_t b0, uint32_t b1) {
  asm("mma.sync.aligned.m16n8k16.row.col.f32.f16.f16.f32 {%0,%1,%2,%3}, {%4,%5,%6,%7}, {%8,%9}, {%0,%1,%2,%3};"
      : "+f"(d[0]), "+f"(d[1]), "+f"(d[2]), "+f"(d[3])
      : "r"(a[0]), "r"(a[1]), "r"(a[2]), "r"(a[3]), "r"(b0), "r"(b1));
}
DEVI void mma_bf16v(float (&d)[4], const uint32_t (&a)[4], uint32_t b0, uint32_t b1) {
  asm volatile("mma.sync.aligned.m16n8k16.row.col.f32.bf16.bf16.f32 {%0,%1,%2,%3}, {%4,%5,%6,%7}, {%8,%9}, {%0,%1,%2,%3};"
               : "+f"(d[0]), "+f"(d[1]), "+f"(d[2]), "+f"(d[3])
               : "r"(a[0]), "r"(a[1]), "r"(a[2]), "r"(a[3]), "r"(b0), "r"(b1));
}
DEVI uint32_t pack_bf16(float lo, float hi) {
  uint32_t r;
  asm("cvt.rn.bf16x2.f32 %0, %1, %2;" : "=r"(r) : "f"(hi), "f"(lo));
  return r;
}
DEVI uint32_t pack_f16(float lo, float hi) {
  uint32_t r;
  asm("cvt.rn.f16x2.f32 %0, %1, %2;" : "=r"(r) : "f"(hi), "f"(lo));
  return r;
}
DEVI uint32_t ldg16(const __nv_bfloat16* p) {
  uint32_t v;
  asm volatile("ld.global.nc.u16 %0, [%1];" : "=r"(v) : "l"(p));
  return v;
}
DEVI bool elect_one() {
  uint32_t pred;
  asm volatile("{\n.reg .pred p;\nelect.sync _|p, 0xffffffff;\nselp.u32 %0, 1, 0, p;\n}" : "=r"(pred));
  return pred != 0;
}
DEVI float bf_lo(uint32_t v) { return __uint_as_float(v << 16); }
DEVI float bf_hi(uint32_t v) { return __uint_as_float(v & 0xffff0000u); }
DEVI float bf2f(__nv_bfloat16 v) { return __bfloat162float(v); }
DEVI float round_bf16(float v) { return __bfloat162float(__float2bfloat16_rn(v)); }
DEVI float rcp(float x) { float r; asm("rcp.approx.ftz.f32 %0, %1;" : "=f"(r) : "f"(x)); return r; }
DEVI float ex2(float x) { float r; asm("ex2.approx.ftz.f32 %0, %1;" : "=f"(r) : "f"(x)); return r; }

DEVI void wg_fence() { asm volatile("wgmma.fence.sync.aligned;" ::: "memory"); }
DEVI void wg_commit() { asm volatile("wgmma.commit_group.sync.aligned;" ::: "memory"); }
template <int N> DEVI void wg_wait() { asm volatile("wgmma.wait_group.sync.aligned %0;" ::"n"(N) : "memory"); }
constexpr uint32_t DESC_HI = (1u << 30) | (1024 >> 4);
constexpr uint32_t DESC_HI64 = (2u << 30) | (512 >> 4);
DEVI uint32_t mkdesc(uint32_t saddr, uint32_t lbo) { return ((saddr & 0x3FFFF) >> 4) | ((lbo >> 4) << 16); }

#define R8(b) "%" #b
DEVI void wgmma_n192(float (&d)[96], uint32_t da, uint32_t db, int scale_d) {
  asm volatile(
      "{\n.reg .pred p;\n.reg .b64 da, db;\nsetp.ne.b32 p, %98, 0;\nmov.b64 da, {%96, %100};\nmov.b64 db, {%97, %99};\n"
      "wgmma.mma_async.sync.aligned.m64n192k16.f32.bf16.bf16 "
      "{%0,%1,%2,%3,%4,%5,%6,%7,%8,%9,%10,%11,%12,%13,%14,%15,"
      "%16,%17,%18,%19,%20,%21,%22,%23,%24,%25,%26,%27,%28,%29,%30,%31,"
      "%32,%33,%34,%35,%36,%37,%38,%39,%40,%41,%42,%43,%44,%45,%46,%47,"
      "%48,%49,%50,%51,%52,%53,%54,%55,%56,%57,%58,%59,%60,%61,%62,%63,"
      "%64,%65,%66,%67,%68,%69,%70,%71,%72,%73,%74,%75,%76,%77,%78,%79,"
      "%80,%81,%82,%83,%84,%85,%86,%87,%88,%89,%90,%91,%92,%93,%94,%95}, "
      "da, db, p, 1, 1, 0, 1;\n}"
      : "+f"(d[0]), "+f"(d[1]), "+f"(d[2]), "+f"(d[3]), "+f"(d[4]), "+f"(d[5]), "+f"(d[6]), "+f"(d[7]),
        "+f"(d[8]), "+f"(d[9]), "+f"(d[10]), "+f"(d[11]), "+f"(d[12]), "+f"(d[13]), "+f"(d[14]), "+f"(d[15]),
        "+f"(d[16]), "+f"(d[17]), "+f"(d[18]), "+f"(d[19]), "+f"(d[20]), "+f"(d[21]), "+f"(d[22]), "+f"(d[23]),
        "+f"(d[24]), "+f"(d[25]), "+f"(d[26]), "+f"(d[27]), "+f"(d[28]), "+f"(d[29]), "+f"(d[30]), "+f"(d[31]),
        "+f"(d[32]), "+f"(d[33]), "+f"(d[34]), "+f"(d[35]), "+f"(d[36]), "+f"(d[37]), "+f"(d[38]), "+f"(d[39]),
        "+f"(d[40]), "+f"(d[41]), "+f"(d[42]), "+f"(d[43]), "+f"(d[44]), "+f"(d[45]), "+f"(d[46]), "+f"(d[47]),
        "+f"(d[48]), "+f"(d[49]), "+f"(d[50]), "+f"(d[51]), "+f"(d[52]), "+f"(d[53]), "+f"(d[54]), "+f"(d[55]),
        "+f"(d[56]), "+f"(d[57]), "+f"(d[58]), "+f"(d[59]), "+f"(d[60]), "+f"(d[61]), "+f"(d[62]), "+f"(d[63]),
        "+f"(d[64]), "+f"(d[65]), "+f"(d[66]), "+f"(d[67]), "+f"(d[68]), "+f"(d[69]), "+f"(d[70]), "+f"(d[71]),
        "+f"(d[72]), "+f"(d[73]), "+f"(d[74]), "+f"(d[75]), "+f"(d[76]), "+f"(d[77]), "+f"(d[78]), "+f"(d[79]),
        "+f"(d[80]), "+f"(d[81]), "+f"(d[82]), "+f"(d[83]), "+f"(d[84]), "+f"(d[85]), "+f"(d[86]), "+f"(d[87]),
        "+f"(d[88]), "+f"(d[89]), "+f"(d[90]), "+f"(d[91]), "+f"(d[92]), "+f"(d[93]), "+f"(d[94]), "+f"(d[95])
      : "r"(da), "r"(db), "r"(scale_d), "n"(DESC_HI), "n"(DESC_HI64));
}
DEVI void wgmma_n64(float (&d)[32], uint32_t da, uint32_t db, int scale_d) {
  asm volatile(
      "{\n.reg .pred p;\n.reg .b64 da, db;\nsetp.ne.b32 p, %34, 0;\nmov.b64 da, {%32, %35};\nmov.b64 db, {%33, %35};\n"
      "wgmma.mma_async.sync.aligned.m64n64k16.f32.bf16.bf16 "
      "{%0,%1,%2,%3,%4,%5,%6,%7,%8,%9,%10,%11,%12,%13,%14,%15,"
      "%16,%17,%18,%19,%20,%21,%22,%23,%24,%25,%26,%27,%28,%29,%30,%31}, "
      "da, db, p, 1, 1, 0, 1;\n}"
      : "+f"(d[0]), "+f"(d[1]), "+f"(d[2]), "+f"(d[3]), "+f"(d[4]), "+f"(d[5]), "+f"(d[6]), "+f"(d[7]),
        "+f"(d[8]), "+f"(d[9]), "+f"(d[10]), "+f"(d[11]), "+f"(d[12]), "+f"(d[13]), "+f"(d[14]), "+f"(d[15]),
        "+f"(d[16]), "+f"(d[17]), "+f"(d[18]), "+f"(d[19]), "+f"(d[20]), "+f"(d[21]), "+f"(d[22]), "+f"(d[23]),
        "+f"(d[24]), "+f"(d[25]), "+f"(d[26]), "+f"(d[27]), "+f"(d[28]), "+f"(d[29]), "+f"(d[30]), "+f"(d[31])
      : "r"(da), "r"(db), "r"(scale_d), "n"(DESC_HI));
}

struct C32 { float re, im; };
DEVI C32 csq(C32 a) { return {a.re * a.re - a.im * a.im, 2.f * a.re * a.im}; }
DEVI C32 cmul(C32 a, C32 b) { return {a.re * b.re - a.im * b.im, a.re * b.im + a.im * b.re}; }
DEVI C32 cfresh(float zl, float zi, float m) {
  float mag = ex2(zl * m), ph = zi * m;
  return {mag * __cosf(ph), mag * __sinf(ph)};
}
struct HMul { uint32_t b, bp; };
DEVI HMul mk_mul(float re, float im) { return {pack_f16(re, im), pack_f16(-im, re)}; }
DEVI uint32_t hcmul(uint32_t a, const HMul& m) {
  __half2 ah = *reinterpret_cast<__half2*>(&a);
  __half2 b = *reinterpret_cast<const __half2*>(&m.b), bp = *reinterpret_cast<const __half2*>(&m.bp);
  __half2 r = __hfma2(__high2half2(ah), bp, __hmul2(__low2half2(ah), b));
  return *reinterpret_cast<uint32_t*>(&r);
}
DEVI uint32_t badd(uint32_t a, uint32_t b) {
  __nv_bfloat162 r = __hadd2(*reinterpret_cast<__nv_bfloat162*>(&a), *reinterpret_cast<__nv_bfloat162*>(&b));
  return *reinterpret_cast<uint32_t*>(&r);
}
template <int MU0, int NMU, int DMAX>
DEVI void conv_tail(float (&acc)[16][4], uint32_t p_lane, uint32_t v_base, int back, bool edge, int lane) {
  const int hsel = (lane >> 3) & 1;
  const int row = (lane & 7) + ((lane >> 4) << 3) + PADV - 8 - (back & (hsel ^ 1));
  const uint32_t la = v_base + row * 32 + (((hsel ^ back) ^ ((row >> 2) & 1)) << 4);
  uint32_t M[3][4];
  ldsm_x4_t(M[0], la);
  ldsm_x4_t(M[1], la + 256);
  uint32_t H[2 * NMU];
#pragma unroll
  for (int i = 0; i < 2 * NMU; ++i) H[i ^ 1] = lds32(p_lane + (uint32_t)(MU0 - 1 + i) * 32);
  if (edge) {
    const uint32_t a[4] = {0u, 0u, M[0][0], M[0][1]};
#pragma unroll
    for (int k = 1; k < NMU; ++k) mma_bf16v(acc[MU0 - 2 + 2 * k], a, H[2 * k], H[2 * k + 1]);
  }
#pragma unroll
  for (int delta = -1; delta <= DMAX; ++delta) {
    if (delta + 2 <= DMAX) ldsm_x4_t(M[(delta + 3) % 3], la + (delta + 3) * 256);
#pragma unroll
    for (int k = 0; k < NMU; ++k)
      if (delta + MU0 + 2 * k < 16) mma_bf16v(acc[delta + MU0 + 2 * k], M[(delta + 1) % 3], H[2 * k], H[2 * k + 1]);
  }
}

__global__ void __cluster_dims__(2, 1, 1) __launch_bounds__(NTHREADS, 1)
fused_kernel(const __grid_constant__ Maps maps, const Ptrs p) {
  extern __shared__ __align__(1024) uint8_t smem[];
  const uint32_t sb = s2u(smem);
  const int tid = threadIdx.x, lane = tid & 31;
  const int warp = __shfl_sync(0xffffffffu, tid >> 5, 0);
  const int cta = blockIdx.x;
  const uint32_t rank = cta & 1;
  const int ti = 2 * (cta >> 4) + rank;
  const int tj = (cta >> 1) & 7;
  const int pi = cta >> 3, pj = cta & 7;
  const uint32_t bars = sb + SM_BAR;
#define BAR(i) (bars + 8 * (i))
  const int g = lane >> 2, q = lane & 3;

  auto issue_stage = [&](int ks, int s) {
    const uint32_t st = sb + s * STG_BYTES, fb = BAR(B_FULL + s);
    mbar_expect_tx(fb, STG_BYTES);
    tma_load_2d(st + STG_X, &maps.x, ks * 32, ti * 128, fb);
    tma_load_3d_mc(st + STG_W + rank * 6144, &maps.w, tj * 64, ks * 32 + rank * 16, 0, fb, 3);
  };

  const int kch = warp & 3, krd = warp >> 2;
  float zr, zi, wr, wi;
  unsigned epoch;
  uint32_t r_dskip;
  {
    const size_t po = (size_t)(cta * 4 + kch) * 128 + krd * 32 + lane;
    const uint32_t r_ar = ldg16(p.A_re + po), r_ai = ldg16(p.A_im + po), r_br = ldg16(p.B_re + po), r_bi = ldg16(p.B_im + po);
    const uint32_t r_cr = ldg16(p.C_re + po), r_ci = ldg16(p.C_im + po), r_ldt = ldg16(p.log_dt + cta * 4 + kch);
    epoch = __ldcg(&g_epoch);
    r_dskip = ldg16(p.Dskip + cta * 4 + kch);
    uint4 pt;
    if (tid < 128) pt = __ldg((const uint4*)g_ptab.v + tid);
    if (tid == 384) {
      TS(0);
#pragma unroll
      for (int i = 0; i < B_COUNT; ++i) mbar_init(BAR(i), bar_count(i));
      asm volatile("fence.mbarrier_init.release.cluster;" ::: "memory");
      prefetch_tmap(&maps.x); prefetch_tmap(&maps.w); prefetch_tmap(&maps.u);
    }
    __syncthreads();
    cluster_arrive();
    if (warp >= 12) {
      cluster_wait();
      if (elect_one()) {
        if (warp == 13) {
          mbar_expect_tx(BAR(B_TILE), 16384);
          tma_load_2d(sb + SM_U, &maps.u, tj * 64, ti * 128, BAR(B_TILE));
          prefetch_tmap(&maps.uT); prefetch_tmap(&maps.wo); prefetch_tmap(&maps.o); prefetch_tmap(&maps.yT);
          prefetch_tmap(&maps.out);
        } else {
          if (warp == 12) TS(61);
          { const int ks = warp == 12 ? 0 : warp - 13; issue_stage(ks, ks); }
        }
      }
      __syncwarp();
    }
    if (tid < 128) sts128(sb + SM_PTAB + tid * 16, pt.x, pt.y, pt.z, pt.w);
    const float dt = round_bf16(expf(bf_lo(r_ldt)));
    zr = dt * bf_lo(r_ar); zi = dt * bf_lo(r_ai);
    const float dbr = dt * bf_lo(r_br), dbi = dt * bf_lo(r_bi), cr = bf_lo(r_cr), ci = bf_lo(r_ci);
    wr = cr * dbr - ci * dbi; wi = cr * dbi + ci * dbr;
  }
  {
    const float mz = __uint_as_float(__reduce_max_sync(0xffffffffu, __float_as_uint(fmaxf(zr, 0.f))));
    const int E = min(max((int)(__reduce_max_sync(0xffffffffu, __float_as_uint(fmaxf(fabsf(wr), fabsf(wi)))) >> 23), 1), 252);
    const float sc = __int_as_float((253 - E) << 23), inv = __int_as_float((E + 1) << 23);
    const float zl = (zr - mz) * 1.4426950408889634f;
    const uint32_t tb = sb + SM_VV + kch * VV_BYTES + krd * KG_BYTES;
    const uint32_t sta = tb + (((lane >> 2) << 4) | ((lane & 3) << 2));
    auto put = [&](int r, uint32_t v) { sts32((sta ^ ((r & 7) << 4)) + r * 128, v); };
    const uint32_t lda = tb + ((lane & 7) + (((lane >> 3) & 1) << 3)) * 128;
    const uint32_t ldb = tb + ((lane & 7) + ((lane >> 4) << 3)) * 128;
    C32 e1 = cfresh(zl, zi, 1.f), e2 = csq(e1), e4 = csq(e2), e8 = csq(e4);
    C32 e16 = cfresh(zl, zi, 16.f), e32 = csq(e16), e64 = csq(e32), e128 = csq(e64);
    C32 e256 = cfresh(zl, zi, 256.f), e512 = csq(e256), e1024 = csq(e512), e768 = cmul(e512, e256);
    uint32_t XA[2][4][4];
    {
      const HMul m16 = mk_mul(e16.re, e16.im), m32 = mk_mul(e32.re, e32.im), m64 = mk_mul(e64.re, e64.im);
      const HMul m128 = mk_mul(e128.re, e128.im);
      uint32_t X[16];
      X[0] = 0x00003c00u; X[1] = pack_f16(e8.re, e8.im); X[2] = m16.b; X[4] = m32.b; X[8] = m64.b;
      X[3] = hcmul(X[1], m16); X[5] = hcmul(X[1], m32); X[6] = hcmul(X[2], m32); X[7] = hcmul(X[3], m32);
#pragma unroll
      for (int r = 1; r < 8; ++r) X[8 + r] = hcmul(X[r], m64);
#pragma unroll
      for (int h = 0; h < 2; ++h) {
#pragma unroll
        for (int r = 0; r < 16; ++r) put(r, h == 0 ? X[r] : r == 0 ? m128.b : hcmul(X[r], m128));
        __syncwarp();
#pragma unroll
        for (int k = 0; k < 4; ++k) ldsm_x4(XA[h][k], lda + (((2 * k + (lane >> 4)) ^ (lane & 7)) << 4));
        __syncwarp();
      }
    }
    if (warp >= 14 && elect_one()) {
      issue_stage(warp - 11, warp - 11);
      issue_stage(warp - 9, warp - 9);
      if (warp == 14) l2_prefetch((const char*)p.wqkv + 224 * 3072 + cta * 6912, 6912);
      else l2_prefetch((const char*)p.x + (size_t)cta * 16384, 16384);
    }
    __syncwarp();
    float D[2][3][4];
#pragma unroll
    for (int t = 0; t < 6; ++t) D[t / 3][t % 3][0] = D[t / 3][t % 3][1] = D[t / 3][t % 3][2] = D[t / 3][t % 3][3] = 0.f;
    auto contract = [&](int t0, int nt) {
      __syncwarp();
#pragma unroll
      for (int k = 0; k < 4; ++k) {
        uint32_t b[4];
        ldsm_x4(b, ldb + (((2 * k + ((lane >> 3) & 1)) ^ (lane & 7)) << 4));
#pragma unroll
        for (int h = 0; h < 2; ++h) {
          mma_f16(D[h][t0], XA[h][k], b[0], b[1]);
          if (nt == 2) mma_f16(D[h][t0 + 1], XA[h][k], b[2], b[3]);
        }
      }
      __syncwarp();
    };
    const HMul c1 = mk_mul(e1.re, -e1.im), c2 = mk_mul(e2.re, -e2.im), c4 = mk_mul(e4.re, -e4.im);
    const HMul c256 = mk_mul(e256.re, -e256.im), c512 = mk_mul(e512.re, -e512.im), c768 = mk_mul(e768.re, -e768.im);
    const HMul c1024 = mk_mul(e1024.re, -e1024.im);
    uint32_t W[8];
    W[0] = pack_f16(wr * sc, -wi * sc);
    W[1] = hcmul(W[0], c1); W[2] = hcmul(W[0], c2); W[3] = hcmul(W[1], c2);
    W[4] = hcmul(W[0], c4); W[5] = hcmul(W[1], c4); W[6] = hcmul(W[2], c4); W[7] = hcmul(W[3], c4);
#pragma unroll
    for (int i = 0; i < 8; ++i) put(i, W[i]);
#pragma unroll
    for (int i = 0; i < 4; ++i) put(8 + i, hcmul(W[2 * i], c256));
    put(12, hcmul(W[0], c512)); put(13, hcmul(W[4], c512)); put(14, hcmul(W[0], c768)); put(15, hcmul(W[4], c768));
    contract(0, 2);
    const uint32_t v0 = hcmul(W[0], c1024);
    put(0, v0); put(1, hcmul(v0, c256)); put(2, hcmul(v0, c512)); put(3, hcmul(v0, c768)); put(4, hcmul(v0, c1024));
    contract(2, 1);
    const uint32_t a = tb + (g * 24 + 2 * q) * 4;
#pragma unroll
    for (int t = 0; t < 6; ++t) {
      const float(&d)[4] = D[t / 3][t % 3];
      sts_f32x2(a + (t / 3) * 1536 + (t % 3) * 32, d[0] * inv, d[1] * inv);
      sts_f32x2(a + (t / 3) * 1536 + (t % 3) * 32 + 768, d[2] * inv, d[3] * inv);
    }
    if (mz > 0.f) {
      __syncwarp();
#pragma unroll 1
      for (int i = lane; i < 768; i += 32) {
        const int r = i / 24, y = i - 24 * r;
        sts_f32(tb + i * 4, lds_f32(tb + i * 4) * ex2(mz * 1.4426950408889634f * (koff(y) + 8 * r)));
      }
    }
  }
  if (tid == 0) TS(2);
  if (warp < 12) cluster_wait();
  __syncthreads();

  if (warp < 4) {
#define A_REGS 200
    asm volatile("setmaxnreg.inc.sync.aligned.u32 %0;" ::"n"(A_REGS));
    if (tid == 0) TS(34);
    const int d = cta * 4 + warp;
    const uint32_t vv = sb + SM_VV + warp * VV_BYTES;
    const uint32_t ub = sb + SM_U + warp * U_BYTES;
    const uint32_t pb = sb + SM_P + warp * P_BYTES;
    const float dskip = bf_lo(r_dskip);
#pragma unroll 1
    for (int pass = 0; pass < 2; ++pass) {
      if (pass == 1) {
        const uint32_t kf = vv;
#pragma unroll 2
        for (int i = 0; i < 6; ++i) {
          const uint32_t a = kf + (i * 32 + lane) * 16;
          const uint4 x0 = lds128(a), x1 = lds128(a + KG_BYTES), x2 = lds128(a + 2 * KG_BYTES), x3 = lds128(a + 3 * KG_BYTES);
          auto s4 = [](uint32_t a0, uint32_t a1, uint32_t a2, uint32_t a3) {
            return __float_as_uint((__uint_as_float(a0) + __uint_as_float(a1)) + (__uint_as_float(a2) + __uint_as_float(a3)));
          };
          sts128(a, s4(x0.x, x1.x, x2.x, x3.x), s4(x0.y, x1.y, x2.y, x3.y), s4(x0.z, x1.z, x2.z, x3.z), s4(x0.w, x1.w, x2.w, x3.w));
        }
        __syncwarp();
        const float k1024 = lds_f32(kf + kidx_c(1024) * 4);
        if (lane == 0) {
          sts_f32(kf + SL_ZERO * 4, 0.f);
          sts_f32(kf + SL_510 * 4, lds_f32(kf + kidx_c(510) * 4) - lds_f32(kf + kidx_c(512) * 4));
          sts_f32(kf + SL_0 * 4, lds_f32(kf) + dskip);
        }
        __syncwarp();
        if (tid == 0) TS(36);
        mbar_wait_long(BAR(B_PFREE), 0);
        if (tid == 0) TS(37);
        {
          float prev = 0.f;
#pragma unroll 1
          for (int i0 = 0; i0 < 16; i0 += 4) {
            uint32_t e[4];
            float a[4], b[4];
#pragma unroll
            for (int i = 0; i < 4; ++i) e[i] = lds32(sb + SM_PTAB + ((i0 + i) * 32 + lane) * 4);
#pragma unroll
            for (int i = 0; i < 4; ++i) { a[i] = lds_f32(kf + (e[i] & 0xffff)); b[i] = lds_f32(kf + (e[i] >> 16)); }
#pragma unroll
            for (int i = 0; i < 4; ++i) {
              const uint32_t w = pb + (31 * lane + 2 * (i0 + i)) * 4;
              if (i0 + i > 0) sts32(w - 4, pack_bf16(a[i], prev));
              sts32(w, pack_bf16(b[i], a[i]));
              prev = b[i];
            }
          }
        }
        __syncwarp();
        if (lane == 0) TS(4);
        const int gq = g - 2 * q;
        uint32_t h127, h128;
        {
          const uint32_t kf2 = pack_bf16(k1024, k1024) ^ 0x80008000u;
          h127 = (gq == 4 ? 0x0000ffffu : gq == 5 ? 0xffffffffu : gq == 6 ? 0xffff0000u : 0u) & kf2;
          h128 = (gq == -4 ? 0x0000ffffu : gq == -3 ? 0xffffffffu : gq == -2 ? 0xffff0000u : 0u) & kf2;
        }
        bar_sync(4, 480);
        mbar_wait_long(BAR(B_UCH + warp), 0);
        if (lane == 0) TS(7);
        float acc[16][4];
#pragma unroll
        for (int i = 0; i < 16; ++i) { acc[i][0] = acc[i][1] = acc[i][2] = acc[i][3] = 0.f; }
        {
          const uint32_t pd_lane = pb + (PD_OFF + 16 + gq) * 4;
          const int prow0 = 8 + (lane & 7) + ((lane >> 4) << 3), hs = (lane >> 3) & 1;
          const uint32_t zero = (uint32_t)cta >> 20;
          uint32_t B[2][4][4];
          uint32_t A[4][4];
          const uint32_t la0 = ub + prow0 * 32 + ((hs ^ ((prow0 >> 2) & 1)) << 4);
#pragma unroll
          for (int m2 = 0; m2 < 4; ++m2) ldsm_x4(B[0][m2], la0 + m2 * 512);
#pragma unroll
          for (int i = 0; i < 4; ++i) {
            const uint32_t a = pd_lane + i * 512;
            A[i][0] = lds32(a); A[i][1] = lds32(a + 32); A[i][2] = lds32(a - 32); A[i][3] = lds32(a + zero);
          }
          uint32_t la = la0;
#define UNR_RHO 1
#define UNR_TAIL 1
          constexpr int unr_rho = UNR_RHO, unr_tail = UNR_TAIL;
#pragma unroll unr_rho
          for (int rho = 0; rho < 8; ++rho) {
#pragma unroll
            for (int m2 = 0; m2 < 4; ++m2) ldsm_x4(B[1][m2], la + (4 + m2) * 512);
#pragma unroll
            for (int i = 0; i < 4; ++i)
#pragma unroll
              for (int m = 0; m < 8; ++m) mma_bf16v(acc[m + i], A[i], B[0][m >> 1][2 * (m & 1)], B[0][m >> 1][2 * (m & 1) + 1]);
            const int prow = prow0 - min(rho + 1, 7);
            la = ub + prow * 32 + ((hs ^ ((prow >> 2) & 1)) << 4);
#pragma unroll
            for (int m2 = 0; m2 < 4; ++m2) ldsm_x4(B[0][m2], la + m2 * 512);
            const uint32_t pa = pd_lane + (rho + 1) * 64;
#pragma unroll
            for (int i = 0; i < 4; ++i) {
#pragma unroll
              for (int m = 0; m < 8 - i; ++m)
                mma_bf16v(acc[8 + m + i], A[i], B[1][m >> 1][2 * (m & 1)], B[1][m >> 1][2 * (m & 1) + 1]);
              A[i][0] = lds32(pa + i * 512); A[i][1] = lds32(pa + i * 512 + 32); A[i][2] = lds32(pa + i * 512 - 32);
              A[i][3] = lds32(pa + i * 512 + zero);
            }
          }
          if (lane == 0) TS(40);
          {
            uint32_t b8[4];
            ldsm_x4(b8, la + 4 * 512);
            const uint32_t h63 = lds32(pd_lane + 63 * 32), h64 = lds32(pd_lane + 64 * 32);
            const uint32_t a63[4] = {0u, h127, 0u, 0u}, a32[4] = {h64, 0u, h63, h64}, a64[4] = {h128, 0u, h127, h128};
#pragma unroll
            for (int m2 = 0; m2 < 4; ++m2) ldsm_x4(B[1][m2], la0 + m2 * 512);
#pragma unroll
            for (int m = 0; m < 8; ++m) mma_bf16v(acc[m + 7], a63, B[0][m >> 1][2 * (m & 1)], B[0][m >> 1][2 * (m & 1) + 1]);
#pragma unroll
            for (int m2 = 0; m2 < 2; ++m2) ldsm_x4(B[0][m2], la0 + (4 + m2) * 512);
#pragma unroll
            for (int m = 0; m < 8; ++m) mma_bf16v(acc[m + 4], a32, B[1][m >> 1][2 * (m & 1)], B[1][m >> 1][2 * (m & 1) + 1]);
            mma_bf16v(acc[15], a63, b8[0], b8[1]);
#pragma unroll
            for (int m = 0; m < 8; ++m) mma_bf16v(acc[m + 8], a64, B[1][m >> 1][2 * (m & 1)], B[1][m >> 1][2 * (m & 1) + 1]);
#pragma unroll
            for (int m = 0; m < 4; ++m) mma_bf16v(acc[m + 12], a32, B[0][m >> 1][2 * (m & 1)], B[0][m >> 1][2 * (m & 1) + 1]);
          }
          if (lane == 0) TS(41);
          bar_sync(5, 224);
#pragma unroll unr_tail
          for (int v = 0; v < 4; ++v)
            conv_tail<4, 3, 11>(acc, pb + (P2_OFF + 56 * v + gq - 16) * 4, vv + ((v & 1) ? VV_U3 : VV_U5), v >> 1, v == 0, lane);
          if (lane == 0) TS(42);
#pragma unroll unr_tail
          for (int pi = 0; pi < 2; ++pi)
            conv_tail<8, 5, 7>(acc, pb + (P3_OFF + 88 * pi + gq - 48) * 4, vv + (pi ? VV_U7 : VV_U9), pi, pi == 0, lane);
        }
        if (lane == 0) TS(8);
        __syncwarp();
        {
          const int mt = lane >> 3;
          const uint32_t a = pb + (128 * (mt >> 1) + 16 * (lane & 7) + 8 * (mt & 1)) * 2;
#pragma unroll
          for (int ab = 0; ab < 16; ab += 2)
            stsm_x4_t(a + ab * 256, pack_bf16(acc[ab][0], acc[ab][1]), pack_bf16(acc[ab][2], acc[ab][3]),
                      pack_bf16(acc[ab + 1][0], acc[ab + 1][1]), pack_bf16(acc[ab + 1][2], acc[ab + 1][3]));
        }
        fence_async_smem();
        __syncwarp();
        if (lane < 2) mbar_arrive_cluster(BAR(B_CONVD), lane);
        bar_arrive(3, 384);
        if (elect_one()) {
          bulk_store(p.yT + (size_t)d * 2048, pb, 4096);
          bulk_commit();
          bulk_wait0();
          red_relaxed_add(&g_cnt[(C_Y + (cta >> 4)) * 32], 1);
          TS(9);
        }
        bar_sync(2, 128);
        if (warp == 0 && elect_one()) {
          wait_counter(&g_cnt[(C_Y + tj) * 32], (epoch + 1) * 64);
          TS(28);
          mbar_expect_tx(BAR(B_TILE), 16384);
          tma_load_2d(sb + SM_U, &maps.yT, ti * 128, tj * 64, BAR(B_TILE));
          tma_load_2d(sb + SM_U + 8192, &maps.yT, ti * 128 + 64, tj * 64, BAR(B_TILE));
        }
        __syncwarp();
      }
      mbar_wait_long(BAR(B_TILE), pass);
      if (lane == 0) TS(26 + 3 * pass);
      {
        const int m = lane >> 3, r = lane & 7;
#pragma unroll 2
        for (int it = 0; it < 8; ++it) {
          const int tb = warp * 4 + (it >> 1), cb = (it & 1) * 4 + m;
          const uint32_t at = (tb * 8 + r) * 128 + ((cb ^ r) << 4);
          const uint32_t ac = (tb >> 3) * 8192 + (cb * 8 + r) * 128 + (((tb & 7) ^ (pass ? 0 : tb >> 3) ^ r) << 4);
          uint32_t v[4];
          ldsm_x4_t(v, sb + SM_U + (pass ? ac : at));
          stsm_x4(sb + SM_P + (pass ? at : ac), v[0], v[1], v[2], v[3]);
        }
      }
      if (pass == 0 && tid == 0) TS(35);
      fence_async_smem();
      if (pass == 0) {
        bar_arrive(6, 160);
      } else {
        bar_sync(2, 128);
        if (warp == 0 && elect_one()) {
          tma_store_2d(&maps.out, sb + SM_P, 64 * tj, 128 * ti);
          bulk_commit();
          bulk_wait_read0();
          TS(30);
        }
      }
    }
  } else if (warp < 12) {
    const int w8 = warp - 4;
    const int row = w8 * 16 + (lane & 7) + (((lane >> 3) & 1) << 3);
    uint32_t pq[16];
    {
      float acc[96];
#pragma unroll 1
      for (int ks = 0, s = 0, ph = 0; ks < 16; ++ks) {
        mbar_wait(BAR(B_FULL + s), ph);
        if (tid == 128 && !(ks & 1)) TSR(16, ks == 0 ? 16 : 9 + (ks >> 1) + (ks > 12 ? 43 : 0));
        const uint32_t st = sb + s * STG_BYTES;
        const uint32_t da = mkdesc(st + STG_X + (w8 >> 2) * 4096, 16);
        const uint32_t db = mkdesc(st + STG_W, 2048);
        wg_fence();
        wgmma_n192(acc, da, db, ks != 0);
        wgmma_n192(acc, da + 2, db + 384, 1);
        wg_commit();
        const uint32_t eprev = BAR(B_EMPTY + (s == 0 ? NSTG - 1 : s - 1));
        if (++s == NSTG) { s = 0; ph ^= 1; }
        if (ks > 0) {
          wg_wait<1>();
          if (lane < 2) mbar_arrive_cluster(eprev, lane);
        }
      }
      wg_wait<0>();
      bar_arrive(4, 480);
      if (tid == 128) TS(17);
      auto phi2 = [](float a, float b) -> uint32_t {
        const uint32_t x = pack_bf16(a, b);
        const uint32_t e = pack_bf16(ex2(bf_lo(x) * 1.4426950408889634f), ex2(bf_hi(x) * 1.4426950408889634f));
        const uint32_t m = __hgt2_mask(*reinterpret_cast<const __nv_bfloat162*>(&x), __floats2bfloat162_rn(0.f, 0.f));
        return badd((badd(x, 0x3f803f80u) & m) | (e & ~m), 0x35863586u);
      };
      uint32_t pk[16];
#pragma unroll
      for (int i = 0; i < 16; ++i) pk[i] = phi2(acc[32 + 2 * i], acc[33 + 2 * i]);
      if (tid == 128) TS(53);
      bar_sync(1, 256);
#pragma unroll
      for (int i = 0; i < 8; i += 2) {
        const uint32_t off = row * 128 + (((i + (lane >> 4)) ^ (row & 7)) << 4);
        stsm_x4(sb + SM_PK + off, pk[2 * i], pk[2 * i + 1], pk[2 * i + 2], pk[2 * i + 3]);
        stsm_x4(sb + SM_VS + off, pack_bf16(acc[64 + 4 * i], acc[65 + 4 * i]), pack_bf16(acc[66 + 4 * i], acc[67 + 4 * i]),
                pack_bf16(acc[68 + 4 * i], acc[69 + 4 * i]), pack_bf16(acc[70 + 4 * i], acc[71 + 4 * i]));
      }
      bar_sync(1, 256);
      {
        const int hh = w8 >> 1, dtile = w8 & 1;
        float kv[2][4] = {{0.f, 0.f, 0.f, 0.f}, {0.f, 0.f, 0.f, 0.f}}, zz[2][4] = {{0.f, 0.f, 0.f, 0.f}, {0.f, 0.f, 0.f, 0.f}};
        const int m = lane >> 3;
        const uint32_t aa = sb + SM_VS + ((lane & 7) + ((m >> 1) << 3)) * 128 + (((2 * hh + (m & 1)) ^ (lane & 7)) << 4);
        const uint32_t ab = sb + SM_PK + (lane & 15) * 128 + (((2 * hh + dtile) ^ (lane & 7)) << 4);
#pragma unroll
        for (int ks = 0; ks < 8; ++ks) {
          uint32_t a[4], b0, b1;
          ldsm_x4_t(a, aa + ks * 2048);
          ldsm_x2_t(b0, b1, ab + ks * 2048);
          mma_bf16(kv[ks & 1], a[0], a[1], a[2], a[3], b0, b1);
          mma_bf16(zz[ks & 1], 0x3f803f80u, 0x3f803f80u, 0x3f803f80u, 0x3f803f80u, b0, b1);
        }
        const uint32_t kp = sb + SM_KV + hh * 1088;
        sts128(kp + dtile * 512 + lane * 16, __float_as_uint(kv[0][0] + kv[1][0]), __float_as_uint(kv[0][1] + kv[1][1]),
               __float_as_uint(kv[0][2] + kv[1][2]), __float_as_uint(kv[0][3] + kv[1][3]));
        if (g == 0) sts_f32x2(kp + 1024 + dtile * 32 + q * 8, zz[0][0] + zz[1][0], zz[0][1] + zz[1][1]);
        fence_async_smem();
        __syncwarp();
        if (lane == 0) mbar_arrive(BAR(B_KVP));
        if (tid == 128) TS(55);
      }
#pragma unroll
      for (int i = 0; i < 16; ++i) pq[i] = phi2(acc[2 * i], acc[2 * i + 1]);
    }
    if (tid == 128) TS(56);
    if (warp == 4) mbar_wait_long(BAR(B_KVF), 0);
    bar_sync(1, 256);
    if (tid == 128) TS(19);
    {
      uint32_t kb[4][6];
#pragma unroll
      for (int h = 0; h < 4; ++h) {
        const uint32_t kp = sb + SM_KV + h * 1088;
        const uint4 k0 = lds128(kp + lane * 16), k1 = lds128(kp + 512 + lane * 16);
        const uint32_t za = kp + 1024 + q * 8;
        auto pk2 = [](uint32_t x, uint32_t y) { return pack_bf16(__uint_as_float(x), __uint_as_float(y)); };
        kb[h][0] = pk2(k0.x, k0.y); kb[h][1] = pk2(k1.x, k1.y); kb[h][2] = pk2(k0.z, k0.w); kb[h][3] = pk2(k1.z, k1.w);
        kb[h][4] = pack_bf16(lds_f32(za), lds_f32(za + 4)); kb[h][5] = pack_bf16(lds_f32(za + 32), lds_f32(za + 36));
      }
#pragma unroll
      for (int h = 0; h < 4; ++h) {
        float n0[4] = {0.f, 0.f, 0.f, 0.f}, n1[4] = {0.f, 0.f, 0.f, 0.f}, dn[4] = {0.f, 0.f, 0.f, 0.f};
        mma_bf16(n0, pq[4 * h], pq[4 * h + 1], pq[4 * h + 2], pq[4 * h + 3], kb[h][0], kb[h][1]);
        mma_bf16(n1, pq[4 * h], pq[4 * h + 1], pq[4 * h + 2], pq[4 * h + 3], kb[h][2], kb[h][3]);
        mma_bf16(dn, pq[4 * h], pq[4 * h + 1], pq[4 * h + 2], pq[4 * h + 3], kb[h][4], kb[h][5]);
        const uint32_t dd = pack_bf16(dn[0], dn[2]);
        const uint32_t d2 = pack_bf16(bf_lo(dd) + 1e-6f, bf_hi(dd) + 1e-6f);
        const float r0 = rcp(bf_lo(d2)), r1 = rcp(bf_hi(d2));
        const uint32_t x0 = pack_bf16(n0[0], n0[1]), x1 = pack_bf16(n0[2], n0[3]);
        const uint32_t x2 = pack_bf16(n1[0], n1[1]), x3 = pack_bf16(n1[2], n1[3]);
        stsm_x4(sb + SM_QS + row * 128 + (((2 * h + (lane >> 4)) ^ (row & 7)) << 4),
                pack_bf16(bf_lo(x0) * r0, bf_hi(x0) * r0), pack_bf16(bf_lo(x1) * r1, bf_hi(x1) * r1),
                pack_bf16(bf_lo(x2) * r0, bf_hi(x2) * r0), pack_bf16(bf_lo(x3) * r1, bf_hi(x3) * r1));
      }
    }
    fence_async_smem();
    __syncwarp();
    if (lane == 0) mbar_arrive(BAR(B_OST));
    if (tid == 128) TS(57);
    if (warp == 4) mbar_wait_long(BAR(B_WO), 0);
    bar_sync(3, 384);
    {
      float o[32];
#pragma unroll 1
      for (int c = 0; c < 8; ++c) {
        mbar_wait_long(BAR(B_RF + c), 0);
        if (tid == 128) TSR(22, c == 0 ? 22 : 43 + c);
        const uint32_t slot = c < 4 ? SM_QS + c * 16384 : c < 7 ? SM_VV + (c - 4) * 16384 : SM_QS;
        const uint32_t da = mkdesc(sb + slot + (w8 >> 2) * 8192, 16);
        const uint32_t db = mkdesc(sb + SM_WO + c * 8192, 8192);
        wg_fence();
#pragma unroll
        for (int k = 0; k < 4; ++k) wgmma_n64(o, da + 2 * k, db + 128 * k, (c | k) != 0);
        wg_commit();
        if (c == 1) {
          wg_wait<1>();
          if (lane < 2) mbar_arrive_cluster(BAR(B_RE), lane);
        }
      }
      wg_wait<0>();
      if (tid == 128) TS(51);
      bar_sync(1, 256);
#pragma unroll
      for (int i = 0; i < 8; i += 2)
        stsm_x4(sb + SM_BOUT + row * 128 + (((i + (lane >> 4)) ^ (row & 7)) << 4), pack_bf16(o[4 * i], o[4 * i + 1]),
                pack_bf16(o[4 * i + 2], o[4 * i + 3]), pack_bf16(o[4 * i + 4], o[4 * i + 5]), pack_bf16(o[4 * i + 6], o[4 * i + 7]));
      fence_async_smem();
      bar_sync(1, 256);
      if (tid == 128) TS(52);
      if (warp == 4 && elect_one()) {
        tma_store_2d(&maps.out, sb + SM_BOUT, 512 + 64 * pj, 128 * pi);
        bulk_commit();
        bulk_wait_read0();
        TS(23);
      }
    }
  } else {
    asm volatile("setmaxnreg.dec.sync.aligned.u32 40;");
    if (warp == 12) {
      if (elect_one()) {
#pragma unroll 1
        for (int ks = NSTG, s = 0, ph = 0; ks < 16; ++ks) {
          mbar_wait(BAR(B_EMPTY + s), ph);
          issue_stage(ks, s);
          if (ks == NSTG) l2_prefetch((const char*)p.wo + (size_t)cta * 4096, 4096);
          if (++s == NSTG) { s = 0; ph ^= 1; }
        }
        mbar_wait(BAR(B_EMPTY + 6), 1);
        mbar_expect_tx(BAR(B_WO), 65536);
        tma_load_2d(sb + SM_WO, &maps.wo, pj * 64, 0, BAR(B_WO));
        tma_load_2d(sb + SM_WO + 32768, &maps.wo, pj * 64, 256, BAR(B_WO));
        float* kvg = &g_kv[epoch & 1][tj][0];
        mbar_wait_long(BAR(B_KVP), 0);
        bulk_reduce_add_f32(kvg, sb + SM_KV, 4352);
        bulk_commit();
        bulk_wait0();
        red_relaxed_add(&g_cnt[(C_KV + tj) * 32], 1);
        TS(18);
        wait_counter(&g_cnt[(C_KV + tj) * 32], (epoch + 1) * 16);
        mbar_expect_tx(BAR(B_KVF), 4352);
        bulk_load(sb + SM_KV, kvg, 4352, BAR(B_KVF));
        mbar_wait_long(BAR(B_OST), 0);
        tma_store_2d(&maps.o, sb + SM_QS, tj * 64, ti * 128);
        tma_store_2d(&maps.o, sb + SM_QS + 8192, tj * 64, ti * 128 + 64);
        bulk_commit();
        bulk_wait0();
        red_relaxed_add(&g_cnt[(C_O + ti) * 32], 1);
        TS(20);
        mbar_arrive_cluster(BAR(B_SLOT), 0);
        mbar_arrive_cluster(BAR(B_SLOT), 1);
        wait_counter(&g_cnt[(C_O + pi) * 32], (epoch + 1) * 8);
        if (cta == 0) g_epoch = epoch + 1;
        mbar_wait(BAR(B_SLOT), 0);
        TS(21);
#pragma unroll 1
        for (int c = 0; c < 8; ++c) {
          if (c == 4) mbar_wait_long(BAR(B_CONVD), 0);
          if (c == 7) mbar_wait(BAR(B_RE), 0);
          const uint32_t slot = c < 4 ? SM_QS + c * 16384 : c < 7 ? SM_VV + (c - 4) * 16384 : SM_QS;
          mbar_expect_tx(BAR(B_RF + c), 16384);
          tma_load_2d_mc(sb + slot + rank * 8192, &maps.o, c * 64, pi * 128 + rank * 64, BAR(B_RF + c), 3);
        }
      }
    } else if (warp == 13) {
      bar_sync(6, 160);
      sts128(sb + SM_U + (lane >> 4) * U_BYTES + (lane & 15) * 16, 0, 0, 0, 0);
      sts128(sb + SM_U + (2 + (lane >> 4)) * U_BYTES + (lane & 15) * 16, 0, 0, 0, 0);
      __syncwarp();
      if (elect_one()) {
        tma_store_2d(&maps.uT, sb + SM_P, ti * 128, tj * 64);
        tma_store_2d(&maps.uT, sb + SM_P + 8192, ti * 128 + 64, tj * 64);
        bulk_commit();
        bulk_wait_read0();
        mbar_arrive(BAR(B_PFREE));
        bulk_wait0();
        red_relaxed_add(&g_cnt[(C_U + tj) * 32], 1);
        TS(27);
        wait_counter(&g_cnt[(C_U + (cta >> 4)) * 32], (epoch + 1) * 16);
#pragma unroll 1
        for (int c = 0; c < 4; ++c) {
          mbar_expect_tx(BAR(B_UCH + c), 4096);
          bulk_load(sb + SM_U + c * U_BYTES + 256, p.uT + (size_t)(cta * 4 + c) * 2048, 4096, BAR(B_UCH + c));
        }
        TS(3);
      }
      __syncwarp();
      if (ti == 0) {
        float4* z = (float4*)&g_kv[(epoch & 1) ^ 1][tj][0];
#pragma unroll 1
        for (int i = lane; i < 272; i += 32) z[i] = make_float4(0.f, 0.f, 0.f, 0.f);
      }
    }
    if (warp >= 13) {
      bar_sync(4, 480);
      auto swz = [](int k, int pad) { const int r = (k >> 1) + pad; return (uint32_t)(r * 32 + (((k & 1) ^ ((r >> 2) & 1)) << 4)); };
      const uint32_t o0 = swz(lane - 3, 8), o1 = swz(lane - 2, 8), o2 = swz(lane - 1, 8), ow = swz(lane - 2, PADV);
      const uint32_t oz = swz(lane - 18, PADV);
#pragma unroll 1
      for (int item = warp - 13; item < 28; item += 3) {
        const int ch = item / 7, it = item - 7 * ch;
        const int k = -2 + 32 * it + lane;
        const uint32_t ua = sb + SM_U + ch * U_BYTES + it * 512, vb = sb + SM_VV + ch * VV_BYTES;
        const uint32_t a0 = ua + o0, a1 = ua + o1, a2 = ua + o2, aw = vb + it * 512 + ow;
        mbar_wait_long(BAR(B_UCH + ch), 0);
        if (it == 0 && lane < 16) {
          sts128(vb + oz + VV_U3, 0, 0, 0, 0); sts128(vb + oz + VV_U5, 0, 0, 0, 0);
          sts128(vb + oz + VV_U7, 0, 0, 0, 0); sts128(vb + oz + VV_U9, 0, 0, 0, 0);
        }
        const uint4 t0 = lds128(a0), t1 = lds128(a1), t2 = lds128(a2);
        const uint32_t E[12] = {t0.x, t0.y, t0.z, t0.w, t1.x, t1.y, t1.z, t1.w, t2.x, t2.y, t2.z, t2.w};
        uint32_t O[8];
#pragma unroll
        for (int j = 0; j < 8; ++j) O[j] = __byte_perm(E[j + 1], E[j + 2], 0x5432);
        uint32_t s3[6], s5[4], s7[4], s9[4];
#pragma unroll
        for (int j = 0; j < 6; ++j) s3[j] = badd(badd(O[j], O[j + 1]), E[j + 2]);
#pragma unroll
        for (int j = 0; j < 4; ++j) {
          s5[j] = badd(s3[j + 2], badd(E[j + 3], E[j + 5]));
          s7[j] = badd(s5[j], badd(O[j + 1], O[j + 4]));
          s9[j] = badd(s7[j], badd(E[j + 2], E[j + 6]));
        }
        if (k < 208) { sts128(aw + VV_U3, s3[0], s3[1], s3[2], s3[3]); sts128(aw + VV_U5, s5[0], s5[1], s5[2], s5[3]); }
        if (k < 144) { sts128(aw + VV_U7, s7[0], s7[1], s7[2], s7[3]); sts128(aw + VV_U9, s9[0], s9[1], s9[2], s9[3]); }
      }
      if (tid == 416) TS(6);
      bar_arrive(5, 224);
    }
  }
  __syncwarp();
  cluster_arrive();
  cluster_wait();
  if (tid == 0) TS(31);
#undef BAR
}

typedef CUresult (*EncodeFn)(CUtensorMap*, CUtensorMapDataType, cuuint32_t, void*, const cuuint64_t*, const cuuint64_t*,
                             const cuuint32_t*, const cuuint32_t*, CUtensorMapInterleave, CUtensorMapSwizzle,
                             CUtensorMapL2promotion, CUtensorMapFloatOOBfill);

static void make_map(EncodeFn enc, CUtensorMap* m, const void* base, uint64_t inner, uint64_t outer, uint32_t box_in,
                     uint32_t box_out, CUtensorMapSwizzle swz = CU_TENSOR_MAP_SWIZZLE_128B) {
  cuuint64_t gd[2] = {inner, outer};
  cuuint64_t gs[1] = {inner * 2};
  cuuint32_t bd[2] = {box_in, box_out};
  cuuint32_t es[2] = {1, 1};
  enc(m, CU_TENSOR_MAP_DATA_TYPE_BFLOAT16, 2, const_cast<void*>(base), gd, gs, bd, es, CU_TENSOR_MAP_INTERLEAVE_NONE,
      swz, CU_TENSOR_MAP_L2_PROMOTION_L2_128B, CU_TENSOR_MAP_FLOAT_OOB_FILL_NONE);
}

}

extern "C" void kernel_launch(void* const* d_in, const int* in_sizes, int n_in, void* d_out, int out_size) {
  using namespace s4la;
  (void)in_sizes; (void)n_in; (void)out_size;
  static EncodeFn enc = nullptr;
  static void *uT = nullptr, *yT = nullptr, *oS = nullptr;
  if (!enc) {
    void* fn = nullptr;
    cudaDriverEntryPointQueryResult qr;
    cudaGetDriverEntryPoint("cuTensorMapEncodeTiled", &fn, cudaEnableDefault, &qr);
    enc = (EncodeFn)fn;
    cudaGetSymbolAddress(&uT, g_uT);
    cudaGetSymbolAddress(&yT, g_yT);
    cudaGetSymbolAddress(&oS, g_o);
    cudaFuncSetAttribute(fused_kernel, cudaFuncAttributeMaxDynamicSharedMemorySize, SM_TOTAL);
  }
  const __nv_bfloat16* const* in = (const __nv_bfloat16* const*)d_in;
  Maps maps;
  make_map(enc, &maps.x, in[9], 512, 2048, 32, 128, CU_TENSOR_MAP_SWIZZLE_64B);
  {
    cuuint64_t gd[3] = {512, 512, 3};
    cuuint64_t gs[2] = {3072, 1024};
    cuuint32_t bd[3] = {64, 16, 3};
    cuuint32_t es[3] = {1, 1, 1};
    enc(&maps.w, CU_TENSOR_MAP_DATA_TYPE_BFLOAT16, 3, const_cast<__nv_bfloat16*>(in[10]), gd, gs, bd, es,
        CU_TENSOR_MAP_INTERLEAVE_NONE, CU_TENSOR_MAP_SWIZZLE_128B, CU_TENSOR_MAP_L2_PROMOTION_L2_128B,
        CU_TENSOR_MAP_FLOAT_OOB_FILL_NONE);
  }
  make_map(enc, &maps.wo, in[11], 512, 512, 64, 256);
  make_map(enc, &maps.u, in[0], 512, 2048, 64, 128);
  make_map(enc, &maps.uT, uT, 2048, 512, 64, 64);
  make_map(enc, &maps.yT, yT, 2048, 512, 64, 64);
  make_map(enc, &maps.o, oS, 512, 2048, 64, 64);
  make_map(enc, &maps.out, d_out, 1024, 2048, 64, 128);
  Ptrs p;
  p.A_re = in[1]; p.A_im = in[2]; p.B_re = in[3]; p.B_im = in[4]; p.C_re = in[5]; p.C_im = in[6];
  p.log_dt = in[7]; p.Dskip = in[8]; p.x = in[9]; p.wqkv = in[10]; p.wo = in[11];
  p.uT = (__nv_bfloat16*)uT; p.yT = (__nv_bfloat16*)yT;
  fused_kernel<<<NCTA, NTHREADS, SM_TOTAL, cudaStreamPerThread>>>(maps, p);
}
```

```cpp
#include <cuda_runtime.h>
#include <cuda_bf16.h>
#include <cuda_fp16.h>
#include <cuda.h>
#include <stdint.h>

#define DEVI __device__ __forceinline__

namespace s4la {

constexpr int NTHREADS = 512;
constexpr int NCTA = 128;

constexpr int NSTG = 7;
constexpr uint32_t STG_BYTES = 20480, STG_X = 0, STG_W = 8192;
constexpr uint32_t SM_QS = 0;
constexpr uint32_t SM_PK = SM_QS + 16384, SM_VS = SM_QS + 32768;
constexpr uint32_t SM_WO = 65536;
constexpr uint32_t SM_KV = 131072;
constexpr uint32_t SM_BOUT = 16384;
constexpr uint32_t SM_U = 143360, U_BYTES = 4352;
constexpr uint32_t SM_P = 160768, P_BYTES = 4096;
constexpr uint32_t SM_VV = 177152, VV_BYTES = 12800;
constexpr uint32_t VV_U5 = 0, VV_U3 = 3712, VV_U9 = 7424, VV_U7 = 10112;
constexpr uint32_t KG_BYTES = 3200;
constexpr uint32_t SM_BAR = SM_VV + 4 * VV_BYTES;
constexpr uint32_t SM_PTAB = SM_BAR + 320;
constexpr uint32_t SM_TOTAL = SM_PTAB + 2048;
static_assert(SM_TOTAL <= 232448, "shared memory");
constexpr int PADV = 12;

enum { B_FULL = 0, B_EMPTY = 7, B_TILE = 14, B_UCH = 15, B_KVP = 19, B_KVF = 20, B_OST = 21, B_RF = 22, B_WO = 30, B_RE = 31, B_PFREE = 32, B_CONVD = 33, B_SLOT = 34, B_COUNT = 35 };
__host__ __device__ constexpr int bar_count(int i) {
  return (i >= B_EMPTY && i < B_TILE) ? 16 : (i == B_KVP || i == B_OST || i == B_CONVD) ? 8 : i == B_RE ? 16 : i == B_SLOT ? 2 : 1;
}

constexpr int PD_OFF = 0, P2_OFF = 544, P3_OFF = 768;

constexpr int SL_K2048 = 20, SL_ZERO = 21, SL_510 = 22, SL_0 = 23;
__host__ __device__ constexpr int koff(int y) {
  return y < 8 ? y : y < 12 ? 256 + 2 * (y - 8) : y < 16 ? 512 + 256 * ((y - 12) >> 1) + 4 * (y & 1) : 1024 + 256 * (y - 16);
}
__host__ __device__ constexpr int kidx_c(int l) {
  const int y = l < 256 ? (l & 7) : l < 512 ? 8 + ((l & 7) >> 1) : l < 1024 ? 12 + (((l - 512) >> 8) << 1) + ((l >> 2) & 1)
                                                                            : 16 + ((l - 1024) >> 8);
  return ((l >> 3) & 31) * 24 + y;
}
constexpr int slot_direct(int l) {
  if (l < 0 || l > 510) return SL_ZERO;
  if (l == 510) return SL_510;
  if (l == 0) return SL_0;
  return kidx_c(l < 256 ? l : ((l + ((l >> 1) & 1)) & ~1));
}
constexpr int slot_seg2(int v, int k) { return (k >= 32 && k < 64) ? kidx_c(16 * k + 4 * v) : SL_ZERO; }
constexpr int slot_seg3(int pi, int k) {
  return (k >= 64 && k < 128) ? kidx_c(16 * k + 8 * pi) : ((k == 128 && pi == 0) ? SL_K2048 : SL_ZERO);
}
constexpr int slot_word(int w) {
  return w < 0 ? SL_ZERO : w < 544 ? slot_direct(w - 16) : w < 768 ? slot_seg2((w - 544) / 56, 16 + (w - 544) % 56)
       : w < 944 ? slot_seg3((w - 768) / 88, 48 + (w - 768) % 88) : SL_ZERO;
}
struct PTab { uint32_t v[512]; };
constexpr PTab make_ptab() {
  PTab t{};
  for (int lane = 0; lane < 32; ++lane)
    for (int i = 0; i < 16; ++i)
      t.v[i * 32 + lane] = (slot_word(31 * lane - 1 + 2 * i) * 4) | ((slot_word(31 * lane + 2 * i) * 4) << 16);
  return t;
}
__device__ const PTab g_ptab = make_ptab();

__device__ __nv_bfloat16 g_uT[512 * 2048];
__device__ __nv_bfloat16 g_yT[512 * 2048];
__device__ __nv_bfloat16 g_o[2048 * 512];
__device__ float g_kv[2][8][4 * 272];
__device__ unsigned g_cnt[64 * 32];
__device__ unsigned g_epoch;
#define TS(slot) do { } while (0)
#define TSR(on, slot) do { } while (0)
#define TSD(slot) do { } while (0)
enum { C_U = 0, C_KV = 8, C_O = 16, C_Y = 32 };

struct Maps {
  CUtensorMap x, w, wo, u, uT, yT, o, out;
};
struct Ptrs {
  const __nv_bfloat16 *A_re, *A_im, *B_re, *B_im, *C_re, *C_im, *log_dt, *Dskip;
  const __nv_bfloat16 *x, *wqkv, *wo;
  __nv_bfloat16 *uT, *yT;
};

DEVI uint32_t s2u(const void* p) { return (uint32_t)__cvta_generic_to_shared(p); }
DEVI void mbar_init(uint32_t b, uint32_t c) { asm volatile("mbarrier.init.shared::cta.b64 [%0], %1;" ::"r"(b), "r"(c) : "memory"); }
DEVI void mbar_expect_tx(uint32_t b, uint32_t bytes) {
  asm volatile("mbarrier.arrive.expect_tx.shared::cta.b64 _, [%0], %1;" ::"r"(b), "r"(bytes) : "memory");
}
DEVI void mbar_arrive(uint32_t b) { asm volatile("mbarrier.arrive.shared::cta.b64 _, [%0];" ::"r"(b) : "memory"); }
DEVI void mbar_arrive_cluster(uint32_t b, uint32_t cta) {
  asm volatile("{\n.reg .b32 r;\nmapa.shared::cluster.u32 r, %0, %1;\nmbarrier.arrive.shared::cluster.b64 _, [r];\n}"
               ::"r"(b), "r"(cta) : "memory");
}
DEVI void mbar_wait(uint32_t b, uint32_t parity) {
  asm volatile("{\n.reg .pred p;\nLAB_WAIT:\nmbarrier.try_wait.parity.shared::cta.b64 p, [%0], %1;\n@!p bra LAB_WAIT;\n}"
               ::"r"(b), "r"(parity) : "memory");
}
DEVI void mbar_wait_long(uint32_t b, uint32_t parity) {
  asm volatile("{\n.reg .pred p;\nLAB_WAIT:\nmbarrier.try_wait.parity.shared::cta.b64 p, [%0], %1, 0x989680;\n@!p bra LAB_WAIT;\n}"
               ::"r"(b), "r"(parity) : "memory");
}
DEVI void bar_sync(int id, int n) { asm volatile("bar.sync %0, %1;" ::"r"(id), "r"(n) : "memory"); }
DEVI void bar_arrive(int id, int n) { asm volatile("bar.arrive %0, %1;" ::"r"(id), "r"(n) : "memory"); }
DEVI void fence_async_smem() { asm volatile("fence.proxy.async.shared::cta;" ::: "memory"); }
DEVI void fence_async_all() { asm volatile("fence.proxy.async;" ::: "memory"); }
DEVI void cluster_arrive() { asm volatile("barrier.cluster.arrive.relaxed.aligned;" ::: "memory"); }
DEVI void cluster_wait() { asm volatile("barrier.cluster.wait.aligned;" ::: "memory"); }

DEVI void tma_load_2d(uint32_t dst, const CUtensorMap* m, int c0, int c1, uint32_t bar) {
  asm volatile("cp.async.bulk.tensor.2d.shared::cluster.global.mbarrier::complete_tx::bytes [%0], [%1, {%3, %4}], [%2];"
               ::"r"(dst), "l"(m), "r"(bar), "r"(c0), "r"(c1) : "memory");
}
DEVI void tma_load_2d_mc(uint32_t dst, const CUtensorMap* m, int c0, int c1, uint32_t bar, uint16_t mask) {
  asm volatile("cp.async.bulk.tensor.2d.shared::cluster.global.mbarrier::complete_tx::bytes.multicast::cluster [%0], [%1, {%3, %4}], [%2], %5;"
               ::"r"(dst), "l"(m), "r"(bar), "r"(c0), "r"(c1), "h"(mask) : "memory");
}
DEVI void tma_load_3d_mc(uint32_t dst, const CUtensorMap* m, int c0, int c1, int c2, uint32_t bar, uint16_t mask) {
  asm volatile("cp.async.bulk.tensor.3d.shared::cluster.global.mbarrier::complete_tx::bytes.multicast::cluster [%0], [%1, {%3, %4, %5}], [%2], %6;"
               ::"r"(dst), "l"(m), "r"(bar), "r"(c0), "r"(c1), "r"(c2), "h"(mask) : "memory");
}
DEVI void tma_store_2d(const CUtensorMap* m, uint32_t src, int c0, int c1) {
  asm volatile("cp.async.bulk.tensor.2d.global.shared::cta.bulk_group [%0, {%2, %3}], [%1];"
               ::"l"(m), "r"(src), "r"(c0), "r"(c1) : "memory");
}
DEVI void bulk_load(uint32_t dst, const void* src, uint32_t bytes, uint32_t bar) {
  asm volatile("cp.async.bulk.shared::cluster.global.mbarrier::complete_tx::bytes [%0], [%1], %2, [%3];"
               ::"r"(dst), "l"(src), "r"(bytes), "r"(bar) : "memory");
}
DEVI void bulk_store(void* dst, uint32_t src, uint32_t bytes) {
  asm volatile("cp.async.bulk.global.shared::cta.bulk_group [%0], [%1], %2;" ::"l"(dst), "r"(src), "r"(bytes) : "memory");
}
DEVI void bulk_reduce_add_f32(void* dst, uint32_t src, uint32_t bytes) {
  asm volatile("cp.reduce.async.bulk.global.shared::cta.bulk_group.add.f32 [%0], [%1], %2;" ::"l"(dst), "r"(src), "r"(bytes) : "memory");
}
DEVI void bulk_commit() { asm volatile("cp.async.bulk.commit_group;" ::: "memory"); }
DEVI void bulk_wait0() { asm volatile("cp.async.bulk.wait_group 0;" ::: "memory"); }
DEVI void bulk_wait_read0() { asm volatile("cp.async.bulk.wait_group.read 0;" ::: "memory"); }
DEVI void l2_prefetch(const void* p, uint32_t bytes) {
  asm volatile("cp.async.bulk.prefetch.L2.global [%0], %1;" ::"l"(p), "r"(bytes) : "memory");
}
DEVI void prefetch_tmap(const CUtensorMap* m) { asm volatile("prefetch.tensormap [%0];" ::"l"(m) : "memory"); }

DEVI void red_release_add(unsigned* p, unsigned v) {
  asm volatile("red.release.gpu.global.add.u32 [%0], %1;" ::"l"(p), "r"(v) : "memory");
}
DEVI void red_relaxed_add(unsigned* p, unsigned v) {
  asm volatile("red.relaxed.gpu.global.add.u32 [%0], %1;" ::"l"(p), "r"(v) : "memory");
}
DEVI unsigned ld_relaxed(const unsigned* p) {
  unsigned v;
  asm volatile("ld.relaxed.gpu.global.u32 %0, [%1];" : "=r"(v) : "l"(p) : "memory");
  return v;
}
DEVI void wait_counter(const unsigned* p, unsigned target) {
#pragma unroll 1
  for (int it = 0; (int)(ld_relaxed(p) - target) < 0; ++it)
    if (it > (1 << 22)) __trap();
}

DEVI void ldsm_x4(uint32_t (&r)[4], uint32_t a) {
  asm volatile("ldmatrix.sync.aligned.m8n8.x4.shared.b16 {%0,%1,%2,%3}, [%4];"
               : "=r"(r[0]), "=r"(r[1]), "=r"(r[2]), "=r"(r[3]) : "r"(a) : "memory");
}
DEVI void ldsm_x4_t(uint32_t (&r)[4], uint32_t a) {
  asm volatile("ldmatrix.sync.aligned.m8n8.x4.trans.shared.b16 {%0,%1,%2,%3}, [%4];"
               : "=r"(r[0]), "=r"(r[1]), "=r"(r[2]), "=r"(r[3]) : "r"(a) : "memory");
}
DEVI void ldsm_x2_t(uint32_t& r0, uint32_t& r1, uint32_t a) {
  asm volatile("ldmatrix.sync.aligned.m8n8.x2.trans.shared.b16 {%0,%1}, [%2];" : "=r"(r0), "=r"(r1) : "r"(a) : "memory");
}
DEVI void stsm_x4(uint32_t a, uint32_t r0, uint32_t r1, uint32_t r2, uint32_t r3) {
  asm volatile("stmatrix.sync.aligned.m8n8.x4.shared.b16 [%0], {%1,%2,%3,%4};"
               ::"r"(a), "r"(r0), "r"(r1), "r"(r2), "r"(r3) : "memory");
}
DEVI void stsm_x4_t(uint32_t a, uint32_t r0, uint32_t r1, uint32_t r2, uint32_t r3) {
  asm volatile("stmatrix.sync.aligned.m8n8.x4.trans.shared.b16 [%0], {%1,%2,%3,%4};"
               ::"r"(a), "r"(r0), "r"(r1), "r"(r2), "r"(r3) : "memory");
}
DEVI uint32_t lds32(uint32_t a) { uint32_t v; asm volatile("ld.shared.b32 %0, [%1];" : "=r"(v) : "r"(a) : "memory"); return v; }
DEVI float lds_f32(uint32_t a) { float v; asm volatile("ld.shared.f32 %0, [%1];" : "=f"(v) : "r"(a) : "memory"); return v; }
DEVI void sts32(uint32_t a, uint32_t v) { asm volatile("st.shared.b32 [%0], %1;" ::"r"(a), "r"(v) : "memory"); }
DEVI void sts_f32(uint32_t a, float v) { asm volatile("st.shared.f32 [%0], %1;" ::"r"(a), "f"(v) : "memory"); }
DEVI void sts_f32x2(uint32_t a, float x, float y) { asm volatile("st.shared.v2.f32 [%0], {%1,%2};" ::"r"(a), "f"(x), "f"(y) : "memory"); }
DEVI uint4 lds128(uint32_t a) {
  uint4 v;
  asm volatile("ld.shared.v4.b32 {%0,%1,%2,%3}, [%4];" : "=r"(v.x), "=r"(v.y), "=r"(v.z), "=r"(v.w) : "r"(a) : "memory");
  return v;
}
DEVI void sts128(uint32_t a, uint32_t x, uint32_t y, uint32_t z, uint32_t w) {
  asm volatile("st.shared.v4.b32 [%0], {%1,%2,%3,%4};" ::"r"(a), "r"(x), "r"(y), "r"(z), "r"(w) : "memory");
}

DEVI void mma_bf16(float (&d)[4], uint32_t a0, uint32_t a1, uint32_t a2, uint32_t a3, uint32_t b0, uint32_t b1) {
  asm("mma.sync.aligned.m16n8k16.row.col.f32.bf16.bf16.f32 {%0,%1,%2,%3}, {%4,%5,%6,%7}, {%8,%9}, {%0,%1,%2,%3};"
      : "+f"(d[0]), "+f"(d[1]), "+f"(d[2]), "+f"(d[3])
      : "r"(a0), "r"(a1), "r"(a2), "r"(a3), "r"(b0), "r"(b1));
}
DEVI void mma_f16(float (&d)[4], const uint32_t (&a)[4], uint32_t b0, uint32_t b1) {
  asm("mma.sync.aligned.m16n8k16.row.col.f32.f16.f16.f32 {%0,%1,%2,%3}, {%4,%5,%6,%7}, {%8,%9}, {%0,%1,%2,%3};"
      : "+f"(d[0]), "+f"(d[1]), "+f"(d[2]), "+f"(d[3])
      : "r"(a[0]), "r"(a[1]), "r"(a[2]), "r"(a[3]), "r"(b0), "r"(b1));
}
DEVI void mma_bf16v(float (&d)[4], const uint32_t (&a)[4], uint32_t b0, uint32_t b1) {
  asm volatile("mma.sync.aligned.m16n8k16.row.col.f32.bf16.bf16.f32 {%0,%1,%2,%3}, {%4,%5,%6,%7}, {%8,%9}, {%0,%1,%2,%3};"
               : "+f"(d[0]), "+f"(d[1]), "+f"(d[2]), "+f"(d[3])
               : "r"(a[0]), "r"(a[1]), "r"(a[2]), "r"(a[3]), "r"(b0), "r"(b1));
}
DEVI uint32_t pack_bf16(float lo, float hi) {
  uint32_t r;
  asm("cvt.rn.bf16x2.f32 %0, %1, %2;" : "=r"(r) : "f"(hi), "f"(lo));
  return r;
}
DEVI uint32_t pack_f16(float lo, float hi) {
  uint32_t r;
  asm("cvt.rn.f16x2.f32 %0, %1, %2;" : "=r"(r) : "f"(hi), "f"(lo));
  return r;
}
DEVI uint32_t ldg16(const __nv_bfloat16* p) {
  uint32_t v;
  asm volatile("ld.global.nc.u16 %0, [%1];" : "=r"(v) : "l"(p));
  return v;
}
DEVI bool elect_one() {
  uint32_t pred;
  asm volatile("{\n.reg .pred p;\nelect.sync _|p, 0xffffffff;\nselp.u32 %0, 1, 0, p;\n}" : "=r"(pred));
  return pred != 0;
}
DEVI float bf_lo(uint32_t v) { return __uint_as_float(v << 16); }
DEVI float bf_hi(uint32_t v) { return __uint_as_float(v & 0xffff0000u); }
DEVI float bf2f(__nv_bfloat16 v) { return __bfloat162float(v); }
DEVI float round_bf16(float v) { return __bfloat162float(__float2bfloat16_rn(v)); }
DEVI float rcp(float x) { float r; asm("rcp.approx.ftz.f32 %0, %1;" : "=f"(r) : "f"(x)); return r; }
DEVI float ex2(float x) { float r; asm("ex2.approx.ftz.f32 %0, %1;" : "=f"(r) : "f"(x)); return r; }

DEVI void wg_fence() { asm volatile("wgmma.fence.sync.aligned;" ::: "memory"); }
DEVI void wg_commit() { asm volatile("wgmma.commit_group.sync.aligned;" ::: "memory"); }
template <int N> DEVI void wg_wait() { asm volatile("wgmma.wait_group.sync.aligned %0;" ::"n"(N) : "memory"); }
constexpr uint32_t DESC_HI = (1u << 30) | (1024 >> 4);
constexpr uint32_t DESC_HI64 = (2u << 30) | (512 >> 4);
DEVI uint32_t mkdesc(uint32_t saddr, uint32_t lbo) { return ((saddr & 0x3FFFF) >> 4) | ((lbo >> 4) << 16); }

#define R8(b) "%" #b
DEVI void wgmma_n192(float (&d)[96], uint32_t da, uint32_t db, int scale_d) {
  asm volatile(
      "{\n.reg .pred p;\n.reg .b64 da, db;\nsetp.ne.b32 p, %98, 0;\nmov.b64 da, {%96, %100};\nmov.b64 db, {%97, %99};\n"
      "wgmma.mma_async.sync.aligned.m64n192k16.f32.bf16.bf16 "
      "{%0,%1,%2,%3,%4,%5,%6,%7,%8,%9,%10,%11,%12,%13,%14,%15,"
      "%16,%17,%18,%19,%20,%21,%22,%23,%24,%25,%26,%27,%28,%29,%30,%31,"
      "%32,%33,%34,%35,%36,%37,%38,%39,%40,%41,%42,%43,%44,%45,%46,%47,"
      "%48,%49,%50,%51,%52,%53,%54,%55,%56,%57,%58,%59,%60,%61,%62,%63,"
      "%64,%65,%66,%67,%68,%69,%70,%71,%72,%73,%74,%75,%76,%77,%78,%79,"
      "%80,%81,%82,%83,%84,%85,%86,%87,%88,%89,%90,%91,%92,%93,%94,%95}, "
      "da, db, p, 1, 1, 0, 1;\n}"
      : "+f"(d[0]), "+f"(d[1]), "+f"(d[2]), "+f"(d[3]), "+f"(d[4]), "+f"(d[5]), "+f"(d[6]), "+f"(d[7]),
        "+f"(d[8]), "+f"(d[9]), "+f"(d[10]), "+f"(d[11]), "+f"(d[12]), "+f"(d[13]), "+f"(d[14]), "+f"(d[15]),
        "+f"(d[16]), "+f"(d[17]), "+f"(d[18]), "+f"(d[19]), "+f"(d[20]), "+f"(d[21]), "+f"(d[22]), "+f"(d[23]),
        "+f"(d[24]), "+f"(d[25]), "+f"(d[26]), "+f"(d[27]), "+f"(d[28]), "+f"(d[29]), "+f"(d[30]), "+f"(d[31]),
        "+f"(d[32]), "+f"(d[33]), "+f"(d[34]), "+f"(d[35]), "+f"(d[36]), "+f"(d[37]), "+f"(d[38]), "+f"(d[39]),
        "+f"(d[40]), "+f"(d[41]), "+f"(d[42]), "+f"(d[43]), "+f"(d[44]), "+f"(d[45]), "+f"(d[46]), "+f"(d[47]),
        "+f"(d[48]), "+f"(d[49]), "+f"(d[50]), "+f"(d[51]), "+f"(d[52]), "+f"(d[53]), "+f"(d[54]), "+f"(d[55]),
        "+f"(d[56]), "+f"(d[57]), "+f"(d[58]), "+f"(d[59]), "+f"(d[60]), "+f"(d[61]), "+f"(d[62]), "+f"(d[63]),
        "+f"(d[64]), "+f"(d[65]), "+f"(d[66]), "+f"(d[67]), "+f"(d[68]), "+f"(d[69]), "+f"(d[70]), "+f"(d[71]),
        "+f"(d[72]), "+f"(d[73]), "+f"(d[74]), "+f"(d[75]), "+f"(d[76]), "+f"(d[77]), "+f"(d[78]), "+f"(d[79]),
        "+f"(d[80]), "+f"(d[81]), "+f"(d[82]), "+f"(d[83]), "+f"(d[84]), "+f"(d[85]), "+f"(d[86]), "+f"(d[87]),
        "+f"(d[88]), "+f"(d[89]), "+f"(d[90]), "+f"(d[91]), "+f"(d[92]), "+f"(d[93]), "+f"(d[94]), "+f"(d[95])
      : "r"(da), "r"(db), "r"(scale_d), "n"(DESC_HI), "n"(DESC_HI64));
}
DEVI void wgmma_n64(float (&d)[32], uint32_t da, uint32_t db, int scale_d) {
  asm volatile(
      "{\n.reg .pred p;\n.reg .b64 da, db;\nsetp.ne.b32 p, %34, 0;\nmov.b64 da, {%32, %35};\nmov.b64 db, {%33, %35};\n"
      "wgmma.mma_async.sync.aligned.m64n64k16.f32.bf16.bf16 "
      "{%0,%1,%2,%3,%4,%5,%6,%7,%8,%9,%10,%11,%12,%13,%14,%15,"
      "%16,%17,%18,%19,%20,%21,%22,%23,%24,%25,%26,%27,%28,%29,%30,%31}, "
      "da, db, p, 1, 1, 0, 1;\n}"
      : "+f"(d[0]), "+f"(d[1]), "+f"(d[2]), "+f"(d[3]), "+f"(d[4]), "+f"(d[5]), "+f"(d[6]), "+f"(d[7]),
        "+f"(d[8]), "+f"(d[9]), "+f"(d[10]), "+f"(d[11]), "+f"(d[12]), "+f"(d[13]), "+f"(d[14]), "+f"(d[15]),
        "+f"(d[16]), "+f"(d[17]), "+f"(d[18]), "+f"(d[19]), "+f"(d[20]), "+f"(d[21]), "+f"(d[22]), "+f"(d[23]),
        "+f"(d[24]), "+f"(d[25]), "+f"(d[26]), "+f"(d[27]), "+f"(d[28]), "+f"(d[29]), "+f"(d[30]), "+f"(d[31])
      : "r"(da), "r"(db), "r"(scale_d), "n"(DESC_HI));
}

struct C32 { float re, im; };
DEVI C32 csq(C32 a) { return {a.re * a.re - a.im * a.im, 2.f * a.re * a.im}; }
DEVI C32 cmul(C32 a, C32 b) { return {a.re * b.re - a.im * b.im, a.re * b.im + a.im * b.re}; }
DEVI C32 cfresh(float zl, float zi, float m) {
  float mag = ex2(zl * m), ph = zi * m;
  return {mag * __cosf(ph), mag * __sinf(ph)};
}
struct HMul { uint32_t b, bp; };
DEVI HMul mk_mul(float re, float im) { return {pack_f16(re, im), pack_f16(-im, re)}; }
DEVI uint32_t hcmul(uint32_t a, const HMul& m) {
  __half2 ah = *reinterpret_cast<__half2*>(&a);
  __half2 b = *reinterpret_cast<const __half2*>(&m.b), bp = *reinterpret_cast<const __half2*>(&m.bp);
  __half2 r = __hfma2(__high2half2(ah), bp, __hmul2(__low2half2(ah), b));
  return *reinterpret_cast<uint32_t*>(&r);
}
DEVI uint32_t badd(uint32_t a, uint32_t b) {
  __nv_bfloat162 r = __hadd2(*reinterpret_cast<__nv_bfloat162*>(&a), *reinterpret_cast<__nv_bfloat162*>(&b));
  return *reinterpret_cast<uint32_t*>(&r);
}
template <int MU0, int NMU, int DMAX>
DEVI void conv_tail(float (&acc)[16][4], uint32_t p_lane, uint32_t v_base, int back, bool edge, int lane) {
  const int hsel = (lane >> 3) & 1;
  const int row = (lane & 7) + ((lane >> 4) << 3) + PADV - 8 - (back & (hsel ^ 1));
  const uint32_t la = v_base + row * 32 + (((hsel ^ back) ^ ((row >> 2) & 1)) << 4);
  uint32_t M[3][4];
  ldsm_x4_t(M[0], la);
  ldsm_x4_t(M[1], la + 256);
  uint32_t H[2 * NMU];
#pragma unroll
  for (int i = 0; i < 2 * NMU; ++i) H[i ^ 1] = lds32(p_lane + (uint32_t)(MU0 - 1 + i) * 32);
  if (edge) {
    const uint32_t a[4] = {0u, 0u, M[0][0], M[0][1]};
#pragma unroll
    for (int k = 1; k < NMU; ++k) mma_bf16v(acc[MU0 - 2 + 2 * k], a, H[2 * k], H[2 * k + 1]);
  }
#pragma unroll
  for (int delta = -1; delta <= DMAX; ++delta) {
    if (delta + 2 <= DMAX) ldsm_x4_t(M[(delta + 3) % 3], la + (delta + 3) * 256);
#pragma unroll
    for (int k = 0; k < NMU; ++k)
      if (delta + MU0 + 2 * k < 16) mma_bf16v(acc[delta + MU0 + 2 * k], M[(delta + 1) % 3], H[2 * k], H[2 * k + 1]);
  }
}

__global__ void __cluster_dims__(2, 1, 1) __launch_bounds__(NTHREADS, 1)
fused_kernel(const __grid_constant__ Maps maps, const Ptrs p) {
  extern __shared__ __align__(1024) uint8_t smem[];
  const uint32_t sb = s2u(smem);
  const int tid = threadIdx.x, lane = tid & 31;
  const int warp = __shfl_sync(0xffffffffu, tid >> 5, 0);
  const int cta = blockIdx.x;
  const uint32_t rank = cta & 1;
  const int ti = 2 * (cta >> 4) + rank;
  const int tj = (cta >> 1) & 7;
  const int pi = cta >> 3, pj = cta & 7;
  const uint32_t bars = sb + SM_BAR;
#define BAR(i) (bars + 8 * (i))
  const int g = lane >> 2, q = lane & 3;

  auto issue_stage = [&](int ks, int s) {
    const uint32_t st = sb + s * STG_BYTES, fb = BAR(B_FULL + s);
    mbar_expect_tx(fb, STG_BYTES);
    tma_load_2d(st + STG_X, &maps.x, ks * 32, ti * 128, fb);
    tma_load_3d_mc(st + STG_W + rank * 6144, &maps.w, tj * 64, ks * 32 + rank * 16, 0, fb, 3);
  };

  const int kch = warp & 3, krd = warp >> 2;
  float zr, zi, wr, wi;
  unsigned epoch;
  uint32_t r_dskip;
  {
    const size_t po = (size_t)(cta * 4 + kch) * 128 + krd * 32 + lane;
    const uint32_t r_ar = ldg16(p.A_re + po), r_ai = ldg16(p.A_im + po), r_br = ldg16(p.B_re + po), r_bi = ldg16(p.B_im + po);
    const uint32_t r_cr = ldg16(p.C_re + po), r_ci = ldg16(p.C_im + po), r_ldt = ldg16(p.log_dt + cta * 4 + kch);
    epoch = __ldcg(&g_epoch);
    r_dskip = ldg16(p.Dskip + cta * 4 + kch);
    uint4 pt;
    if (tid < 128) pt = __ldg((const uint4*)g_ptab.v + tid);
    if (tid == 384) {
      TS(0);
#pragma unroll
      for (int i = 0; i < B_COUNT; ++i) mbar_init(BAR(i), bar_count(i));
      asm volatile("fence.mbarrier_init.release.cluster;" ::: "memory");
      prefetch_tmap(&maps.x); prefetch_tmap(&maps.w); prefetch_tmap(&maps.u);
    }
    __syncthreads();
    cluster_arrive();
    if (warp >= 12) {
      cluster_wait();
      if (elect_one()) {
        if (warp == 13) {
          mbar_expect_tx(BAR(B_TILE), 16384);
          tma_load_2d(sb + SM_U, &maps.u, tj * 64, ti * 128, BAR(B_TILE));
          prefetch_tmap(&maps.uT); prefetch_tmap(&maps.wo); prefetch_tmap(&maps.o); prefetch_tmap(&maps.yT);
          prefetch_tmap(&maps.out);
        } else {
          if (warp == 12) TS(61);
          { const int ks = warp == 12 ? 0 : warp - 13; issue_stage(ks, ks); }
        }
      }
      __syncwarp();
    }
    if (tid < 128) sts128(sb + SM_PTAB + tid * 16, pt.x, pt.y, pt.z, pt.w);
    const float dt = round_bf16(expf(bf_lo(r_ldt)));
    zr = dt * bf_lo(r_ar); zi = dt * bf_lo(r_ai);
    const float dbr = dt * bf_lo(r_br), dbi = dt * bf_lo(r_bi), cr = bf_lo(r_cr), ci = bf_lo(r_ci);
    wr = cr * dbr - ci * dbi; wi = cr * dbi + ci * dbr;
  }
  {
    const float mz = __uint_as_float(__reduce_max_sync(0xffffffffu, __float_as_uint(fmaxf(zr, 0.f))));
    const int E = min(max((int)(__reduce_max_sync(0xffffffffu, __float_as_uint(fmaxf(fabsf(wr), fabsf(wi)))) >> 23), 1), 252);
    const float sc = __int_as_float((253 - E) << 23), inv = __int_as_float((E + 1) << 23);
    const float zl = (zr - mz) * 1.4426950408889634f;
    const uint32_t tb = sb + SM_VV + kch * VV_BYTES + krd * KG_BYTES;
    const uint32_t sta = tb + (((lane >> 2) << 4) | ((lane & 3) << 2));
    auto put = [&](int r, uint32_t v) { sts32((sta ^ ((r & 7) << 4)) + r * 128, v); };
    const uint32_t lda = tb + ((lane & 7) + (((lane >> 3) & 1) << 3)) * 128;
    const uint32_t ldb = tb + ((lane & 7) + ((lane >> 4) << 3)) * 128;
    C32 e1 = cfresh(zl, zi, 1.f), e2 = csq(e1), e4 = csq(e2), e8 = csq(e4);
    C32 e16 = cfresh(zl, zi, 16.f), e32 = csq(e16), e64 = csq(e32), e128 = csq(e64);
    C32 e256 = cfresh(zl, zi, 256.f), e512 = csq(e256), e1024 = csq(e512), e768 = cmul(e512, e256);
    uint32_t XA[2][4][4];
    {
      const HMul m16 = mk_mul(e16.re, e16.im), m32 = mk_mul(e32.re, e32.im), m64 = mk_mul(e64.re, e64.im);
      const HMul m128 = mk_mul(e128.re, e128.im);
      uint32_t X[16];
      X[0] = 0x00003c00u; X[1] = pack_f16(e8.re, e8.im); X[2] = m16.b; X[4] = m32.b; X[8] = m64.b;
      X[3] = hcmul(X[1], m16); X[5] = hcmul(X[1], m32); X[6] = hcmul(X[2], m32); X[7] = hcmul(X[3], m32);
#pragma unroll
      for (int r = 1; r < 8; ++r) X[8 + r] = hcmul(X[r], m64);
#pragma unroll
      for (int h = 0; h < 2; ++h) {
#pragma unroll
        for (int r = 0; r < 16; ++r) put(r, h == 0 ? X[r] : r == 0 ? m128.b : hcmul(X[r], m128));
        __syncwarp();
#pragma unroll
        for (int k = 0; k < 4; ++k) ldsm_x4(XA[h][k], lda + (((2 * k + (lane >> 4)) ^ (lane & 7)) << 4));
        __syncwarp();
      }
    }
    if (warp >= 14 && elect_one()) {
      issue_stage(warp - 11, warp - 11);
      issue_stage(warp - 9, warp - 9);
      if (warp == 14) l2_prefetch((const char*)p.wqkv + 224 * 3072 + cta * 6912, 6912);
      else l2_prefetch((const char*)p.x + (size_t)cta * 16384, 16384);
    }
    __syncwarp();
    float D[2][3][4];
#pragma unroll
    for (int t = 0; t < 6; ++t) D[t / 3][t % 3][0] = D[t / 3][t % 3][1] = D[t / 3][t % 3][2] = D[t / 3][t % 3][3] = 0.f;
    auto contract = [&](int t0, int nt) {
      __syncwarp();
#pragma unroll
      for (int k = 0; k < 4; ++k) {
        uint32_t b[4];
        ldsm_x4(b, ldb + (((2 * k + ((lane >> 3) & 1)) ^ (lane & 7)) << 4));
#pragma unroll
        for (int h = 0; h < 2; ++h) {
          mma_f16(D[h][t0], XA[h][k], b[0], b[1]);
          if (nt == 2) mma_f16(D[h][t0 + 1], XA[h][k], b[2], b[3]);
        }
      }
      __syncwarp();
    };
    const HMul c1 = mk_mul(e1.re, -e1.im), c2 = mk_mul(e2.re, -e2.im), c4 = mk_mul(e4.re, -e4.im);
    const HMul c256 = mk_mul(e256.re, -e256.im), c512 = mk_mul(e512.re, -e512.im), c768 = mk_mul(e768.re, -e768.im);
    const HMul c1024 = mk_mul(e1024.re, -e1024.im);
    uint32_t W[8];
    W[0] = pack_f16(wr * sc, -wi * sc);
    W[1] = hcmul(W[0], c1); W[2] = hcmul(W[0], c2); W[3] = hcmul(W[1], c2);
    W[4] = hcmul(W[0], c4); W[5] = hcmul(W[1], c4); W[6] = hcmul(W[2], c4); W[7] = hcmul(W[3], c4);
#pragma unroll
    for (int i = 0; i < 8; ++i) put(i, W[i]);
#pragma unroll
    for (int i = 0; i < 4; ++i) put(8 + i, hcmul(W[2 * i], c256));
    put(12, hcmul(W[0], c512)); put(13, hcmul(W[4], c512)); put(14, hcmul(W[0], c768)); put(15, hcmul(W[4], c768));
    contract(0, 2);
    const uint32_t v0 = hcmul(W[0], c1024);
    put(0, v0); put(1, hcmul(v0, c256)); put(2, hcmul(v0, c512)); put(3, hcmul(v0, c768)); put(4, hcmul(v0, c1024));
    contract(2, 1);
    const uint32_t a = tb + (g * 24 + 2 * q) * 4;
#pragma unroll
    for (int t = 0; t < 6; ++t) {
      const float(&d)[4] = D[t / 3][t % 3];
      sts_f32x2(a + (t / 3) * 1536 + (t % 3) * 32, d[0] * inv, d[1] * inv);
      sts_f32x2(a + (t / 3) * 1536 + (t % 3) * 32 + 768, d[2] * inv, d[3] * inv);
    }
    if (mz > 0.f) {
      __syncwarp();
#pragma unroll 1
      for (int i = lane; i < 768; i += 32) {
        const int r = i / 24, y = i - 24 * r;
        sts_f32(tb + i * 4, lds_f32(tb + i * 4) * ex2(mz * 1.4426950408889634f * (koff(y) + 8 * r)));
      }
    }
  }
  if (tid == 0) TS(2);
  if (warp < 12) cluster_wait();
  __syncthreads();

  if (warp < 4) {
#define A_REGS 200
    asm volatile("setmaxnreg.inc.sync.aligned.u32 %0;" ::"n"(A_REGS));
    if (tid == 0) TS(34);
    const int d = cta * 4 + warp;
    const uint32_t vv = sb + SM_VV + warp * VV_BYTES;
    const uint32_t ub = sb + SM_U + warp * U_BYTES;
    const uint32_t pb = sb + SM_P + warp * P_BYTES;
    const float dskip = bf_lo(r_dskip);
#pragma unroll 1
    for (int pass = 0; pass < 2; ++pass) {
      if (pass == 1) {
        const uint32_t kf = vv;
#pragma unroll 2
        for (int i = 0; i < 6; ++i) {
          const uint32_t a = kf + (i * 32 + lane) * 16;
          const uint4 x0 = lds128(a), x1 = lds128(a + KG_BYTES), x2 = lds128(a + 2 * KG_BYTES), x3 = lds128(a + 3 * KG_BYTES);
          auto s4 = [](uint32_t a0, uint32_t a1, uint32_t a2, uint32_t a3) {
            return __float_as_uint((__uint_as_float(a0) + __uint_as_float(a1)) + (__uint_as_float(a2) + __uint_as_float(a3)));
          };
          sts128(a, s4(x0.x, x1.x, x2.x, x3.x), s4(x0.y, x1.y, x2.y, x3.y), s4(x0.z, x1.z, x2.z, x3.z), s4(x0.w, x1.w, x2.w, x3.w));
        }
        __syncwarp();
        const float k1024 = lds_f32(kf + kidx_c(1024) * 4);
        if (lane == 0) {
          sts_f32(kf + SL_ZERO * 4, 0.f);
          sts_f32(kf + SL_510 * 4, lds_f32(kf + kidx_c(510) * 4) - lds_f32(kf + kidx_c(512) * 4));
          sts_f32(kf + SL_0 * 4, lds_f32(kf) + dskip);
        }
        __syncwarp();
        if (tid == 0) TS(36);
        mbar_wait_long(BAR(B_PFREE), 0);
        if (tid == 0) TS(37);
        {
          float prev = 0.f;
#pragma unroll 1
          for (int i0 = 0; i0 < 16; i0 += 4) {
            uint32_t e[4];
            float a[4], b[4];
#pragma unroll
            for (int i = 0; i < 4; ++i) e[i] = lds32(sb + SM_PTAB + ((i0 + i) * 32 + lane) * 4);
#pragma unroll
            for (int i = 0; i < 4; ++i) { a[i] = lds_f32(kf + (e[i] & 0xffff)); b[i] = lds_f32(kf + (e[i] >> 16)); }
#pragma unroll
            for (int i = 0; i < 4; ++i) {
              const uint32_t w = pb + (31 * lane + 2 * (i0 + i)) * 4;
              if (i0 + i > 0) sts32(w - 4, pack_bf16(a[i], prev));
              sts32(w, pack_bf16(b[i], a[i]));
              prev = b[i];
            }
          }
        }
        __syncwarp();
        if (lane == 0) TS(4);
        const int gq = g - 2 * q;
        uint32_t h127, h128;
        {
          const uint32_t kf2 = pack_bf16(k1024, k1024) ^ 0x80008000u;
          h127 = (gq == 4 ? 0x0000ffffu : gq == 5 ? 0xffffffffu : gq == 6 ? 0xffff0000u : 0u) & kf2;
          h128 = (gq == -4 ? 0x0000ffffu : gq == -3 ? 0xffffffffu : gq == -2 ? 0xffff0000u : 0u) & kf2;
        }
        bar_arrive(7, 384);
        bar_sync(4, 384);
        mbar_wait_long(BAR(B_UCH + warp), 0);
        if (lane == 0) TS(7);
        float acc[16][4];
#pragma unroll
        for (int i = 0; i < 16; ++i) { acc[i][0] = acc[i][1] = acc[i][2] = acc[i][3] = 0.f; }
        {
          const uint32_t pd_lane = pb + (PD_OFF + 16 + gq) * 4;
          const int prow0 = 8 + (lane & 7) + ((lane >> 4) << 3), hs = (lane >> 3) & 1;
          const uint32_t zero = (uint32_t)cta >> 20;
          uint32_t B[2][4][4];
          uint32_t A[4][4];
          const uint32_t la0 = ub + prow0 * 32 + ((hs ^ ((prow0 >> 2) & 1)) << 4);
#pragma unroll
          for (int m2 = 0; m2 < 4; ++m2) ldsm_x4(B[0][m2], la0 + m2 * 512);
#pragma unroll
          for (int i = 0; i < 4; ++i) {
            const uint32_t a = pd_lane + i * 512;
            A[i][0] = lds32(a); A[i][1] = lds32(a + 32); A[i][2] = lds32(a - 32); A[i][3] = lds32(a + zero);
          }
          uint32_t la = la0;
#define UNR_RHO 1
#define UNR_TAIL 1
          constexpr int unr_rho = UNR_RHO, unr_tail = UNR_TAIL;
#pragma unroll unr_rho
          for (int rho = 0; rho < 8; ++rho) {
#pragma unroll
            for (int m2 = 0; m2 < 4; ++m2) ldsm_x4(B[1][m2], la + (4 + m2) * 512);
#pragma unroll
            for (int i = 0; i < 4; ++i)
#pragma unroll
              for (int m = 0; m < 8; ++m) mma_bf16v(acc[m + i], A[i], B[0][m >> 1][2 * (m & 1)], B[0][m >> 1][2 * (m & 1) + 1]);
            const int prow = prow0 - min(rho + 1, 7);
            la = ub + prow * 32 + ((hs ^ ((prow >> 2) & 1)) << 4);
#pragma unroll
            for (int m2 = 0; m2 < 4; ++m2) ldsm_x4(B[0][m2], la + m2 * 512);
            const uint32_t pa = pd_lane + (rho + 1) * 64;
#pragma unroll
            for (int i = 0; i < 4; ++i) {
#pragma unroll
              for (int m = 0; m < 8 - i; ++m)
                mma_bf16v(acc[8 + m + i], A[i], B[1][m >> 1][2 * (m & 1)], B[1][m >> 1][2 * (m & 1) + 1]);
              A[i][0] = lds32(pa + i * 512); A[i][1] = lds32(pa + i * 512 + 32); A[i][2] = lds32(pa + i * 512 - 32);
              A[i][3] = lds32(pa + i * 512 + zero);
            }
          }
          if (lane == 0) TS(40);
          {
            uint32_t b8[4];
            ldsm_x4(b8, la + 4 * 512);
            const uint32_t h63 = lds32(pd_lane + 63 * 32), h64 = lds32(pd_lane + 64 * 32);
            const uint32_t a63[4] = {0u, h127, 0u, 0u}, a32[4] = {h64, 0u, h63, h64}, a64[4] = {h128, 0u, h127, h128};
#pragma unroll
            for (int m2 = 0; m2 < 4; ++m2) ldsm_x4(B[1][m2], la0 + m2 * 512);
#pragma unroll
            for (int m = 0; m < 8; ++m) mma_bf16v(acc[m + 7], a63, B[0][m >> 1][2 * (m & 1)], B[0][m >> 1][2 * (m & 1) + 1]);
#pragma unroll
            for (int m2 = 0; m2 < 2; ++m2) ldsm_x4(B[0][m2], la0 + (4 + m2) * 512);
#pragma unroll
            for (int m = 0; m < 8; ++m) mma_bf16v(acc[m + 4], a32, B[1][m >> 1][2 * (m & 1)], B[1][m >> 1][2 * (m & 1) + 1]);
            mma_bf16v(acc[15], a63, b8[0], b8[1]);
#pragma unroll
            for (int m = 0; m < 8; ++m) mma_bf16v(acc[m + 8], a64, B[1][m >> 1][2 * (m & 1)], B[1][m >> 1][2 * (m & 1) + 1]);
#pragma unroll
            for (int m = 0; m < 4; ++m) mma_bf16v(acc[m + 12], a32, B[0][m >> 1][2 * (m & 1)], B[0][m >> 1][2 * (m & 1) + 1]);
          }
          if (lane == 0) TS(41);
          bar_sync(5, 384);
#pragma unroll unr_tail
          for (int v = 0; v < 4; ++v)
            conv_tail<4, 3, 11>(acc, pb + (P2_OFF + 56 * v + gq - 16) * 4, vv + ((v & 1) ? VV_U3 : VV_U5), v >> 1, v == 0, lane);
          if (lane == 0) TS(42);
#pragma unroll unr_tail
          for (int pi = 0; pi < 2; ++pi)
            conv_tail<8, 5, 7>(acc, pb + (P3_OFF + 88 * pi + gq - 48) * 4, vv + (pi ? VV_U7 : VV_U9), pi, pi == 0, lane);
        }
        if (lane == 0) TS(8);
        __syncwarp();
        {
          const int mt = lane >> 3;
          const uint32_t a = pb + (128 * (mt >> 1) + 16 * (lane & 7) + 8 * (mt & 1)) * 2;
#pragma unroll
          for (int ab = 0; ab < 16; ab += 2)
            stsm_x4_t(a + ab * 256, pack_bf16(acc[ab][0], acc[ab][1]), pack_bf16(acc[ab][2], acc[ab][3]),
                      pack_bf16(acc[ab + 1][0], acc[ab + 1][1]), pack_bf16(acc[ab + 1][2], acc[ab + 1][3]));
        }
        fence_async_smem();
        __syncwarp();
        if (lane < 2) mbar_arrive_cluster(BAR(B_CONVD), lane);
        bar_arrive(3, 384);
        if (elect_one()) {
          bulk_store(p.yT + (size_t)d * 2048, pb, 4096);
          bulk_commit();
          bulk_wait0();
          red_relaxed_add(&g_cnt[(C_Y + (cta >> 4)) * 32], 1);
          TS(9);
        }
        bar_sync(2, 128);
        if (warp == 0 && elect_one()) {
          wait_counter(&g_cnt[(C_Y + tj) * 32], (epoch + 1) * 64);
          TS(28);
          mbar_expect_tx(BAR(B_TILE), 16384);
          tma_load_2d(sb + SM_U, &maps.yT, ti * 128, tj * 64, BAR(B_TILE));
          tma_load_2d(sb + SM_U + 8192, &maps.yT, ti * 128 + 64, tj * 64, BAR(B_TILE));
        }
        __syncwarp();
      }
      mbar_wait_long(BAR(B_TILE), pass);
      if (lane == 0) TS(26 + 3 * pass);
      {
        const int m = lane >> 3, r = lane & 7;
#pragma unroll 2
        for (int it = 0; it < 8; ++it) {
          const int tb = warp * 4 + (it >> 1), cb = (it & 1) * 4 + m;
          const uint32_t at = (tb * 8 + r) * 128 + ((cb ^ r) << 4);
          const uint32_t ac = (tb >> 3) * 8192 + (cb * 8 + r) * 128 + (((tb & 7) ^ (pass ? 0 : tb >> 3) ^ r) << 4);
          uint32_t v[4];
          ldsm_x4_t(v, sb + SM_U + (pass ? ac : at));
          stsm_x4(sb + SM_P + (pass ? at : ac), v[0], v[1], v[2], v[3]);
        }
      }
      if (pass == 0 && tid == 0) TS(35);
      fence_async_smem();
      if (pass == 0) {
        bar_arrive(6, 160);
      } else {
        bar_sync(2, 128);
        if (warp == 0 && elect_one()) {
          tma_store_2d(&maps.out, sb + SM_P, 64 * tj, 128 * ti);
          bulk_commit();
          bulk_wait_read0();
          TS(30);
        }
      }
    }
  } else if (warp < 12) {
    const int w8 = warp - 4;
    const int row = w8 * 16 + (lane & 7) + (((lane >> 3) & 1) << 3);
    uint32_t pq[16];
    {
      float acc[96];
#pragma unroll 1
      for (int ks = 0, s = 0, ph = 0; ks < 16; ++ks) {
        mbar_wait(BAR(B_FULL + s), ph);
        if (tid == 128 && !(ks & 1)) TSR(16, ks == 0 ? 16 : 9 + (ks >> 1) + (ks > 12 ? 43 : 0));
        const uint32_t st = sb + s * STG_BYTES;
        const uint32_t da = mkdesc(st + STG_X + (w8 >> 2) * 4096, 16);
        const uint32_t db = mkdesc(st + STG_W, 2048);
        wg_fence();
        wgmma_n192(acc, da, db, ks != 0);
        wgmma_n192(acc, da + 2, db + 384, 1);
        wg_commit();
        const uint32_t eprev = BAR(B_EMPTY + (s == 0 ? NSTG - 1 : s - 1));
        if (++s == NSTG) { s = 0; ph ^= 1; }
        if (ks > 0) {
          wg_wait<1>();
          if (lane < 2) mbar_arrive_cluster(eprev, lane);
        }
      }
      wg_wait<0>();
      bar_arrive(4, 384);
      if (tid == 128) TS(17);
      auto phi2 = [](float a, float b) -> uint32_t {
        const uint32_t x = pack_bf16(a, b);
        const uint32_t e = pack_bf16(ex2(bf_lo(x) * 1.4426950408889634f), ex2(bf_hi(x) * 1.4426950408889634f));
        const uint32_t m = __hgt2_mask(*reinterpret_cast<const __nv_bfloat162*>(&x), __floats2bfloat162_rn(0.f, 0.f));
        return badd((badd(x, 0x3f803f80u) & m) | (e & ~m), 0x35863586u);
      };
      uint32_t pk[16];
#pragma unroll
      for (int i = 0; i < 16; ++i) pk[i] = phi2(acc[32 + 2 * i], acc[33 + 2 * i]);
      if (tid == 128) TS(53);
      bar_sync(1, 256);
#pragma unroll
      for (int i = 0; i < 8; i += 2) {
        const uint32_t off = row * 128 + (((i + (lane >> 4)) ^ (row & 7)) << 4);
        stsm_x4(sb + SM_PK + off, pk[2 * i], pk[2 * i + 1], pk[2 * i + 2], pk[2 * i + 3]);
        stsm_x4(sb + SM_VS + off, pack_bf16(acc[64 + 4 * i], acc[65 + 4 * i]), pack_bf16(acc[66 + 4 * i], acc[67 + 4 * i]),
                pack_bf16(acc[68 + 4 * i], acc[69 + 4 * i]), pack_bf16(acc[70 + 4 * i], acc[71 + 4 * i]));
      }
      bar_sync(1, 256);
      {
        const int hh = w8 >> 1, dtile = w8 & 1;
        float kv[2][4] = {{0.f, 0.f, 0.f, 0.f}, {0.f, 0.f, 0.f, 0.f}}, zz[2][4] = {{0.f, 0.f, 0.f, 0.f}, {0.f, 0.f, 0.f, 0.f}};
        const int m = lane >> 3;
        const uint32_t aa = sb + SM_VS + ((lane & 7) + ((m >> 1) << 3)) * 128 + (((2 * hh + (m & 1)) ^ (lane & 7)) << 4);
        const uint32_t ab = sb + SM_PK + (lane & 15) * 128 + (((2 * hh + dtile) ^ (lane & 7)) << 4);
#pragma unroll
        for (int ks = 0; ks < 8; ++ks) {
          uint32_t a[4], b0, b1;
          ldsm_x4_t(a, aa + ks * 2048);
          ldsm_x2_t(b0, b1, ab + ks * 2048);
          mma_bf16(kv[ks & 1], a[0], a[1], a[2], a[3], b0, b1);
          mma_bf16(zz[ks & 1], 0x3f803f80u, 0x3f803f80u, 0x3f803f80u, 0x3f803f80u, b0, b1);
        }
        const uint32_t kp = sb + SM_KV + hh * 1088;
        sts128(kp + dtile * 512 + lane * 16, __float_as_uint(kv[0][0] + kv[1][0]), __float_as_uint(kv[0][1] + kv[1][1]),
               __float_as_uint(kv[0][2] + kv[1][2]), __float_as_uint(kv[0][3] + kv[1][3]));
        if (g == 0) sts_f32x2(kp + 1024 + dtile * 32 + q * 8, zz[0][0] + zz[1][0], zz[0][1] + zz[1][1]);
        fence_async_smem();
        __syncwarp();
        if (lane == 0) mbar_arrive(BAR(B_KVP));
        if (tid == 128) TS(55);
      }
#pragma unroll
      for (int i = 0; i < 16; ++i) pq[i] = phi2(acc[2 * i], acc[2 * i + 1]);
    }
    if (tid == 128) TS(56);
    {
      const int ch = w8 >> 1;
      const uint32_t ub = sb + SM_U + ch * U_BYTES, vb = sb + SM_VV + ch * VV_BYTES;
      auto swz = [](int k, int pad) { const int r = (k >> 1) + pad; return (uint32_t)(r * 32 + (((k & 1) ^ ((r >> 2) & 1)) << 4)); };
      int k = -2 + (w8 & 1) * 32 + lane;
      uint32_t a0 = ub + swz(k - 1, 8), a1 = ub + swz(k, 8), a2 = ub + swz(k + 1, 8), aw = vb + swz(k, PADV);
      bar_sync(7, 384);
      mbar_wait_long(BAR(B_UCH + ch), 0);
      if (lane < 16 && !(w8 & 1)) {
        const uint32_t az = vb + swz(lane - 18, PADV);
        sts128(az + VV_U3, 0, 0, 0, 0); sts128(az + VV_U5, 0, 0, 0, 0); sts128(az + VV_U7, 0, 0, 0, 0); sts128(az + VV_U9, 0, 0, 0, 0);
      }
#pragma unroll 1
      for (; k - lane < 208; k += 64, a0 += 1024, a1 += 1024, a2 += 1024, aw += 1024) {
        const uint4 t0 = lds128(a0), t1 = lds128(a1), t2 = lds128(a2);
        const uint32_t E[12] = {t0.x, t0.y, t0.z, t0.w, t1.x, t1.y, t1.z, t1.w, t2.x, t2.y, t2.z, t2.w};
        uint32_t O[8];
#pragma unroll
        for (int j = 0; j < 8; ++j) O[j] = __byte_perm(E[j + 1], E[j + 2], 0x5432);
        uint32_t s3[6], s5[4], s7[4], s9[4];
#pragma unroll
        for (int j = 0; j < 6; ++j) s3[j] = badd(badd(O[j], O[j + 1]), E[j + 2]);
#pragma unroll
        for (int j = 0; j < 4; ++j) {
          s5[j] = badd(s3[j + 2], badd(E[j + 3], E[j + 5]));
          s7[j] = badd(s5[j], badd(O[j + 1], O[j + 4]));
          s9[j] = badd(s7[j], badd(E[j + 2], E[j + 6]));
        }
        if (k < 208) { sts128(aw + VV_U3, s3[0], s3[1], s3[2], s3[3]); sts128(aw + VV_U5, s5[0], s5[1], s5[2], s5[3]); }
        if (k < 144) { sts128(aw + VV_U7, s7[0], s7[1], s7[2], s7[3]); sts128(aw + VV_U9, s9[0], s9[1], s9[2], s9[3]); }
      }
      bar_arrive(5, 384);
    }
    if (tid == 128) TS(6);
    if (warp == 4) mbar_wait_long(BAR(B_KVF), 0);
    bar_sync(1, 256);
    if (tid == 128) TS(19);
    {
      uint32_t kb[4][6];
#pragma unroll
      for (int h = 0; h < 4; ++h) {
        const uint32_t kp = sb + SM_KV + h * 1088;
        const uint4 k0 = lds128(kp + lane * 16), k1 = lds128(kp + 512 + lane * 16);
        const uint32_t za = kp + 1024 + q * 8;
        auto pk2 = [](uint32_t x, uint32_t y) { return pack_bf16(__uint_as_float(x), __uint_as_float(y)); };
        kb[h][0] = pk2(k0.x, k0.y); kb[h][1] = pk2(k1.x, k1.y); kb[h][2] = pk2(k0.z, k0.w); kb[h][3] = pk2(k1.z, k1.w);
        kb[h][4] = pack_bf16(lds_f32(za), lds_f32(za + 4)); kb[h][5] = pack_bf16(lds_f32(za + 32), lds_f32(za + 36));
      }
#pragma unroll
      for (int h = 0; h < 4; ++h) {
        float n0[4] = {0.f, 0.f, 0.f, 0.f}, n1[4] = {0.f, 0.f, 0.f, 0.f}, dn[4] = {0.f, 0.f, 0.f, 0.f};
        mma_bf16(n0, pq[4 * h], pq[4 * h + 1], pq[4 * h + 2], pq[4 * h + 3], kb[h][0], kb[h][1]);
        mma_bf16(n1, pq[4 * h], pq[4 * h + 1], pq[4 * h + 2], pq[4 * h + 3], kb[h][2], kb[h][3]);
        mma_bf16(dn, pq[4 * h], pq[4 * h + 1], pq[4 * h + 2], pq[4 * h + 3], kb[h][4], kb[h][5]);
        const uint32_t dd = pack_bf16(dn[0], dn[2]);
        const uint32_t d2 = pack_bf16(bf_lo(dd) + 1e-6f, bf_hi(dd) + 1e-6f);
        const float r0 = rcp(bf_lo(d2)), r1 = rcp(bf_hi(d2));
        const uint32_t x0 = pack_bf16(n0[0], n0[1]), x1 = pack_bf16(n0[2], n0[3]);
        const uint32_t x2 = pack_bf16(n1[0], n1[1]), x3 = pack_bf16(n1[2], n1[3]);
        stsm_x4(sb + SM_QS + row * 128 + (((2 * h + (lane >> 4)) ^ (row & 7)) << 4),
                pack_bf16(bf_lo(x0) * r0, bf_hi(x0) * r0), pack_bf16(bf_lo(x1) * r1, bf_hi(x1) * r1),
                pack_bf16(bf_lo(x2) * r0, bf_hi(x2) * r0), pack_bf16(bf_lo(x3) * r1, bf_hi(x3) * r1));
      }
    }
    fence_async_smem();
    __syncwarp();
    if (lane == 0) mbar_arrive(BAR(B_OST));
    if (tid == 128) TS(57);
    if (warp == 4) mbar_wait_long(BAR(B_WO), 0);
    bar_sync(3, 384);
    {
      float o[32];
#pragma unroll 1
      for (int c = 0; c < 8; ++c) {
        mbar_wait_long(BAR(B_RF + c), 0);
        if (tid == 128) TSR(22, c == 0 ? 22 : 43 + c);
        const uint32_t slot = c < 4 ? SM_QS + c * 16384 : c < 7 ? SM_VV + (c - 4) * 16384 : SM_QS;
        const uint32_t da = mkdesc(sb + slot + (w8 >> 2) * 8192, 16);
        const uint32_t db = mkdesc(sb + SM_WO + c * 8192, 8192);
        wg_fence();
#pragma unroll
        for (int k = 0; k < 4; ++k) wgmma_n64(o, da + 2 * k, db + 128 * k, (c | k) != 0);
        wg_commit();
        if (c == 1) {
          wg_wait<1>();
          if (lane < 2) mbar_arrive_cluster(BAR(B_RE), lane);
        }
      }
      wg_wait<0>();
      if (tid == 128) TS(51);
      bar_sync(1, 256);
#pragma unroll
      for (int i = 0; i < 8; i += 2)
        stsm_x4(sb + SM_BOUT + row * 128 + (((i + (lane >> 4)) ^ (row & 7)) << 4), pack_bf16(o[4 * i], o[4 * i + 1]),
                pack_bf16(o[4 * i + 2], o[4 * i + 3]), pack_bf16(o[4 * i + 4], o[4 * i + 5]), pack_bf16(o[4 * i + 6], o[4 * i + 7]));
      fence_async_smem();
      bar_sync(1, 256);
      if (tid == 128) TS(52);
      if (warp == 4 && elect_one()) {
        tma_store_2d(&maps.out, sb + SM_BOUT, 512 + 64 * pj, 128 * pi);
        bulk_commit();
        bulk_wait_read0();
        TS(23);
      }
    }
  } else {
    asm volatile("setmaxnreg.dec.sync.aligned.u32 40;");
    if (warp == 12) {
      if (elect_one()) {
#pragma unroll 1
        for (int ks = NSTG, s = 0, ph = 0; ks < 16; ++ks) {
          mbar_wait(BAR(B_EMPTY + s), ph);
          issue_stage(ks, s);
          if (ks == NSTG) l2_prefetch((const char*)p.wo + (size_t)cta * 4096, 4096);
          if (++s == NSTG) { s = 0; ph ^= 1; }
        }
        mbar_wait(BAR(B_EMPTY + 6), 1);
        mbar_expect_tx(BAR(B_WO), 65536);
        tma_load_2d(sb + SM_WO, &maps.wo, pj * 64, 0, BAR(B_WO));
        tma_load_2d(sb + SM_WO + 32768, &maps.wo, pj * 64, 256, BAR(B_WO));
        float* kvg = &g_kv[epoch & 1][tj][0];
        mbar_wait_long(BAR(B_KVP), 0);
        bulk_reduce_add_f32(kvg, sb + SM_KV, 4352);
        bulk_commit();
        bulk_wait0();
        red_relaxed_add(&g_cnt[(C_KV + tj) * 32], 1);
        TS(18);
        wait_counter(&g_cnt[(C_KV + tj) * 32], (epoch + 1) * 16);
        mbar_expect_tx(BAR(B_KVF), 4352);
        bulk_load(sb + SM_KV, kvg, 4352, BAR(B_KVF));
        mbar_wait_long(BAR(B_OST), 0);
        tma_store_2d(&maps.o, sb + SM_QS, tj * 64, ti * 128);
        tma_store_2d(&maps.o, sb + SM_QS + 8192, tj * 64, ti * 128 + 64);
        bulk_commit();
        bulk_wait0();
        red_relaxed_add(&g_cnt[(C_O + ti) * 32], 1);
        TS(20);
        mbar_arrive_cluster(BAR(B_SLOT), 0);
        mbar_arrive_cluster(BAR(B_SLOT), 1);
        wait_counter(&g_cnt[(C_O + pi) * 32], (epoch + 1) * 8);
        if (cta == 0) g_epoch = epoch + 1;
        mbar_wait(BAR(B_SLOT), 0);
        TS(21);
#pragma unroll 1
        for (int c = 0; c < 8; ++c) {
          if (c == 4) mbar_wait_long(BAR(B_CONVD), 0);
          if (c == 7) mbar_wait(BAR(B_RE), 0);
          const uint32_t slot = c < 4 ? SM_QS + c * 16384 : c < 7 ? SM_VV + (c - 4) * 16384 : SM_QS;
          mbar_expect_tx(BAR(B_RF + c), 16384);
          tma_load_2d_mc(sb + slot + rank * 8192, &maps.o, c * 64, pi * 128 + rank * 64, BAR(B_RF + c), 3);
        }
      }
    } else if (warp == 13) {
      bar_sync(6, 160);
      sts128(sb + SM_U + (lane >> 4) * U_BYTES + (lane & 15) * 16, 0, 0, 0, 0);
      sts128(sb + SM_U + (2 + (lane >> 4)) * U_BYTES + (lane & 15) * 16, 0, 0, 0, 0);
      __syncwarp();
      if (elect_one()) {
        tma_store_2d(&maps.uT, sb + SM_P, ti * 128, tj * 64);
        tma_store_2d(&maps.uT, sb + SM_P + 8192, ti * 128 + 64, tj * 64);
        bulk_commit();
        bulk_wait_read0();
        mbar_arrive(BAR(B_PFREE));
        bulk_wait0();
        red_relaxed_add(&g_cnt[(C_U + tj) * 32], 1);
        TS(27);
        wait_counter(&g_cnt[(C_U + (cta >> 4)) * 32], (epoch + 1) * 16);
#pragma unroll 1
        for (int c = 0; c < 4; ++c) {
          mbar_expect_tx(BAR(B_UCH + c), 4096);
          bulk_load(sb + SM_U + c * U_BYTES + 256, p.uT + (size_t)(cta * 4 + c) * 2048, 4096, BAR(B_UCH + c));
        }
        TS(3);
      }
      __syncwarp();
      if (ti == 0) {
        float4* z = (float4*)&g_kv[(epoch & 1) ^ 1][tj][0];
#pragma unroll 1
        for (int i = lane; i < 272; i += 32) z[i] = make_float4(0.f, 0.f, 0.f, 0.f);
      }
    }
  }
  __syncwarp();
  cluster_arrive();
  cluster_wait();
  if (tid == 0) TS(31);
#undef BAR
}

typedef CUresult (*EncodeFn)(CUtensorMap*, CUtensorMapDataType, cuuint32_t, void*, const cuuint64_t*, const cuuint64_t*,
                             const cuuint32_t*, const cuuint32_t*, CUtensorMapInterleave, CUtensorMapSwizzle,
                             CUtensorMapL2promotion, CUtensorMapFloatOOBfill);

static void make_map(EncodeFn enc, CUtensorMap* m, const void* base, uint64_t inner, uint64_t outer, uint32_t box_in,
                     uint32_t box_out, CUtensorMapSwizzle swz = CU_TENSOR_MAP_SWIZZLE_128B) {
  cuuint64_t gd[2] = {inner, outer};
  cuuint64_t gs[1] = {inner * 2};
  cuuint32_t bd[2] = {box_in, box_out};
  cuuint32_t es[2] = {1, 1};
  enc(m, CU_TENSOR_MAP_DATA_TYPE_BFLOAT16, 2, const_cast<void*>(base), gd, gs, bd, es, CU_TENSOR_MAP_INTERLEAVE_NONE,
      swz, CU_TENSOR_MAP_L2_PROMOTION_L2_128B, CU_TENSOR_MAP_FLOAT_OOB_FILL_NONE);
}

}

extern "C" void kernel_launch(void* const* d_in, const int* in_sizes, int n_in, void* d_out, int out_size) {
  using namespace s4la;
  (void)in_sizes; (void)n_in; (void)out_size;
  static EncodeFn enc = nullptr;
  static void *uT = nullptr, *yT = nullptr, *oS = nullptr;
  if (!enc) {
    void* fn = nullptr;
    cudaDriverEntryPointQueryResult qr;
    cudaGetDriverEntryPoint("cuTensorMapEncodeTiled", &fn, cudaEnableDefault, &qr);
    enc = (EncodeFn)fn;
    cudaGetSymbolAddress(&uT, g_uT);
    cudaGetSymbolAddress(&yT, g_yT);
    cudaGetSymbolAddress(&oS, g_o);
    cudaFuncSetAttribute(fused_kernel, cudaFuncAttributeMaxDynamicSharedMemorySize, SM_TOTAL);
  }
  const __nv_bfloat16* const* in = (const __nv_bfloat16* const*)d_in;
  Maps maps;
  make_map(enc, &maps.x, in[9], 512, 2048, 32, 128, CU_TENSOR_MAP_SWIZZLE_64B);
  {
    cuuint64_t gd[3] = {512, 512, 3};
    cuuint64_t gs[2] = {3072, 1024};
    cuuint32_t bd[3] = {64, 16, 3};
    cuuint32_t es[3] = {1, 1, 1};
    enc(&maps.w, CU_TENSOR_MAP_DATA_TYPE_BFLOAT16, 3, const_cast<__nv_bfloat16*>(in[10]), gd, gs, bd, es,
        CU_TENSOR_MAP_INTERLEAVE_NONE, CU_TENSOR_MAP_SWIZZLE_128B, CU_TENSOR_MAP_L2_PROMOTION_L2_128B,
        CU_TENSOR_MAP_FLOAT_OOB_FILL_NONE);
  }
  make_map(enc, &maps.wo, in[11], 512, 512, 64, 256);
  make_map(enc, &maps.u, in[0], 512, 2048, 64, 128);
  make_map(enc, &maps.uT, uT, 2048, 512, 64, 64);
  make_map(enc, &maps.yT, yT, 2048, 512, 64, 64);
  make_map(enc, &maps.o, oS, 512, 2048, 64, 64);
  make_map(enc, &maps.out, d_out, 1024, 2048, 64, 128);
  Ptrs p;
  p.A_re = in[1]; p.A_im = in[2]; p.B_re = in[3]; p.B_im = in[4]; p.C_re = in[5]; p.C_im = in[6];
  p.log_dt = in[7]; p.Dskip = in[8]; p.x = in[9]; p.wqkv = in[10]; p.wo = in[11];
  p.uT = (__nv_bfloat16*)uT; p.yT = (__nv_bfloat16*)yT;
  fused_kernel<<<NCTA, NTHREADS, SM_TOTAL, cudaStreamPerThread>>>(maps, p);
}
```

```cpp
#include <cuda_runtime.h>
#include <cuda_bf16.h>
#include <cuda_fp16.h>
#include <cuda.h>
#include <stdint.h>

#define DEVI __device__ __forceinline__

namespace s4la {

constexpr int NTHREADS = 512;
constexpr int NCTA = 128;

constexpr int NSTG = 7;
constexpr uint32_t STG_BYTES = 20480, STG_X = 0, STG_W = 8192;
constexpr uint32_t SM_QS = 0;
constexpr uint32_t SM_PK = SM_QS + 16384, SM_VS = SM_QS + 32768;
constexpr uint32_t SM_WO = 65536;
constexpr uint32_t SM_KV = 131072;
constexpr uint32_t SM_BOUT = 16384;
constexpr uint32_t SM_U = 143360, U_BYTES = 4352;
constexpr uint32_t SM_P = 160768, P_BYTES = 4096;
constexpr uint32_t SM_VV = 177152, VV_BYTES = 12800;
constexpr uint32_t VV_U5 = 0, VV_U3 = 3712, VV_U9 = 7424, VV_U7 = 10112;
constexpr uint32_t KG_BYTES = 3200;
constexpr uint32_t SM_BAR = SM_VV + 4 * VV_BYTES;
constexpr uint32_t SM_PTAB = SM_BAR + 320;
constexpr uint32_t SM_TOTAL = SM_PTAB + 2048;
static_assert(SM_TOTAL <= 232448, "shared memory");
constexpr int PADV = 12;

enum { B_FULL = 0, B_EMPTY = 7, B_TILE = 14, B_UCH = 15, B_KVP = 19, B_KVF = 20, B_OST = 21, B_RF = 22, B_WO = 30, B_RE = 31, B_PFREE = 32, B_CONVD = 33, B_SLOT = 34, B_COUNT = 35 };
__host__ __device__ constexpr int bar_count(int i) {
  return (i >= B_EMPTY && i < B_TILE) ? 16 : (i == B_KVP || i == B_OST || i == B_CONVD) ? 8 : i == B_RE ? 16 : i == B_SLOT ? 2 : 1;
}

constexpr int PD_OFF = 0, P2_OFF = 544, P3_OFF = 768;

constexpr int SL_K2048 = 20, SL_ZERO = 21, SL_510 = 22, SL_0 = 23;
__host__ __device__ constexpr int koff(int y) {
  return y < 8 ? y : y < 12 ? 256 + 2 * (y - 8) : y < 16 ? 512 + 256 * ((y - 12) >> 1) + 4 * (y & 1) : 1024 + 256 * (y - 16);
}
__host__ __device__ constexpr int kidx_c(int l) {
  const int y = l < 256 ? (l & 7) : l < 512 ? 8 + ((l & 7) >> 1) : l < 1024 ? 12 + (((l - 512) >> 8) << 1) + ((l >> 2) & 1)
                                                                            : 16 + ((l - 1024) >> 8);
  return ((l >> 3) & 31) * 24 + y;
}
constexpr int slot_direct(int l) {
  if (l < 0 || l > 510) return SL_ZERO;
  if (l == 510) return SL_510;
  if (l == 0) return SL_0;
  return kidx_c(l < 256 ? l : ((l + ((l >> 1) & 1)) & ~1));
}
constexpr int slot_seg2(int v, int k) { return (k >= 32 && k < 64) ? kidx_c(16 * k + 4 * v) : SL_ZERO; }
constexpr int slot_seg3(int pi, int k) {
  return (k >= 64 && k < 128) ? kidx_c(16 * k + 8 * pi) : ((k == 128 && pi == 0) ? SL_K2048 : SL_ZERO);
}
constexpr int slot_word(int w) {
  return w < 0 ? SL_ZERO : w < 544 ? slot_direct(w - 16) : w < 768 ? slot_seg2((w - 544) / 56, 16 + (w - 544) % 56)
       : w < 944 ? slot_seg3((w - 768) / 88, 48 + (w - 768) % 88) : SL_ZERO;
}
struct PTab { uint32_t v[512]; };
constexpr PTab make_ptab() {
  PTab t{};
  for (int lane = 0; lane < 32; ++lane)
    for (int i = 0; i < 16; ++i)
      t.v[i * 32 + lane] = (slot_word(31 * lane - 1 + 2 * i) * 4) | ((slot_word(31 * lane + 2 * i) * 4) << 16);
  return t;
}
__device__ const PTab g_ptab = make_ptab();

__device__ __nv_bfloat16 g_uT[512 * 2048];
__device__ __nv_bfloat16 g_yT[512 * 2048];
__device__ __nv_bfloat16 g_o[2048 * 512];
__device__ float g_kv[2][8][4 * 272];
__device__ unsigned g_cnt[64 * 32];
__device__ unsigned g_epoch;
#define TS(slot) do { } while (0)
#define TSR(on, slot) do { } while (0)
#define TSD(slot) do { } while (0)
enum { C_U = 0, C_KV = 8, C_O = 16, C_Y = 32 };

struct Maps {
  CUtensorMap x, w, wo, u, uT, yT, o, out;
};
struct Ptrs {
  const __nv_bfloat16 *A_re, *A_im, *B_re, *B_im, *C_re, *C_im, *log_dt, *Dskip;
  const __nv_bfloat16 *x, *wqkv, *wo;
  __nv_bfloat16 *uT, *yT;
};

DEVI uint32_t s2u(const void* p) { return (uint32_t)__cvta_generic_to_shared(p); }
DEVI void mbar_init(uint32_t b, uint32_t c) { asm volatile("mbarrier.init.shared::cta.b64 [%0], %1;" ::"r"(b), "r"(c) : "memory"); }
DEVI void mbar_expect_tx(uint32_t b, uint32_t bytes) {
  asm volatile("mbarrier.arrive.expect_tx.shared::cta.b64 _, [%0], %1;" ::"r"(b), "r"(bytes) : "memory");
}
DEVI void mbar_arrive(uint32_t b) { asm volatile("mbarrier.arrive.shared::cta.b64 _, [%0];" ::"r"(b) : "memory"); }
DEVI void mbar_arrive_cluster(uint32_t b, uint32_t cta) {
  asm volatile("{\n.reg .b32 r;\nmapa.shared::cluster.u32 r, %0, %1;\nmbarrier.arrive.shared::cluster.b64 _, [r];\n}"
               ::"r"(b), "r"(cta) : "memory");
}
DEVI void mbar_wait(uint32_t b, uint32_t parity) {
  asm volatile("{\n.reg .pred p;\nLAB_WAIT:\nmbarrier.try_wait.parity.shared::cta.b64 p, [%0], %1;\n@!p bra LAB_WAIT;\n}"
               ::"r"(b), "r"(parity) : "memory");
}
DEVI void mbar_wait_long(uint32_t b, uint32_t parity) {
  asm volatile("{\n.reg .pred p;\nLAB_WAIT:\nmbarrier.try_wait.parity.shared::cta.b64 p, [%0], %1, 0x989680;\n@!p bra LAB_WAIT;\n}"
               ::"r"(b), "r"(parity) : "memory");
}
DEVI void bar_sync(int id, int n) { asm volatile("bar.sync %0, %1;" ::"r"(id), "r"(n) : "memory"); }
DEVI void bar_arrive(int id, int n) { asm volatile("bar.arrive %0, %1;" ::"r"(id), "r"(n) : "memory"); }
DEVI void fence_async_smem() { asm volatile("fence.proxy.async.shared::cta;" ::: "memory"); }
DEVI void fence_async_all() { asm volatile("fence.proxy.async;" ::: "memory"); }
DEVI void cluster_arrive() { asm volatile("barrier.cluster.arrive.relaxed.aligned;" ::: "memory"); }
DEVI void cluster_wait() { asm volatile("barrier.cluster.wait.aligned;" ::: "memory"); }

DEVI void tma_load_2d(uint32_t dst, const CUtensorMap* m, int c0, int c1, uint32_t bar) {
  asm volatile("cp.async.bulk.tensor.2d.shared::cluster.global.mbarrier::complete_tx::bytes [%0], [%1, {%3, %4}], [%2];"
               ::"r"(dst), "l"(m), "r"(bar), "r"(c0), "r"(c1) : "memory");
}
DEVI void tma_load_2d_mc(uint32_t dst, const CUtensorMap* m, int c0, int c1, uint32_t bar, uint16_t mask) {
  asm volatile("cp.async.bulk.tensor.2d.shared::cluster.global.mbarrier::complete_tx::bytes.multicast::cluster [%0], [%1, {%3, %4}], [%2], %5;"
               ::"r"(dst), "l"(m), "r"(bar), "r"(c0), "r"(c1), "h"(mask) : "memory");
}
DEVI void tma_load_3d_mc(uint32_t dst, const CUtensorMap* m, int c0, int c1, int c2, uint32_t bar, uint16_t mask) {
  asm volatile("cp.async.bulk.tensor.3d.shared::cluster.global.mbarrier::complete_tx::bytes.multicast::cluster [%0], [%1, {%3, %4, %5}], [%2], %6;"
               ::"r"(dst), "l"(m), "r"(bar), "r"(c0), "r"(c1), "r"(c2), "h"(mask) : "memory");
}
DEVI void tma_store_2d(const CUtensorMap* m, uint32_t src, int c0, int c1) {
  asm volatile("cp.async.bulk.tensor.2d.global.shared::cta.bulk_group [%0, {%2, %3}], [%1];"
               ::"l"(m), "r"(src), "r"(c0), "r"(c1) : "memory");
}
DEVI void bulk_load(uint32_t dst, const void* src, uint32_t bytes, uint32_t bar) {
  asm volatile("cp.async.bulk.shared::cluster.global.mbarrier::complete_tx::bytes [%0], [%1], %2, [%3];"
               ::"r"(dst), "l"(src), "r"(bytes), "r"(bar) : "memory");
}
DEVI void bulk_store(void* dst, uint32_t src, uint32_t bytes) {
  asm volatile("cp.async.bulk.global.shared::cta.bulk_group [%0], [%1], %2;" ::"l"(dst), "r"(src), "r"(bytes) : "memory");
}
DEVI void bulk_reduce_add_f32(void* dst, uint32_t src, uint32_t bytes) {
  asm volatile("cp.reduce.async.bulk.global.shared::cta.bulk_group.add.f32 [%0], [%1], %2;" ::"l"(dst), "r"(src), "r"(bytes) : "memory");
}
DEVI void bulk_commit() { asm volatile("cp.async.bulk.commit_group;" ::: "memory"); }
DEVI void bulk_wait0() { asm volatile("cp.async.bulk.wait_group 0;" ::: "memory"); }
DEVI void bulk_wait_read0() { asm volatile("cp.async.bulk.wait_group.read 0;" ::: "memory"); }
DEVI void l2_prefetch(const void* p, uint32_t bytes) {
  asm volatile("cp.async.bulk.prefetch.L2.global [%0], %1;" ::"l"(p), "r"(bytes) : "memory");
}
DEVI void prefetch_tmap(const CUtensorMap* m) { asm volatile("prefetch.tensormap [%0];" ::"l"(m) : "memory"); }

DEVI void red_release_add(unsigned* p, unsigned v) {
  asm volatile("red.release.gpu.global.add.u32 [%0], %1;" ::"l"(p), "r"(v) : "memory");
}
DEVI void red_relaxed_add(unsigned* p, unsigned v) {
  asm volatile("red.relaxed.gpu.global.add.u32 [%0], %1;" ::"l"(p), "r"(v) : "memory");
}
DEVI unsigned ld_relaxed(const unsigned* p) {
  unsigned v;
  asm volatile("ld.relaxed.gpu.global.u32 %0, [%1];" : "=r"(v) : "l"(p) : "memory");
  return v;
}
DEVI void wait_counter(const unsigned* p, unsigned target) {
#pragma unroll 1
  for (int it = 0; (int)(ld_relaxed(p) - target) < 0; ++it)
    if (it > (1 << 22)) __trap();
}

DEVI void ldsm_x4(uint32_t (&r)[4], uint32_t a) {
  asm volatile("ldmatrix.sync.aligned.m8n8.x4.shared.b16 {%0,%1,%2,%3}, [%4];"
               : "=r"(r[0]), "=r"(r[1]), "=r"(r[2]), "=r"(r[3]) : "r"(a) : "memory");
}
DEVI void ldsm_x4_t(uint32_t (&r)[4], uint32_t a) {
  asm volatile("ldmatrix.sync.aligned.m8n8.x4.trans.shared.b16 {%0,%1,%2,%3}, [%4];"
               : "=r"(r[0]), "=r"(r[1]), "=r"(r[2]), "=r"(r[3]) : "r"(a) : "memory");
}
DEVI void ldsm_x2_t(uint32_t& r0, uint32_t& r1, uint32_t a) {
  asm volatile("ldmatrix.sync.aligned.m8n8.x2.trans.shared.b16 {%0,%1}, [%2];" : "=r"(r0), "=r"(r1) : "r"(a) : "memory");
}
DEVI void stsm_x4(uint32_t a, uint32_t r0, uint32_t r1, uint32_t r2, uint32_t r3) {
  asm volatile("stmatrix.sync.aligned.m8n8.x4.shared.b16 [%0], {%1,%2,%3,%4};"
               ::"r"(a), "r"(r0), "r"(r1), "r"(r2), "r"(r3) : "memory");
}
DEVI void stsm_x4_t(uint32_t a, uint32_t r0, uint32_t r1, uint32_t r2, uint32_t r3) {
  asm volatile("stmatrix.sync.aligned.m8n8.x4.trans.shared.b16 [%0], {%1,%2,%3,%4};"
               ::"r"(a), "r"(r0), "r"(r1), "r"(r2), "r"(r3) : "memory");
}
DEVI uint32_t lds32(uint32_t a) { uint32_t v; asm volatile("ld.shared.b32 %0, [%1];" : "=r"(v) : "r"(a) : "memory"); return v; }
DEVI float lds_f32(uint32_t a) { float v; asm volatile("ld.shared.f32 %0, [%1];" : "=f"(v) : "r"(a) : "memory"); return v; }
DEVI void sts32(uint32_t a, uint32_t v) { asm volatile("st.shared.b32 [%0], %1;" ::"r"(a), "r"(v) : "memory"); }
DEVI void sts_f32(uint32_t a, float v) { asm volatile("st.shared.f32 [%0], %1;" ::"r"(a), "f"(v) : "memory"); }
DEVI void sts_f32x2(uint32_t a, float x, float y) { asm volatile("st.shared.v2.f32 [%0], {%1,%2};" ::"r"(a), "f"(x), "f"(y) : "memory"); }
DEVI uint4 lds128(uint32_t a) {
  uint4 v;
  asm volatile("ld.shared.v4.b32 {%0,%1,%2,%3}, [%4];" : "=r"(v.x), "=r"(v.y), "=r"(v.z), "=r"(v.w) : "r"(a) : "memory");
  return v;
}
DEVI void sts128(uint32_t a, uint32_t x, uint32_t y, uint32_t z, uint32_t w) {
  asm volatile("st.shared.v4.b32 [%0], {%1,%2,%3,%4};" ::"r"(a), "r"(x), "r"(y), "r"(z), "r"(w) : "memory");
}

DEVI void mma_bf16(float (&d)[4], uint32_t a0, uint32_t a1, uint32_t a2, uint32_t a3, uint32_t b0, uint32_t b1) {
  asm("mma.sync.aligned.m16n8k16.row.col.f32.bf16.bf16.f32 {%0,%1,%2,%3}, {%4,%5,%6,%7}, {%8,%9}, {%0,%1,%2,%3};"
      : "+f"(d[0]), "+f"(d[1]), "+f"(d[2]), "+f"(d[3])
      : "r"(a0), "r"(a1), "r"(a2), "r"(a3), "r"(b0), "r"(b1));
}
DEVI void mma_f16(float (&d)[4], const uint32_t (&a)[4], uint32_t b0, uint32_t b1) {
  asm("mma.sync.aligned.m16n8k16.row.col.f32.f16.f16.f32 {%0,%1,%2,%3}, {%4,%5,%6,%7}, {%8,%9}, {%0,%1,%2,%3};"
      : "+f"(d[0]), "+f"(d[1]), "+f"(d[2]), "+f"(d[3])
      : "r"(a[0]), "r"(a[1]), "r"(a[2]), "r"(a[3]), "r"(b0), "r"(b1));
}
DEVI void mma_bf16v(float (&d)[4], const uint32_t (&a)[4], uint32_t b0, uint32_t b1) {
  asm volatile("mma.sync.aligned.m16n8k16.row.col.f32.bf16.bf16.f32 {%0,%1,%2,%3}, {%4,%5,%6,%7}, {%8,%9}, {%0,%1,%2,%3};"
               : "+f"(d[0]), "+f"(d[1]), "+f"(d[2]), "+f"(d[3])
               : "r"(a[0]), "r"(a[1]), "r"(a[2]), "r"(a[3]), "r"(b0), "r"(b1));
}
DEVI uint32_t pack_bf16(float lo, float hi) {
  uint32_t r;
  asm("cvt.rn.bf16x2.f32 %0, %1, %2;" : "=r"(r) : "f"(hi), "f"(lo));
  return r;
}
DEVI uint32_t pack_f16(float lo, float hi) {
  uint32_t r;
  asm("cvt.rn.f16x2.f32 %0, %1, %2;" : "=r"(r) : "f"(hi), "f"(lo));
  return r;
}
DEVI uint32_t ldg16(const __nv_bfloat16* p) {
  uint32_t v;
  asm volatile("ld.global.nc.u16 %0, [%1];" : "=r"(v) : "l"(p));
  return v;
}
DEVI bool elect_one() {
  uint32_t pred;
  asm volatile("{\n.reg .pred p;\nelect.sync _|p, 0xffffffff;\nselp.u32 %0, 1, 0, p;\n}" : "=r"(pred));
  return pred != 0;
}
DEVI float bf_lo(uint32_t v) { return __uint_as_float(v << 16); }
DEVI float bf_hi(uint32_t v) { return __uint_as_float(v & 0xffff0000u); }
DEVI float bf2f(__nv_bfloat16 v) { return __bfloat162float(v); }
DEVI float round_bf16(float v) { return __bfloat162float(__float2bfloat16_rn(v)); }
DEVI float rcp(float x) { float r; asm("rcp.approx.ftz.f32 %0, %1;" : "=f"(r) : "f"(x)); return r; }
DEVI float ex2(float x) { float r; asm("ex2.approx.ftz.f32 %0, %1;" : "=f"(r) : "f"(x)); return r; }

DEVI void wg_fence() { asm volatile("wgmma.fence.sync.aligned;" ::: "memory"); }
DEVI void wg_commit() { asm volatile("wgmma.commit_group.sync.aligned;" ::: "memory"); }
template <int N> DEVI void wg_wait() { asm volatile("wgmma.wait_group.sync.aligned %0;" ::"n"(N) : "memory"); }
constexpr uint32_t DESC_HI = (1u << 30) | (1024 >> 4);
constexpr uint32_t DESC_HI64 = (2u << 30) | (512 >> 4);
DEVI uint32_t mkdesc(uint32_t saddr, uint32_t lbo) { return ((saddr & 0x3FFFF) >> 4) | ((lbo >> 4) << 16); }

#define R8(b) "%" #b
DEVI void wgmma_n192(float (&d)[96], uint32_t da, uint32_t db, int scale_d) {
  asm volatile(
      "{\n.reg .pred p;\n.reg .b64 da, db;\nsetp.ne.b32 p, %98, 0;\nmov.b64 da, {%96, %100};\nmov.b64 db, {%97, %99};\n"
      "wgmma.mma_async.sync.aligned.m64n192k16.f32.bf16.bf16 "
      "{%0,%1,%2,%3,%4,%5,%6,%7,%8,%9,%10,%11,%12,%13,%14,%15,"
      "%16,%17,%18,%19,%20,%21,%22,%23,%24,%25,%26,%27,%28,%29,%30,%31,"
      "%32,%33,%34,%35,%36,%37,%38,%39,%40,%41,%42,%43,%44,%45,%46,%47,"
      "%48,%49,%50,%51,%52,%53,%54,%55,%56,%57,%58,%59,%60,%61,%62,%63,"
      "%64,%65,%66,%67,%68,%69,%70,%71,%72,%73,%74,%75,%76,%77,%78,%79,"
      "%80,%81,%82,%83,%84,%85,%86,%87,%88,%89,%90,%91,%92,%93,%94,%95}, "
      "da, db, p, 1, 1, 0, 1;\n}"
      : "+f"(d[0]), "+f"(d[1]), "+f"(d[2]), "+f"(d[3]), "+f"(d[4]), "+f"(d[5]), "+f"(d[6]), "+f"(d[7]),
        "+f"(d[8]), "+f"(d[9]), "+f"(d[10]), "+f"(d[11]), "+f"(d[12]), "+f"(d[13]), "+f"(d[14]), "+f"(d[15]),
        "+f"(d[16]), "+f"(d[17]), "+f"(d[18]), "+f"(d[19]), "+f"(d[20]), "+f"(d[21]), "+f"(d[22]), "+f"(d[23]),
        "+f"(d[24]), "+f"(d[25]), "+f"(d[26]), "+f"(d[27]), "+f"(d[28]), "+f"(d[29]), "+f"(d[30]), "+f"(d[31]),
        "+f"(d[32]), "+f"(d[33]), "+f"(d[34]), "+f"(d[35]), "+f"(d[36]), "+f"(d[37]), "+f"(d[38]), "+f"(d[39]),
        "+f"(d[40]), "+f"(d[41]), "+f"(d[42]), "+f"(d[43]), "+f"(d[44]), "+f"(d[45]), "+f"(d[46]), "+f"(d[47]),
        "+f"(d[48]), "+f"(d[49]), "+f"(d[50]), "+f"(d[51]), "+f"(d[52]), "+f"(d[53]), "+f"(d[54]), "+f"(d[55]),
        "+f"(d[56]), "+f"(d[57]), "+f"(d[58]), "+f"(d[59]), "+f"(d[60]), "+f"(d[61]), "+f"(d[62]), "+f"(d[63]),
        "+f"(d[64]), "+f"(d[65]), "+f"(d[66]), "+f"(d[67]), "+f"(d[68]), "+f"(d[69]), "+f"(d[70]), "+f"(d[71]),
        "+f"(d[72]), "+f"(d[73]), "+f"(d[74]), "+f"(d[75]), "+f"(d[76]), "+f"(d[77]), "+f"(d[78]), "+f"(d[79]),
        "+f"(d[80]), "+f"(d[81]), "+f"(d[82]), "+f"(d[83]), "+f"(d[84]), "+f"(d[85]), "+f"(d[86]), "+f"(d[87]),
        "+f"(d[88]), "+f"(d[89]), "+f"(d[90]), "+f"(d[91]), "+f"(d[92]), "+f"(d[93]), "+f"(d[94]), "+f"(d[95])
      : "r"(da), "r"(db), "r"(scale_d), "n"(DESC_HI), "n"(DESC_HI64));
}
DEVI void wgmma_n64(float (&d)[32], uint32_t da, uint32_t db, int scale_d) {
  asm volatile(
      "{\n.reg .pred p;\n.reg .b64 da, db;\nsetp.ne.b32 p, %34, 0;\nmov.b64 da, {%32, %35};\nmov.b64 db, {%33, %35};\n"
      "wgmma.mma_async.sync.aligned.m64n64k16.f32.bf16.bf16 "
      "{%0,%1,%2,%3,%4,%5,%6,%7,%8,%9,%10,%11,%12,%13,%14,%15,"
      "%16,%17,%18,%19,%20,%21,%22,%23,%24,%25,%26,%27,%28,%29,%30,%31}, "
      "da, db, p, 1, 1, 0, 1;\n}"
      : "+f"(d[0]), "+f"(d[1]), "+f"(d[2]), "+f"(d[3]), "+f"(d[4]), "+f"(d[5]), "+f"(d[6]), "+f"(d[7]),
        "+f"(d[8]), "+f"(d[9]), "+f"(d[10]), "+f"(d[11]), "+f"(d[12]), "+f"(d[13]), "+f"(d[14]), "+f"(d[15]),
        "+f"(d[16]), "+f"(d[17]), "+f"(d[18]), "+f"(d[19]), "+f"(d[20]), "+f"(d[21]), "+f"(d[22]), "+f"(d[23]),
        "+f"(d[24]), "+f"(d[25]), "+f"(d[26]), "+f"(d[27]), "+f"(d[28]), "+f"(d[29]), "+f"(d[30]), "+f"(d[31])
      : "r"(da), "r"(db), "r"(scale_d), "n"(DESC_HI));
}

struct C32 { float re, im; };
DEVI C32 csq(C32 a) { return {a.re * a.re - a.im * a.im, 2.f * a.re * a.im}; }
DEVI C32 cmul(C32 a, C32 b) { return {a.re * b.re - a.im * b.im, a.re * b.im + a.im * b.re}; }
DEVI C32 cfresh(float zl, float zi, float m) {
  float mag = ex2(zl * m), ph = zi * m;
  return {mag * __cosf(ph), mag * __sinf(ph)};
}
struct HMul { uint32_t b, bp; };
DEVI HMul mk_mul(float re, float im) { return {pack_f16(re, im), pack_f16(-im, re)}; }
DEVI uint32_t hcmul(uint32_t a, const HMul& m) {
  __half2 ah = *reinterpret_cast<__half2*>(&a);
  __half2 b = *reinterpret_cast<const __half2*>(&m.b), bp = *reinterpret_cast<const __half2*>(&m.bp);
  __half2 r = __hfma2(__high2half2(ah), bp, __hmul2(__low2half2(ah), b));
  return *reinterpret_cast<uint32_t*>(&r);
}
DEVI uint32_t badd(uint32_t a, uint32_t b) {
  __nv_bfloat162 r = __hadd2(*reinterpret_cast<__nv_bfloat162*>(&a), *reinterpret_cast<__nv_bfloat162*>(&b));
  return *reinterpret_cast<uint32_t*>(&r);
}
template <int MU0, int NMU, int DMAX>
DEVI void conv_tail(float (&acc)[16][4], uint32_t p_lane, uint32_t v_base, int back, bool edge, int lane) {
  const int hsel = (lane >> 3) & 1;
  const int row = (lane & 7) + ((lane >> 4) << 3) + PADV - 8 - (back & (hsel ^ 1));
  const uint32_t la = v_base + row * 32 + (((hsel ^ back) ^ ((row >> 2) & 1)) << 4);
  uint32_t M[3][4];
  ldsm_x4_t(M[0], la);
  ldsm_x4_t(M[1], la + 256);
  uint32_t H[2 * NMU];
#pragma unroll
  for (int i = 0; i < 2 * NMU; ++i) H[i ^ 1] = lds32(p_lane + (uint32_t)(MU0 - 1 + i) * 32);
  if (edge) {
    const uint32_t a[4] = {0u, 0u, M[0][0], M[0][1]};
#pragma unroll
    for (int k = 1; k < NMU; ++k) mma_bf16v(acc[MU0 - 2 + 2 * k], a, H[2 * k], H[2 * k + 1]);
  }
#pragma unroll
  for (int delta = -1; delta <= DMAX; ++delta) {
    if (delta + 2 <= DMAX) ldsm_x4_t(M[(delta + 3) % 3], la + (delta + 3) * 256);
#pragma unroll
    for (int k = 0; k < NMU; ++k)
      if (delta + MU0 + 2 * k < 16) mma_bf16v(acc[delta + MU0 + 2 * k], M[(delta + 1) % 3], H[2 * k], H[2 * k + 1]);
  }
}

__global__ void __cluster_dims__(2, 1, 1) __launch_bounds__(NTHREADS, 1)
fused_kernel(const __grid_constant__ Maps maps, const Ptrs p) {
  extern __shared__ __align__(1024) uint8_t smem[];
  const uint32_t sb = s2u(smem);
  const int tid = threadIdx.x, lane = tid & 31;
  const int warp = __shfl_sync(0xffffffffu, tid >> 5, 0);
  const int cta = blockIdx.x;
  const uint32_t rank = cta & 1;
  const int ti = 2 * (cta >> 4) + rank;
  const int tj = (cta >> 1) & 7;
  const int pi = cta >> 3, pj = cta & 7;
  const uint32_t bars = sb + SM_BAR;
#define BAR(i) (bars + 8 * (i))
  const int g = lane >> 2, q = lane & 3;

  auto issue_stage = [&](int ks, int s) {
    const uint32_t st = sb + s * STG_BYTES, fb = BAR(B_FULL + s);
    mbar_expect_tx(fb, STG_BYTES);
    tma_load_2d(st + STG_X, &maps.x, ks * 32, ti * 128, fb);
    tma_load_3d_mc(st + STG_W + rank * 6144, &maps.w, tj * 64, ks * 32 + rank * 16, 0, fb, 3);
  };

  const int kch = warp & 3, krd = warp >> 2;
  float zr, zi, wr, wi;
  unsigned epoch;
  uint32_t r_dskip;
  {
    const size_t po = (size_t)(cta * 4 + kch) * 128 + krd * 32 + lane;
    const uint32_t r_ar = ldg16(p.A_re + po), r_ai = ldg16(p.A_im + po), r_br = ldg16(p.B_re + po), r_bi = ldg16(p.B_im + po);
    const uint32_t r_cr = ldg16(p.C_re + po), r_ci = ldg16(p.C_im + po), r_ldt = ldg16(p.log_dt + cta * 4 + kch);
    epoch = __ldcg(&g_epoch);
    r_dskip = ldg16(p.Dskip + cta * 4 + kch);
    uint4 pt;
    if (tid < 128) pt = __ldg((const uint4*)g_ptab.v + tid);
    if (tid == 384) {
      TS(0);
#pragma unroll
      for (int i = 0; i < B_COUNT; ++i) mbar_init(BAR(i), bar_count(i));
      asm volatile("fence.mbarrier_init.release.cluster;" ::: "memory");
      prefetch_tmap(&maps.x); prefetch_tmap(&maps.w); prefetch_tmap(&maps.u);
    }
    __syncthreads();
    cluster_arrive();
    if (warp >= 12) {
      cluster_wait();
      if (elect_one()) {
        if (warp == 13) {
          mbar_expect_tx(BAR(B_TILE), 16384);
          tma_load_2d(sb + SM_U, &maps.u, tj * 64, ti * 128, BAR(B_TILE));
          prefetch_tmap(&maps.uT); prefetch_tmap(&maps.wo); prefetch_tmap(&maps.o); prefetch_tmap(&maps.yT);
          prefetch_tmap(&maps.out);
        } else {
          if (warp == 12) TS(61);
          { const int ks = warp == 12 ? 0 : warp - 13; issue_stage(ks, ks); }
        }
      }
      __syncwarp();
    }
    if (tid < 128) sts128(sb + SM_PTAB + tid * 16, pt.x, pt.y, pt.z, pt.w);
    const float dt = round_bf16(expf(bf_lo(r_ldt)));
    zr = dt * bf_lo(r_ar); zi = dt * bf_lo(r_ai);
    const float dbr = dt * bf_lo(r_br), dbi = dt * bf_lo(r_bi), cr = bf_lo(r_cr), ci = bf_lo(r_ci);
    wr = cr * dbr - ci * dbi; wi = cr * dbi + ci * dbr;
  }
  {
    const float mz = __uint_as_float(__reduce_max_sync(0xffffffffu, __float_as_uint(fmaxf(zr, 0.f))));
    const int E = min(max((int)(__reduce_max_sync(0xffffffffu, __float_as_uint(fmaxf(fabsf(wr), fabsf(wi)))) >> 23), 1), 252);
    const float sc = __int_as_float((253 - E) << 23), inv = __int_as_float((E + 1) << 23);
    const float zl = (zr - mz) * 1.4426950408889634f;
    const uint32_t tb = sb + SM_VV + kch * VV_BYTES + krd * KG_BYTES;
    const uint32_t sta = tb + (((lane >> 2) << 4) | ((lane & 3) << 2));
    auto put = [&](int r, uint32_t v) { sts32((sta ^ ((r & 7) << 4)) + r * 128, v); };
    const uint32_t lda = tb + ((lane & 7) + (((lane >> 3) & 1) << 3)) * 128;
    const uint32_t ldb = tb + ((lane & 7) + ((lane >> 4) << 3)) * 128;
    C32 e1 = cfresh(zl, zi, 1.f), e2 = csq(e1), e4 = csq(e2), e8 = csq(e4);
    C32 e16 = cfresh(zl, zi, 16.f), e32 = csq(e16), e64 = csq(e32), e128 = csq(e64);
    C32 e256 = cfresh(zl, zi, 256.f), e512 = csq(e256), e1024 = csq(e512), e768 = cmul(e512, e256);
    uint32_t XA[2][4][4];
    {
      const HMul m16 = mk_mul(e16.re, e16.im), m32 = mk_mul(e32.re, e32.im), m64 = mk_mul(e64.re, e64.im);
      const HMul m128 = mk_mul(e128.re, e128.im);
      uint32_t X[16];
      X[0] = 0x00003c00u; X[1] = pack_f16(e8.re, e8.im); X[2] = m16.b; X[4] = m32.b; X[8] = m64.b;
      X[3] = hcmul(X[1], m16); X[5] = hcmul(X[1], m32); X[6] = hcmul(X[2], m32); X[7] = hcmul(X[3], m32);
#pragma unroll
      for (int r = 1; r < 8; ++r) X[8 + r] = hcmul(X[r], m64);
#pragma unroll
      for (int h = 0; h < 2; ++h) {
#pragma unroll
        for (int r = 0; r < 16; ++r) put(r, h == 0 ? X[r] : r == 0 ? m128.b : hcmul(X[r], m128));
        __syncwarp();
#pragma unroll
        for (int k = 0; k < 4; ++k) ldsm_x4(XA[h][k], lda + (((2 * k + (lane >> 4)) ^ (lane & 7)) << 4));
        __syncwarp();
      }
    }
    if (warp >= 14 && elect_one()) {
      issue_stage(warp - 11, warp - 11);
      issue_stage(warp - 9, warp - 9);
      if (warp == 14) l2_prefetch((const char*)p.wqkv + 224 * 3072 + cta * 6912, 6912);
      else l2_prefetch((const char*)p.x + (size_t)cta * 16384, 16384);
    }
    __syncwarp();
    float D[2][3][4];
#pragma unroll
    for (int t = 0; t < 6; ++t) D[t / 3][t % 3][0] = D[t / 3][t % 3][1] = D[t / 3][t % 3][2] = D[t / 3][t % 3][3] = 0.f;
    auto contract = [&](int t0, int nt) {
      __syncwarp();
#pragma unroll
      for (int k = 0; k < 4; ++k) {
        uint32_t b[4];
        ldsm_x4(b, ldb + (((2 * k + ((lane >> 3) & 1)) ^ (lane & 7)) << 4));
#pragma unroll
        for (int h = 0; h < 2; ++h) {
          mma_f16(D[h][t0], XA[h][k], b[0], b[1]);
          if (nt == 2) mma_f16(D[h][t0 + 1], XA[h][k], b[2], b[3]);
        }
      }
      __syncwarp();
    };
    const HMul c1 = mk_mul(e1.re, -e1.im), c2 = mk_mul(e2.re, -e2.im), c4 = mk_mul(e4.re, -e4.im);
    const HMul c256 = mk_mul(e256.re, -e256.im), c512 = mk_mul(e512.re, -e512.im), c768 = mk_mul(e768.re, -e768.im);
    const HMul c1024 = mk_mul(e1024.re, -e1024.im);
    uint32_t W[8];
    W[0] = pack_f16(wr * sc, -wi * sc);
    W[1] = hcmul(W[0], c1); W[2] = hcmul(W[0], c2); W[3] = hcmul(W[1], c2);
    W[4] = hcmul(W[0], c4); W[5] = hcmul(W[1], c4); W[6] = hcmul(W[2], c4); W[7] = hcmul(W[3], c4);
#pragma unroll
    for (int i = 0; i < 8; ++i) put(i, W[i]);
#pragma unroll
    for (int i = 0; i < 4; ++i) put(8 + i, hcmul(W[2 * i], c256));
    put(12, hcmul(W[0], c512)); put(13, hcmul(W[4], c512)); put(14, hcmul(W[0], c768)); put(15, hcmul(W[4], c768));
    contract(0, 2);
    const uint32_t v0 = hcmul(W[0], c1024);
    put(0, v0); put(1, hcmul(v0, c256)); put(2, hcmul(v0, c512)); put(3, hcmul(v0, c768)); put(4, hcmul(v0, c1024));
    contract(2, 1);
    const uint32_t a = tb + (g * 24 + 2 * q) * 4;
#pragma unroll
    for (int t = 0; t < 6; ++t) {
      const float(&d)[4] = D[t / 3][t % 3];
      sts_f32x2(a + (t / 3) * 1536 + (t % 3) * 32, d[0] * inv, d[1] * inv);
      sts_f32x2(a + (t / 3) * 1536 + (t % 3) * 32 + 768, d[2] * inv, d[3] * inv);
    }
    if (mz > 0.f) {
      __syncwarp();
#pragma unroll 1
      for (int i = lane; i < 768; i += 32) {
        const int r = i / 24, y = i - 24 * r;
        sts_f32(tb + i * 4, lds_f32(tb + i * 4) * ex2(mz * 1.4426950408889634f * (koff(y) + 8 * r)));
      }
    }
  }
  if (tid == 0) TS(2);
  if (warp < 12) cluster_wait();
  __syncthreads();

  if (warp < 4) {
#define A_REGS 200
    asm volatile("setmaxnreg.inc.sync.aligned.u32 %0;" ::"n"(A_REGS));
    if (tid == 0) TS(34);
    const int d = cta * 4 + warp;
    const uint32_t vv = sb + SM_VV + warp * VV_BYTES;
    const uint32_t ub = sb + SM_U + warp * U_BYTES;
    const uint32_t pb = sb + SM_P + warp * P_BYTES;
    const float dskip = bf_lo(r_dskip);
#pragma unroll 1
    for (int pass = 0; pass < 2; ++pass) {
      if (pass == 1) {
        const uint32_t kf = vv;
#pragma unroll 2
        for (int i = 0; i < 6; ++i) {
          const uint32_t a = kf + (i * 32 + lane) * 16;
          const uint4 x0 = lds128(a), x1 = lds128(a + KG_BYTES), x2 = lds128(a + 2 * KG_BYTES), x3 = lds128(a + 3 * KG_BYTES);
          auto s4 = [](uint32_t a0, uint32_t a1, uint32_t a2, uint32_t a3) {
            return __float_as_uint((__uint_as_float(a0) + __uint_as_float(a1)) + (__uint_as_float(a2) + __uint_as_float(a3)));
          };
          sts128(a, s4(x0.x, x1.x, x2.x, x3.x), s4(x0.y, x1.y, x2.y, x3.y), s4(x0.z, x1.z, x2.z, x3.z), s4(x0.w, x1.w, x2.w, x3.w));
        }
        __syncwarp();
        const float k1024 = lds_f32(kf + kidx_c(1024) * 4);
        if (lane == 0) {
          sts_f32(kf + SL_ZERO * 4, 0.f);
          sts_f32(kf + SL_510 * 4, lds_f32(kf + kidx_c(510) * 4) - lds_f32(kf + kidx_c(512) * 4));
          sts_f32(kf + SL_0 * 4, lds_f32(kf) + dskip);
        }
        __syncwarp();
        if (tid == 0) TS(36);
        mbar_wait_long(BAR(B_PFREE), 0);
        if (tid == 0) TS(37);
        {
          float prev = 0.f;
#pragma unroll 1
          for (int i0 = 0; i0 < 16; i0 += 4) {
            uint32_t e[4];
            float a[4], b[4];
#pragma unroll
            for (int i = 0; i < 4; ++i) e[i] = lds32(sb + SM_PTAB + ((i0 + i) * 32 + lane) * 4);
#pragma unroll
            for (int i = 0; i < 4; ++i) { a[i] = lds_f32(kf + (e[i] & 0xffff)); b[i] = lds_f32(kf + (e[i] >> 16)); }
#pragma unroll
            for (int i = 0; i < 4; ++i) {
              const uint32_t w = pb + (31 * lane + 2 * (i0 + i)) * 4;
              if (i0 + i > 0) sts32(w - 4, pack_bf16(a[i], prev));
              sts32(w, pack_bf16(b[i], a[i]));
              prev = b[i];
            }
          }
        }
        __syncwarp();
        if (lane == 0) TS(4);
        const int gq = g - 2 * q;
        uint32_t h127, h128;
        {
          const uint32_t kf2 = pack_bf16(k1024, k1024) ^ 0x80008000u;
          h127 = (gq == 4 ? 0x0000ffffu : gq == 5 ? 0xffffffffu : gq == 6 ? 0xffff0000u : 0u) & kf2;
          h128 = (gq == -4 ? 0x0000ffffu : gq == -3 ? 0xffffffffu : gq == -2 ? 0xffff0000u : 0u) & kf2;
        }
        __syncwarp();
        mbar_wait_long(BAR(B_UCH + warp), 0);
        {
          auto swz = [](int k, int pad) { const int r = (k >> 1) + pad; return (uint32_t)(r * 32 + (((k & 1) ^ ((r >> 2) & 1)) << 4)); };
          uint32_t a0 = ub + swz(lane - 3, 8), a1 = ub + swz(lane - 2, 8), a2 = ub + swz(lane - 1, 8), aw = vv + swz(lane - 2, PADV);
          if (lane < 16) {
            const uint32_t az = vv + swz(lane - 18, PADV);
            sts128(az + VV_U3, 0, 0, 0, 0); sts128(az + VV_U5, 0, 0, 0, 0); sts128(az + VV_U7, 0, 0, 0, 0); sts128(az + VV_U9, 0, 0, 0, 0);
          }
#pragma unroll 1
          for (int k = lane - 2; k - lane < 208; k += 32, a0 += 512, a1 += 512, a2 += 512, aw += 512) {
          const uint4 t0 = lds128(a0), t1 = lds128(a1), t2 = lds128(a2);
          const uint32_t E[12] = {t0.x, t0.y, t0.z, t0.w, t1.x, t1.y, t1.z, t1.w, t2.x, t2.y, t2.z, t2.w};
          uint32_t O[8];
#pragma unroll
          for (int j = 0; j < 8; ++j) O[j] = __byte_perm(E[j + 1], E[j + 2], 0x5432);
          uint32_t s3[6], s5[4], s7[4], s9[4];
#pragma unroll
          for (int j = 0; j < 6; ++j) s3[j] = badd(badd(O[j], O[j + 1]), E[j + 2]);
#pragma unroll
          for (int j = 0; j < 4; ++j) {
            s5[j] = badd(s3[j + 2], badd(E[j + 3], E[j + 5]));
            s7[j] = badd(s5[j], badd(O[j + 1], O[j + 4]));
            s9[j] = badd(s7[j], badd(E[j + 2], E[j + 6]));
          }
          if (k < 208) { sts128(aw + VV_U3, s3[0], s3[1], s3[2], s3[3]); sts128(aw + VV_U5, s5[0], s5[1], s5[2], s5[3]); }
          if (k < 144) { sts128(aw + VV_U7, s7[0], s7[1], s7[2], s7[3]); sts128(aw + VV_U9, s9[0], s9[1], s9[2], s9[3]); }
          }
          __syncwarp();
        }
        if (lane == 0) TS(6);
        bar_sync(4, 384);
        if (lane == 0) TS(7);
        float acc[16][4];
#pragma unroll
        for (int i = 0; i < 16; ++i) { acc[i][0] = acc[i][1] = acc[i][2] = acc[i][3] = 0.f; }
        {
          const uint32_t pd_lane = pb + (PD_OFF + 16 + gq) * 4;
          const int prow0 = 8 + (lane & 7) + ((lane >> 4) << 3), hs = (lane >> 3) & 1;
          const uint32_t zero = (uint32_t)cta >> 20;
          uint32_t B[2][4][4];
          uint32_t A[4][4];
          const uint32_t la0 = ub + prow0 * 32 + ((hs ^ ((prow0 >> 2) & 1)) << 4);
#pragma unroll
          for (int m2 = 0; m2 < 4; ++m2) ldsm_x4(B[0][m2], la0 + m2 * 512);
#pragma unroll
          for (int i = 0; i < 4; ++i) {
            const uint32_t a = pd_lane + i * 512;
            A[i][0] = lds32(a); A[i][1] = lds32(a + 32); A[i][2] = lds32(a - 32); A[i][3] = lds32(a + zero);
          }
          uint32_t la = la0;
#define UNR_RHO 8
#define UNR_TAIL 2
          constexpr int unr_rho = UNR_RHO, unr_tail = UNR_TAIL;
#pragma unroll unr_rho
          for (int rho = 0; rho < 8; ++rho) {
#pragma unroll
            for (int m2 = 0; m2 < 4; ++m2) ldsm_x4(B[1][m2], la + (4 + m2) * 512);
#pragma unroll
            for (int i = 0; i < 4; ++i)
#pragma unroll
              for (int m = 0; m < 8; ++m) mma_bf16v(acc[m + i], A[i], B[0][m >> 1][2 * (m & 1)], B[0][m >> 1][2 * (m & 1) + 1]);
            const int prow = prow0 - min(rho + 1, 7);
            la = ub + prow * 32 + ((hs ^ ((prow >> 2) & 1)) << 4);
#pragma unroll
            for (int m2 = 0; m2 < 4; ++m2) ldsm_x4(B[0][m2], la + m2 * 512);
            const uint32_t pa = pd_lane + (rho + 1) * 64;
#pragma unroll
            for (int i = 0; i < 4; ++i) {
#pragma unroll
              for (int m = 0; m < 8 - i; ++m)
                mma_bf16v(acc[8 + m + i], A[i], B[1][m >> 1][2 * (m & 1)], B[1][m >> 1][2 * (m & 1) + 1]);
              A[i][0] = lds32(pa + i * 512); A[i][1] = lds32(pa + i * 512 + 32); A[i][2] = lds32(pa + i * 512 - 32);
              A[i][3] = lds32(pa + i * 512 + zero);
            }
          }
          if (lane == 0) TS(40);
          {
            uint32_t b8[4];
            ldsm_x4(b8, la + 4 * 512);
            const uint32_t h63 = lds32(pd_lane + 63 * 32), h64 = lds32(pd_lane + 64 * 32);
            const uint32_t a63[4] = {0u, h127, 0u, 0u}, a32[4] = {h64, 0u, h63, h64}, a64[4] = {h128, 0u, h127, h128};
#pragma unroll
            for (int m2 = 0; m2 < 4; ++m2) ldsm_x4(B[1][m2], la0 + m2 * 512);
#pragma unroll
            for (int m = 0; m < 8; ++m) mma_bf16v(acc[m + 7], a63, B[0][m >> 1][2 * (m & 1)], B[0][m >> 1][2 * (m & 1) + 1]);
#pragma unroll
            for (int m2 = 0; m2 < 2; ++m2) ldsm_x4(B[0][m2], la0 + (4 + m2) * 512);
#pragma unroll
            for (int m = 0; m < 8; ++m) mma_bf16v(acc[m + 4], a32, B[1][m >> 1][2 * (m & 1)], B[1][m >> 1][2 * (m & 1) + 1]);
            mma_bf16v(acc[15], a63, b8[0], b8[1]);
#pragma unroll
            for (int m = 0; m < 8; ++m) mma_bf16v(acc[m + 8], a64, B[1][m >> 1][2 * (m & 1)], B[1][m >> 1][2 * (m & 1) + 1]);
#pragma unroll
            for (int m = 0; m < 4; ++m) mma_bf16v(acc[m + 12], a32, B[0][m >> 1][2 * (m & 1)], B[0][m >> 1][2 * (m & 1) + 1]);
          }
          if (lane == 0) TS(41);
#pragma unroll unr_tail
          for (int v = 0; v < 4; ++v)
            conv_tail<4, 3, 11>(acc, pb + (P2_OFF + 56 * v + gq - 16) * 4, vv + ((v & 1) ? VV_U3 : VV_U5), v >> 1, v == 0, lane);
          if (lane == 0) TS(42);
#pragma unroll unr_tail
          for (int pi = 0; pi < 2; ++pi)
            conv_tail<8, 5, 7>(acc, pb + (P3_OFF + 88 * pi + gq - 48) * 4, vv + (pi ? VV_U7 : VV_U9), pi, pi == 0, lane);
        }
        if (lane == 0) TS(8);
        __syncwarp();
        {
          const int mt = lane >> 3;
          const uint32_t a = pb + (128 * (mt >> 1) + 16 * (lane & 7) + 8 * (mt & 1)) * 2;
#pragma unroll
          for (int ab = 0; ab < 16; ab += 2)
            stsm_x4_t(a + ab * 256, pack_bf16(acc[ab][0], acc[ab][1]), pack_bf16(acc[ab][2], acc[ab][3]),
                      pack_bf16(acc[ab + 1][0], acc[ab + 1][1]), pack_bf16(acc[ab + 1][2], acc[ab + 1][3]));
        }
        fence_async_smem();
        __syncwarp();
        if (lane < 2) mbar_arrive_cluster(BAR(B_CONVD), lane);
        bar_arrive(3, 384);
        if (elect_one()) {
          bulk_store(p.yT + (size_t)d * 2048, pb, 4096);
          bulk_commit();
          bulk_wait0();
          red_relaxed_add(&g_cnt[(C_Y + (cta >> 4)) * 32], 1);
          TS(9);
        }
        bar_sync(2, 128);
        if (warp == 0 && elect_one()) {
          wait_counter(&g_cnt[(C_Y + tj) * 32], (epoch + 1) * 64);
          TS(28);
          mbar_expect_tx(BAR(B_TILE), 16384);
          tma_load_2d(sb + SM_U, &maps.yT, ti * 128, tj * 64, BAR(B_TILE));
          tma_load_2d(sb + SM_U + 8192, &maps.yT, ti * 128 + 64, tj * 64, BAR(B_TILE));
        }
        __syncwarp();
      }
      mbar_wait_long(BAR(B_TILE), pass);
      if (lane == 0) TS(26 + 3 * pass);
      {
        const int m = lane >> 3, r = lane & 7;
#pragma unroll 2
        for (int it = 0; it < 8; ++it) {
          const int tb = warp * 4 + (it >> 1), cb = (it & 1) * 4 + m;
          const uint32_t at = (tb * 8 + r) * 128 + ((cb ^ r) << 4);
          const uint32_t ac = (tb >> 3) * 8192 + (cb * 8 + r) * 128 + (((tb & 7) ^ (pass ? 0 : tb >> 3) ^ r) << 4);
          uint32_t v[4];
          ldsm_x4_t(v, sb + SM_U + (pass ? ac : at));
          stsm_x4(sb + SM_P + (pass ? at : ac), v[0], v[1], v[2], v[3]);
        }
      }
      if (pass == 0 && tid == 0) TS(35);
      fence_async_smem();
      if (pass == 0) {
        bar_arrive(6, 160);
      } else {
        bar_sync(2, 128);
        if (warp == 0 && elect_one()) {
          tma_store_2d(&maps.out, sb + SM_P, 64 * tj, 128 * ti);
          bulk_commit();
          bulk_wait_read0();
          TS(30);
        }
      }
    }
  } else if (warp < 12) {
    const int w8 = warp - 4;
    const int row = w8 * 16 + (lane & 7) + (((lane >> 3) & 1) << 3);
    uint32_t pq[16];
    {
      float acc[96];
#pragma unroll 1
      for (int ks = 0, s = 0, ph = 0; ks < 16; ++ks) {
        mbar_wait(BAR(B_FULL + s), ph);
        if (tid == 128 && !(ks & 1)) TSR(16, ks == 0 ? 16 : 9 + (ks >> 1) + (ks > 12 ? 43 : 0));
        const uint32_t st = sb + s * STG_BYTES;
        const uint32_t da = mkdesc(st + STG_X + (w8 >> 2) * 4096, 16);
        const uint32_t db = mkdesc(st + STG_W, 2048);
        wg_fence();
        wgmma_n192(acc, da, db, ks != 0);
        wgmma_n192(acc, da + 2, db + 384, 1);
        wg_commit();
        const uint32_t eprev = BAR(B_EMPTY + (s == 0 ? NSTG - 1 : s - 1));
        if (++s == NSTG) { s = 0; ph ^= 1; }
        if (ks > 0) {
          wg_wait<1>();
          if (lane < 2) mbar_arrive_cluster(eprev, lane);
        }
      }
      wg_wait<0>();
      if (tid == 128) TS(17);
      auto phi2 = [](float a, float b) -> uint32_t {
        const uint32_t x = pack_bf16(a, b);
        const uint32_t e = pack_bf16(ex2(bf_lo(x) * 1.4426950408889634f), ex2(bf_hi(x) * 1.4426950408889634f));
        const uint32_t m = __hgt2_mask(*reinterpret_cast<const __nv_bfloat162*>(&x), __floats2bfloat162_rn(0.f, 0.f));
        return badd((badd(x, 0x3f803f80u) & m) | (e & ~m), 0x35863586u);
      };
      uint32_t pk[16];
#pragma unroll
      for (int i = 0; i < 16; ++i) pk[i] = phi2(acc[32 + 2 * i], acc[33 + 2 * i]);
      if (tid == 128) TS(53);
      bar_sync(1, 256);
#pragma unroll
      for (int i = 0; i < 8; i += 2) {
        const uint32_t off = row * 128 + (((i + (lane >> 4)) ^ (row & 7)) << 4);
        stsm_x4(sb + SM_PK + off, pk[2 * i], pk[2 * i + 1], pk[2 * i + 2], pk[2 * i + 3]);
        stsm_x4(sb + SM_VS + off, pack_bf16(acc[64 + 4 * i], acc[65 + 4 * i]), pack_bf16(acc[66 + 4 * i], acc[67 + 4 * i]),
                pack_bf16(acc[68 + 4 * i], acc[69 + 4 * i]), pack_bf16(acc[70 + 4 * i], acc[71 + 4 * i]));
      }
      bar_sync(1, 256);
      {
        const int hh = w8 >> 1, dtile = w8 & 1;
        float kv[2][4] = {{0.f, 0.f, 0.f, 0.f}, {0.f, 0.f, 0.f, 0.f}}, zz[2][4] = {{0.f, 0.f, 0.f, 0.f}, {0.f, 0.f, 0.f, 0.f}};
        const int m = lane >> 3;
        const uint32_t aa = sb + SM_VS + ((lane & 7) + ((m >> 1) << 3)) * 128 + (((2 * hh + (m & 1)) ^ (lane & 7)) << 4);
        const uint32_t ab = sb + SM_PK + (lane & 15) * 128 + (((2 * hh + dtile) ^ (lane & 7)) << 4);
#pragma unroll
        for (int ks = 0; ks < 8; ++ks) {
          uint32_t a[4], b0, b1;
          ldsm_x4_t(a, aa + ks * 2048);
          ldsm_x2_t(b0, b1, ab + ks * 2048);
          mma_bf16(kv[ks & 1], a[0], a[1], a[2], a[3], b0, b1);
          mma_bf16(zz[ks & 1], 0x3f803f80u, 0x3f803f80u, 0x3f803f80u, 0x3f803f80u, b0, b1);
        }
        const uint32_t kp = sb + SM_KV + hh * 1088;
        sts128(kp + dtile * 512 + lane * 16, __float_as_uint(kv[0][0] + kv[1][0]), __float_as_uint(kv[0][1] + kv[1][1]),
               __float_as_uint(kv[0][2] + kv[1][2]), __float_as_uint(kv[0][3] + kv[1][3]));
        if (g == 0) sts_f32x2(kp + 1024 + dtile * 32 + q * 8, zz[0][0] + zz[1][0], zz[0][1] + zz[1][1]);
        fence_async_smem();
        __syncwarp();
        if (lane == 0) mbar_arrive(BAR(B_KVP));
        bar_arrive(4, 384);
        if (tid == 128) TS(55);
      }
#pragma unroll
      for (int i = 0; i < 16; ++i) pq[i] = phi2(acc[2 * i], acc[2 * i + 1]);
    }
    if (tid == 128) TS(56);
    if (warp == 4) mbar_wait_long(BAR(B_KVF), 0);
    bar_sync(1, 256);
    if (tid == 128) TS(19);
    {
      uint32_t kb[4][6];
#pragma unroll
      for (int h = 0; h < 4; ++h) {
        const uint32_t kp = sb + SM_KV + h * 1088;
        const uint4 k0 = lds128(kp + lane * 16), k1 = lds128(kp + 512 + lane * 16);
        const uint32_t za = kp + 1024 + q * 8;
        auto pk2 = [](uint32_t x, uint32_t y) { return pack_bf16(__uint_as_float(x), __uint_as_float(y)); };
        kb[h][0] = pk2(k0.x, k0.y); kb[h][1] = pk2(k1.x, k1.y); kb[h][2] = pk2(k0.z, k0.w); kb[h][3] = pk2(k1.z, k1.w);
        kb[h][4] = pack_bf16(lds_f32(za), lds_f32(za + 4)); kb[h][5] = pack_bf16(lds_f32(za + 32), lds_f32(za + 36));
      }
#pragma unroll
      for (int h = 0; h < 4; ++h) {
        float n0[4] = {0.f, 0.f, 0.f, 0.f}, n1[4] = {0.f, 0.f, 0.f, 0.f}, dn[4] = {0.f, 0.f, 0.f, 0.f};
        mma_bf16(n0, pq[4 * h], pq[4 * h + 1], pq[4 * h + 2], pq[4 * h + 3], kb[h][0], kb[h][1]);
        mma_bf16(n1, pq[4 * h], pq[4 * h + 1], pq[4 * h + 2], pq[4 * h + 3], kb[h][2], kb[h][3]);
        mma_bf16(dn, pq[4 * h], pq[4 * h + 1], pq[4 * h + 2], pq[4 * h + 3], kb[h][4], kb[h][5]);
        const uint32_t dd = pack_bf16(dn[0], dn[2]);
        const uint32_t d2 = pack_bf16(bf_lo(dd) + 1e-6f, bf_hi(dd) + 1e-6f);
        const float r0 = rcp(bf_lo(d2)), r1 = rcp(bf_hi(d2));
        const uint32_t x0 = pack_bf16(n0[0], n0[1]), x1 = pack_bf16(n0[2], n0[3]);
        const uint32_t x2 = pack_bf16(n1[0], n1[1]), x3 = pack_bf16(n1[2], n1[3]);
        stsm_x4(sb + SM_QS + row * 128 + (((2 * h + (lane >> 4)) ^ (row & 7)) << 4),
                pack_bf16(bf_lo(x0) * r0, bf_hi(x0) * r0), pack_bf16(bf_lo(x1) * r1, bf_hi(x1) * r1),
                pack_bf16(bf_lo(x2) * r0, bf_hi(x2) * r0), pack_bf16(bf_lo(x3) * r1, bf_hi(x3) * r1));
      }
    }
    fence_async_smem();
    __syncwarp();
    if (lane == 0) mbar_arrive(BAR(B_OST));
    if (tid == 128) TS(57);
    if (warp == 4) mbar_wait_long(BAR(B_WO), 0);
    bar_sync(3, 384);
    {
      float o[32];
#pragma unroll 1
      for (int c = 0; c < 8; ++c) {
        mbar_wait_long(BAR(B_RF + c), 0);
        if (tid == 128) TSR(22, c == 0 ? 22 : 43 + c);
        const uint32_t slot = c < 4 ? SM_QS + c * 16384 : c < 7 ? SM_VV + (c - 4) * 16384 : SM_QS;
        const uint32_t da = mkdesc(sb + slot + (w8 >> 2) * 8192, 16);
        const uint32_t db = mkdesc(sb + SM_WO + c * 8192, 8192);
        wg_fence();
#pragma unroll
        for (int k = 0; k < 4; ++k) wgmma_n64(o, da + 2 * k, db + 128 * k, (c | k) != 0);
        wg_commit();
        if (c == 1) {
          wg_wait<1>();
          if (lane < 2) mbar_arrive_cluster(BAR(B_RE), lane);
        }
      }
      wg_wait<0>();
      if (tid == 128) TS(51);
      bar_sync(1, 256);
#pragma unroll
      for (int i = 0; i < 8; i += 2)
        stsm_x4(sb + SM_BOUT + row * 128 + (((i + (lane >> 4)) ^ (row & 7)) << 4), pack_bf16(o[4 * i], o[4 * i + 1]),
                pack_bf16(o[4 * i + 2], o[4 * i + 3]), pack_bf16(o[4 * i + 4], o[4 * i + 5]), pack_bf16(o[4 * i + 6], o[4 * i + 7]));
      fence_async_smem();
      bar_sync(1, 256);
      if (tid == 128) TS(52);
      if (warp == 4 && elect_one()) {
        tma_store_2d(&maps.out, sb + SM_BOUT, 512 + 64 * pj, 128 * pi);
        bulk_commit();
        bulk_wait_read0();
        TS(23);
      }
    }
  } else {
    asm volatile("setmaxnreg.dec.sync.aligned.u32 40;");
    if (warp == 12) {
      if (elect_one()) {
#pragma unroll 1
        for (int ks = NSTG, s = 0, ph = 0; ks < 16; ++ks) {
          mbar_wait(BAR(B_EMPTY + s), ph);
          issue_stage(ks, s);
          if (ks == NSTG) l2_prefetch((const char*)p.wo + (size_t)cta * 4096, 4096);
          if (++s == NSTG) { s = 0; ph ^= 1; }
        }
        mbar_wait(BAR(B_EMPTY + 6), 1);
        mbar_expect_tx(BAR(B_WO), 65536);
        tma_load_2d(sb + SM_WO, &maps.wo, pj * 64, 0, BAR(B_WO));
        tma_load_2d(sb + SM_WO + 32768, &maps.wo, pj * 64, 256, BAR(B_WO));
        float* kvg = &g_kv[epoch & 1][tj][0];
        mbar_wait_long(BAR(B_KVP), 0);
        bulk_reduce_add_f32(kvg, sb + SM_KV, 4352);
        bulk_commit();
        bulk_wait0();
        red_relaxed_add(&g_cnt[(C_KV + tj) * 32], 1);
        TS(18);
        wait_counter(&g_cnt[(C_KV + tj) * 32], (epoch + 1) * 16);
        mbar_expect_tx(BAR(B_KVF), 4352);
        bulk_load(sb + SM_KV, kvg, 4352, BAR(B_KVF));
        mbar_wait_long(BAR(B_OST), 0);
        tma_store_2d(&maps.o, sb + SM_QS, tj * 64, ti * 128);
        tma_store_2d(&maps.o, sb + SM_QS + 8192, tj * 64, ti * 128 + 64);
        bulk_commit();
        bulk_wait0();
        red_relaxed_add(&g_cnt[(C_O + ti) * 32], 1);
        TS(20);
        mbar_arrive_cluster(BAR(B_SLOT), 0);
        mbar_arrive_cluster(BAR(B_SLOT), 1);
        wait_counter(&g_cnt[(C_O + pi) * 32], (epoch + 1) * 8);
        if (cta == 0) g_epoch = epoch + 1;
        mbar_wait(BAR(B_SLOT), 0);
        TS(21);
#pragma unroll 1
        for (int c = 0; c < 8; ++c) {
          if (c == 4) mbar_wait_long(BAR(B_CONVD), 0);
          if (c == 7) mbar_wait(BAR(B_RE), 0);
          const uint32_t slot = c < 4 ? SM_QS + c * 16384 : c < 7 ? SM_VV + (c - 4) * 16384 : SM_QS;
          mbar_expect_tx(BAR(B_RF + c), 16384);
          tma_load_2d_mc(sb + slot + rank * 8192, &maps.o, c * 64, pi * 128 + rank * 64, BAR(B_RF + c), 3);
        }
      }
    } else if (warp == 13) {
      bar_sync(6, 160);
      sts128(sb + SM_U + (lane >> 4) * U_BYTES + (lane & 15) * 16, 0, 0, 0, 0);
      sts128(sb + SM_U + (2 + (lane >> 4)) * U_BYTES + (lane & 15) * 16, 0, 0, 0, 0);
      __syncwarp();
      if (elect_one()) {
        tma_store_2d(&maps.uT, sb + SM_P, ti * 128, tj * 64);
        tma_store_2d(&maps.uT, sb + SM_P + 8192, ti * 128 + 64, tj * 64);
        bulk_commit();
        bulk_wait_read0();
        mbar_arrive(BAR(B_PFREE));
        bulk_wait0();
        red_relaxed_add(&g_cnt[(C_U + tj) * 32], 1);
        TS(27);
        wait_counter(&g_cnt[(C_U + (cta >> 4)) * 32], (epoch + 1) * 16);
#pragma unroll 1
        for (int c = 0; c < 4; ++c) {
          mbar_expect_tx(BAR(B_UCH + c), 4096);
          bulk_load(sb + SM_U + c * U_BYTES + 256, p.uT + (size_t)(cta * 4 + c) * 2048, 4096, BAR(B_UCH + c));
        }
        TS(3);
      }
      __syncwarp();
      if (ti == 0) {
        float4* z = (float4*)&g_kv[(epoch & 1) ^ 1][tj][0];
#pragma unroll 1
        for (int i = lane; i < 272; i += 32) z[i] = make_float4(0.f, 0.f, 0.f, 0.f);
      }
    }
  }
  __syncwarp();
  cluster_arrive();
  cluster_wait();
  if (tid == 0) TS(31);
#undef BAR
}

typedef CUresult (*EncodeFn)(CUtensorMap*, CUtensorMapDataType, cuuint32_t, void*, const cuuint64_t*, const cuuint64_t*,
                             const cuuint32_t*, const cuuint32_t*, CUtensorMapInterleave, CUtensorMapSwizzle,
                             CUtensorMapL2promotion, CUtensorMapFloatOOBfill);

static void make_map(EncodeFn enc, CUtensorMap* m, const void* base, uint64_t inner, uint64_t outer, uint32_t box_in,
                     uint32_t box_out, CUtensorMapSwizzle swz = CU_TENSOR_MAP_SWIZZLE_128B) {
  cuuint64_t gd[2] = {inner, outer};
  cuuint64_t gs[1] = {inner * 2};
  cuuint32_t bd[2] = {box_in, box_out};
  cuuint32_t es[2] = {1, 1};
  enc(m, CU_TENSOR_MAP_DATA_TYPE_BFLOAT16, 2, const_cast<void*>(base), gd, gs, bd, es, CU_TENSOR_MAP_INTERLEAVE_NONE,
      swz, CU_TENSOR_MAP_L2_PROMOTION_L2_128B, CU_TENSOR_MAP_FLOAT_OOB_FILL_NONE);
}

}

extern "C" void kernel_launch(void* const* d_in, const int* in_sizes, int n_in, void* d_out, int out_size) {
  using namespace s4la;
  (void)in_sizes; (void)n_in; (void)out_size;
  static EncodeFn enc = nullptr;
  static void *uT = nullptr, *yT = nullptr, *oS = nullptr;
  if (!enc) {
    void* fn = nullptr;
    cudaDriverEntryPointQueryResult qr;
    cudaGetDriverEntryPoint("cuTensorMapEncodeTiled", &fn, cudaEnableDefault, &qr);
    enc = (EncodeFn)fn;
    cudaGetSymbolAddress(&uT, g_uT);
    cudaGetSymbolAddress(&yT, g_yT);
    cudaGetSymbolAddress(&oS, g_o);
    cudaFuncSetAttribute(fused_kernel, cudaFuncAttributeMaxDynamicSharedMemorySize, SM_TOTAL);
  }
  const __nv_bfloat16* const* in = (const __nv_bfloat16* const*)d_in;
  Maps maps;
  make_map(enc, &maps.x, in[9], 512, 2048, 32, 128, CU_TENSOR_MAP_SWIZZLE_64B);
  {
    cuuint64_t gd[3] = {512, 512, 3};
    cuuint64_t gs[2] = {3072, 1024};
    cuuint32_t bd[3] = {64, 16, 3};
    cuuint32_t es[3] = {1, 1, 1};
    enc(&maps.w, CU_TENSOR_MAP_DATA_TYPE_BFLOAT16, 3, const_cast<__nv_bfloat16*>(in[10]), gd, gs, bd, es,
        CU_TENSOR_MAP_INTERLEAVE_NONE, CU_TENSOR_MAP_SWIZZLE_128B, CU_TENSOR_MAP_L2_PROMOTION_L2_128B,
        CU_TENSOR_MAP_FLOAT_OOB_FILL_NONE);
  }
  make_map(enc, &maps.wo, in[11], 512, 512, 64, 256);
  make_map(enc, &maps.u, in[0], 512, 2048, 64, 128);
  make_map(enc, &maps.uT, uT, 2048, 512, 64, 64);
  make_map(enc, &maps.yT, yT, 2048, 512, 64, 64);
  make_map(enc, &maps.o, oS, 512, 2048, 64, 64);
  make_map(enc, &maps.out, d_out, 1024, 2048, 64, 128);
  Ptrs p;
  p.A_re = in[1]; p.A_im = in[2]; p.B_re = in[3]; p.B_im = in[4]; p.C_re = in[5]; p.C_im = in[6];
  p.log_dt = in[7]; p.Dskip = in[8]; p.x = in[9]; p.wqkv = in[10]; p.wo = in[11];
  p.uT = (__nv_bfloat16*)uT; p.yT = (__nv_bfloat16*)yT;
  fused_kernel<<<NCTA, NTHREADS, SM_TOTAL, cudaStreamPerThread>>>(maps, p);
}
```

```cpp
#include <cuda_runtime.h>
#include <cuda_bf16.h>
#include <cuda_fp16.h>
#include <cuda.h>
#include <stdint.h>

#define DEVI __device__ __forceinline__

namespace s4la {

constexpr int NTHREADS = 512;
constexpr int NCTA = 128;

constexpr int NSTG = 7;
constexpr uint32_t STG_BYTES = 20480, STG_X = 0, STG_W = 8192;
constexpr uint32_t SM_QS = 0;
constexpr uint32_t SM_PK = SM_QS + 16384, SM_VS = SM_QS + 32768;
constexpr uint32_t SM_WO = 65536;
constexpr uint32_t SM_KV = 131072;
constexpr uint32_t SM_BOUT = 16384;
constexpr uint32_t SM_U = 143360, U_BYTES = 4352;
constexpr uint32_t SM_P = 160768, P_BYTES = 4096;
constexpr uint32_t SM_VV = 177152, VV_BYTES = 12800;
constexpr uint32_t VV_U5 = 0, VV_U3 = 3712, VV_U9 = 7424, VV_U7 = 10112;
constexpr uint32_t KG_BYTES = 3200;
constexpr uint32_t SM_BAR = SM_VV + 4 * VV_BYTES;
constexpr uint32_t SM_PTAB = SM_BAR + 320;
constexpr uint32_t SM_TOTAL = SM_PTAB + 2048;
static_assert(SM_TOTAL <= 232448, "shared memory");
constexpr int PADV = 12;

enum { B_FULL = 0, B_EMPTY = 7, B_TILE = 14, B_UCH = 15, B_KVP = 19, B_KVF = 20, B_OST = 21, B_RF = 22, B_WO = 30, B_RE = 31, B_PFREE = 32, B_CONVD = 33, B_SLOT = 34, B_COUNT = 35 };
__host__ __device__ constexpr int bar_count(int i) {
  return (i >= B_EMPTY && i < B_TILE) ? 16 : (i == B_KVP || i == B_OST || i == B_CONVD) ? 8 : i == B_RE ? 16 : i == B_SLOT ? 2 : 1;
}

constexpr int PD_OFF = 0, P2_OFF = 544, P3_OFF = 768;

constexpr int SL_K2048 = 20, SL_ZERO = 21, SL_510 = 22, SL_0 = 23;
__host__ __device__ constexpr int koff(int y) {
  return y < 8 ? y : y < 12 ? 256 + 2 * (y - 8) : y < 16 ? 512 + 256 * ((y - 12) >> 1) + 4 * (y & 1) : 1024 + 256 * (y - 16);
}
__host__ __device__ constexpr int kidx_c(int l) {
  const int y = l < 256 ? (l & 7) : l < 512 ? 8 + ((l & 7) >> 1) : l < 1024 ? 12 + (((l - 512) >> 8) << 1) + ((l >> 2) & 1)
                                                                            : 16 + ((l - 1024) >> 8);
  return ((l >> 3) & 31) * 24 + y;
}
constexpr int slot_direct(int l) {
  if (l < 0 || l > 510) return SL_ZERO;
  if (l == 510) return SL_510;
  if (l == 0) return SL_0;
  return kidx_c(l < 256 ? l : ((l + ((l >> 1) & 1)) & ~1));
}
constexpr int slot_seg2(int v, int k) { return (k >= 32 && k < 64) ? kidx_c(16 * k + 4 * v) : SL_ZERO; }
constexpr int slot_seg3(int pi, int k) {
  return (k >= 64 && k < 128) ? kidx_c(16 * k + 8 * pi) : ((k == 128 && pi == 0) ? SL_K2048 : SL_ZERO);
}
constexpr int slot_word(int w) {
  return w < 0 ? SL_ZERO : w < 544 ? slot_direct(w - 16) : w < 768 ? slot_seg2((w - 544) / 56, 16 + (w - 544) % 56)
       : w < 944 ? slot_seg3((w - 768) / 88, 48 + (w - 768) % 88) : SL_ZERO;
}
struct PTab { uint32_t v[512]; };
constexpr PTab make_ptab() {
  PTab t{};
  for (int lane = 0; lane < 32; ++lane)
    for (int i = 0; i < 16; ++i)
      t.v[i * 32 + lane] = (slot_word(31 * lane - 1 + 2 * i) * 4) | ((slot_word(31 * lane + 2 * i) * 4) << 16);
  return t;
}
__device__ const PTab g_ptab = make_ptab();

__device__ __nv_bfloat16 g_uT[512 * 2048];
__device__ __nv_bfloat16 g_yT[512 * 2048];
__device__ __nv_bfloat16 g_o[2048 * 512];
__device__ float g_kv[2][8][4 * 272];
__device__ unsigned g_cnt[64 * 32];
__device__ unsigned g_epoch;
#define TS(slot) do { } while (0)
#define TSR(on, slot) do { } while (0)
#define TSD(slot) do { } while (0)
enum { C_U = 0, C_KV = 8, C_O = 16, C_Y = 32 };

struct Maps {
  CUtensorMap x, w, wo, u, uT, yT, o, out;
};
struct Ptrs {
  const __nv_bfloat16 *A_re, *A_im, *B_re, *B_im, *C_re, *C_im, *log_dt, *Dskip;
  const __nv_bfloat16 *x, *wqkv, *wo;
  __nv_bfloat16 *uT, *yT;
};

DEVI uint32_t s2u(const void* p) { return (uint32_t)__cvta_generic_to_shared(p); }
DEVI void mbar_init(uint32_t b, uint32_t c) { asm volatile("mbarrier.init.shared::cta.b64 [%0], %1;" ::"r"(b), "r"(c) : "memory"); }
DEVI void mbar_expect_tx(uint32_t b, uint32_t bytes) {
  asm volatile("mbarrier.arrive.expect_tx.shared::cta.b64 _, [%0], %1;" ::"r"(b), "r"(bytes) : "memory");
}
DEVI void mbar_arrive(uint32_t b) { asm volatile("mbarrier.arrive.shared::cta.b64 _, [%0];" ::"r"(b) : "memory"); }
DEVI void mbar_arrive_cluster(uint32_t b, uint32_t cta) {
  asm volatile("{\n.reg .b32 r;\nmapa.shared::cluster.u32 r, %0, %1;\nmbarrier.arrive.shared::cluster.b64 _, [r];\n}"
               ::"r"(b), "r"(cta) : "memory");
}
DEVI void mbar_wait(uint32_t b, uint32_t parity) {
  asm volatile("{\n.reg .pred p;\nLAB_WAIT:\nmbarrier.try_wait.parity.shared::cta.b64 p, [%0], %1;\n@!p bra LAB_WAIT;\n}"
               ::"r"(b), "r"(parity) : "memory");
}
DEVI void mbar_wait_long(uint32_t b, uint32_t parity) {
  asm volatile("{\n.reg .pred p;\nLAB_WAIT:\nmbarrier.try_wait.parity.shared::cta.b64 p, [%0], %1, 0x989680;\n@!p bra LAB_WAIT;\n}"
               ::"r"(b), "r"(parity) : "memory");
}
DEVI void bar_sync(int id, int n) { asm volatile("bar.sync %0, %1;" ::"r"(id), "r"(n) : "memory"); }
DEVI void bar_arrive(int id, int n) { asm volatile("bar.arrive %0, %1;" ::"r"(id), "r"(n) : "memory"); }
DEVI void fence_async_smem() { asm volatile("fence.proxy.async.shared::cta;" ::: "memory"); }
DEVI void fence_async_all() { asm volatile("fence.proxy.async;" ::: "memory"); }
DEVI void cluster_arrive() { asm volatile("barrier.cluster.arrive.relaxed.aligned;" ::: "memory"); }
DEVI void cluster_wait() { asm volatile("barrier.cluster.wait.aligned;" ::: "memory"); }

DEVI void tma_load_2d(uint32_t dst, const CUtensorMap* m, int c0, int c1, uint32_t bar) {
  asm volatile("cp.async.bulk.tensor.2d.shared::cluster.global.mbarrier::complete_tx::bytes [%0], [%1, {%3, %4}], [%2];"
               ::"r"(dst), "l"(m), "r"(bar), "r"(c0), "r"(c1) : "memory");
}
DEVI void tma_load_2d_mc(uint32_t dst, const CUtensorMap* m, int c0, int c1, uint32_t bar, uint16_t mask) {
  asm volatile("cp.async.bulk.tensor.2d.shared::cluster.global.mbarrier::complete_tx::bytes.multicast::cluster [%0], [%1, {%3, %4}], [%2], %5;"
               ::"r"(dst), "l"(m), "r"(bar), "r"(c0), "r"(c1), "h"(mask) : "memory");
}
DEVI void tma_load_3d_mc(uint32_t dst, const CUtensorMap* m, int c0, int c1, int c2, uint32_t bar, uint16_t mask) {
  asm volatile("cp.async.bulk.tensor.3d.shared::cluster.global.mbarrier::complete_tx::bytes.multicast::cluster [%0], [%1, {%3, %4, %5}], [%2], %6;"
               ::"r"(dst), "l"(m), "r"(bar), "r"(c0), "r"(c1), "r"(c2), "h"(mask) : "memory");
}
DEVI void tma_store_2d(const CUtensorMap* m, uint32_t src, int c0, int c1) {
  asm volatile("cp.async.bulk.tensor.2d.global.shared::cta.bulk_group [%0, {%2, %3}], [%1];"
               ::"l"(m), "r"(src), "r"(c0), "r"(c1) : "memory");
}
DEVI void bulk_load(uint32_t dst, const void* src, uint32_t bytes, uint32_t bar) {
  asm volatile("cp.async.bulk.shared::cluster.global.mbarrier::complete_tx::bytes [%0], [%1], %2, [%3];"
               ::"r"(dst), "l"(src), "r"(bytes), "r"(bar) : "memory");
}
DEVI void bulk_store(void* dst, uint32_t src, uint32_t bytes) {
  asm volatile("cp.async.bulk.global.shared::cta.bulk_group [%0], [%1], %2;" ::"l"(dst), "r"(src), "r"(bytes) : "memory");
}
DEVI void bulk_reduce_add_f32(void* dst, uint32_t src, uint32_t bytes) {
  asm volatile("cp.reduce.async.bulk.global.shared::cta.bulk_group.add.f32 [%0], [%1], %2;" ::"l"(dst), "r"(src), "r"(bytes) : "memory");
}
DEVI void bulk_commit() { asm volatile("cp.async.bulk.commit_group;" ::: "memory"); }
DEVI void bulk_wait0() { asm volatile("cp.async.bulk.wait_group 0;" ::: "memory"); }
DEVI void bulk_wait_read0() { asm volatile("cp.async.bulk.wait_group.read 0;" ::: "memory"); }
DEVI void l2_prefetch(const void* p, uint32_t bytes) {
  asm volatile("cp.async.bulk.prefetch.L2.global [%0], %1;" ::"l"(p), "r"(bytes) : "memory");
}
DEVI void prefetch_tmap(const CUtensorMap* m) { asm volatile("prefetch.tensormap [%0];" ::"l"(m) : "memory"); }

DEVI void red_release_add(unsigned* p, unsigned v) {
  asm volatile("red.release.gpu.global.add.u32 [%0], %1;" ::"l"(p), "r"(v) : "memory");
}
DEVI void red_relaxed_add(unsigned* p, unsigned v) {
  asm volatile("red.relaxed.gpu.global.add.u32 [%0], %1;" ::"l"(p), "r"(v) : "memory");
}
DEVI unsigned ld_relaxed(const unsigned* p) {
  unsigned v;
  asm volatile("ld.relaxed.gpu.global.u32 %0, [%1];" : "=r"(v) : "l"(p) : "memory");
  return v;
}
DEVI void wait_counter(const unsigned* p, unsigned target) {
#pragma unroll 1
  for (int it = 0; (int)(ld_relaxed(p) - target) < 0; ++it)
    if (it > (1 << 22)) __trap();
}

DEVI void ldsm_x4(uint32_t (&r)[4], uint32_t a) {
  asm volatile("ldmatrix.sync.aligned.m8n8.x4.shared.b16 {%0,%1,%2,%3}, [%4];"
               : "=r"(r[0]), "=r"(r[1]), "=r"(r[2]), "=r"(r[3]) : "r"(a) : "memory");
}
DEVI void ldsm_x4_t(uint32_t (&r)[4], uint32_t a) {
  asm volatile("ldmatrix.sync.aligned.m8n8.x4.trans.shared.b16 {%0,%1,%2,%3}, [%4];"
               : "=r"(r[0]), "=r"(r[1]), "=r"(r[2]), "=r"(r[3]) : "r"(a) : "memory");
}
DEVI void ldsm_x2_t(uint32_t& r0, uint32_t& r1, uint32_t a) {
  asm volatile("ldmatrix.sync.aligned.m8n8.x2.trans.shared.b16 {%0,%1}, [%2];" : "=r"(r0), "=r"(r1) : "r"(a) : "memory");
}
DEVI void stsm_x4(uint32_t a, uint32_t r0, uint32_t r1, uint32_t r2, uint32_t r3) {
  asm volatile("stmatrix.sync.aligned.m8n8.x4.shared.b16 [%0], {%1,%2,%3,%4};"
               ::"r"(a), "r"(r0), "r"(r1), "r"(r2), "r"(r3) : "memory");
}
DEVI void stsm_x4_t(uint32_t a, uint32_t r0, uint32_t r1, uint32_t r2, uint32_t r3) {
  asm volatile("stmatrix.sync.aligned.m8n8.x4.trans.shared.b16 [%0], {%1,%2,%3,%4};"
               ::"r"(a), "r"(r0), "r"(r1), "r"(r2), "r"(r3) : "memory");
}
DEVI uint32_t lds32(uint32_t a) { uint32_t v; asm volatile("ld.shared.b32 %0, [%1];" : "=r"(v) : "r"(a) : "memory"); return v; }
DEVI float lds_f32(uint32_t a) { float v; asm volatile("ld.shared.f32 %0, [%1];" : "=f"(v) : "r"(a) : "memory"); return v; }
DEVI void sts32(uint32_t a, uint32_t v) { asm volatile("st.shared.b32 [%0], %1;" ::"r"(a), "r"(v) : "memory"); }
DEVI void sts_f32(uint32_t a, float v) { asm volatile("st.shared.f32 [%0], %1;" ::"r"(a), "f"(v) : "memory"); }
DEVI void sts_f32x2(uint32_t a, float x, float y) { asm volatile("st.shared.v2.f32 [%0], {%1,%2};" ::"r"(a), "f"(x), "f"(y) : "memory"); }
DEVI uint4 lds128(uint32_t a) {
  uint4 v;
  asm volatile("ld.shared.v4.b32 {%0,%1,%2,%3}, [%4];" : "=r"(v.x), "=r"(v.y), "=r"(v.z), "=r"(v.w) : "r"(a) : "memory");
  return v;
}
DEVI void sts128(uint32_t a, uint32_t x, uint32_t y, uint32_t z, uint32_t w) {
  asm volatile("st.shared.v4.b32 [%0], {%1,%2,%3,%4};" ::"r"(a), "r"(x), "r"(y), "r"(z), "r"(w) : "memory");
}

DEVI void mma_bf16(float (&d)[4], uint32_t a0, uint32_t a1, uint32_t a2, uint32_t a3, uint32_t b0, uint32_t b1) {
  asm("mma.sync.aligned.m16n8k16.row.col.f32.bf16.bf16.f32 {%0,%1,%2,%3}, {%4,%5,%6,%7}, {%8,%9}, {%0,%1,%2,%3};"
      : "+f"(d[0]), "+f"(d[1]), "+f"(d[2]), "+f"(d[3])
      : "r"(a0), "r"(a1), "r"(a2), "r"(a3), "r"(b0), "r"(b1));
}
DEVI void mma_f16(float (&d)[4], const uint32_t (&a)[4], uint32_t b0, uint32_t b1) {
  asm("mma.sync.aligned.m16n8k16.row.col.f32.f16.f16.f32 {%0,%1,%2,%3}, {%4,%5,%6,%7}, {%8,%9}, {%0,%1,%2,%3};"
      : "+f"(d[0]), "+f"(d[1]), "+f"(d[2]), "+f"(d[3])
      : "r"(a[0]), "r"(a[1]), "r"(a[2]), "r"(a[3]), "r"(b0), "r"(b1));
}
DEVI void mma_bf16v(float (&d)[4], const uint32_t (&a)[4], uint32_t b0, uint32_t b1) {
  asm volatile("mma.sync.aligned.m16n8k16.row.col.f32.bf16.bf16.f32 {%0,%1,%2,%3}, {%4,%5,%6,%7}, {%8,%9}, {%0,%1,%2,%3};"
               : "+f"(d[0]), "+f"(d[1]), "+f"(d[2]), "+f"(d[3])
               : "r"(a[0]), "r"(a[1]), "r"(a[2]), "r"(a[3]), "r"(b0), "r"(b1));
}
DEVI uint32_t pack_bf16(float lo, float hi) {
  uint32_t r;
  asm("cvt.rn.bf16x2.f32 %0, %1, %2;" : "=r"(r) : "f"(hi), "f"(lo));
  return r;
}
DEVI uint32_t pack_f16(float lo, float hi) {
  uint32_t r;
  asm("cvt.rn.f16x2.f32 %0, %1, %2;" : "=r"(r) : "f"(hi), "f"(lo));
  return r;
}
DEVI uint32_t ldg16(const __nv_bfloat16* p) {
  uint32_t v;
  asm volatile("ld.global.nc.u16 %0, [%1];" : "=r"(v) : "l"(p));
  return v;
}
DEVI bool elect_one() {
  uint32_t pred;
  asm volatile("{\n.reg .pred p;\nelect.sync _|p, 0xffffffff;\nselp.u32 %0, 1, 0, p;\n}" : "=r"(pred));
  return pred != 0;
}
DEVI float bf_lo(uint32_t v) { return __uint_as_float(v << 16); }
DEVI float bf_hi(uint32_t v) { return __uint_as_float(v & 0xffff0000u); }
DEVI float bf2f(__nv_bfloat16 v) { return __bfloat162float(v); }
DEVI float round_bf16(float v) { return __bfloat162float(__float2bfloat16_rn(v)); }
DEVI float rcp(float x) { float r; asm("rcp.approx.ftz.f32 %0, %1;" : "=f"(r) : "f"(x)); return r; }
DEVI float ex2(float x) { float r; asm("ex2.approx.ftz.f32 %0, %1;" : "=f"(r) : "f"(x)); return r; }

DEVI void wg_fence() { asm volatile("wgmma.fence.sync.aligned;" ::: "memory"); }
DEVI void wg_commit() { asm volatile("wgmma.commit_group.sync.aligned;" ::: "memory"); }
template <int N> DEVI void wg_wait() { asm volatile("wgmma.wait_group.sync.aligned %0;" ::"n"(N) : "memory"); }
constexpr uint32_t DESC_HI = (1u << 30) | (1024 >> 4);
constexpr uint32_t DESC_HI64 = (2u << 30) | (512 >> 4);
DEVI uint32_t mkdesc(uint32_t saddr, uint32_t lbo) { return ((saddr & 0x3FFFF) >> 4) | ((lbo >> 4) << 16); }

#define R8(b) "%" #b
DEVI void wgmma_n192(float (&d)[96], uint32_t da, uint32_t db, int scale_d) {
  asm volatile(
      "{\n.reg .pred p;\n.reg .b64 da, db;\nsetp.ne.b32 p, %98, 0;\nmov.b64 da, {%96, %100};\nmov.b64 db, {%97, %99};\n"
      "wgmma.mma_async.sync.aligned.m64n192k16.f32.bf16.bf16 "
      "{%0,%1,%2,%3,%4,%5,%6,%7,%8,%9,%10,%11,%12,%13,%14,%15,"
      "%16,%17,%18,%19,%20,%21,%22,%23,%24,%25,%26,%27,%28,%29,%30,%31,"
      "%32,%33,%34,%35,%36,%37,%38,%39,%40,%41,%42,%43,%44,%45,%46,%47,"
      "%48,%49,%50,%51,%52,%53,%54,%55,%56,%57,%58,%59,%60,%61,%62,%63,"
      "%64,%65,%66,%67,%68,%69,%70,%71,%72,%73,%74,%75,%76,%77,%78,%79,"
      "%80,%81,%82,%83,%84,%85,%86,%87,%88,%89,%90,%91,%92,%93,%94,%95}, "
      "da, db, p, 1, 1, 0, 1;\n}"
      : "+f"(d[0]), "+f"(d[1]), "+f"(d[2]), "+f"(d[3]), "+f"(d[4]), "+f"(d[5]), "+f"(d[6]), "+f"(d[7]),
        "+f"(d[8]), "+f"(d[9]), "+f"(d[10]), "+f"(d[11]), "+f"(d[12]), "+f"(d[13]), "+f"(d[14]), "+f"(d[15]),
        "+f"(d[16]), "+f"(d[17]), "+f"(d[18]), "+f"(d[19]), "+f"(d[20]), "+f"(d[21]), "+f"(d[22]), "+f"(d[23]),
        "+f"(d[24]), "+f"(d[25]), "+f"(d[26]), "+f"(d[27]), "+f"(d[28]), "+f"(d[29]), "+f"(d[30]), "+f"(d[31]),
        "+f"(d[32]), "+f"(d[33]), "+f"(d[34]), "+f"(d[35]), "+f"(d[36]), "+f"(d[37]), "+f"(d[38]), "+f"(d[39]),
        "+f"(d[40]), "+f"(d[41]), "+f"(d[42]), "+f"(d[43]), "+f"(d[44]), "+f"(d[45]), "+f"(d[46]), "+f"(d[47]),
        "+f"(d[48]), "+f"(d[49]), "+f"(d[50]), "+f"(d[51]), "+f"(d[52]), "+f"(d[53]), "+f"(d[54]), "+f"(d[55]),
        "+f"(d[56]), "+f"(d[57]), "+f"(d[58]), "+f"(d[59]), "+f"(d[60]), "+f"(d[61]), "+f"(d[62]), "+f"(d[63]),
        "+f"(d[64]), "+f"(d[65]), "+f"(d[66]), "+f"(d[67]), "+f"(d[68]), "+f"(d[69]), "+f"(d[70]), "+f"(d[71]),
        "+f"(d[72]), "+f"(d[73]), "+f"(d[74]), "+f"(d[75]), "+f"(d[76]), "+f"(d[77]), "+f"(d[78]), "+f"(d[79]),
        "+f"(d[80]), "+f"(d[81]), "+f"(d[82]), "+f"(d[83]), "+f"(d[84]), "+f"(d[85]), "+f"(d[86]), "+f"(d[87]),
        "+f"(d[88]), "+f"(d[89]), "+f"(d[90]), "+f"(d[91]), "+f"(d[92]), "+f"(d[93]), "+f"(d[94]), "+f"(d[95])
      : "r"(da), "r"(db), "r"(scale_d), "n"(DESC_HI), "n"(DESC_HI64));
}
DEVI void wgmma_n64(float (&d)[32], uint32_t da, uint32_t db, int scale_d) {
  asm volatile(
      "{\n.reg .pred p;\n.reg .b64 da, db;\nsetp.ne.b32 p, %34, 0;\nmov.b64 da, {%32, %35};\nmov.b64 db, {%33, %35};\n"
      "wgmma.mma_async.sync.aligned.m64n64k16.f32.bf16.bf16 "
      "{%0,%1,%2,%3,%4,%5,%6,%7,%8,%9,%10,%11,%12,%13,%14,%15,"
      "%16,%17,%18,%19,%20,%21,%22,%23,%24,%25,%26,%27,%28,%29,%30,%31}, "
      "da, db, p, 1, 1, 0, 1;\n}"
      : "+f"(d[0]), "+f"(d[1]), "+f"(d[2]), "+f"(d[3]), "+f"(d[4]), "+f"(d[5]), "+f"(d[6]), "+f"(d[7]),
        "+f"(d[8]), "+f"(d[9]), "+f"(d[10]), "+f"(d[11]), "+f"(d[12]), "+f"(d[13]), "+f"(d[14]), "+f"(d[15]),
        "+f"(d[16]), "+f"(d[17]), "+f"(d[18]), "+f"(d[19]), "+f"(d[20]), "+f"(d[21]), "+f"(d[22]), "+f"(d[23]),
        "+f"(d[24]), "+f"(d[25]), "+f"(d[26]), "+f"(d[27]), "+f"(d[28]), "+f"(d[29]), "+f"(d[30]), "+f"(d[31])
      : "r"(da), "r"(db), "r"(scale_d), "n"(DESC_HI));
}

struct C32 { float re, im; };
DEVI C32 csq(C32 a) { return {a.re * a.re - a.im * a.im, 2.f * a.re * a.im}; }
DEVI C32 cmul(C32 a, C32 b) { return {a.re * b.re - a.im * b.im, a.re * b.im + a.im * b.re}; }
DEVI C32 cfresh(float zl, float zi, float m) {
  float mag = ex2(zl * m), ph = zi * m;
  return {mag * __cosf(ph), mag * __sinf(ph)};
}
struct HMul { uint32_t b, bp; };
DEVI HMul mk_mul(float re, float im) { return {pack_f16(re, im), pack_f16(-im, re)}; }
DEVI uint32_t hcmul(uint32_t a, const HMul& m) {
  __half2 ah = *reinterpret_cast<__half2*>(&a);
  __half2 b = *reinterpret_cast<const __half2*>(&m.b), bp = *reinterpret_cast<const __half2*>(&m.bp);
  __half2 r = __hfma2(__high2half2(ah), bp, __hmul2(__low2half2(ah), b));
  return *reinterpret_cast<uint32_t*>(&r);
}
DEVI uint32_t badd(uint32_t a, uint32_t b) {
  __nv_bfloat162 r = __hadd2(*reinterpret_cast<__nv_bfloat162*>(&a), *reinterpret_cast<__nv_bfloat162*>(&b));
  return *reinterpret_cast<uint32_t*>(&r);
}
template <int MU0, int NMU, int DMAX>
DEVI void conv_tail(float (&acc)[16][4], uint32_t p_lane, uint32_t v_base, int back, bool edge, int lane) {
  const int hsel = (lane >> 3) & 1;
  const int row = (lane & 7) + ((lane >> 4) << 3) + PADV - 8 - (back & (hsel ^ 1));
  const uint32_t la = v_base + row * 32 + (((hsel ^ back) ^ ((row >> 2) & 1)) << 4);
  uint32_t M[3][4];
  ldsm_x4_t(M[0], la);
  ldsm_x4_t(M[1], la + 256);
  uint32_t H[2 * NMU];
#pragma unroll
  for (int i = 0; i < 2 * NMU; ++i) H[i ^ 1] = lds32(p_lane + (uint32_t)(MU0 - 1 + i) * 32);
  if (edge) {
    const uint32_t a[4] = {0u, 0u, M[0][0], M[0][1]};
#pragma unroll
    for (int k = 1; k < NMU; ++k) mma_bf16v(acc[MU0 - 2 + 2 * k], a, H[2 * k], H[2 * k + 1]);
  }
#pragma unroll
  for (int delta = -1; delta <= DMAX; ++delta) {
    if (delta + 2 <= DMAX) ldsm_x4_t(M[(delta + 3) % 3], la + (delta + 3) * 256);
#pragma unroll
    for (int k = 0; k < NMU; ++k)
      if (delta + MU0 + 2 * k < 16) mma_bf16v(acc[delta + MU0 + 2 * k], M[(delta + 1) % 3], H[2 * k], H[2 * k + 1]);
  }
}

DEVI void box_filters(uint32_t sb, uint32_t bars, int idx, int lane) {
  auto swz = [](int k, int pad) { const int r = (k >> 1) + pad; return (uint32_t)(r * 32 + (((k & 1) ^ ((r >> 2) & 1)) << 4)); };
  const uint32_t o0 = swz(lane - 3, 8), o1 = swz(lane - 2, 8), o2 = swz(lane - 1, 8), ow = swz(lane - 2, PADV), oz = swz(lane - 18, PADV);
#pragma unroll 1
  for (int ch = 0; ch < 4; ++ch) {
    const int k = 32 * idx - 2 + lane;
    const uint32_t ua = sb + SM_U + ch * U_BYTES + idx * 512, vb = sb + SM_VV + ch * VV_BYTES;
    const uint32_t a0 = ua + o0, a1 = ua + o1, a2 = ua + o2, aw = vb + idx * 512 + ow;
    mbar_wait_long(bars + 8 * (B_UCH + ch), 0);
    if (idx == 0 && lane < 16) {
      sts128(vb + oz + VV_U3, 0, 0, 0, 0); sts128(vb + oz + VV_U5, 0, 0, 0, 0);
      sts128(vb + oz + VV_U7, 0, 0, 0, 0); sts128(vb + oz + VV_U9, 0, 0, 0, 0);
    }
    const uint4 t0 = lds128(a0), t1 = lds128(a1), t2 = lds128(a2);
    const uint32_t E[12] = {t0.x, t0.y, t0.z, t0.w, t1.x, t1.y, t1.z, t1.w, t2.x, t2.y, t2.z, t2.w};
    uint32_t O[8];
#pragma unroll
    for (int j = 0; j < 8; ++j) O[j] = __byte_perm(E[j + 1], E[j + 2], 0x5432);
    uint32_t s3[6], s5[4], s7[4], s9[4];
#pragma unroll
    for (int j = 0; j < 6; ++j) s3[j] = badd(badd(O[j], O[j + 1]), E[j + 2]);
#pragma unroll
    for (int j = 0; j < 4; ++j) {
      s5[j] = badd(s3[j + 2], badd(E[j + 3], E[j + 5]));
      s7[j] = badd(s5[j], badd(O[j + 1], O[j + 4]));
      s9[j] = badd(s7[j], badd(E[j + 2], E[j + 6]));
    }
    if (k < 208) { sts128(aw + VV_U3, s3[0], s3[1], s3[2], s3[3]); sts128(aw + VV_U5, s5[0], s5[1], s5[2], s5[3]); }
    if (k < 144) { sts128(aw + VV_U7, s7[0], s7[1], s7[2], s7[3]); sts128(aw + VV_U9, s9[0], s9[1], s9[2], s9[3]); }
  }
}

__global__ void __cluster_dims__(2, 1, 1) __launch_bounds__(NTHREADS, 1)
fused_kernel(const __grid_constant__ Maps maps, const Ptrs p) {
  extern __shared__ __align__(1024) uint8_t smem[];
  const uint32_t sb = s2u(smem);
  const int tid = threadIdx.x, lane = tid & 31;
  const int warp = __shfl_sync(0xffffffffu, tid >> 5, 0);
  const int cta = blockIdx.x;
  const uint32_t rank = cta & 1;
  const int ti = 2 * (cta >> 4) + rank;
  const int tj = (cta >> 1) & 7;
  const int pi = cta >> 3, pj = cta & 7;
  const uint32_t bars = sb + SM_BAR;
#define BAR(i) (bars + 8 * (i))
  const int g = lane >> 2, q = lane & 3;

  auto issue_stage = [&](int ks, int s) {
    const uint32_t st = sb + s * STG_BYTES, fb = BAR(B_FULL + s);
    mbar_expect_tx(fb, STG_BYTES);
    tma_load_2d(st + STG_X, &maps.x, ks * 32, ti * 128, fb);
    tma_load_3d_mc(st + STG_W + rank * 6144, &maps.w, tj * 64, ks * 32 + rank * 16, 0, fb, 3);
  };

  const int kch = warp & 3, krd = warp >> 2;
  float zr, zi, wr, wi;
  unsigned epoch;
  uint32_t r_dskip;
  {
    const size_t po = (size_t)(cta * 4 + kch) * 128 + krd * 32 + lane;
    const uint32_t r_ar = ldg16(p.A_re + po), r_ai = ldg16(p.A_im + po), r_br = ldg16(p.B_re + po), r_bi = ldg16(p.B_im + po);
    const uint32_t r_cr = ldg16(p.C_re + po), r_ci = ldg16(p.C_im + po), r_ldt = ldg16(p.log_dt + cta * 4 + kch);
    epoch = __ldcg(&g_epoch);
    r_dskip = ldg16(p.Dskip + cta * 4 + kch);
    uint4 pt;
    if (tid < 128) pt = __ldg((const uint4*)g_ptab.v + tid);
    if (tid == 384) {
      TS(0);
#pragma unroll
      for (int i = 0; i < B_COUNT; ++i) mbar_init(BAR(i), bar_count(i));
      asm volatile("fence.mbarrier_init.release.cluster;" ::: "memory");
      prefetch_tmap(&maps.x); prefetch_tmap(&maps.w); prefetch_tmap(&maps.u);
    }
    __syncthreads();
    cluster_arrive();
    if (warp >= 12) {
      cluster_wait();
      if (elect_one()) {
        if (warp == 13) {
          mbar_expect_tx(BAR(B_TILE), 16384);
          tma_load_2d(sb + SM_U, &maps.u, tj * 64, ti * 128, BAR(B_TILE));
          prefetch_tmap(&maps.uT); prefetch_tmap(&maps.wo); prefetch_tmap(&maps.o); prefetch_tmap(&maps.yT);
          prefetch_tmap(&maps.out);
        } else {
          if (warp == 12) TS(61);
          { const int ks = warp == 12 ? 0 : warp - 13; issue_stage(ks, ks); }
        }
      }
      __syncwarp();
    }
    if (tid < 128) sts128(sb + SM_PTAB + tid * 16, pt.x, pt.y, pt.z, pt.w);
    const float dt = round_bf16(expf(bf_lo(r_ldt)));
    zr = dt * bf_lo(r_ar); zi = dt * bf_lo(r_ai);
    const float dbr = dt * bf_lo(r_br), dbi = dt * bf_lo(r_bi), cr = bf_lo(r_cr), ci = bf_lo(r_ci);
    wr = cr * dbr - ci * dbi; wi = cr * dbi + ci * dbr;
  }
  {
    const float mz = __uint_as_float(__reduce_max_sync(0xffffffffu, __float_as_uint(fmaxf(zr, 0.f))));
    const int E = min(max((int)(__reduce_max_sync(0xffffffffu, __float_as_uint(fmaxf(fabsf(wr), fabsf(wi)))) >> 23), 1), 252);
    const float sc = __int_as_float((253 - E) << 23), inv = __int_as_float((E + 1) << 23);
    const float zl = (zr - mz) * 1.4426950408889634f;
    const uint32_t tb = sb + SM_VV + kch * VV_BYTES + krd * KG_BYTES;
    const uint32_t sta = tb + (((lane >> 2) << 4) | ((lane & 3) << 2));
    auto put = [&](int r, uint32_t v) { sts32((sta ^ ((r & 7) << 4)) + r * 128, v); };
    const uint32_t lda = tb + ((lane & 7) + (((lane >> 3) & 1) << 3)) * 128;
    const uint32_t ldb = tb + ((lane & 7) + ((lane >> 4) << 3)) * 128;
    C32 e1 = cfresh(zl, zi, 1.f), e2 = csq(e1), e4 = csq(e2), e8 = csq(e4);
    C32 e16 = cfresh(zl, zi, 16.f), e32 = csq(e16), e64 = csq(e32), e128 = csq(e64);
    C32 e256 = cfresh(zl, zi, 256.f), e512 = csq(e256), e1024 = csq(e512), e768 = cmul(e512, e256);
    uint32_t XA[2][4][4];
    {
      const HMul m16 = mk_mul(e16.re, e16.im), m32 = mk_mul(e32.re, e32.im), m64 = mk_mul(e64.re, e64.im);
      const HMul m128 = mk_mul(e128.re, e128.im);
      uint32_t X[16];
      X[0] = 0x00003c00u; X[1] = pack_f16(e8.re, e8.im); X[2] = m16.b; X[4] = m32.b; X[8] = m64.b;
      X[3] = hcmul(X[1], m16); X[5] = hcmul(X[1], m32); X[6] = hcmul(X[2], m32); X[7] = hcmul(X[3], m32);
#pragma unroll
      for (int r = 1; r < 8; ++r) X[8 + r] = hcmul(X[r], m64);
#pragma unroll
      for (int h = 0; h < 2; ++h) {
#pragma unroll
        for (int r = 0; r < 16; ++r) put(r, h == 0 ? X[r] : r == 0 ? m128.b : hcmul(X[r], m128));
        __syncwarp();
#pragma unroll
        for (int k = 0; k < 4; ++k) ldsm_x4(XA[h][k], lda + (((2 * k + (lane >> 4)) ^ (lane & 7)) << 4));
        __syncwarp();
      }
    }
    if (warp >= 14 && elect_one()) {
      issue_stage(warp - 11, warp - 11);
      issue_stage(warp - 9, warp - 9);
      if (warp == 14) l2_prefetch((const char*)p.wqkv + 224 * 3072 + cta * 6912, 6912);
      else l2_prefetch((const char*)p.x + (size_t)cta * 16384, 16384);
    }
    __syncwarp();
    float D[2][3][4];
#pragma unroll
    for (int t = 0; t < 6; ++t) D[t / 3][t % 3][0] = D[t / 3][t % 3][1] = D[t / 3][t % 3][2] = D[t / 3][t % 3][3] = 0.f;
    auto contract = [&](int t0, int nt) {
      __syncwarp();
#pragma unroll
      for (int k = 0; k < 4; ++k) {
        uint32_t b[4];
        ldsm_x4(b, ldb + (((2 * k + ((lane >> 3) & 1)) ^ (lane & 7)) << 4));
#pragma unroll
        for (int h = 0; h < 2; ++h) {
          mma_f16(D[h][t0], XA[h][k], b[0], b[1]);
          if (nt == 2) mma_f16(D[h][t0 + 1], XA[h][k], b[2], b[3]);
        }
      }
      __syncwarp();
    };
    const HMul c1 = mk_mul(e1.re, -e1.im), c2 = mk_mul(e2.re, -e2.im), c4 = mk_mul(e4.re, -e4.im);
    const HMul c256 = mk_mul(e256.re, -e256.im), c512 = mk_mul(e512.re, -e512.im), c768 = mk_mul(e768.re, -e768.im);
    const HMul c1024 = mk_mul(e1024.re, -e1024.im);
    uint32_t W[8];
    W[0] = pack_f16(wr * sc, -wi * sc);
    W[1] = hcmul(W[0], c1); W[2] = hcmul(W[0], c2); W[3] = hcmul(W[1], c2);
    W[4] = hcmul(W[0], c4); W[5] = hcmul(W[1], c4); W[6] = hcmul(W[2], c4); W[7] = hcmul(W[3], c4);
#pragma unroll
    for (int i = 0; i < 8; ++i) put(i, W[i]);
#pragma unroll
    for (int i = 0; i < 4; ++i) put(8 + i, hcmul(W[2 * i], c256));
    put(12, hcmul(W[0], c512)); put(13, hcmul(W[4], c512)); put(14, hcmul(W[0], c768)); put(15, hcmul(W[4], c768));
    contract(0, 2);
    const uint32_t v0 = hcmul(W[0], c1024);
    put(0, v0); put(1, hcmul(v0, c256)); put(2, hcmul(v0, c512)); put(3, hcmul(v0, c768)); put(4, hcmul(v0, c1024));
    contract(2, 1);
    const uint32_t a = tb + (g * 24 + 2 * q) * 4;
#pragma unroll
    for (int t = 0; t < 6; ++t) {
      const float(&d)[4] = D[t / 3][t % 3];
      sts_f32x2(a + (t / 3) * 1536 + (t % 3) * 32, d[0] * inv, d[1] * inv);
      sts_f32x2(a + (t / 3) * 1536 + (t % 3) * 32 + 768, d[2] * inv, d[3] * inv);
    }
    if (mz > 0.f) {
      __syncwarp();
#pragma unroll 1
      for (int i = lane; i < 768; i += 32) {
        const int r = i / 24, y = i - 24 * r;
        sts_f32(tb + i * 4, lds_f32(tb + i * 4) * ex2(mz * 1.4426950408889634f * (koff(y) + 8 * r)));
      }
    }
  }
  if (tid == 0) TS(2);
  if (warp < 12) cluster_wait();
  __syncthreads();

  if (warp < 4) {
#define A_REGS 200
    asm volatile("setmaxnreg.inc.sync.aligned.u32 %0;" ::"n"(A_REGS));
    if (tid == 0) TS(34);
    const int d = cta * 4 + warp;
    const uint32_t vv = sb + SM_VV + warp * VV_BYTES;
    const uint32_t ub = sb + SM_U + warp * U_BYTES;
    const uint32_t pb = sb + SM_P + warp * P_BYTES;
    const float dskip = bf_lo(r_dskip);
#pragma unroll 1
    for (int pass = 0; pass < 2; ++pass) {
      if (pass == 1) {
        const uint32_t kf = vv;
#pragma unroll 2
        for (int i = 0; i < 6; ++i) {
          const uint32_t a = kf + (i * 32 + lane) * 16;
          const uint4 x0 = lds128(a), x1 = lds128(a + KG_BYTES), x2 = lds128(a + 2 * KG_BYTES), x3 = lds128(a + 3 * KG_BYTES);
          auto s4 = [](uint32_t a0, uint32_t a1, uint32_t a2, uint32_t a3) {
            return __float_as_uint((__uint_as_float(a0) + __uint_as_float(a1)) + (__uint_as_float(a2) + __uint_as_float(a3)));
          };
          sts128(a, s4(x0.x, x1.x, x2.x, x3.x), s4(x0.y, x1.y, x2.y, x3.y), s4(x0.z, x1.z, x2.z, x3.z), s4(x0.w, x1.w, x2.w, x3.w));
        }
        __syncwarp();
        const float k1024 = lds_f32(kf + kidx_c(1024) * 4);
        if (lane == 0) {
          sts_f32(kf + SL_ZERO * 4, 0.f);
          sts_f32(kf + SL_510 * 4, lds_f32(kf + kidx_c(510) * 4) - lds_f32(kf + kidx_c(512) * 4));
          sts_f32(kf + SL_0 * 4, lds_f32(kf) + dskip);
        }
        __syncwarp();
        if (tid == 0) TS(36);
        mbar_wait_long(BAR(B_PFREE), 0);
        if (tid == 0) TS(37);
        {
          float prev = 0.f;
#pragma unroll 1
          for (int i0 = 0; i0 < 16; i0 += 4) {
            uint32_t e[4];
            float a[4], b[4];
#pragma unroll
            for (int i = 0; i < 4; ++i) e[i] = lds32(sb + SM_PTAB + ((i0 + i) * 32 + lane) * 4);
#pragma unroll
            for (int i = 0; i < 4; ++i) { a[i] = lds_f32(kf + (e[i] & 0xffff)); b[i] = lds_f32(kf + (e[i] >> 16)); }
#pragma unroll
            for (int i = 0; i < 4; ++i) {
              const uint32_t w = pb + (31 * lane + 2 * (i0 + i)) * 4;
              if (i0 + i > 0) sts32(w - 4, pack_bf16(a[i], prev));
              sts32(w, pack_bf16(b[i], a[i]));
              prev = b[i];
            }
          }
        }
        __syncwarp();
        if (lane == 0) TS(4);
        const int gq = g - 2 * q;
        uint32_t h127, h128;
        {
          const uint32_t kf2 = pack_bf16(k1024, k1024) ^ 0x80008000u;
          h127 = (gq == 4 ? 0x0000ffffu : gq == 5 ? 0xffffffffu : gq == 6 ? 0xffff0000u : 0u) & kf2;
          h128 = (gq == -4 ? 0x0000ffffu : gq == -3 ? 0xffffffffu : gq == -2 ? 0xffff0000u : 0u) & kf2;
        }
        bar_sync(7, 224);
        box_filters(sb, bars, warp, lane);
        bar_sync(5, 224);
        if (lane == 0) TS(6);
        bar_sync(4, 384);
        if (lane == 0) TS(7);
        float acc[16][4];
#pragma unroll
        for (int i = 0; i < 16; ++i) { acc[i][0] = acc[i][1] = acc[i][2] = acc[i][3] = 0.f; }
        {
          const uint32_t pd_lane = pb + (PD_OFF + 16 + gq) * 4;
          const int prow0 = 8 + (lane & 7) + ((lane >> 4) << 3), hs = (lane >> 3) & 1;
          const uint32_t zero = (uint32_t)cta >> 20;
          uint32_t B[2][4][4];
          uint32_t A[4][4];
          const uint32_t la0 = ub + prow0 * 32 + ((hs ^ ((prow0 >> 2) & 1)) << 4);
#pragma unroll
          for (int m2 = 0; m2 < 4; ++m2) ldsm_x4(B[0][m2], la0 + m2 * 512);
#pragma unroll
          for (int i = 0; i < 4; ++i) {
            const uint32_t a = pd_lane + i * 512;
            A[i][0] = lds32(a); A[i][1] = lds32(a + 32); A[i][2] = lds32(a - 32); A[i][3] = lds32(a + zero);
          }
          uint32_t la = la0;
#define UNR_RHO 8
#define UNR_TAIL 2
          constexpr int unr_rho = UNR_RHO, unr_tail = UNR_TAIL;
#pragma unroll unr_rho
          for (int rho = 0; rho < 8; ++rho) {
#pragma unroll
            for (int m2 = 0; m2 < 4; ++m2) ldsm_x4(B[1][m2], la + (4 + m2) * 512);
#pragma unroll
            for (int i = 0; i < 4; ++i)
#pragma unroll
              for (int m = 0; m < 8; ++m) mma_bf16v(acc[m + i], A[i], B[0][m >> 1][2 * (m & 1)], B[0][m >> 1][2 * (m & 1) + 1]);
            const int prow = prow0 - min(rho + 1, 7);
            la = ub + prow * 32 + ((hs ^ ((prow >> 2) & 1)) << 4);
#pragma unroll
            for (int m2 = 0; m2 < 4; ++m2) ldsm_x4(B[0][m2], la + m2 * 512);
            const uint32_t pa = pd_lane + (rho + 1) * 64;
#pragma unroll
            for (int i = 0; i < 4; ++i) {
#pragma unroll
              for (int m = 0; m < 8 - i; ++m)
                mma_bf16v(acc[8 + m + i], A[i], B[1][m >> 1][2 * (m & 1)], B[1][m >> 1][2 * (m & 1) + 1]);
              A[i][0] = lds32(pa + i * 512); A[i][1] = lds32(pa + i * 512 + 32); A[i][2] = lds32(pa + i * 512 - 32);
              A[i][3] = lds32(pa + i * 512 + zero);
            }
          }
          if (lane == 0) TS(40);
          {
            uint32_t b8[4];
            ldsm_x4(b8, la + 4 * 512);
            const uint32_t h63 = lds32(pd_lane + 63 * 32), h64 = lds32(pd_lane + 64 * 32);
            const uint32_t a63[4] = {0u, h127, 0u, 0u}, a32[4] = {h64, 0u, h63, h64}, a64[4] = {h128, 0u, h127, h128};
#pragma unroll
            for (int m2 = 0; m2 < 4; ++m2) ldsm_x4(B[1][m2], la0 + m2 * 512);
#pragma unroll
            for (int m = 0; m < 8; ++m) mma_bf16v(acc[m + 7], a63, B[0][m >> 1][2 * (m & 1)], B[0][m >> 1][2 * (m & 1) + 1]);
#pragma unroll
            for (int m2 = 0; m2 < 2; ++m2) ldsm_x4(B[0][m2], la0 + (4 + m2) * 512);
#pragma unroll
            for (int m = 0; m < 8; ++m) mma_bf16v(acc[m + 4], a32, B[1][m >> 1][2 * (m & 1)], B[1][m >> 1][2 * (m & 1) + 1]);
            mma_bf16v(acc[15], a63, b8[0], b8[1]);
#pragma unroll
            for (int m = 0; m < 8; ++m) mma_bf16v(acc[m + 8], a64, B[1][m >> 1][2 * (m & 1)], B[1][m >> 1][2 * (m & 1) + 1]);
#pragma unroll
            for (int m = 0; m < 4; ++m) mma_bf16v(acc[m + 12], a32, B[0][m >> 1][2 * (m & 1)], B[0][m >> 1][2 * (m & 1) + 1]);
          }
          if (lane == 0) TS(41);
#pragma unroll unr_tail
          for (int v = 0; v < 4; ++v)
            conv_tail<4, 3, 11>(acc, pb + (P2_OFF + 56 * v + gq - 16) * 4, vv + ((v & 1) ? VV_U3 : VV_U5), v >> 1, v == 0, lane);
          if (lane == 0) TS(42);
#pragma unroll unr_tail
          for (int pi = 0; pi < 2; ++pi)
            conv_tail<8, 5, 7>(acc, pb + (P3_OFF + 88 * pi + gq - 48) * 4, vv + (pi ? VV_U7 : VV_U9), pi, pi == 0, lane);
        }
        if (lane == 0) TS(8);
        __syncwarp();
        {
          const int mt = lane >> 3;
          const uint32_t a = pb + (128 * (mt >> 1) + 16 * (lane & 7) + 8 * (mt & 1)) * 2;
#pragma unroll
          for (int ab = 0; ab < 16; ab += 2)
            stsm_x4_t(a + ab * 256, pack_bf16(acc[ab][0], acc[ab][1]), pack_bf16(acc[ab][2], acc[ab][3]),
                      pack_bf16(acc[ab + 1][0], acc[ab + 1][1]), pack_bf16(acc[ab + 1][2], acc[ab + 1][3]));
        }
        fence_async_smem();
        __syncwarp();
        if (lane < 2) mbar_arrive_cluster(BAR(B_CONVD), lane);
        bar_arrive(3, 384);
        if (elect_one()) {
          bulk_store(p.yT + (size_t)d * 2048, pb, 4096);
          bulk_commit();
          bulk_wait0();
          red_relaxed_add(&g_cnt[(C_Y + (cta >> 4)) * 32], 1);
          TS(9);
        }
        bar_sync(2, 128);
        if (warp == 0 && elect_one()) {
          wait_counter(&g_cnt[(C_Y + tj) * 32], (epoch + 1) * 64);
          TS(28);
          mbar_expect_tx(BAR(B_TILE), 16384);
          tma_load_2d(sb + SM_U, &maps.yT, ti * 128, tj * 64, BAR(B_TILE));
          tma_load_2d(sb + SM_U + 8192, &maps.yT, ti * 128 + 64, tj * 64, BAR(B_TILE));
        }
        __syncwarp();
      }
      mbar_wait_long(BAR(B_TILE), pass);
      if (lane == 0) TS(26 + 3 * pass);
      {
        const int m = lane >> 3, r = lane & 7;
#pragma unroll 2
        for (int it = 0; it < 8; ++it) {
          const int tb = warp * 4 + (it >> 1), cb = (it & 1) * 4 + m;
          const uint32_t at = (tb * 8 + r) * 128 + ((cb ^ r) << 4);
          const uint32_t ac = (tb >> 3) * 8192 + (cb * 8 + r) * 128 + (((tb & 7) ^ (pass ? 0 : tb >> 3) ^ r) << 4);
          uint32_t v[4];
          ldsm_x4_t(v, sb + SM_U + (pass ? ac : at));
          stsm_x4(sb + SM_P + (pass ? at : ac), v[0], v[1], v[2], v[3]);
        }
      }
      if (pass == 0 && tid == 0) TS(35);
      fence_async_smem();
      if (pass == 0) {
        bar_arrive(6, 160);
      } else {
        bar_sync(2, 128);
        if (warp == 0 && elect_one()) {
          tma_store_2d(&maps.out, sb + SM_P, 64 * tj, 128 * ti);
          bulk_commit();
          bulk_wait_read0();
          TS(30);
        }
      }
    }
  } else if (warp < 12) {
    const int w8 = warp - 4;
    const int row = w8 * 16 + (lane & 7) + (((lane >> 3) & 1) << 3);
    uint32_t pq[16];
    {
      float acc[96];
#pragma unroll 1
      for (int ks = 0, s = 0, ph = 0; ks < 16; ++ks) {
        mbar_wait(BAR(B_FULL + s), ph);
        if (tid == 128 && !(ks & 1)) TSR(16, ks == 0 ? 16 : 9 + (ks >> 1) + (ks > 12 ? 43 : 0));
        const uint32_t st = sb + s * STG_BYTES;
        const uint32_t da = mkdesc(st + STG_X + (w8 >> 2) * 4096, 16);
        const uint32_t db = mkdesc(st + STG_W, 2048);
        wg_fence();
        wgmma_n192(acc, da, db, ks != 0);
        wgmma_n192(acc, da + 2, db + 384, 1);
        wg_commit();
        const uint32_t eprev = BAR(B_EMPTY + (s == 0 ? NSTG - 1 : s - 1));
        if (++s == NSTG) { s = 0; ph ^= 1; }
        if (ks > 0) {
          wg_wait<1>();
          if (lane < 2) mbar_arrive_cluster(eprev, lane);
        }
      }
      wg_wait<0>();
      if (tid == 128) TS(17);
      auto phi2 = [](float a, float b) -> uint32_t {
        const uint32_t x = pack_bf16(a, b);
        const uint32_t e = pack_bf16(ex2(bf_lo(x) * 1.4426950408889634f), ex2(bf_hi(x) * 1.4426950408889634f));
        const uint32_t m = __hgt2_mask(*reinterpret_cast<const __nv_bfloat162*>(&x), __floats2bfloat162_rn(0.f, 0.f));
        return badd((badd(x, 0x3f803f80u) & m) | (e & ~m), 0x35863586u);
      };
      uint32_t pk[16];
#pragma unroll
      for (int i = 0; i < 16; ++i) pk[i] = phi2(acc[32 + 2 * i], acc[33 + 2 * i]);
      if (tid == 128) TS(53);
      bar_sync(1, 256);
#pragma unroll
      for (int i = 0; i < 8; i += 2) {
        const uint32_t off = row * 128 + (((i + (lane >> 4)) ^ (row & 7)) << 4);
        stsm_x4(sb + SM_PK + off, pk[2 * i], pk[2 * i + 1], pk[2 * i + 2], pk[2 * i + 3]);
        stsm_x4(sb + SM_VS + off, pack_bf16(acc[64 + 4 * i], acc[65 + 4 * i]), pack_bf16(acc[66 + 4 * i], acc[67 + 4 * i]),
                pack_bf16(acc[68 + 4 * i], acc[69 + 4 * i]), pack_bf16(acc[70 + 4 * i], acc[71 + 4 * i]));
      }
      bar_sync(1, 256);
      {
        const int hh = w8 >> 1, dtile = w8 & 1;
        float kv[2][4] = {{0.f, 0.f, 0.f, 0.f}, {0.f, 0.f, 0.f, 0.f}}, zz[2][4] = {{0.f, 0.f, 0.f, 0.f}, {0.f, 0.f, 0.f, 0.f}};
        const int m = lane >> 3;
        const uint32_t aa = sb + SM_VS + ((lane & 7) + ((m >> 1) << 3)) * 128 + (((2 * hh + (m & 1)) ^ (lane & 7)) << 4);
        const uint32_t ab = sb + SM_PK + (lane & 15) * 128 + (((2 * hh + dtile) ^ (lane & 7)) << 4);
#pragma unroll
        for (int ks = 0; ks < 8; ++ks) {
          uint32_t a[4], b0, b1;
          ldsm_x4_t(a, aa + ks * 2048);
          ldsm_x2_t(b0, b1, ab + ks * 2048);
          mma_bf16(kv[ks & 1], a[0], a[1], a[2], a[3], b0, b1);
          mma_bf16(zz[ks & 1], 0x3f803f80u, 0x3f803f80u, 0x3f803f80u, 0x3f803f80u, b0, b1);
        }
        const uint32_t kp = sb + SM_KV + hh * 1088;
        sts128(kp + dtile * 512 + lane * 16, __float_as_uint(kv[0][0] + kv[1][0]), __float_as_uint(kv[0][1] + kv[1][1]),
               __float_as_uint(kv[0][2] + kv[1][2]), __float_as_uint(kv[0][3] + kv[1][3]));
        if (g == 0) sts_f32x2(kp + 1024 + dtile * 32 + q * 8, zz[0][0] + zz[1][0], zz[0][1] + zz[1][1]);
        fence_async_smem();
        __syncwarp();
        if (lane == 0) mbar_arrive(BAR(B_KVP));
        bar_arrive(4, 384);
        if (tid == 128) TS(55);
      }
#pragma unroll
      for (int i = 0; i < 16; ++i) pq[i] = phi2(acc[2 * i], acc[2 * i + 1]);
    }
    if (tid == 128) TS(56);
    if (warp == 4) mbar_wait_long(BAR(B_KVF), 0);
    bar_sync(1, 256);
    if (tid == 128) TS(19);
    {
      uint32_t kb[4][6];
#pragma unroll
      for (int h = 0; h < 4; ++h) {
        const uint32_t kp = sb + SM_KV + h * 1088;
        const uint4 k0 = lds128(kp + lane * 16), k1 = lds128(kp + 512 + lane * 16);
        const uint32_t za = kp + 1024 + q * 8;
        auto pk2 = [](uint32_t x, uint32_t y) { return pack_bf16(__uint_as_float(x), __uint_as_float(y)); };
        kb[h][0] = pk2(k0.x, k0.y); kb[h][1] = pk2(k1.x, k1.y); kb[h][2] = pk2(k0.z, k0.w); kb[h][3] = pk2(k1.z, k1.w);
        kb[h][4] = pack_bf16(lds_f32(za), lds_f32(za + 4)); kb[h][5] = pack_bf16(lds_f32(za + 32), lds_f32(za + 36));
      }
#pragma unroll
      for (int h = 0; h < 4; ++h) {
        float n0[4] = {0.f, 0.f, 0.f, 0.f}, n1[4] = {0.f, 0.f, 0.f, 0.f}, dn[4] = {0.f, 0.f, 0.f, 0.f};
        mma_bf16(n0, pq[4 * h], pq[4 * h + 1], pq[4 * h + 2], pq[4 * h + 3], kb[h][0], kb[h][1]);
        mma_bf16(n1, pq[4 * h], pq[4 * h + 1], pq[4 * h + 2], pq[4 * h + 3], kb[h][2], kb[h][3]);
        mma_bf16(dn, pq[4 * h], pq[4 * h + 1], pq[4 * h + 2], pq[4 * h + 3], kb[h][4], kb[h][5]);
        const uint32_t dd = pack_bf16(dn[0], dn[2]);
        const uint32_t d2 = pack_bf16(bf_lo(dd) + 1e-6f, bf_hi(dd) + 1e-6f);
        const float r0 = rcp(bf_lo(d2)), r1 = rcp(bf_hi(d2));
        const uint32_t x0 = pack_bf16(n0[0], n0[1]), x1 = pack_bf16(n0[2], n0[3]);
        const uint32_t x2 = pack_bf16(n1[0], n1[1]), x3 = pack_bf16(n1[2], n1[3]);
        stsm_x4(sb + SM_QS + row * 128 + (((2 * h + (lane >> 4)) ^ (row & 7)) << 4),
                pack_bf16(bf_lo(x0) * r0, bf_hi(x0) * r0), pack_bf16(bf_lo(x1) * r1, bf_hi(x1) * r1),
                pack_bf16(bf_lo(x2) * r0, bf_hi(x2) * r0), pack_bf16(bf_lo(x3) * r1, bf_hi(x3) * r1));
      }
    }
    fence_async_smem();
    __syncwarp();
    if (lane == 0) mbar_arrive(BAR(B_OST));
    if (tid == 128) TS(57);
    if (warp == 4) mbar_wait_long(BAR(B_WO), 0);
    bar_sync(3, 384);
    {
      float o[32];
#pragma unroll 1
      for (int c = 0; c < 8; ++c) {
        mbar_wait_long(BAR(B_RF + c), 0);
        if (tid == 128) TSR(22, c == 0 ? 22 : 43 + c);
        const uint32_t slot = c < 4 ? SM_QS + c * 16384 : c < 7 ? SM_VV + (c - 4) * 16384 : SM_QS;
        const uint32_t da = mkdesc(sb + slot + (w8 >> 2) * 8192, 16);
        const uint32_t db = mkdesc(sb + SM_WO + c * 8192, 8192);
        wg_fence();
#pragma unroll
        for (int k = 0; k < 4; ++k) wgmma_n64(o, da + 2 * k, db + 128 * k, (c | k) != 0);
        wg_commit();
        if (c == 1) {
          wg_wait<1>();
          if (lane < 2) mbar_arrive_cluster(BAR(B_RE), lane);
        }
      }
      wg_wait<0>();
      if (tid == 128) TS(51);
      bar_sync(1, 256);
#pragma unroll
      for (int i = 0; i < 8; i += 2)
        stsm_x4(sb + SM_BOUT + row * 128 + (((i + (lane >> 4)) ^ (row & 7)) << 4), pack_bf16(o[4 * i], o[4 * i + 1]),
                pack_bf16(o[4 * i + 2], o[4 * i + 3]), pack_bf16(o[4 * i + 4], o[4 * i + 5]), pack_bf16(o[4 * i + 6], o[4 * i + 7]));
      fence_async_smem();
      bar_sync(1, 256);
      if (tid == 128) TS(52);
      if (warp == 4 && elect_one()) {
        tma_store_2d(&maps.out, sb + SM_BOUT, 512 + 64 * pj, 128 * pi);
        bulk_commit();
        bulk_wait_read0();
        TS(23);
      }
    }
  } else {
    asm volatile("setmaxnreg.dec.sync.aligned.u32 40;");
    if (warp == 12) {
      if (elect_one()) {
#pragma unroll 1
        for (int ks = NSTG, s = 0, ph = 0; ks < 16; ++ks) {
          mbar_wait(BAR(B_EMPTY + s), ph);
          issue_stage(ks, s);
          if (ks == NSTG) l2_prefetch((const char*)p.wo + (size_t)cta * 4096, 4096);
          if (++s == NSTG) { s = 0; ph ^= 1; }
        }
        mbar_wait(BAR(B_EMPTY + 6), 1);
        mbar_expect_tx(BAR(B_WO), 65536);
        tma_load_2d(sb + SM_WO, &maps.wo, pj * 64, 0, BAR(B_WO));
        tma_load_2d(sb + SM_WO + 32768, &maps.wo, pj * 64, 256, BAR(B_WO));
        float* kvg = &g_kv[epoch & 1][tj][0];
        mbar_wait_long(BAR(B_KVP), 0);
        bulk_reduce_add_f32(kvg, sb + SM_KV, 4352);
        bulk_commit();
        bulk_wait0();
        red_relaxed_add(&g_cnt[(C_KV + tj) * 32], 1);
        TS(18);
        wait_counter(&g_cnt[(C_KV + tj) * 32], (epoch + 1) * 16);
        mbar_expect_tx(BAR(B_KVF), 4352);
        bulk_load(sb + SM_KV, kvg, 4352, BAR(B_KVF));
        mbar_wait_long(BAR(B_OST), 0);
        tma_store_2d(&maps.o, sb + SM_QS, tj * 64, ti * 128);
        tma_store_2d(&maps.o, sb + SM_QS + 8192, tj * 64, ti * 128 + 64);
        bulk_commit();
        bulk_wait0();
        red_relaxed_add(&g_cnt[(C_O + ti) * 32], 1);
        TS(20);
        mbar_arrive_cluster(BAR(B_SLOT), 0);
        mbar_arrive_cluster(BAR(B_SLOT), 1);
        wait_counter(&g_cnt[(C_O + pi) * 32], (epoch + 1) * 8);
        if (cta == 0) g_epoch = epoch + 1;
        mbar_wait(BAR(B_SLOT), 0);
        TS(21);
#pragma unroll 1
        for (int c = 0; c < 8; ++c) {
          if (c == 4) mbar_wait_long(BAR(B_CONVD), 0);
          if (c == 7) mbar_wait(BAR(B_RE), 0);
          const uint32_t slot = c < 4 ? SM_QS + c * 16384 : c < 7 ? SM_VV + (c - 4) * 16384 : SM_QS;
          mbar_expect_tx(BAR(B_RF + c), 16384);
          tma_load_2d_mc(sb + slot + rank * 8192, &maps.o, c * 64, pi * 128 + rank * 64, BAR(B_RF + c), 3);
        }
      }
    } else if (warp == 13) {
      bar_sync(6, 160);
      sts128(sb + SM_U + (lane >> 4) * U_BYTES + (lane & 15) * 16, 0, 0, 0, 0);
      sts128(sb + SM_U + (2 + (lane >> 4)) * U_BYTES + (lane & 15) * 16, 0, 0, 0, 0);
      __syncwarp();
      if (elect_one()) {
        tma_store_2d(&maps.uT, sb + SM_P, ti * 128, tj * 64);
        tma_store_2d(&maps.uT, sb + SM_P + 8192, ti * 128 + 64, tj * 64);
        bulk_commit();
        bulk_wait_read0();
        mbar_arrive(BAR(B_PFREE));
        bulk_wait0();
        red_relaxed_add(&g_cnt[(C_U + tj) * 32], 1);
        TS(27);
        wait_counter(&g_cnt[(C_U + (cta >> 4)) * 32], (epoch + 1) * 16);
#pragma unroll 1
        for (int c = 0; c < 4; ++c) {
          mbar_expect_tx(BAR(B_UCH + c), 4096);
          bulk_load(sb + SM_U + c * U_BYTES + 256, p.uT + (size_t)(cta * 4 + c) * 2048, 4096, BAR(B_UCH + c));
        }
        TS(3);
      }
      __syncwarp();
      if (ti == 0) {
        float4* z = (float4*)&g_kv[(epoch & 1) ^ 1][tj][0];
#pragma unroll 1
        for (int i = lane; i < 272; i += 32) z[i] = make_float4(0.f, 0.f, 0.f, 0.f);
      }
    }
    if (warp >= 13) {
      bar_sync(7, 224);
      box_filters(sb, bars, warp - 9, lane);
      bar_arrive(5, 224);
    }
  }
  __syncwarp();
  cluster_arrive();
  cluster_wait();
  if (tid == 0) TS(31);
#undef BAR
}

typedef CUresult (*EncodeFn)(CUtensorMap*, CUtensorMapDataType, cuuint32_t, void*, const cuuint64_t*, const cuuint64_t*,
                             const cuuint32_t*, const cuuint32_t*, CUtensorMapInterleave, CUtensorMapSwizzle,
                             CUtensorMapL2promotion, CUtensorMapFloatOOBfill);

static void make_map(EncodeFn enc, CUtensorMap* m, const void* base, uint64_t inner, uint64_t outer, uint32_t box_in,
                     uint32_t box_out, CUtensorMapSwizzle swz = CU_TENSOR_MAP_SWIZZLE_128B) {
  cuuint64_t gd[2] = {inner, outer};
  cuuint64_t gs[1] = {inner * 2};
  cuuint32_t bd[2] = {box_in, box_out};
  cuuint32_t es[2] = {1, 1};
  enc(m, CU_TENSOR_MAP_DATA_TYPE_BFLOAT16, 2, const_cast<void*>(base), gd, gs, bd, es, CU_TENSOR_MAP_INTERLEAVE_NONE,
      swz, CU_TENSOR_MAP_L2_PROMOTION_L2_128B, CU_TENSOR_MAP_FLOAT_OOB_FILL_NONE);
}

}

extern "C" void kernel_launch(void* const* d_in, const int* in_sizes, int n_in, void* d_out, int out_size) {
  using namespace s4la;
  (void)in_sizes; (void)n_in; (void)out_size;
  static EncodeFn enc = nullptr;
  static void *uT = nullptr, *yT = nullptr, *oS = nullptr;
  if (!enc) {
    void* fn = nullptr;
    cudaDriverEntryPointQueryResult qr;
    cudaGetDriverEntryPoint("cuTensorMapEncodeTiled", &fn, cudaEnableDefault, &qr);
    enc = (EncodeFn)fn;
    cudaGetSymbolAddress(&uT, g_uT);
    cudaGetSymbolAddress(&yT, g_yT);
    cudaGetSymbolAddress(&oS, g_o);
    cudaFuncSetAttribute(fused_kernel, cudaFuncAttributeMaxDynamicSharedMemorySize, SM_TOTAL);
  }
  const __nv_bfloat16* const* in = (const __nv_bfloat16* const*)d_in;
  Maps maps;
  make_map(enc, &maps.x, in[9], 512, 2048, 32, 128, CU_TENSOR_MAP_SWIZZLE_64B);
  {
    cuuint64_t gd[3] = {512, 512, 3};
    cuuint64_t gs[2] = {3072, 1024};
    cuuint32_t bd[3] = {64, 16, 3};
    cuuint32_t es[3] = {1, 1, 1};
    enc(&maps.w, CU_TENSOR_MAP_DATA_TYPE_BFLOAT16, 3, const_cast<__nv_bfloat16*>(in[10]), gd, gs, bd, es,
        CU_TENSOR_MAP_INTERLEAVE_NONE, CU_TENSOR_MAP_SWIZZLE_128B, CU_TENSOR_MAP_L2_PROMOTION_L2_128B,
        CU_TENSOR_MAP_FLOAT_OOB_FILL_NONE);
  }
  make_map(enc, &maps.wo, in[11], 512, 512, 64, 256);
  make_map(enc, &maps.u, in[0], 512, 2048, 64, 128);
  make_map(enc, &maps.uT, uT, 2048, 512, 64, 64);
  make_map(enc, &maps.yT, yT, 2048, 512, 64, 64);
  make_map(enc, &maps.o, oS, 512, 2048, 64, 64);
  make_map(enc, &maps.out, d_out, 1024, 2048, 64, 128);
  Ptrs p;
  p.A_re = in[1]; p.A_im = in[2]; p.B_re = in[3]; p.B_im = in[4]; p.C_re = in[5]; p.C_im = in[6];
  p.log_dt = in[7]; p.Dskip = in[8]; p.x = in[9]; p.wqkv = in[10]; p.wo = in[11];
  p.uT = (__nv_bfloat16*)uT; p.yT = (__nv_bfloat16*)yT;
  fused_kernel<<<NCTA, NTHREADS, SM_TOTAL, cudaStreamPerThread>>>(maps, p);
}
```

```cpp
#include <cuda_runtime.h>
#include <cuda_bf16.h>
#include <cuda_fp16.h>
#include <cuda.h>
#include <stdint.h>

#define DEVI __device__ __forceinline__

namespace s4la {

constexpr int NTHREADS = 512;
constexpr int NCTA = 128;

constexpr int NSTG = 7;
constexpr uint32_t STG_BYTES = 20480, STG_X = 0, STG_W = 8192;
constexpr uint32_t SM_QS = 0;
constexpr uint32_t SM_PK = SM_QS + 16384, SM_VS = SM_QS + 32768;
constexpr uint32_t SM_WO = 65536;
constexpr uint32_t SM_KV = 131072;
constexpr uint32_t SM_BOUT = 16384;
constexpr uint32_t SM_U = 143360, U_BYTES = 4352;
constexpr uint32_t SM_P = 160768, P_BYTES = 4096;
constexpr uint32_t SM_VV = 177152, VV_BYTES = 12800;
constexpr uint32_t VV_U5 = 0, VV_U3 = 3712, VV_U9 = 7424, VV_U7 = 10112;
constexpr uint32_t KG_BYTES = 3200;
constexpr uint32_t SM_BAR = SM_VV + 4 * VV_BYTES;
constexpr uint32_t SM_PTAB = SM_BAR + 320;
constexpr uint32_t SM_TOTAL = SM_PTAB + 2048;
static_assert(SM_TOTAL <= 232448, "shared memory");
constexpr int PADV = 12;

enum { B_FULL = 0, B_EMPTY = 7, B_TILE = 14, B_UCH = 15, B_KVP = 19, B_KVF = 20, B_OST = 21, B_RF = 22, B_WO = 30, B_RE = 31, B_PFREE = 32, B_CONVD = 33, B_SLOT = 34, B_COUNT = 35 };
__host__ __device__ constexpr int bar_count(int i) {
  return (i >= B_EMPTY && i < B_TILE) ? 16 : (i == B_KVP || i == B_OST || i == B_CONVD) ? 8 : i == B_RE ? 16 : i == B_SLOT ? 2 : 1;
}

constexpr int PD_OFF = 0, P2_OFF = 544, P3_OFF = 768;

constexpr int SL_K2048 = 20, SL_ZERO = 21, SL_510 = 22, SL_0 = 23;
__host__ __device__ constexpr int koff(int y) {
  return y < 8 ? y : y < 12 ? 256 + 2 * (y - 8) : y < 16 ? 512 + 256 * ((y - 12) >> 1) + 4 * (y & 1) : 1024 + 256 * (y - 16);
}
__host__ __device__ constexpr int kidx_c(int l) {
  const int y = l < 256 ? (l & 7) : l < 512 ? 8 + ((l & 7) >> 1) : l < 1024 ? 12 + (((l - 512) >> 8) << 1) + ((l >> 2) & 1)
                                                                            : 16 + ((l - 1024) >> 8);
  return ((l >> 3) & 31) * 24 + y;
}
constexpr int slot_direct(int l) {
  if (l < 0 || l > 510) return SL_ZERO;
  if (l == 510) return SL_510;
  if (l == 0) return SL_0;
  return kidx_c(l < 256 ? l : ((l + ((l >> 1) & 1)) & ~1));
}
constexpr int slot_seg2(int v, int k) { return (k >= 32 && k < 64) ? kidx_c(16 * k + 4 * v) : SL_ZERO; }
constexpr int slot_seg3(int pi, int k) {
  return (k >= 64 && k < 128) ? kidx_c(16 * k + 8 * pi) : ((k == 128 && pi == 0) ? SL_K2048 : SL_ZERO);
}
constexpr int slot_word(int w) {
  return w < 0 ? SL_ZERO : w < 544 ? slot_direct(w - 16) : w < 768 ? slot_seg2((w - 544) / 56, 16 + (w - 544) % 56)
       : w < 944 ? slot_seg3((w - 768) / 88, 48 + (w - 768) % 88) : SL_ZERO;
}
struct PTab { uint32_t v[512]; };
constexpr PTab make_ptab() {
  PTab t{};
  for (int lane = 0; lane < 32; ++lane)
    for (int i = 0; i < 16; ++i)
      t.v[i * 32 + lane] = (slot_word(31 * lane - 1 + 2 * i) * 4) | ((slot_word(31 * lane + 2 * i) * 4) << 16);
  return t;
}
__device__ const PTab g_ptab = make_ptab();

__device__ __nv_bfloat16 g_uT[512 * 2048];
__device__ __nv_bfloat16 g_yT[512 * 2048];
__device__ __nv_bfloat16 g_o[2048 * 512];
__device__ float g_kv[2][8][4 * 272];
__device__ unsigned g_cnt[64 * 32];
__device__ unsigned g_epoch;
#define TS(slot) do { } while (0)
#define TSR(on, slot) do { } while (0)
#define TSD(slot) do { } while (0)
enum { C_U = 0, C_KV = 8, C_O = 16, C_Y = 32 };

struct Maps {
  CUtensorMap x, w, wo, u, uT, yT, o, out;
};
struct Ptrs {
  const __nv_bfloat16 *A_re, *A_im, *B_re, *B_im, *C_re, *C_im, *log_dt, *Dskip;
  const __nv_bfloat16 *x, *wqkv, *wo;
  __nv_bfloat16 *uT, *yT;
};

DEVI uint32_t s2u(const void* p) { return (uint32_t)__cvta_generic_to_shared(p); }
DEVI void mbar_init(uint32_t b, uint32_t c) { asm volatile("mbarrier.init.shared::cta.b64 [%0], %1;" ::"r"(b), "r"(c) : "memory"); }
DEVI void mbar_expect_tx(uint32_t b, uint32_t bytes) {
  asm volatile("mbarrier.arrive.expect_tx.shared::cta.b64 _, [%0], %1;" ::"r"(b), "r"(bytes) : "memory");
}
DEVI void mbar_arrive(uint32_t b) { asm volatile("mbarrier.arrive.shared::cta.b64 _, [%0];" ::"r"(b) : "memory"); }
DEVI void mbar_arrive_cluster(uint32_t b, uint32_t cta) {
  asm volatile("{\n.reg .b32 r;\nmapa.shared::cluster.u32 r, %0, %1;\nmbarrier.arrive.shared::cluster.b64 _, [r];\n}"
               ::"r"(b), "r"(cta) : "memory");
}
DEVI void mbar_wait(uint32_t b, uint32_t parity) {
  asm volatile("{\n.reg .pred p;\nLAB_WAIT:\nmbarrier.try_wait.parity.shared::cta.b64 p, [%0], %1;\n@!p bra LAB_WAIT;\n}"
               ::"r"(b), "r"(parity) : "memory");
}
DEVI void mbar_wait_long(uint32_t b, uint32_t parity) {
  asm volatile("{\n.reg .pred p;\nLAB_WAIT:\nmbarrier.try_wait.parity.shared::cta.b64 p, [%0], %1, 0x989680;\n@!p bra LAB_WAIT;\n}"
               ::"r"(b), "r"(parity) : "memory");
}
DEVI void bar_sync(int id, int n) { asm volatile("bar.sync %0, %1;" ::"r"(id), "r"(n) : "memory"); }
DEVI void bar_arrive(int id, int n) { asm volatile("bar.arrive %0, %1;" ::"r"(id), "r"(n) : "memory"); }
DEVI void fence_async_smem() { asm volatile("fence.proxy.async.shared::cta;" ::: "memory"); }
DEVI void fence_async_all() { asm volatile("fence.proxy.async;" ::: "memory"); }
DEVI void cluster_arrive() { asm volatile("barrier.cluster.arrive.relaxed.aligned;" ::: "memory"); }
DEVI void cluster_wait() { asm volatile("barrier.cluster.wait.aligned;" ::: "memory"); }

DEVI void tma_load_2d(uint32_t dst, const CUtensorMap* m, int c0, int c1, uint32_t bar) {
  asm volatile("cp.async.bulk.tensor.2d.shared::cluster.global.mbarrier::complete_tx::bytes [%0], [%1, {%3, %4}], [%2];"
               ::"r"(dst), "l"(m), "r"(bar), "r"(c0), "r"(c1) : "memory");
}
DEVI void tma_load_2d_mc(uint32_t dst, const CUtensorMap* m, int c0, int c1, uint32_t bar, uint16_t mask) {
  asm volatile("cp.async.bulk.tensor.2d.shared::cluster.global.mbarrier::complete_tx::bytes.multicast::cluster [%0], [%1, {%3, %4}], [%2], %5;"
               ::"r"(dst), "l"(m), "r"(bar), "r"(c0), "r"(c1), "h"(mask) : "memory");
}
DEVI void tma_load_3d_mc(uint32_t dst, const CUtensorMap* m, int c0, int c1, int c2, uint32_t bar, uint16_t mask) {
  asm volatile("cp.async.bulk.tensor.3d.shared::cluster.global.mbarrier::complete_tx::bytes.multicast::cluster [%0], [%1, {%3, %4, %5}], [%2], %6;"
               ::"r"(dst), "l"(m), "r"(bar), "r"(c0), "r"(c1), "r"(c2), "h"(mask) : "memory");
}
DEVI void tma_store_2d(const CUtensorMap* m, uint32_t src, int c0, int c1) {
  asm volatile("cp.async.bulk.tensor.2d.global.shared::cta.bulk_group [%0, {%2, %3}], [%1];"
               ::"l"(m), "r"(src), "r"(c0), "r"(c1) : "memory");
}
DEVI void bulk_load(uint32_t dst, const void* src, uint32_t bytes, uint32_t bar) {
  asm volatile("cp.async.bulk.shared::cluster.global.mbarrier::complete_tx::bytes [%0], [%1], %2, [%3];"
               ::"r"(dst), "l"(src), "r"(bytes), "r"(bar) : "memory");
}
DEVI void bulk_store(void* dst, uint32_t src, uint32_t bytes) {
  asm volatile("cp.async.bulk.global.shared::cta.bulk_group [%0], [%1], %2;" ::"l"(dst), "r"(src), "r"(bytes) : "memory");
}
DEVI void bulk_reduce_add_f32(void* dst, uint32_t src, uint32_t bytes) {
  asm volatile("cp.reduce.async.bulk.global.shared::cta.bulk_group.add.f32 [%0], [%1], %2;" ::"l"(dst), "r"(src), "r"(bytes) : "memory");
}
DEVI void bulk_commit() { asm volatile("cp.async.bulk.commit_group;" ::: "memory"); }
DEVI void bulk_wait0() { asm volatile("cp.async.bulk.wait_group 0;" ::: "memory"); }
DEVI void bulk_wait_read0() { asm volatile("cp.async.bulk.wait_group.read 0;" ::: "memory"); }
DEVI void l2_prefetch(const void* p, uint32_t bytes) {
  asm volatile("cp.async.bulk.prefetch.L2.global [%0], %1;" ::"l"(p), "r"(bytes) : "memory");
}
DEVI void prefetch_tmap(const CUtensorMap* m) { asm volatile("prefetch.tensormap [%0];" ::"l"(m) : "memory"); }

DEVI void red_release_add(unsigned* p, unsigned v) {
  asm volatile("red.release.gpu.global.add.u32 [%0], %1;" ::"l"(p), "r"(v) : "memory");
}
DEVI void red_relaxed_add(unsigned* p, unsigned v) {
  asm volatile("red.relaxed.gpu.global.add.u32 [%0], %1;" ::"l"(p), "r"(v) : "memory");
}
DEVI unsigned ld_relaxed(const unsigned* p) {
  unsigned v;
  asm volatile("ld.relaxed.gpu.global.u32 %0, [%1];" : "=r"(v) : "l"(p) : "memory");
  return v;
}
DEVI void wait_counter(const unsigned* p, unsigned target) {
#pragma unroll 1
  for (int it = 0; (int)(ld_relaxed(p) - target) < 0; ++it)
    if (it > (1 << 22)) __trap();
}

DEVI void ldsm_x4(uint32_t (&r)[4], uint32_t a) {
  asm volatile("ldmatrix.sync.aligned.m8n8.x4.shared.b16 {%0,%1,%2,%3}, [%4];"
               : "=r"(r[0]), "=r"(r[1]), "=r"(r[2]), "=r"(r[3]) : "r"(a) : "memory");
}
DEVI void ldsm_x4_t(uint32_t (&r)[4], uint32_t a) {
  asm volatile("ldmatrix.sync.aligned.m8n8.x4.trans.shared.b16 {%0,%1,%2,%3}, [%4];"
               : "=r"(r[0]), "=r"(r[1]), "=r"(r[2]), "=r"(r[3]) : "r"(a) : "memory");
}
DEVI void ldsm_x2_t(uint32_t& r0, uint32_t& r1, uint32_t a) {
  asm volatile("ldmatrix.sync.aligned.m8n8.x2.trans.shared.b16 {%0,%1}, [%2];" : "=r"(r0), "=r"(r1) : "r"(a) : "memory");
}
DEVI void stsm_x4(uint32_t a, uint32_t r0, uint32_t r1, uint32_t r2, uint32_t r3) {
  asm volatile("stmatrix.sync.aligned.m8n8.x4.shared.b16 [%0], {%1,%2,%3,%4};"
               ::"r"(a), "r"(r0), "r"(r1), "r"(r2), "r"(r3) : "memory");
}
DEVI void stsm_x4_t(uint32_t a, uint32_t r0, uint32_t r1, uint32_t r2, uint32_t r3) {
  asm volatile("stmatrix.sync.aligned.m8n8.x4.trans.shared.b16 [%0], {%1,%2,%3,%4};"
               ::"r"(a), "r"(r0), "r"(r1), "r"(r2), "r"(r3) : "memory");
}
DEVI uint32_t lds32(uint32_t a) { uint32_t v; asm volatile("ld.shared.b32 %0, [%1];" : "=r"(v) : "r"(a) : "memory"); return v; }
DEVI float lds_f32(uint32_t a) { float v; asm volatile("ld.shared.f32 %0, [%1];" : "=f"(v) : "r"(a) : "memory"); return v; }
DEVI void sts32(uint32_t a, uint32_t v) { asm volatile("st.shared.b32 [%0], %1;" ::"r"(a), "r"(v) : "memory"); }
DEVI void sts_f32(uint32_t a, float v) { asm volatile("st.shared.f32 [%0], %1;" ::"r"(a), "f"(v) : "memory"); }
DEVI void sts_f32x2(uint32_t a, float x, float y) { asm volatile("st.shared.v2.f32 [%0], {%1,%2};" ::"r"(a), "f"(x), "f"(y) : "memory"); }
DEVI uint4 lds128(uint32_t a) {
  uint4 v;
  asm volatile("ld.shared.v4.b32 {%0,%1,%2,%3}, [%4];" : "=r"(v.x), "=r"(v.y), "=r"(v.z), "=r"(v.w) : "r"(a) : "memory");
  return v;
}
DEVI void sts128(uint32_t a, uint32_t x, uint32_t y, uint32_t z, uint32_t w) {
  asm volatile("st.shared.v4.b32 [%0], {%1,%2,%3,%4};" ::"r"(a), "r"(x), "r"(y), "r"(z), "r"(w) : "memory");
}

DEVI void mma_bf16(float (&d)[4], uint32_t a0, uint32_t a1, uint32_t a2, uint32_t a3, uint32_t b0, uint32_t b1) {
  asm("mma.sync.aligned.m16n8k16.row.col.f32.bf16.bf16.f32 {%0,%1,%2,%3}, {%4,%5,%6,%7}, {%8,%9}, {%0,%1,%2,%3};"
      : "+f"(d[0]), "+f"(d[1]), "+f"(d[2]), "+f"(d[3])
      : "r"(a0), "r"(a1), "r"(a2), "r"(a3), "r"(b0), "r"(b1));
}
DEVI void mma_f16(float (&d)[4], const uint32_t (&a)[4], uint32_t b0, uint32_t b1) {
  asm("mma.sync.aligned.m16n8k16.row.col.f32.f16.f16.f32 {%0,%1,%2,%3}, {%4,%5,%6,%7}, {%8,%9}, {%0,%1,%2,%3};"
      : "+f"(d[0]), "+f"(d[1]), "+f"(d[2]), "+f"(d[3])
      : "r"(a[0]), "r"(a[1]), "r"(a[2]), "r"(a[3]), "r"(b0), "r"(b1));
}
DEVI void mma_bf16v(float (&d)[4], const uint32_t (&a)[4], uint32_t b0, uint32_t b1) {
  asm volatile("mma.sync.aligned.m16n8k16.row.col.f32.bf16.bf16.f32 {%0,%1,%2,%3}, {%4,%5,%6,%7}, {%8,%9}, {%0,%1,%2,%3};"
               : "+f"(d[0]), "+f"(d[1]), "+f"(d[2]), "+f"(d[3])
               : "r"(a[0]), "r"(a[1]), "r"(a[2]), "r"(a[3]), "r"(b0), "r"(b1));
}
DEVI uint32_t pack_bf16(float lo, float hi) {
  uint32_t r;
  asm("cvt.rn.bf16x2.f32 %0, %1, %2;" : "=r"(r) : "f"(hi), "f"(lo));
  return r;
}
DEVI uint32_t pack_f16(float lo, float hi) {
  uint32_t r;
  asm("cvt.rn.f16x2.f32 %0, %1, %2;" : "=r"(r) : "f"(hi), "f"(lo));
  return r;
}
DEVI uint32_t ldg16(const __nv_bfloat16* p) {
  uint32_t v;
  asm volatile("ld.global.nc.u16 %0, [%1];" : "=r"(v) : "l"(p));
  return v;
}
DEVI bool elect_one() {
  uint32_t pred;
  asm volatile("{\n.reg .pred p;\nelect.sync _|p, 0xffffffff;\nselp.u32 %0, 1, 0, p;\n}" : "=r"(pred));
  return pred != 0;
}
DEVI float bf_lo(uint32_t v) { return __uint_as_float(v << 16); }
DEVI float bf_hi(uint32_t v) { return __uint_as_float(v & 0xffff0000u); }
DEVI float bf2f(__nv_bfloat16 v) { return __bfloat162float(v); }
DEVI float round_bf16(float v) { return __bfloat162float(__float2bfloat16_rn(v)); }
DEVI float rcp(float x) { float r; asm("rcp.approx.ftz.f32 %0, %1;" : "=f"(r) : "f"(x)); return r; }
DEVI float ex2(float x) { float r; asm("ex2.approx.ftz.f32 %0, %1;" : "=f"(r) : "f"(x)); return r; }

DEVI void wg_fence() { asm volatile("wgmma.fence.sync.aligned;" ::: "memory"); }
DEVI void wg_commit() { asm volatile("wgmma.commit_group.sync.aligned;" ::: "memory"); }
template <int N> DEVI void wg_wait() { asm volatile("wgmma.wait_group.sync.aligned %0;" ::"n"(N) : "memory"); }
constexpr uint32_t DESC_HI = (1u << 30) | (1024 >> 4);
constexpr uint32_t DESC_HI64 = (2u << 30) | (512 >> 4);
DEVI uint32_t mkdesc(uint32_t saddr, uint32_t lbo) { return ((saddr & 0x3FFFF) >> 4) | ((lbo >> 4) << 16); }

#define R8(b) "%" #b
DEVI void wgmma_n192(float (&d)[96], uint32_t da, uint32_t db, int scale_d) {
  asm volatile(
      "{\n.reg .pred p;\n.reg .b64 da, db;\nsetp.ne.b32 p, %98, 0;\nmov.b64 da, {%96, %100};\nmov.b64 db, {%97, %99};\n"
      "wgmma.mma_async.sync.aligned.m64n192k16.f32.bf16.bf16 "
      "{%0,%1,%2,%3,%4,%5,%6,%7,%8,%9,%10,%11,%12,%13,%14,%15,"
      "%16,%17,%18,%19,%20,%21,%22,%23,%24,%25,%26,%27,%28,%29,%30,%31,"
      "%32,%33,%34,%35,%36,%37,%38,%39,%40,%41,%42,%43,%44,%45,%46,%47,"
      "%48,%49,%50,%51,%52,%53,%54,%55,%56,%57,%58,%59,%60,%61,%62,%63,"
      "%64,%65,%66,%67,%68,%69,%70,%71,%72,%73,%74,%75,%76,%77,%78,%79,"
      "%80,%81,%82,%83,%84,%85,%86,%87,%88,%89,%90,%91,%92,%93,%94,%95}, "
      "da, db, p, 1, 1, 0, 1;\n}"
      : "+f"(d[0]), "+f"(d[1]), "+f"(d[2]), "+f"(d[3]), "+f"(d[4]), "+f"(d[5]), "+f"(d[6]), "+f"(d[7]),
        "+f"(d[8]), "+f"(d[9]), "+f"(d[10]), "+f"(d[11]), "+f"(d[12]), "+f"(d[13]), "+f"(d[14]), "+f"(d[15]),
        "+f"(d[16]), "+f"(d[17]), "+f"(d[18]), "+f"(d[19]), "+f"(d[20]), "+f"(d[21]), "+f"(d[22]), "+f"(d[23]),
        "+f"(d[24]), "+f"(d[25]), "+f"(d[26]), "+f"(d[27]), "+f"(d[28]), "+f"(d[29]), "+f"(d[30]), "+f"(d[31]),
        "+f"(d[32]), "+f"(d[33]), "+f"(d[34]), "+f"(d[35]), "+f"(d[36]), "+f"(d[37]), "+f"(d[38]), "+f"(d[39]),
        "+f"(d[40]), "+f"(d[41]), "+f"(d[42]), "+f"(d[43]), "+f"(d[44]), "+f"(d[45]), "+f"(d[46]), "+f"(d[47]),
        "+f"(d[48]), "+f"(d[49]), "+f"(d[50]), "+f"(d[51]), "+f"(d[52]), "+f"(d[53]), "+f"(d[54]), "+f"(d[55]),
        "+f"(d[56]), "+f"(d[57]), "+f"(d[58]), "+f"(d[59]), "+f"(d[60]), "+f"(d[61]), "+f"(d[62]), "+f"(d[63]),
        "+f"(d[64]), "+f"(d[65]), "+f"(d[66]), "+f"(d[67]), "+f"(d[68]), "+f"(d[69]), "+f"(d[70]), "+f"(d[71]),
        "+f"(d[72]), "+f"(d[73]), "+f"(d[74]), "+f"(d[75]), "+f"(d[76]), "+f"(d[77]), "+f"(d[78]), "+f"(d[79]),
        "+f"(d[80]), "+f"(d[81]), "+f"(d[82]), "+f"(d[83]), "+f"(d[84]), "+f"(d[85]), "+f"(d[86]), "+f"(d[87]),
        "+f"(d[88]), "+f"(d[89]), "+f"(d[90]), "+f"(d[91]), "+f"(d[92]), "+f"(d[93]), "+f"(d[94]), "+f"(d[95])
      : "r"(da), "r"(db), "r"(scale_d), "n"(DESC_HI), "n"(DESC_HI64));
}
DEVI void wgmma_n64(float (&d)[32], uint32_t da, uint32_t db, int scale_d) {
  asm volatile(
      "{\n.reg .pred p;\n.reg .b64 da, db;\nsetp.ne.b32 p, %34, 0;\nmov.b64 da, {%32, %35};\nmov.b64 db, {%33, %35};\n"
      "wgmma.mma_async.sync.aligned.m64n64k16.f32.bf16.bf16 "
      "{%0,%1,%2,%3,%4,%5,%6,%7,%8,%9,%10,%11,%12,%13,%14,%15,"
      "%16,%17,%18,%19,%20,%21,%22,%23,%24,%25,%26,%27,%28,%29,%30,%31}, "
      "da, db, p, 1, 1, 0, 1;\n}"
      : "+f"(d[0]), "+f"(d[1]), "+f"(d[2]), "+f"(d[3]), "+f"(d[4]), "+f"(d[5]), "+f"(d[6]), "+f"(d[7]),
        "+f"(d[8]), "+f"(d[9]), "+f"(d[10]), "+f"(d[11]), "+f"(d[12]), "+f"(d[13]), "+f"(d[14]), "+f"(d[15]),
        "+f"(d[16]), "+f"(d[17]), "+f"(d[18]), "+f"(d[19]), "+f"(d[20]), "+f"(d[21]), "+f"(d[22]), "+f"(d[23]),
        "+f"(d[24]), "+f"(d[25]), "+f"(d[26]), "+f"(d[27]), "+f"(d[28]), "+f"(d[29]), "+f"(d[30]), "+f"(d[31])
      : "r"(da), "r"(db), "r"(scale_d), "n"(DESC_HI));
}

struct C32 { float re, im; };
DEVI C32 csq(C32 a) { return {a.re * a.re - a.im * a.im, 2.f * a.re * a.im}; }
DEVI C32 cmul(C32 a, C32 b) { return {a.re * b.re - a.im * b.im, a.re * b.im + a.im * b.re}; }
DEVI C32 cfresh(float zl, float zi, float m) {
  float mag = ex2(zl * m), ph = zi * m;
  return {mag * __cosf(ph), mag * __sinf(ph)};
}
struct HMul { uint32_t b, bp; };
DEVI HMul mk_mul(float re, float im) { return {pack_f16(re, im), pack_f16(-im, re)}; }
DEVI uint32_t hcmul(uint32_t a, const HMul& m) {
  __half2 ah = *reinterpret_cast<__half2*>(&a);
  __half2 b = *reinterpret_cast<const __half2*>(&m.b), bp = *reinterpret_cast<const __half2*>(&m.bp);
  __half2 r = __hfma2(__high2half2(ah), bp, __hmul2(__low2half2(ah), b));
  return *reinterpret_cast<uint32_t*>(&r);
}
DEVI uint32_t badd(uint32_t a, uint32_t b) {
  __nv_bfloat162 r = __hadd2(*reinterpret_cast<__nv_bfloat162*>(&a), *reinterpret_cast<__nv_bfloat162*>(&b));
  return *reinterpret_cast<uint32_t*>(&r);
}
template <int MU0, int NMU, int DMAX>
DEVI void conv_tail(float (&acc)[16][4], uint32_t p_lane, uint32_t v_base, int back, bool edge, int lane) {
  const int hsel = (lane >> 3) & 1;
  const int row = (lane & 7) + ((lane >> 4) << 3) + PADV - 8 - (back & (hsel ^ 1));
  const uint32_t la = v_base + row * 32 + (((hsel ^ back) ^ ((row >> 2) & 1)) << 4);
  uint32_t M[3][4];
  ldsm_x4_t(M[0], la);
  ldsm_x4_t(M[1], la + 256);
  uint32_t H[2 * NMU];
#pragma unroll
  for (int i = 0; i < 2 * NMU; ++i) H[i ^ 1] = lds32(p_lane + (uint32_t)(MU0 - 1 + i) * 32);
  if (edge) {
    const uint32_t a[4] = {0u, 0u, M[0][0], M[0][1]};
#pragma unroll
    for (int k = 1; k < NMU; ++k) mma_bf16v(acc[MU0 - 2 + 2 * k], a, H[2 * k], H[2 * k + 1]);
  }
#pragma unroll
  for (int delta = -1; delta <= DMAX; ++delta) {
    if (delta + 2 <= DMAX) ldsm_x4_t(M[(delta + 3) % 3], la + (delta + 3) * 256);
#pragma unroll
    for (int k = 0; k < NMU; ++k)
      if (delta + MU0 + 2 * k < 16) mma_bf16v(acc[delta + MU0 + 2 * k], M[(delta + 1) % 3], H[2 * k], H[2 * k + 1]);
  }
}

template <int NB>
DEVI void box_filters(uint32_t sb, uint32_t bars, int idx, int lane) {
  auto swz = [](int k, int pad) { const int r = (k >> 1) + pad; return (uint32_t)(r * 32 + (((k & 1) ^ ((r >> 2) & 1)) << 4)); };
  const uint32_t o0 = swz(lane - 3, 8), o1 = swz(lane - 2, 8), o2 = swz(lane - 1, 8), ow = swz(lane - 2, PADV), oz = swz(lane - 18, PADV);
  const int k = 32 * idx - 2 + lane;
#pragma unroll 1
  for (int c2 = 0; c2 < 4; c2 += NB) {
    uint4 t[NB][3];
#pragma unroll
    for (int b = 0; b < NB; ++b) mbar_wait_long(bars + 8 * (B_UCH + c2 + b), 0);
#pragma unroll
    for (int b = 0; b < NB; ++b) {
      const uint32_t ua = sb + SM_U + (c2 + b) * U_BYTES + idx * 512;
      t[b][0] = lds128(ua + o0); t[b][1] = lds128(ua + o1); t[b][2] = lds128(ua + o2);
    }
#pragma unroll
    for (int b = 0; b < NB; ++b) {
      const uint32_t vb = sb + SM_VV + (c2 + b) * VV_BYTES, aw = vb + idx * 512 + ow;
      const uint32_t E[12] = {t[b][0].x, t[b][0].y, t[b][0].z, t[b][0].w, t[b][1].x, t[b][1].y, t[b][1].z, t[b][1].w,
                              t[b][2].x, t[b][2].y, t[b][2].z, t[b][2].w};
      uint32_t O[8];
#pragma unroll
      for (int j = 0; j < 8; ++j) O[j] = __byte_perm(E[j + 1], E[j + 2], 0x5432);
      uint32_t s3[6], s5[4], s7[4], s9[4];
#pragma unroll
      for (int j = 0; j < 6; ++j) s3[j] = badd(badd(O[j], O[j + 1]), E[j + 2]);
#pragma unroll
      for (int j = 0; j < 4; ++j) {
        s5[j] = badd(s3[j + 2], badd(E[j + 3], E[j + 5]));
        s7[j] = badd(s5[j], badd(O[j + 1], O[j + 4]));
        s9[j] = badd(s7[j], badd(E[j + 2], E[j + 6]));
      }
      if (k < 208) { sts128(aw + VV_U3, s3[0], s3[1], s3[2], s3[3]); sts128(aw + VV_U5, s5[0], s5[1], s5[2], s5[3]); }
      if (k < 144) { sts128(aw + VV_U7, s7[0], s7[1], s7[2], s7[3]); sts128(aw + VV_U9, s9[0], s9[1], s9[2], s9[3]); }
      if (idx == 0 && lane < 16) {
        sts128(vb + oz + VV_U3, 0, 0, 0, 0); sts128(vb + oz + VV_U5, 0, 0, 0, 0);
        sts128(vb + oz + VV_U7, 0, 0, 0, 0); sts128(vb + oz + VV_U9, 0, 0, 0, 0);
      }
    }
  }
}

__global__ void __cluster_dims__(2, 1, 1) __launch_bounds__(NTHREADS, 1)
fused_kernel(const __grid_constant__ Maps maps, const Ptrs p) {
  extern __shared__ __align__(1024) uint8_t smem[];
  const uint32_t sb = s2u(smem);
  const int tid = threadIdx.x, lane = tid & 31;
  const int warp = __shfl_sync(0xffffffffu, tid >> 5, 0);
  const int cta = blockIdx.x;
  const uint32_t rank = cta & 1;
  const int ti = 2 * (cta >> 4) + rank;
  const int tj = (cta >> 1) & 7;
  const int pi = cta >> 3, pj = cta & 7;
  const uint32_t bars = sb + SM_BAR;
#define BAR(i) (bars + 8 * (i))
  const int g = lane >> 2, q = lane & 3;

  auto issue_stage = [&](int ks, int s) {
    const uint32_t st = sb + s * STG_BYTES, fb = BAR(B_FULL + s);
    mbar_expect_tx(fb, STG_BYTES);
    tma_load_2d(st + STG_X, &maps.x, ks * 32, ti * 128, fb);
    tma_load_3d_mc(st + STG_W + rank * 6144, &maps.w, tj * 64, ks * 32 + rank * 16, 0, fb, 3);
  };

  const int kch = warp & 3, krd = warp >> 2;
  float zr, zi, wr, wi;
  unsigned epoch;
  uint32_t r_dskip;
  {
    const size_t po = (size_t)(cta * 4 + kch) * 128 + krd * 32 + lane;
    const uint32_t r_ar = ldg16(p.A_re + po), r_ai = ldg16(p.A_im + po), r_br = ldg16(p.B_re + po), r_bi = ldg16(p.B_im + po);
    const uint32_t r_cr = ldg16(p.C_re + po), r_ci = ldg16(p.C_im + po), r_ldt = ldg16(p.log_dt + cta * 4 + kch);
    epoch = __ldcg(&g_epoch);
    r_dskip = ldg16(p.Dskip + cta * 4 + kch);
    uint4 pt;
    if (tid < 128) pt = __ldg((const uint4*)g_ptab.v + tid);
    if (tid == 384) {
      TS(0);
#pragma unroll
      for (int i = 0; i < B_COUNT; ++i) mbar_init(BAR(i), bar_count(i));
      asm volatile("fence.mbarrier_init.release.cluster;" ::: "memory");
      prefetch_tmap(&maps.x); prefetch_tmap(&maps.w); prefetch_tmap(&maps.u);
    }
    __syncthreads();
    cluster_arrive();
    if (warp >= 12) {
      cluster_wait();
      if (elect_one()) {
        if (warp == 13) {
          mbar_expect_tx(BAR(B_TILE), 16384);
          tma_load_2d(sb + SM_U, &maps.u, tj * 64, ti * 128, BAR(B_TILE));
          prefetch_tmap(&maps.uT); prefetch_tmap(&maps.wo); prefetch_tmap(&maps.o); prefetch_tmap(&maps.yT);
          prefetch_tmap(&maps.out);
        } else {
          if (warp == 12) TS(61);
          { const int ks = warp == 12 ? 0 : warp - 13; issue_stage(ks, ks); }
        }
      }
      __syncwarp();
    }
    if (tid < 128) sts128(sb + SM_PTAB + tid * 16, pt.x, pt.y, pt.z, pt.w);
    const float dt = round_bf16(expf(bf_lo(r_ldt)));
    zr = dt * bf_lo(r_ar); zi = dt * bf_lo(r_ai);
    const float dbr = dt * bf_lo(r_br), dbi = dt * bf_lo(r_bi), cr = bf_lo(r_cr), ci = bf_lo(r_ci);
    wr = cr * dbr - ci * dbi; wi = cr * dbi + ci * dbr;
  }
  {
    const float mz = __uint_as_float(__reduce_max_sync(0xffffffffu, __float_as_uint(fmaxf(zr, 0.f))));
    const int E = min(max((int)(__reduce_max_sync(0xffffffffu, __float_as_uint(fmaxf(fabsf(wr), fabsf(wi)))) >> 23), 1), 252);
    const float sc = __int_as_float((253 - E) << 23), inv = __int_as_float((E + 1) << 23);
    const float zl = (zr - mz) * 1.4426950408889634f;
    const uint32_t tb = sb + SM_VV + kch * VV_BYTES + krd * KG_BYTES;
    const uint32_t sta = tb + (((lane >> 2) << 4) | ((lane & 3) << 2));
    auto put = [&](int r, uint32_t v) { sts32((sta ^ ((r & 7) << 4)) + r * 128, v); };
    const uint32_t lda = tb + ((lane & 7) + (((lane >> 3) & 1) << 3)) * 128;
    const uint32_t ldb = tb + ((lane & 7) + ((lane >> 4) << 3)) * 128;
    C32 e1 = cfresh(zl, zi, 1.f), e2 = csq(e1), e4 = csq(e2), e8 = csq(e4);
    C32 e16 = cfresh(zl, zi, 16.f), e32 = csq(e16), e64 = csq(e32), e128 = csq(e64);
    C32 e256 = cfresh(zl, zi, 256.f), e512 = csq(e256), e1024 = csq(e512), e768 = cmul(e512, e256);
    uint32_t XA[2][4][4];
    {
      const HMul m16 = mk_mul(e16.re, e16.im), m32 = mk_mul(e32.re, e32.im), m64 = mk_mul(e64.re, e64.im);
      const HMul m128 = mk_mul(e128.re, e128.im);
      uint32_t X[16];
      X[0] = 0x00003c00u; X[1] = pack_f16(e8.re, e8.im); X[2] = m16.b; X[4] = m32.b; X[8] = m64.b;
      X[3] = hcmul(X[1], m16); X[5] = hcmul(X[1], m32); X[6] = hcmul(X[2], m32); X[7] = hcmul(X[3], m32);
#pragma unroll
      for (int r = 1; r < 8; ++r) X[8 + r] = hcmul(X[r], m64);
#pragma unroll
      for (int h = 0; h < 2; ++h) {
#pragma unroll
        for (int r = 0; r < 16; ++r) put(r, h == 0 ? X[r] : r == 0 ? m128.b : hcmul(X[r], m128));
        __syncwarp();
#pragma unroll
        for (int k = 0; k < 4; ++k) ldsm_x4(XA[h][k], lda + (((2 * k + (lane >> 4)) ^ (lane & 7)) << 4));
        __syncwarp();
      }
    }
    if (warp >= 14 && elect_one()) {
      issue_stage(warp - 11, warp - 11);
      issue_stage(warp - 9, warp - 9);
      if (warp == 14) l2_prefetch((const char*)p.wqkv + 224 * 3072 + cta * 6912, 6912);
      else l2_prefetch((const char*)p.x + (size_t)cta * 16384, 16384);
    }
    __syncwarp();
    float D[2][3][4];
#pragma unroll
    for (int t = 0; t < 6; ++t) D[t / 3][t % 3][0] = D[t / 3][t % 3][1] = D[t / 3][t % 3][2] = D[t / 3][t % 3][3] = 0.f;
    auto contract = [&](int t0, int nt) {
      __syncwarp();
#pragma unroll
      for (int k = 0; k < 4; ++k) {
        uint32_t b[4];
        ldsm_x4(b, ldb + (((2 * k + ((lane >> 3) & 1)) ^ (lane & 7)) << 4));
#pragma unroll
        for (int h = 0; h < 2; ++h) {
          mma_f16(D[h][t0], XA[h][k], b[0], b[1]);
          if (nt == 2) mma_f16(D[h][t0 + 1], XA[h][k], b[2], b[3]);
        }
      }
      __syncwarp();
    };
    const HMul c1 = mk_mul(e1.re, -e1.im), c2 = mk_mul(e2.re, -e2.im), c4 = mk_mul(e4.re, -e4.im);
    const HMul c256 = mk_mul(e256.re, -e256.im), c512 = mk_mul(e512.re, -e512.im), c768 = mk_mul(e768.re, -e768.im);
    const HMul c1024 = mk_mul(e1024.re, -e1024.im);
    uint32_t W[8];
    W[0] = pack_f16(wr * sc, -wi * sc);
    W[1] = hcmul(W[0], c1); W[2] = hcmul(W[0], c2); W[3] = hcmul(W[1], c2);
    W[4] = hcmul(W[0], c4); W[5] = hcmul(W[1], c4); W[6] = hcmul(W[2], c4); W[7] = hcmul(W[3], c4);
#pragma unroll
    for (int i = 0; i < 8; ++i) put(i, W[i]);
#pragma unroll
    for (int i = 0; i < 4; ++i) put(8 + i, hcmul(W[2 * i], c256));
    put(12, hcmul(W[0], c512)); put(13, hcmul(W[4], c512)); put(14, hcmul(W[0], c768)); put(15, hcmul(W[4], c768));
    contract(0, 2);
    const uint32_t v0 = hcmul(W[0], c1024);
    put(0, v0); put(1, hcmul(v0, c256)); put(2, hcmul(v0, c512)); put(3, hcmul(v0, c768)); put(4, hcmul(v0, c1024));
    contract(2, 1);
    const uint32_t a = tb + (g * 24 + 2 * q) * 4;
#pragma unroll
    for (int t = 0; t < 6; ++t) {
      const float(&d)[4] = D[t / 3][t % 3];
      sts_f32x2(a + (t / 3) * 1536 + (t % 3) * 32, d[0] * inv, d[1] * inv);
      sts_f32x2(a + (t / 3) * 1536 + (t % 3) * 32 + 768, d[2] * inv, d[3] * inv);
    }
    if (mz > 0.f) {
      __syncwarp();
#pragma unroll 1
      for (int i = lane; i < 768; i += 32) {
        const int r = i / 24, y = i - 24 * r;
        sts_f32(tb + i * 4, lds_f32(tb + i * 4) * ex2(mz * 1.4426950408889634f * (koff(y) + 8 * r)));
      }
    }
  }
  if (tid == 0) TS(2);
  if (warp < 12) cluster_wait();
  __syncthreads();

  if (warp < 4) {
#define A_REGS 200
    asm volatile("setmaxnreg.inc.sync.aligned.u32 %0;" ::"n"(A_REGS));
    if (tid == 0) TS(34);
    const int d = cta * 4 + warp;
    const uint32_t vv = sb + SM_VV + warp * VV_BYTES;
    const uint32_t ub = sb + SM_U + warp * U_BYTES;
    const uint32_t pb = sb + SM_P + warp * P_BYTES;
    const float dskip = bf_lo(r_dskip);
#pragma unroll 1
    for (int pass = 0; pass < 2; ++pass) {
      if (pass == 1) {
        const uint32_t kf = vv;
#pragma unroll 2
        for (int i = 0; i < 6; ++i) {
          const uint32_t a = kf + (i * 32 + lane) * 16;
          const uint4 x0 = lds128(a), x1 = lds128(a + KG_BYTES), x2 = lds128(a + 2 * KG_BYTES), x3 = lds128(a + 3 * KG_BYTES);
          auto s4 = [](uint32_t a0, uint32_t a1, uint32_t a2, uint32_t a3) {
            return __float_as_uint((__uint_as_float(a0) + __uint_as_float(a1)) + (__uint_as_float(a2) + __uint_as_float(a3)));
          };
          sts128(a, s4(x0.x, x1.x, x2.x, x3.x), s4(x0.y, x1.y, x2.y, x3.y), s4(x0.z, x1.z, x2.z, x3.z), s4(x0.w, x1.w, x2.w, x3.w));
        }
        __syncwarp();
        const float k1024 = lds_f32(kf + kidx_c(1024) * 4);
        if (lane == 0) {
          sts_f32(kf + SL_ZERO * 4, 0.f);
          sts_f32(kf + SL_510 * 4, lds_f32(kf + kidx_c(510) * 4) - lds_f32(kf + kidx_c(512) * 4));
          sts_f32(kf + SL_0 * 4, lds_f32(kf) + dskip);
        }
        __syncwarp();
        if (tid == 0) TS(36);
        mbar_wait_long(BAR(B_PFREE), 0);
        if (tid == 0) TS(37);
        {
          float prev = 0.f;
#pragma unroll 1
          for (int i0 = 0; i0 < 16; i0 += 4) {
            uint32_t e[4];
            float a[4], b[4];
#pragma unroll
            for (int i = 0; i < 4; ++i) e[i] = lds32(sb + SM_PTAB + ((i0 + i) * 32 + lane) * 4);
#pragma unroll
            for (int i = 0; i < 4; ++i) { a[i] = lds_f32(kf + (e[i] & 0xffff)); b[i] = lds_f32(kf + (e[i] >> 16)); }
#pragma unroll
            for (int i = 0; i < 4; ++i) {
              const uint32_t w = pb + (31 * lane + 2 * (i0 + i)) * 4;
              if (i0 + i > 0) sts32(w - 4, pack_bf16(a[i], prev));
              sts32(w, pack_bf16(b[i], a[i]));
              prev = b[i];
            }
          }
        }
        __syncwarp();
        if (lane == 0) TS(4);
        const int gq = g - 2 * q;
        uint32_t h127, h128;
        {
          const uint32_t kf2 = pack_bf16(k1024, k1024) ^ 0x80008000u;
          h127 = (gq == 4 ? 0x0000ffffu : gq == 5 ? 0xffffffffu : gq == 6 ? 0xffff0000u : 0u) & kf2;
          h128 = (gq == -4 ? 0x0000ffffu : gq == -3 ? 0xffffffffu : gq == -2 ? 0xffff0000u : 0u) & kf2;
        }
        bar_sync(7, 128);
#pragma unroll 1
        for (int idx = warp; idx < 7; idx += 4) box_filters<4>(sb, bars, idx, lane);
        bar_sync(5, 128);
        if (lane == 0) TS(6);
        bar_sync(4, 384);
        if (lane == 0) TS(7);
        float acc[16][4];
#pragma unroll
        for (int i = 0; i < 16; ++i) { acc[i][0] = acc[i][1] = acc[i][2] = acc[i][3] = 0.f; }
        {
          const uint32_t pd_lane = pb + (PD_OFF + 16 + gq) * 4;
          const int prow0 = 8 + (lane & 7) + ((lane >> 4) << 3), hs = (lane >> 3) & 1;
          const uint32_t zero = (uint32_t)cta >> 20;
          uint32_t B[2][4][4];
          uint32_t A[4][4];
          const uint32_t la0 = ub + prow0 * 32 + ((hs ^ ((prow0 >> 2) & 1)) << 4);
#pragma unroll
          for (int m2 = 0; m2 < 4; ++m2) ldsm_x4(B[0][m2], la0 + m2 * 512);
#pragma unroll
          for (int i = 0; i < 4; ++i) {
            const uint32_t a = pd_lane + i * 512;
            A[i][0] = lds32(a); A[i][1] = lds32(a + 32); A[i][2] = lds32(a - 32); A[i][3] = lds32(a + zero);
          }
          uint32_t la = la0;
#define UNR_RHO 8
#define UNR_TAIL 2
          constexpr int unr_rho = UNR_RHO, unr_tail = UNR_TAIL;
#pragma unroll unr_rho
          for (int rho = 0; rho < 8; ++rho) {
#pragma unroll
            for (int m2 = 0; m2 < 4; ++m2) ldsm_x4(B[1][m2], la + (4 + m2) * 512);
#pragma unroll
            for (int i = 0; i < 4; ++i)
#pragma unroll
              for (int m = 0; m < 8; ++m) mma_bf16v(acc[m + i], A[i], B[0][m >> 1][2 * (m & 1)], B[0][m >> 1][2 * (m & 1) + 1]);
            const int prow = prow0 - min(rho + 1, 7);
            la = ub + prow * 32 + ((hs ^ ((prow >> 2) & 1)) << 4);
#pragma unroll
            for (int m2 = 0; m2 < 4; ++m2) ldsm_x4(B[0][m2], la + m2 * 512);
            const uint32_t pa = pd_lane + (rho + 1) * 64;
#pragma unroll
            for (int i = 0; i < 4; ++i) {
#pragma unroll
              for (int m = 0; m < 8 - i; ++m)
                mma_bf16v(acc[8 + m + i], A[i], B[1][m >> 1][2 * (m & 1)], B[1][m >> 1][2 * (m & 1) + 1]);
              A[i][0] = lds32(pa + i * 512); A[i][1] = lds32(pa + i * 512 + 32); A[i][2] = lds32(pa + i * 512 - 32);
              A[i][3] = lds32(pa + i * 512 + zero);
            }
          }
          if (lane == 0) TS(40);
          {
            uint32_t b8[4];
            ldsm_x4(b8, la + 4 * 512);
            const uint32_t h63 = lds32(pd_lane + 63 * 32), h64 = lds32(pd_lane + 64 * 32);
            const uint32_t a63[4] = {0u, h127, 0u, 0u}, a32[4] = {h64, 0u, h63, h64}, a64[4] = {h128, 0u, h127, h128};
#pragma unroll
            for (int m2 = 0; m2 < 4; ++m2) ldsm_x4(B[1][m2], la0 + m2 * 512);
#pragma unroll
            for (int m = 0; m < 8; ++m) mma_bf16v(acc[m + 7], a63, B[0][m >> 1][2 * (m & 1)], B[0][m >> 1][2 * (m & 1) + 1]);
#pragma unroll
            for (int m2 = 0; m2 < 2; ++m2) ldsm_x4(B[0][m2], la0 + (4 + m2) * 512);
#pragma unroll
            for (int m = 0; m < 8; ++m) mma_bf16v(acc[m + 4], a32, B[1][m >> 1][2 * (m & 1)], B[1][m >> 1][2 * (m & 1) + 1]);
            mma_bf16v(acc[15], a63, b8[0], b8[1]);
#pragma unroll
            for (int m = 0; m < 8; ++m) mma_bf16v(acc[m + 8], a64, B[1][m >> 1][2 * (m & 1)], B[1][m >> 1][2 * (m & 1) + 1]);
#pragma unroll
            for (int m = 0; m < 4; ++m) mma_bf16v(acc[m + 12], a32, B[0][m >> 1][2 * (m & 1)], B[0][m >> 1][2 * (m & 1) + 1]);
          }
          if (lane == 0) TS(41);
#pragma unroll unr_tail
          for (int v = 0; v < 4; ++v)
            conv_tail<4, 3, 11>(acc, pb + (P2_OFF + 56 * v + gq - 16) * 4, vv + ((v & 1) ? VV_U3 : VV_U5), v >> 1, v == 0, lane);
          if (lane == 0) TS(42);
#pragma unroll unr_tail
          for (int pi = 0; pi < 2; ++pi)
            conv_tail<8, 5, 7>(acc, pb + (P3_OFF + 88 * pi + gq - 48) * 4, vv + (pi ? VV_U7 : VV_U9), pi, pi == 0, lane);
        }
        if (lane == 0) TS(8);
        __syncwarp();
        {
          const int mt = lane >> 3;
          const uint32_t a = pb + (128 * (mt >> 1) + 16 * (lane & 7) + 8 * (mt & 1)) * 2;
#pragma unroll
          for (int ab = 0; ab < 16; ab += 2)
            stsm_x4_t(a + ab * 256, pack_bf16(acc[ab][0], acc[ab][1]), pack_bf16(acc[ab][2], acc[ab][3]),
                      pack_bf16(acc[ab + 1][0], acc[ab + 1][1]), pack_bf16(acc[ab + 1][2], acc[ab + 1][3]));
        }
        fence_async_smem();
        __syncwarp();
        if (lane < 2) mbar_arrive_cluster(BAR(B_CONVD), lane);
        bar_arrive(3, 384);
        if (elect_one()) {
          bulk_store(p.yT + (size_t)d * 2048, pb, 4096);
          bulk_commit();
          bulk_wait0();
          red_relaxed_add(&g_cnt[(C_Y + (cta >> 4)) * 32], 1);
          TS(9);
        }
        bar_sync(2, 128);
        if (warp == 0 && elect_one()) {
          wait_counter(&g_cnt[(C_Y + tj) * 32], (epoch + 1) * 64);
          TS(28);
          mbar_expect_tx(BAR(B_TILE), 16384);
          tma_load_2d(sb + SM_U, &maps.yT, ti * 128, tj * 64, BAR(B_TILE));
          tma_load_2d(sb + SM_U + 8192, &maps.yT, ti * 128 + 64, tj * 64, BAR(B_TILE));
        }
        __syncwarp();
      }
      mbar_wait_long(BAR(B_TILE), pass);
      if (lane == 0) TS(26 + 3 * pass);
      {
        const int m = lane >> 3, r = lane & 7;
#pragma unroll 2
        for (int it = 0; it < 8; ++it) {
          const int tb = warp * 4 + (it >> 1), cb = (it & 1) * 4 + m;
          const uint32_t at = (tb * 8 + r) * 128 + ((cb ^ r) << 4);
          const uint32_t ac = (tb >> 3) * 8192 + (cb * 8 + r) * 128 + (((tb & 7) ^ (pass ? 0 : tb >> 3) ^ r) << 4);
          uint32_t v[4];
          ldsm_x4_t(v, sb + SM_U + (pass ? ac : at));
          stsm_x4(sb + SM_P + (pass ? at : ac), v[0], v[1], v[2], v[3]);
        }
      }
      if (pass == 0 && tid == 0) TS(35);
      fence_async_smem();
      if (pass == 0) {
        bar_arrive(6, 160);
      } else {
        bar_sync(2, 128);
        if (warp == 0 && elect_one()) {
          tma_store_2d(&maps.out, sb + SM_P, 64 * tj, 128 * ti);
          bulk_commit();
          bulk_wait_read0();
          TS(30);
        }
      }
    }
  } else if (warp < 12) {
    const int w8 = warp - 4;
    const int row = w8 * 16 + (lane & 7) + (((lane >> 3) & 1) << 3);
    uint32_t pq[16];
    {
      float acc[96];
#pragma unroll 1
      for (int ks = 0, s = 0, ph = 0; ks < 16; ++ks) {
        mbar_wait(BAR(B_FULL + s), ph);
        if (tid == 128 && !(ks & 1)) TSR(16, ks == 0 ? 16 : 9 + (ks >> 1) + (ks > 12 ? 43 : 0));
        const uint32_t st = sb + s * STG_BYTES;
        const uint32_t da = mkdesc(st + STG_X + (w8 >> 2) * 4096, 16);
        const uint32_t db = mkdesc(st + STG_W, 2048);
        wg_fence();
        wgmma_n192(acc, da, db, ks != 0);
        wgmma_n192(acc, da + 2, db + 384, 1);
        wg_commit();
        const uint32_t eprev = BAR(B_EMPTY + (s == 0 ? NSTG - 1 : s - 1));
        if (++s == NSTG) { s = 0; ph ^= 1; }
        if (ks > 0) {
          wg_wait<1>();
          if (lane < 2) mbar_arrive_cluster(eprev, lane);
        }
      }
      wg_wait<0>();
      if (tid == 128) TS(17);
      auto phi2 = [](float a, float b) -> uint32_t {
        const uint32_t x = pack_bf16(a, b);
        const uint32_t e = pack_bf16(ex2(bf_lo(x) * 1.4426950408889634f), ex2(bf_hi(x) * 1.4426950408889634f));
        const uint32_t m = __hgt2_mask(*reinterpret_cast<const __nv_bfloat162*>(&x), __floats2bfloat162_rn(0.f, 0.f));
        return badd((badd(x, 0x3f803f80u) & m) | (e & ~m), 0x35863586u);
      };
      uint32_t pk[16];
#pragma unroll
      for (int i = 0; i < 16; ++i) pk[i] = phi2(acc[32 + 2 * i], acc[33 + 2 * i]);
      if (tid == 128) TS(53);
      bar_sync(1, 256);
#pragma unroll
      for (int i = 0; i < 8; i += 2) {
        const uint32_t off = row * 128 + (((i + (lane >> 4)) ^ (row & 7)) << 4);
        stsm_x4(sb + SM_PK + off, pk[2 * i], pk[2 * i + 1], pk[2 * i + 2], pk[2 * i + 3]);
        stsm_x4(sb + SM_VS + off, pack_bf16(acc[64 + 4 * i], acc[65 + 4 * i]), pack_bf16(acc[66 + 4 * i], acc[67 + 4 * i]),
                pack_bf16(acc[68 + 4 * i], acc[69 + 4 * i]), pack_bf16(acc[70 + 4 * i], acc[71 + 4 * i]));
      }
      bar_sync(1, 256);
      {
        const int hh = w8 >> 1, dtile = w8 & 1;
        float kv[2][4] = {{0.f, 0.f, 0.f, 0.f}, {0.f, 0.f, 0.f, 0.f}}, zz[2][4] = {{0.f, 0.f, 0.f, 0.f}, {0.f, 0.f, 0.f, 0.f}};
        const int m = lane >> 3;
        const uint32_t aa = sb + SM_VS + ((lane & 7) + ((m >> 1) << 3)) * 128 + (((2 * hh + (m & 1)) ^ (lane & 7)) << 4);
        const uint32_t ab = sb + SM_PK + (lane & 15) * 128 + (((2 * hh + dtile) ^ (lane & 7)) << 4);
#pragma unroll
        for (int ks = 0; ks < 8; ++ks) {
          uint32_t a[4], b0, b1;
          ldsm_x4_t(a, aa + ks * 2048);
          ldsm_x2_t(b0, b1, ab + ks * 2048);
          mma_bf16(kv[ks & 1], a[0], a[1], a[2], a[3], b0, b1);
          mma_bf16(zz[ks & 1], 0x3f803f80u, 0x3f803f80u, 0x3f803f80u, 0x3f803f80u, b0, b1);
        }
        const uint32_t kp = sb + SM_KV + hh * 1088;
        sts128(kp + dtile * 512 + lane * 16, __float_as_uint(kv[0][0] + kv[1][0]), __float_as_uint(kv[0][1] + kv[1][1]),
               __float_as_uint(kv[0][2] + kv[1][2]), __float_as_uint(kv[0][3] + kv[1][3]));
        if (g == 0) sts_f32x2(kp + 1024 + dtile * 32 + q * 8, zz[0][0] + zz[1][0], zz[0][1] + zz[1][1]);
        fence_async_smem();
        __syncwarp();
        if (lane == 0) mbar_arrive(BAR(B_KVP));
        bar_arrive(4, 384);
        if (tid == 128) TS(55);
      }
#pragma unroll
      for (int i = 0; i < 16; ++i) pq[i] = phi2(acc[2 * i], acc[2 * i + 1]);
    }
    if (tid == 128) TS(56);
    if (warp == 4) mbar_wait_long(BAR(B_KVF), 0);
    bar_sync(1, 256);
    if (tid == 128) TS(19);
    {
      uint32_t kb[4][6];
#pragma unroll
      for (int h = 0; h < 4; ++h) {
        const uint32_t kp = sb + SM_KV + h * 1088;
        const uint4 k0 = lds128(kp + lane * 16), k1 = lds128(kp + 512 + lane * 16);
        const uint32_t za = kp + 1024 + q * 8;
        auto pk2 = [](uint32_t x, uint32_t y) { return pack_bf16(__uint_as_float(x), __uint_as_float(y)); };
        kb[h][0] = pk2(k0.x, k0.y); kb[h][1] = pk2(k1.x, k1.y); kb[h][2] = pk2(k0.z, k0.w); kb[h][3] = pk2(k1.z, k1.w);
        kb[h][4] = pack_bf16(lds_f32(za), lds_f32(za + 4)); kb[h][5] = pack_bf16(lds_f32(za + 32), lds_f32(za + 36));
      }
#pragma unroll
      for (int h = 0; h < 4; ++h) {
        float n0[4] = {0.f, 0.f, 0.f, 0.f}, n1[4] = {0.f, 0.f, 0.f, 0.f}, dn[4] = {0.f, 0.f, 0.f, 0.f};
        mma_bf16(n0, pq[4 * h], pq[4 * h + 1], pq[4 * h + 2], pq[4 * h + 3], kb[h][0], kb[h][1]);
        mma_bf16(n1, pq[4 * h], pq[4 * h + 1], pq[4 * h + 2], pq[4 * h + 3], kb[h][2], kb[h][3]);
        mma_bf16(dn, pq[4 * h], pq[4 * h + 1], pq[4 * h + 2], pq[4 * h + 3], kb[h][4], kb[h][5]);
        const uint32_t dd = pack_bf16(dn[0], dn[2]);
        const uint32_t d2 = pack_bf16(bf_lo(dd) + 1e-6f, bf_hi(dd) + 1e-6f);
        const float r0 = rcp(bf_lo(d2)), r1 = rcp(bf_hi(d2));
        const uint32_t x0 = pack_bf16(n0[0], n0[1]), x1 = pack_bf16(n0[2], n0[3]);
        const uint32_t x2 = pack_bf16(n1[0], n1[1]), x3 = pack_bf16(n1[2], n1[3]);
        stsm_x4(sb + SM_QS + row * 128 + (((2 * h + (lane >> 4)) ^ (row & 7)) << 4),
                pack_bf16(bf_lo(x0) * r0, bf_hi(x0) * r0), pack_bf16(bf_lo(x1) * r1, bf_hi(x1) * r1),
                pack_bf16(bf_lo(x2) * r0, bf_hi(x2) * r0), pack_bf16(bf_lo(x3) * r1, bf_hi(x3) * r1));
      }
    }
    fence_async_smem();
    __syncwarp();
    if (lane == 0) mbar_arrive(BAR(B_OST));
    if (tid == 128) TS(57);
    if (warp == 4) mbar_wait_long(BAR(B_WO), 0);
    bar_sync(3, 384);
    {
      float o[32];
#pragma unroll 1
      for (int c = 0; c < 8; ++c) {
        mbar_wait_long(BAR(B_RF + c), 0);
        if (tid == 128) TSR(22, c == 0 ? 22 : 43 + c);
        const uint32_t slot = c < 4 ? SM_QS + c * 16384 : c < 7 ? SM_VV + (c - 4) * 16384 : SM_QS;
        const uint32_t da = mkdesc(sb + slot + (w8 >> 2) * 8192, 16);
        const uint32_t db = mkdesc(sb + SM_WO + c * 8192, 8192);
        wg_fence();
#pragma unroll
        for (int k = 0; k < 4; ++k) wgmma_n64(o, da + 2 * k, db + 128 * k, (c | k) != 0);
        wg_commit();
        if (c == 1) {
          wg_wait<1>();
          if (lane < 2) mbar_arrive_cluster(BAR(B_RE), lane);
        }
      }
      wg_wait<0>();
      if (tid == 128) TS(51);
      bar_sync(1, 256);
#pragma unroll
      for (int i = 0; i < 8; i += 2)
        stsm_x4(sb + SM_BOUT + row * 128 + (((i + (lane >> 4)) ^ (row & 7)) << 4), pack_bf16(o[4 * i], o[4 * i + 1]),
                pack_bf16(o[4 * i + 2], o[4 * i + 3]), pack_bf16(o[4 * i + 4], o[4 * i + 5]), pack_bf16(o[4 * i + 6], o[4 * i + 7]));
      fence_async_smem();
      bar_sync(1, 256);
      if (tid == 128) TS(52);
      if (warp == 4 && elect_one()) {
        tma_store_2d(&maps.out, sb + SM_BOUT, 512 + 64 * pj, 128 * pi);
        bulk_commit();
        bulk_wait_read0();
        TS(23);
      }
    }
  } else {
    asm volatile("setmaxnreg.dec.sync.aligned.u32 40;");
    if (warp == 12) {
      if (elect_one()) {
#pragma unroll 1
        for (int ks = NSTG, s = 0, ph = 0; ks < 16; ++ks) {
          mbar_wait(BAR(B_EMPTY + s), ph);
          issue_stage(ks, s);
          if (ks == NSTG) l2_prefetch((const char*)p.wo + (size_t)cta * 4096, 4096);
          if (++s == NSTG) { s = 0; ph ^= 1; }
        }
        mbar_wait(BAR(B_EMPTY + 6), 1);
        mbar_expect_tx(BAR(B_WO), 65536);
        tma_load_2d(sb + SM_WO, &maps.wo, pj * 64, 0, BAR(B_WO));
        tma_load_2d(sb + SM_WO + 32768, &maps.wo, pj * 64, 256, BAR(B_WO));
        float* kvg = &g_kv[epoch & 1][tj][0];
        mbar_wait_long(BAR(B_KVP), 0);
        bulk_reduce_add_f32(kvg, sb + SM_KV, 4352);
        bulk_commit();
        bulk_wait0();
        red_relaxed_add(&g_cnt[(C_KV + tj) * 32], 1);
        TS(18);
        wait_counter(&g_cnt[(C_KV + tj) * 32], (epoch + 1) * 16);
        mbar_expect_tx(BAR(B_KVF), 4352);
        bulk_load(sb + SM_KV, kvg, 4352, BAR(B_KVF));
        mbar_wait_long(BAR(B_OST), 0);
        tma_store_2d(&maps.o, sb + SM_QS, tj * 64, ti * 128);
        tma_store_2d(&maps.o, sb + SM_QS + 8192, tj * 64, ti * 128 + 64);
        bulk_commit();
        bulk_wait0();
        red_relaxed_add(&g_cnt[(C_O + ti) * 32], 1);
        TS(20);
        mbar_arrive_cluster(BAR(B_SLOT), 0);
        mbar_arrive_cluster(BAR(B_SLOT), 1);
        wait_counter(&g_cnt[(C_O + pi) * 32], (epoch + 1) * 8);
        if (cta == 0) g_epoch = epoch + 1;
        mbar_wait(BAR(B_SLOT), 0);
        TS(21);
#pragma unroll 1
        for (int c = 0; c < 8; ++c) {
          if (c == 4) mbar_wait_long(BAR(B_CONVD), 0);
          if (c == 7) mbar_wait(BAR(B_RE), 0);
          const uint32_t slot = c < 4 ? SM_QS + c * 16384 : c < 7 ? SM_VV + (c - 4) * 16384 : SM_QS;
          mbar_expect_tx(BAR(B_RF + c), 16384);
          tma_load_2d_mc(sb + slot + rank * 8192, &maps.o, c * 64, pi * 128 + rank * 64, BAR(B_RF + c), 3);
        }
      }
    } else if (warp == 13) {
      bar_sync(6, 160);
      sts128(sb + SM_U + (lane >> 4) * U_BYTES + (lane & 15) * 16, 0, 0, 0, 0);
      sts128(sb + SM_U + (2 + (lane >> 4)) * U_BYTES + (lane & 15) * 16, 0, 0, 0, 0);
      __syncwarp();
      if (elect_one()) {
        tma_store_2d(&maps.uT, sb + SM_P, ti * 128, tj * 64);
        tma_store_2d(&maps.uT, sb + SM_P + 8192, ti * 128 + 64, tj * 64);
        bulk_commit();
        bulk_wait_read0();
        mbar_arrive(BAR(B_PFREE));
        bulk_wait0();
        red_relaxed_add(&g_cnt[(C_U + tj) * 32], 1);
        TS(27);
        wait_counter(&g_cnt[(C_U + (cta >> 4)) * 32], (epoch + 1) * 16);
#pragma unroll 1
        for (int c = 0; c < 4; ++c) {
          mbar_expect_tx(BAR(B_UCH + c), 4096);
          bulk_load(sb + SM_U + c * U_BYTES + 256, p.uT + (size_t)(cta * 4 + c) * 2048, 4096, BAR(B_UCH + c));
        }
        TS(3);
      }
      __syncwarp();
      if (ti == 0) {
        float4* z = (float4*)&g_kv[(epoch & 1) ^ 1][tj][0];
#pragma unroll 1
        for (int i = lane; i < 272; i += 32) z[i] = make_float4(0.f, 0.f, 0.f, 0.f);
      }
    }
  }
  __syncwarp();
  cluster_arrive();
  cluster_wait();
  if (tid == 0) TS(31);
#undef BAR
}

typedef CUresult (*EncodeFn)(CUtensorMap*, CUtensorMapDataType, cuuint32_t, void*, const cuuint64_t*, const cuuint64_t*,
                             const cuuint32_t*, const cuuint32_t*, CUtensorMapInterleave, CUtensorMapSwizzle,
                             CUtensorMapL2promotion, CUtensorMapFloatOOBfill);

static void make_map(EncodeFn enc, CUtensorMap* m, const void* base, uint64_t inner, uint64_t outer, uint32_t box_in,
                     uint32_t box_out, CUtensorMapSwizzle swz = CU_TENSOR_MAP_SWIZZLE_128B) {
  cuuint64_t gd[2] = {inner, outer};
  cuuint64_t gs[1] = {inner * 2};
  cuuint32_t bd[2] = {box_in, box_out};
  cuuint32_t es[2] = {1, 1};
  enc(m, CU_TENSOR_MAP_DATA_TYPE_BFLOAT16, 2, const_cast<void*>(base), gd, gs, bd, es, CU_TENSOR_MAP_INTERLEAVE_NONE,
      swz, CU_TENSOR_MAP_L2_PROMOTION_L2_128B, CU_TENSOR_MAP_FLOAT_OOB_FILL_NONE);
}

}

extern "C" void kernel_launch(void* const* d_in, const int* in_sizes, int n_in, void* d_out, int out_size) {
  using namespace s4la;
  (void)in_sizes; (void)n_in; (void)out_size;
  static EncodeFn enc = nullptr;
  static void *uT = nullptr, *yT = nullptr, *oS = nullptr;
  if (!enc) {
    void* fn = nullptr;
    cudaDriverEntryPointQueryResult qr;
    cudaGetDriverEntryPoint("cuTensorMapEncodeTiled", &fn, cudaEnableDefault, &qr);
    enc = (EncodeFn)fn;
    cudaGetSymbolAddress(&uT, g_uT);
    cudaGetSymbolAddress(&yT, g_yT);
    cudaGetSymbolAddress(&oS, g_o);
    cudaFuncSetAttribute(fused_kernel, cudaFuncAttributeMaxDynamicSharedMemorySize, SM_TOTAL);
  }
  const __nv_bfloat16* const* in = (const __nv_bfloat16* const*)d_in;
  Maps maps;
  make_map(enc, &maps.x, in[9], 512, 2048, 32, 128, CU_TENSOR_MAP_SWIZZLE_64B);
  {
    cuuint64_t gd[3] = {512, 512, 3};
    cuuint64_t gs[2] = {3072, 1024};
    cuuint32_t bd[3] = {64, 16, 3};
    cuuint32_t es[3] = {1, 1, 1};
    enc(&maps.w, CU_TENSOR_MAP_DATA_TYPE_BFLOAT16, 3, const_cast<__nv_bfloat16*>(in[10]), gd, gs, bd, es,
        CU_TENSOR_MAP_INTERLEAVE_NONE, CU_TENSOR_MAP_SWIZZLE_128B, CU_TENSOR_MAP_L2_PROMOTION_L2_128B,
        CU_TENSOR_MAP_FLOAT_OOB_FILL_NONE);
  }
  make_map(enc, &maps.wo, in[11], 512, 512, 64, 256);
  make_map(enc, &maps.u, in[0], 512, 2048, 64, 128);
  make_map(enc, &maps.uT, uT, 2048, 512, 64, 64);
  make_map(enc, &maps.yT, yT, 2048, 512, 64, 64);
  make_map(enc, &maps.o, oS, 512, 2048, 64, 64);
  make_map(enc, &maps.out, d_out, 1024, 2048, 64, 128);
  Ptrs p;
  p.A_re = in[1]; p.A_im = in[2]; p.B_re = in[3]; p.B_im = in[4]; p.C_re = in[5]; p.C_im = in[6];
  p.log_dt = in[7]; p.Dskip = in[8]; p.x = in[9]; p.wqkv = in[10]; p.wo = in[11];
  p.uT = (__nv_bfloat16*)uT; p.yT = (__nv_bfloat16*)yT;
  fused_kernel<<<NCTA, NTHREADS, SM_TOTAL, cudaStreamPerThread>>>(maps, p);
}
```

```cpp
#include <cuda_runtime.h>
#include <cuda_bf16.h>
#include <cuda_fp16.h>
#include <cuda.h>
#include <stdint.h>

#define DEVI __device__ __forceinline__

namespace s4la {

constexpr int NTHREADS = 512;
constexpr int NCTA = 128;

constexpr int NSTG = 7;
constexpr uint32_t STG_BYTES = 20480, STG_X = 0, STG_W = 8192;
constexpr uint32_t SM_QS = 0;
constexpr uint32_t SM_PK = SM_QS + 16384, SM_VS = SM_QS + 32768;
constexpr uint32_t SM_WO = 65536;
constexpr uint32_t SM_KV = 131072;
constexpr uint32_t SM_BOUT = 16384;
constexpr uint32_t SM_U = 143360, U_BYTES = 4352;
constexpr uint32_t SM_P = 160768, P_BYTES = 4096;
constexpr uint32_t SM_VV = 177152, VV_BYTES = 12800;
constexpr uint32_t VV_U5 = 0, VV_U3 = 3712, VV_U9 = 7424, VV_U7 = 10112;
constexpr uint32_t KG_BYTES = 3200;
constexpr uint32_t SM_BAR = SM_VV + 4 * VV_BYTES;
constexpr uint32_t SM_PTAB = SM_BAR + 320;
constexpr uint32_t SM_TOTAL = SM_PTAB + 2048;
static_assert(SM_TOTAL <= 232448, "shared memory");
constexpr int PADV = 12;

enum { B_FULL = 0, B_EMPTY = 7, B_TILE = 14, B_UCH = 15, B_KVP = 19, B_KVF = 20, B_OST = 21, B_RF = 22, B_WO = 30, B_RE = 31, B_PFREE = 32, B_CONVD = 33, B_SLOT = 34, B_COUNT = 35 };
__host__ __device__ constexpr int bar_count(int i) {
  return (i >= B_EMPTY && i < B_TILE) ? 16 : (i == B_KVP || i == B_OST || i == B_CONVD) ? 8 : i == B_RE ? 16 : i == B_SLOT ? 2 : 1;
}

constexpr int PD_OFF = 0, P2_OFF = 544, P3_OFF = 768;

constexpr int SL_K2048 = 20, SL_ZERO = 21, SL_510 = 22, SL_0 = 23;
__host__ __device__ constexpr int koff(int y) {
  return y < 8 ? y : y < 12 ? 256 + 2 * (y - 8) : y < 16 ? 512 + 256 * ((y - 12) >> 1) + 4 * (y & 1) : 1024 + 256 * (y - 16);
}
__host__ __device__ constexpr int kidx_c(int l) {
  const int y = l < 256 ? (l & 7) : l < 512 ? 8 + ((l & 7) >> 1) : l < 1024 ? 12 + (((l - 512) >> 8) << 1) + ((l >> 2) & 1)
                                                                            : 16 + ((l - 1024) >> 8);
  return ((l >> 3) & 31) * 24 + y;
}
constexpr int slot_direct(int l) {
  if (l < 0 || l > 510) return SL_ZERO;
  if (l == 510) return SL_510;
  if (l == 0) return SL_0;
  return kidx_c(l < 256 ? l : ((l + ((l >> 1) & 1)) & ~1));
}
constexpr int slot_seg2(int v, int k) { return (k >= 32 && k < 64) ? kidx_c(16 * k + 4 * v) : SL_ZERO; }
constexpr int slot_seg3(int pi, int k) {
  return (k >= 64 && k < 128) ? kidx_c(16 * k + 8 * pi) : ((k == 128 && pi == 0) ? SL_K2048 : SL_ZERO);
}
constexpr int slot_word(int w) {
  return w < 0 ? SL_ZERO : w < 544 ? slot_direct(w - 16) : w < 768 ? slot_seg2((w - 544) / 56, 16 + (w - 544) % 56)
       : w < 944 ? slot_seg3((w - 768) / 88, 48 + (w - 768) % 88) : SL_ZERO;
}
struct PTab { uint32_t v[512]; };
constexpr PTab make_ptab() {
  PTab t{};
  for (int lane = 0; lane < 32; ++lane)
    for (int i = 0; i < 16; ++i)
      t.v[i * 32 + lane] = (slot_word(31 * lane - 1 + 2 * i) * 4) | ((slot_word(31 * lane + 2 * i) * 4) << 16);
  return t;
}
__device__ const PTab g_ptab = make_ptab();

__device__ __nv_bfloat16 g_uT[512 * 2048];
__device__ __nv_bfloat16 g_yT[512 * 2048];
__device__ __nv_bfloat16 g_o[2048 * 512];
__device__ float g_kv[2][8][4 * 272];
__device__ unsigned g_cnt[64 * 32];
__device__ unsigned g_epoch;
#define TS(slot) do { } while (0)
#define TSR(on, slot) do { } while (0)
#define TSD(slot) do { } while (0)
enum { C_U = 0, C_KV = 8, C_O = 16, C_Y = 32 };

struct Maps {
  CUtensorMap x, w, wo, u, uT, yT, o, out, outh;
};
struct Ptrs {
  const __nv_bfloat16 *A_re, *A_im, *B_re, *B_im, *C_re, *C_im, *log_dt, *Dskip;
  const __nv_bfloat16 *x, *wqkv, *wo;
  __nv_bfloat16 *uT, *yT;
};

DEVI uint32_t s2u(const void* p) { return (uint32_t)__cvta_generic_to_shared(p); }
DEVI void mbar_init(uint32_t b, uint32_t c) { asm volatile("mbarrier.init.shared::cta.b64 [%0], %1;" ::"r"(b), "r"(c) : "memory"); }
DEVI void mbar_expect_tx(uint32_t b, uint32_t bytes) {
  asm volatile("mbarrier.arrive.expect_tx.shared::cta.b64 _, [%0], %1;" ::"r"(b), "r"(bytes) : "memory");
}
DEVI void mbar_arrive(uint32_t b) { asm volatile("mbarrier.arrive.shared::cta.b64 _, [%0];" ::"r"(b) : "memory"); }
DEVI void mbar_arrive_cluster(uint32_t b, uint32_t cta) {
  asm volatile("{\n.reg .b32 r;\nmapa.shared::cluster.u32 r, %0, %1;\nmbarrier.arrive.shared::cluster.b64 _, [r];\n}"
               ::"r"(b), "r"(cta) : "memory");
}
DEVI void mbar_wait(uint32_t b, uint32_t parity) {
  asm volatile("{\n.reg .pred p;\nLAB_WAIT:\nmbarrier.try_wait.parity.shared::cta.b64 p, [%0], %1;\n@!p bra LAB_WAIT;\n}"
               ::"r"(b), "r"(parity) : "memory");
}
DEVI void mbar_wait_long(uint32_t b, uint32_t parity) {
  asm volatile("{\n.reg .pred p;\nLAB_WAIT:\nmbarrier.try_wait.parity.shared::cta.b64 p, [%0], %1, 0x989680;\n@!p bra LAB_WAIT;\n}"
               ::"r"(b), "r"(parity) : "memory");
}
DEVI void bar_sync(int id, int n) { asm volatile("bar.sync %0, %1;" ::"r"(id), "r"(n) : "memory"); }
DEVI void bar_arrive(int id, int n) { asm volatile("bar.arrive %0, %1;" ::"r"(id), "r"(n) : "memory"); }
DEVI void fence_async_smem() { asm volatile("fence.proxy.async.shared::cta;" ::: "memory"); }
DEVI void fence_async_all() { asm volatile("fence.proxy.async;" ::: "memory"); }
DEVI void cluster_arrive() { asm volatile("barrier.cluster.arrive.relaxed.aligned;" ::: "memory"); }
DEVI void cluster_wait() { asm volatile("barrier.cluster.wait.aligned;" ::: "memory"); }

DEVI void tma_load_2d(uint32_t dst, const CUtensorMap* m, int c0, int c1, uint32_t bar) {
  asm volatile("cp.async.bulk.tensor.2d.shared::cluster.global.mbarrier::complete_tx::bytes [%0], [%1, {%3, %4}], [%2];"
               ::"r"(dst), "l"(m), "r"(bar), "r"(c0), "r"(c1) : "memory");
}
DEVI void tma_load_2d_mc(uint32_t dst, const CUtensorMap* m, int c0, int c1, uint32_t bar, uint16_t mask) {
  asm volatile("cp.async.bulk.tensor.2d.shared::cluster.global.mbarrier::complete_tx::bytes.multicast::cluster [%0], [%1, {%3, %4}], [%2], %5;"
               ::"r"(dst), "l"(m), "r"(bar), "r"(c0), "r"(c1), "h"(mask) : "memory");
}
DEVI void tma_load_3d_mc(uint32_t dst, const CUtensorMap* m, int c0, int c1, int c2, uint32_t bar, uint16_t mask) {
  asm volatile("cp.async.bulk.tensor.3d.shared::cluster.global.mbarrier::complete_tx::bytes.multicast::cluster [%0], [%1, {%3, %4, %5}], [%2], %6;"
               ::"r"(dst), "l"(m), "r"(bar), "r"(c0), "r"(c1), "r"(c2), "h"(mask) : "memory");
}
DEVI void tma_store_2d(const CUtensorMap* m, uint32_t src, int c0, int c1) {
  asm volatile("cp.async.bulk.tensor.2d.global.shared::cta.bulk_group [%0, {%2, %3}], [%1];"
               ::"l"(m), "r"(src), "r"(c0), "r"(c1) : "memory");
}
DEVI void bulk_load(uint32_t dst, const void* src, uint32_t bytes, uint32_t bar) {
  asm volatile("cp.async.bulk.shared::cluster.global.mbarrier::complete_tx::bytes [%0], [%1], %2, [%3];"
               ::"r"(dst), "l"(src), "r"(bytes), "r"(bar) : "memory");
}
DEVI void bulk_store(void* dst, uint32_t src, uint32_t bytes) {
  asm volatile("cp.async.bulk.global.shared::cta.bulk_group [%0], [%1], %2;" ::"l"(dst), "r"(src), "r"(bytes) : "memory");
}
DEVI void bulk_reduce_add_f32(void* dst, uint32_t src, uint32_t bytes) {
  asm volatile("cp.reduce.async.bulk.global.shared::cta.bulk_group.add.f32 [%0], [%1], %2;" ::"l"(dst), "r"(src), "r"(bytes) : "memory");
}
DEVI void bulk_commit() { asm volatile("cp.async.bulk.commit_group;" ::: "memory"); }
DEVI void bulk_wait0() { asm volatile("cp.async.bulk.wait_group 0;" ::: "memory"); }
DEVI void bulk_wait_read0() { asm volatile("cp.async.bulk.wait_group.read 0;" ::: "memory"); }
DEVI void l2_prefetch(const void* p, uint32_t bytes) {
  asm volatile("cp.async.bulk.prefetch.L2.global [%0], %1;" ::"l"(p), "r"(bytes) : "memory");
}
DEVI void prefetch_tmap(const CUtensorMap* m) { asm volatile("prefetch.tensormap [%0];" ::"l"(m) : "memory"); }

DEVI void red_release_add(unsigned* p, unsigned v) {
  asm volatile("red.release.gpu.global.add.u32 [%0], %1;" ::"l"(p), "r"(v) : "memory");
}
DEVI void red_relaxed_add(unsigned* p, unsigned v) {
  asm volatile("red.relaxed.gpu.global.add.u32 [%0], %1;" ::"l"(p), "r"(v) : "memory");
}
DEVI unsigned ld_relaxed(const unsigned* p) {
  unsigned v;
  asm volatile("ld.relaxed.gpu.global.u32 %0, [%1];" : "=r"(v) : "l"(p) : "memory");
  return v;
}
DEVI void wait_counter(const unsigned* p, unsigned target) {
#pragma unroll 1
  for (int it = 0; (int)(ld_relaxed(p) - target) < 0; ++it)
    if (it > (1 << 22)) __trap();
}

DEVI void ldsm_x4(uint32_t (&r)[4], uint32_t a) {
  asm volatile("ldmatrix.sync.aligned.m8n8.x4.shared.b16 {%0,%1,%2,%3}, [%4];"
               : "=r"(r[0]), "=r"(r[1]), "=r"(r[2]), "=r"(r[3]) : "r"(a) : "memory");
}
DEVI void ldsm_x4_t(uint32_t (&r)[4], uint32_t a) {
  asm volatile("ldmatrix.sync.aligned.m8n8.x4.trans.shared.b16 {%0,%1,%2,%3}, [%4];"
               : "=r"(r[0]), "=r"(r[1]), "=r"(r[2]), "=r"(r[3]) : "r"(a) : "memory");
}
DEVI void ldsm_x2_t(uint32_t& r0, uint32_t& r1, uint32_t a) {
  asm volatile("ldmatrix.sync.aligned.m8n8.x2.trans.shared.b16 {%0,%1}, [%2];" : "=r"(r0), "=r"(r1) : "r"(a) : "memory");
}
DEVI void stsm_x4(uint32_t a, uint32_t r0, uint32_t r1, uint32_t r2, uint32_t r3) {
  asm volatile("stmatrix.sync.aligned.m8n8.x4.shared.b16 [%0], {%1,%2,%3,%4};"
               ::"r"(a), "r"(r0), "r"(r1), "r"(r2), "r"(r3) : "memory");
}
DEVI void stsm_x4_t(uint32_t a, uint32_t r0, uint32_t r1, uint32_t r2, uint32_t r3) {
  asm volatile("stmatrix.sync.aligned.m8n8.x4.trans.shared.b16 [%0], {%1,%2,%3,%4};"
               ::"r"(a), "r"(r0), "r"(r1), "r"(r2), "r"(r3) : "memory");
}
DEVI uint32_t lds32(uint32_t a) { uint32_t v; asm volatile("ld.shared.b32 %0, [%1];" : "=r"(v) : "r"(a) : "memory"); return v; }
DEVI float lds_f32(uint32_t a) { float v; asm volatile("ld.shared.f32 %0, [%1];" : "=f"(v) : "r"(a) : "memory"); return v; }
DEVI void sts32(uint32_t a, uint32_t v) { asm volatile("st.shared.b32 [%0], %1;" ::"r"(a), "r"(v) : "memory"); }
DEVI void sts_f32(uint32_t a, float v) { asm volatile("st.shared.f32 [%0], %1;" ::"r"(a), "f"(v) : "memory"); }
DEVI void sts_f32x2(uint32_t a, float x, float y) { asm volatile("st.shared.v2.f32 [%0], {%1,%2};" ::"r"(a), "f"(x), "f"(y) : "memory"); }
DEVI uint4 lds128(uint32_t a) {
  uint4 v;
  asm volatile("ld.shared.v4.b32 {%0,%1,%2,%3}, [%4];" : "=r"(v.x), "=r"(v.y), "=r"(v.z), "=r"(v.w) : "r"(a) : "memory");
  return v;
}
DEVI void sts128(uint32_t a, uint32_t x, uint32_t y, uint32_t z, uint32_t w) {
  asm volatile("st.shared.v4.b32 [%0], {%1,%2,%3,%4};" ::"r"(a), "r"(x), "r"(y), "r"(z), "r"(w) : "memory");
}

DEVI void mma_bf16(float (&d)[4], uint32_t a0, uint32_t a1, uint32_t a2, uint32_t a3, uint32_t b0, uint32_t b1) {
  asm("mma.sync.aligned.m16n8k16.row.col.f32.bf16.bf16.f32 {%0,%1,%2,%3}, {%4,%5,%6,%7}, {%8,%9}, {%0,%1,%2,%3};"
      : "+f"(d[0]), "+f"(d[1]), "+f"(d[2]), "+f"(d[3])
      : "r"(a0), "r"(a1), "r"(a2), "r"(a3), "r"(b0), "r"(b1));
}
DEVI void mma_f16(float (&d)[4], const uint32_t (&a)[4], uint32_t b0, uint32_t b1) {
  asm("mma.sync.aligned.m16n8k16.row.col.f32.f16.f16.f32 {%0,%1,%2,%3}, {%4,%5,%6,%7}, {%8,%9}, {%0,%1,%2,%3};"
      : "+f"(d[0]), "+f"(d[1]), "+f"(d[2]), "+f"(d[3])
      : "r"(a[0]), "r"(a[1]), "r"(a[2]), "r"(a[3]), "r"(b0), "r"(b1));
}
DEVI void mma_bf16v(float (&d)[4], const uint32_t (&a)[4], uint32_t b0, uint32_t b1) {
  asm volatile("mma.sync.aligned.m16n8k16.row.col.f32.bf16.bf16.f32 {%0,%1,%2,%3}, {%4,%5,%6,%7}, {%8,%9}, {%0,%1,%2,%3};"
               : "+f"(d[0]), "+f"(d[1]), "+f"(d[2]), "+f"(d[3])
               : "r"(a[0]), "r"(a[1]), "r"(a[2]), "r"(a[3]), "r"(b0), "r"(b1));
}
DEVI uint32_t pack_bf16(float lo, float hi) {
  uint32_t r;
  asm("cvt.rn.bf16x2.f32 %0, %1, %2;" : "=r"(r) : "f"(hi), "f"(lo));
  return r;
}
DEVI uint32_t pack_f16(float lo, float hi) {
  uint32_t r;
  asm("cvt.rn.f16x2.f32 %0, %1, %2;" : "=r"(r) : "f"(hi), "f"(lo));
  return r;
}
DEVI uint32_t ldg16(const __nv_bfloat16* p) {
  uint32_t v;
  asm volatile("ld.global.nc.u16 %0, [%1];" : "=r"(v) : "l"(p));
  return v;
}
DEVI bool elect_one() {
  uint32_t pred;
  asm volatile("{\n.reg .pred p;\nelect.sync _|p, 0xffffffff;\nselp.u32 %0, 1, 0, p;\n}" : "=r"(pred));
  return pred != 0;
}
DEVI float bf_lo(uint32_t v) { return __uint_as_float(v << 16); }
DEVI float bf_hi(uint32_t v) { return __uint_as_float(v & 0xffff0000u); }
DEVI float bf2f(__nv_bfloat16 v) { return __bfloat162float(v); }
DEVI float round_bf16(float v) { return __bfloat162float(__float2bfloat16_rn(v)); }
DEVI float rcp(float x) { float r; asm("rcp.approx.ftz.f32 %0, %1;" : "=f"(r) : "f"(x)); return r; }
DEVI float ex2(float x) { float r; asm("ex2.approx.ftz.f32 %0, %1;" : "=f"(r) : "f"(x)); return r; }

DEVI void wg_fence() { asm volatile("wgmma.fence.sync.aligned;" ::: "memory"); }
DEVI void wg_commit() { asm volatile("wgmma.commit_group.sync.aligned;" ::: "memory"); }
template <int N> DEVI void wg_wait() { asm volatile("wgmma.wait_group.sync.aligned %0;" ::"n"(N) : "memory"); }
constexpr uint32_t DESC_HI = (1u << 30) | (1024 >> 4);
constexpr uint32_t DESC_HI64 = (2u << 30) | (512 >> 4);
DEVI uint32_t mkdesc(uint32_t saddr, uint32_t lbo) { return ((saddr & 0x3FFFF) >> 4) | ((lbo >> 4) << 16); }

#define R8(b) "%" #b
DEVI void wgmma_n192(float (&d)[96], uint32_t da, uint32_t db, int scale_d) {
  asm volatile(
      "{\n.reg .pred p;\n.reg .b64 da, db;\nsetp.ne.b32 p, %98, 0;\nmov.b64 da, {%96, %100};\nmov.b64 db, {%97, %99};\n"
      "wgmma.mma_async.sync.aligned.m64n192k16.f32.bf16.bf16 "
      "{%0,%1,%2,%3,%4,%5,%6,%7,%8,%9,%10,%11,%12,%13,%14,%15,"
      "%16,%17,%18,%19,%20,%21,%22,%23,%24,%25,%26,%27,%28,%29,%30,%31,"
      "%32,%33,%34,%35,%36,%37,%38,%39,%40,%41,%42,%43,%44,%45,%46,%47,"
      "%48,%49,%50,%51,%52,%53,%54,%55,%56,%57,%58,%59,%60,%61,%62,%63,"
      "%64,%65,%66,%67,%68,%69,%70,%71,%72,%73,%74,%75,%76,%77,%78,%79,"
      "%80,%81,%82,%83,%84,%85,%86,%87,%88,%89,%90,%91,%92,%93,%94,%95}, "
      "da, db, p, 1, 1, 0, 1;\n}"
      : "+f"(d[0]), "+f"(d[1]), "+f"(d[2]), "+f"(d[3]), "+f"(d[4]), "+f"(d[5]), "+f"(d[6]), "+f"(d[7]),
        "+f"(d[8]), "+f"(d[9]), "+f"(d[10]), "+f"(d[11]), "+f"(d[12]), "+f"(d[13]), "+f"(d[14]), "+f"(d[15]),
        "+f"(d[16]), "+f"(d[17]), "+f"(d[18]), "+f"(d[19]), "+f"(d[20]), "+f"(d[21]), "+f"(d[22]), "+f"(d[23]),
        "+f"(d[24]), "+f"(d[25]), "+f"(d[26]), "+f"(d[27]), "+f"(d[28]), "+f"(d[29]), "+f"(d[30]), "+f"(d[31]),
        "+f"(d[32]), "+f"(d[33]), "+f"(d[34]), "+f"(d[35]), "+f"(d[36]), "+f"(d[37]), "+f"(d[38]), "+f"(d[39]),
        "+f"(d[40]), "+f"(d[41]), "+f"(d[42]), "+f"(d[43]), "+f"(d[44]), "+f"(d[45]), "+f"(d[46]), "+f"(d[47]),
        "+f"(d[48]), "+f"(d[49]), "+f"(d[50]), "+f"(d[51]), "+f"(d[52]), "+f"(d[53]), "+f"(d[54]), "+f"(d[55]),
        "+f"(d[56]), "+f"(d[57]), "+f"(d[58]), "+f"(d[59]), "+f"(d[60]), "+f"(d[61]), "+f"(d[62]), "+f"(d[63]),
        "+f"(d[64]), "+f"(d[65]), "+f"(d[66]), "+f"(d[67]), "+f"(d[68]), "+f"(d[69]), "+f"(d[70]), "+f"(d[71]),
        "+f"(d[72]), "+f"(d[73]), "+f"(d[74]), "+f"(d[75]), "+f"(d[76]), "+f"(d[77]), "+f"(d[78]), "+f"(d[79]),
        "+f"(d[80]), "+f"(d[81]), "+f"(d[82]), "+f"(d[83]), "+f"(d[84]), "+f"(d[85]), "+f"(d[86]), "+f"(d[87]),
        "+f"(d[88]), "+f"(d[89]), "+f"(d[90]), "+f"(d[91]), "+f"(d[92]), "+f"(d[93]), "+f"(d[94]), "+f"(d[95])
      : "r"(da), "r"(db), "r"(scale_d), "n"(DESC_HI), "n"(DESC_HI64));
}
DEVI void wgmma_n64(float (&d)[32], uint32_t da, uint32_t db, int scale_d) {
  asm volatile(
      "{\n.reg .pred p;\n.reg .b64 da, db;\nsetp.ne.b32 p, %34, 0;\nmov.b64 da, {%32, %35};\nmov.b64 db, {%33, %35};\n"
      "wgmma.mma_async.sync.aligned.m64n64k16.f32.bf16.bf16 "
      "{%0,%1,%2,%3,%4,%5,%6,%7,%8,%9,%10,%11,%12,%13,%14,%15,"
      "%16,%17,%18,%19,%20,%21,%22,%23,%24,%25,%26,%27,%28,%29,%30,%31}, "
      "da, db, p, 1, 1, 0, 1;\n}"
      : "+f"(d[0]), "+f"(d[1]), "+f"(d[2]), "+f"(d[3]), "+f"(d[4]), "+f"(d[5]), "+f"(d[6]), "+f"(d[7]),
        "+f"(d[8]), "+f"(d[9]), "+f"(d[10]), "+f"(d[11]), "+f"(d[12]), "+f"(d[13]), "+f"(d[14]), "+f"(d[15]),
        "+f"(d[16]), "+f"(d[17]), "+f"(d[18]), "+f"(d[19]), "+f"(d[20]), "+f"(d[21]), "+f"(d[22]), "+f"(d[23]),
        "+f"(d[24]), "+f"(d[25]), "+f"(d[26]), "+f"(d[27]), "+f"(d[28]), "+f"(d[29]), "+f"(d[30]), "+f"(d[31])
      : "r"(da), "r"(db), "r"(scale_d), "n"(DESC_HI));
}

struct C32 { float re, im; };
DEVI C32 csq(C32 a) { return {a.re * a.re - a.im * a.im, 2.f * a.re * a.im}; }
DEVI C32 cmul(C32 a, C32 b) { return {a.re * b.re - a.im * b.im, a.re * b.im + a.im * b.re}; }
DEVI C32 cfresh(float zl, float zi, float m) {
  float mag = ex2(zl * m), ph = zi * m;
  return {mag * __cosf(ph), mag * __sinf(ph)};
}
struct HMul { uint32_t b, bp; };
DEVI HMul mk_mul(float re, float im) { return {pack_f16(re, im), pack_f16(-im, re)}; }
DEVI uint32_t hcmul(uint32_t a, const HMul& m) {
  __half2 ah = *reinterpret_cast<__half2*>(&a);
  __half2 b = *reinterpret_cast<const __half2*>(&m.b), bp = *reinterpret_cast<const __half2*>(&m.bp);
  __half2 r = __hfma2(__high2half2(ah), bp, __hmul2(__low2half2(ah), b));
  return *reinterpret_cast<uint32_t*>(&r);
}
DEVI uint32_t badd(uint32_t a, uint32_t b) {
  __nv_bfloat162 r = __hadd2(*reinterpret_cast<__nv_bfloat162*>(&a), *reinterpret_cast<__nv_bfloat162*>(&b));
  return *reinterpret_cast<uint32_t*>(&r);
}
template <int MU0, int NMU, int DMAX>
DEVI void conv_tail(float (&acc)[16][4], uint32_t p_lane, uint32_t v_base, int back, bool edge, int lane) {
  const int hsel = (lane >> 3) & 1;
  const int row = (lane & 7) + ((lane >> 4) << 3) + PADV - 8 - (back & (hsel ^ 1));
  const uint32_t la = v_base + row * 32 + (((hsel ^ back) ^ ((row >> 2) & 1)) << 4);
  uint32_t M[3][4];
  ldsm_x4_t(M[0], la);
  ldsm_x4_t(M[1], la + 256);
  uint32_t H[2 * NMU];
#pragma unroll
  for (int i = 0; i < 2 * NMU; ++i) H[i ^ 1] = lds32(p_lane + (uint32_t)(MU0 - 1 + i) * 32);
  if (edge) {
    const uint32_t a[4] = {0u, 0u, M[0][0], M[0][1]};
#pragma unroll
    for (int k = 1; k < NMU; ++k) mma_bf16v(acc[MU0 - 2 + 2 * k], a, H[2 * k], H[2 * k + 1]);
  }
#pragma unroll
  for (int delta = -1; delta <= DMAX; ++delta) {
    if (delta + 2 <= DMAX) ldsm_x4_t(M[(delta + 3) % 3], la + (delta + 3) * 256);
#pragma unroll
    for (int k = 0; k < NMU; ++k)
      if (delta + MU0 + 2 * k < 16) mma_bf16v(acc[delta + MU0 + 2 * k], M[(delta + 1) % 3], H[2 * k], H[2 * k + 1]);
  }
}

template <int NB>
DEVI void box_filters(uint32_t sb, uint32_t bars, int idx, int lane) {
  auto swz = [](int k, int pad) { const int r = (k >> 1) + pad; return (uint32_t)(r * 32 + (((k & 1) ^ ((r >> 2) & 1)) << 4)); };
  const uint32_t o0 = swz(lane - 3, 8), o1 = swz(lane - 2, 8), o2 = swz(lane - 1, 8), ow = swz(lane - 2, PADV), oz = swz(lane - 18, PADV);
  const int k = 32 * idx - 2 + lane;
#pragma unroll 1
  for (int c2 = 0; c2 < 4; c2 += NB) {
    uint4 t[NB][3];
#pragma unroll
    for (int b = 0; b < NB; ++b) mbar_wait_long(bars + 8 * (B_UCH + c2 + b), 0);
#pragma unroll
    for (int b = 0; b < NB; ++b) {
      const uint32_t ua = sb + SM_U + (c2 + b) * U_BYTES + idx * 512;
      t[b][0] = lds128(ua + o0); t[b][1] = lds128(ua + o1); t[b][2] = lds128(ua + o2);
    }
#pragma unroll
    for (int b = 0; b < NB; ++b) {
      const uint32_t vb = sb + SM_VV + (c2 + b) * VV_BYTES, aw = vb + idx * 512 + ow;
      const uint32_t E[12] = {t[b][0].x, t[b][0].y, t[b][0].z, t[b][0].w, t[b][1].x, t[b][1].y, t[b][1].z, t[b][1].w,
                              t[b][2].x, t[b][2].y, t[b][2].z, t[b][2].w};
      uint32_t O[8];
#pragma unroll
      for (int j = 0; j < 8; ++j) O[j] = __byte_perm(E[j + 1], E[j + 2], 0x5432);
      uint32_t s3[6], s5[4], s7[4], s9[4];
#pragma unroll
      for (int j = 0; j < 6; ++j) s3[j] = badd(badd(O[j], O[j + 1]), E[j + 2]);
#pragma unroll
      for (int j = 0; j < 4; ++j) {
        s5[j] = badd(s3[j + 2], badd(E[j + 3], E[j + 5]));
        s7[j] = badd(s5[j], badd(O[j + 1], O[j + 4]));
        s9[j] = badd(s7[j], badd(E[j + 2], E[j + 6]));
      }
      if (k < 208) { sts128(aw + VV_U3, s3[0], s3[1], s3[2], s3[3]); sts128(aw + VV_U5, s5[0], s5[1], s5[2], s5[3]); }
      if (k < 144) { sts128(aw + VV_U7, s7[0], s7[1], s7[2], s7[3]); sts128(aw + VV_U9, s9[0], s9[1], s9[2], s9[3]); }
      if (idx == 0 && lane < 16) {
        sts128(vb + oz + VV_U3, 0, 0, 0, 0); sts128(vb + oz + VV_U5, 0, 0, 0, 0);
        sts128(vb + oz + VV_U7, 0, 0, 0, 0); sts128(vb + oz + VV_U9, 0, 0, 0, 0);
      }
    }
  }
}

__global__ void __cluster_dims__(2, 1, 1) __launch_bounds__(NTHREADS, 1)
fused_kernel(const __grid_constant__ Maps maps, const Ptrs p) {
  extern __shared__ __align__(1024) uint8_t smem[];
  const uint32_t sb = s2u(smem);
  const int tid = threadIdx.x, lane = tid & 31;
  const int warp = __shfl_sync(0xffffffffu, tid >> 5, 0);
  const int cta = blockIdx.x;
  const uint32_t rank = cta & 1;
  const int ti = 2 * (cta >> 4) + rank;
  const int tj = (cta >> 1) & 7;
  const int pi = cta >> 3, pj = cta & 7;
  const uint32_t bars = sb + SM_BAR;
#define BAR(i) (bars + 8 * (i))
  const int g = lane >> 2, q = lane & 3;

  auto issue_stage = [&](int ks, int s) {
    const uint32_t st = sb + s * STG_BYTES, fb = BAR(B_FULL + s);
    mbar_expect_tx(fb, STG_BYTES);
    tma_load_2d(st + STG_X, &maps.x, ks * 32, ti * 128, fb);
    tma_load_3d_mc(st + STG_W + rank * 6144, &maps.w, tj * 64, ks * 32 + rank * 16, 0, fb, 3);
  };

  const int kch = warp & 3, krd = warp >> 2;
  float zr, zi, wr, wi;
  unsigned epoch;
  uint32_t r_dskip;
  {
    const size_t po = (size_t)(cta * 4 + kch) * 128 + krd * 32 + lane;
    const uint32_t r_ar = ldg16(p.A_re + po), r_ai = ldg16(p.A_im + po), r_br = ldg16(p.B_re + po), r_bi = ldg16(p.B_im + po);
    const uint32_t r_cr = ldg16(p.C_re + po), r_ci = ldg16(p.C_im + po), r_ldt = ldg16(p.log_dt + cta * 4 + kch);
    epoch = __ldcg(&g_epoch);
    r_dskip = ldg16(p.Dskip + cta * 4 + kch);
    uint4 pt;
    if (tid < 128) pt = __ldg((const uint4*)g_ptab.v + tid);
    if (tid == 384) {
      TS(0);
#pragma unroll
      for (int i = 0; i < B_COUNT; ++i) mbar_init(BAR(i), bar_count(i));
      asm volatile("fence.mbarrier_init.release.cluster;" ::: "memory");
      prefetch_tmap(&maps.x); prefetch_tmap(&maps.w); prefetch_tmap(&maps.u);
    }
    __syncthreads();
    cluster_arrive();
    if (warp >= 12) {
      cluster_wait();
      if (elect_one()) {
        if (warp == 13) {
          mbar_expect_tx(BAR(B_TILE), 16384);
          tma_load_2d(sb + SM_U, &maps.u, tj * 64, ti * 128, BAR(B_TILE));
          prefetch_tmap(&maps.uT); prefetch_tmap(&maps.wo); prefetch_tmap(&maps.o); prefetch_tmap(&maps.yT);
          prefetch_tmap(&maps.out); prefetch_tmap(&maps.outh);
        } else {
          if (warp == 12) TS(61);
          { const int ks = warp == 12 ? 0 : warp - 13; issue_stage(ks, ks); }
        }
      }
      __syncwarp();
    }
    if (tid < 128) sts128(sb + SM_PTAB + tid * 16, pt.x, pt.y, pt.z, pt.w);
    const float dt = round_bf16(expf(bf_lo(r_ldt)));
    zr = dt * bf_lo(r_ar); zi = dt * bf_lo(r_ai);
    const float dbr = dt * bf_lo(r_br), dbi = dt * bf_lo(r_bi), cr = bf_lo(r_cr), ci = bf_lo(r_ci);
    wr = cr * dbr - ci * dbi; wi = cr * dbi + ci * dbr;
  }
  {
    const float mz = __uint_as_float(__reduce_max_sync(0xffffffffu, __float_as_uint(fmaxf(zr, 0.f))));
    const int E = min(max((int)(__reduce_max_sync(0xffffffffu, __float_as_uint(fmaxf(fabsf(wr), fabsf(wi)))) >> 23), 1), 252);
    const float sc = __int_as_float((253 - E) << 23), inv = __int_as_float((E + 1) << 23);
    const float zl = (zr - mz) * 1.4426950408889634f;
    const uint32_t tb = sb + SM_VV + kch * VV_BYTES + krd * KG_BYTES;
    const uint32_t sta = tb + (((lane >> 2) << 4) | ((lane & 3) << 2));
    auto put = [&](int r, uint32_t v) { sts32((sta ^ ((r & 7) << 4)) + r * 128, v); };
    const uint32_t lda = tb + ((lane & 7) + (((lane >> 3) & 1) << 3)) * 128;
    const uint32_t ldb = tb + ((lane & 7) + ((lane >> 4) << 3)) * 128;
    C32 e1 = cfresh(zl, zi, 1.f), e2 = csq(e1), e4 = csq(e2), e8 = csq(e4);
    C32 e16 = cfresh(zl, zi, 16.f), e32 = csq(e16), e64 = csq(e32), e128 = csq(e64);
    C32 e256 = cfresh(zl, zi, 256.f), e512 = csq(e256), e1024 = csq(e512), e768 = cmul(e512, e256);
    uint32_t XA[2][4][4];
    {
      const HMul m16 = mk_mul(e16.re, e16.im), m32 = mk_mul(e32.re, e32.im), m64 = mk_mul(e64.re, e64.im);
      const HMul m128 = mk_mul(e128.re, e128.im);
      uint32_t X[16];
      X[0] = 0x00003c00u; X[1] = pack_f16(e8.re, e8.im); X[2] = m16.b; X[4] = m32.b; X[8] = m64.b;
      X[3] = hcmul(X[1], m16); X[5] = hcmul(X[1], m32); X[6] = hcmul(X[2], m32); X[7] = hcmul(X[3], m32);
#pragma unroll
      for (int r = 1; r < 8; ++r) X[8 + r] = hcmul(X[r], m64);
#pragma unroll
      for (int h = 0; h < 2; ++h) {
#pragma unroll
        for (int r = 0; r < 16; ++r) put(r, h == 0 ? X[r] : r == 0 ? m128.b : hcmul(X[r], m128));
        __syncwarp();
#pragma unroll
        for (int k = 0; k < 4; ++k) ldsm_x4(XA[h][k], lda + (((2 * k + (lane >> 4)) ^ (lane & 7)) << 4));
        __syncwarp();
      }
    }
    if (warp >= 14 && elect_one()) {
      issue_stage(warp - 11, warp - 11);
      issue_stage(warp - 9, warp - 9);
      if (warp == 14) l2_prefetch((const char*)p.wqkv + 224 * 3072 + cta * 6912, 6912);
      else l2_prefetch((const char*)p.x + (size_t)cta * 16384, 16384);
    }
    __syncwarp();
    float D[2][3][4];
#pragma unroll
    for (int t = 0; t < 6; ++t) D[t / 3][t % 3][0] = D[t / 3][t % 3][1] = D[t / 3][t % 3][2] = D[t / 3][t % 3][3] = 0.f;
    auto contract = [&](int t0, int nt) {
      __syncwarp();
#pragma unroll
      for (int k = 0; k < 4; ++k) {
        uint32_t b[4];
        ldsm_x4(b, ldb + (((2 * k + ((lane >> 3) & 1)) ^ (lane & 7)) << 4));
#pragma unroll
        for (int h = 0; h < 2; ++h) {
          mma_f16(D[h][t0], XA[h][k], b[0], b[1]);
          if (nt == 2) mma_f16(D[h][t0 + 1], XA[h][k], b[2], b[3]);
        }
      }
      __syncwarp();
    };
    const HMul c1 = mk_mul(e1.re, -e1.im), c2 = mk_mul(e2.re, -e2.im), c4 = mk_mul(e4.re, -e4.im);
    const HMul c256 = mk_mul(e256.re, -e256.im), c512 = mk_mul(e512.re, -e512.im), c768 = mk_mul(e768.re, -e768.im);
    const HMul c1024 = mk_mul(e1024.re, -e1024.im);
    uint32_t W[8];
    W[0] = pack_f16(wr * sc, -wi * sc);
    W[1] = hcmul(W[0], c1); W[2] = hcmul(W[0], c2); W[3] = hcmul(W[1], c2);
    W[4] = hcmul(W[0], c4); W[5] = hcmul(W[1], c4); W[6] = hcmul(W[2], c4); W[7] = hcmul(W[3], c4);
#pragma unroll
    for (int i = 0; i < 8; ++i) put(i, W[i]);
#pragma unroll
    for (int i = 0; i < 4; ++i) put(8 + i, hcmul(W[2 * i], c256));
    put(12, hcmul(W[0], c512)); put(13, hcmul(W[4], c512)); put(14, hcmul(W[0], c768)); put(15, hcmul(W[4], c768));
    contract(0, 2);
    const uint32_t v0 = hcmul(W[0], c1024);
    put(0, v0); put(1, hcmul(v0, c256)); put(2, hcmul(v0, c512)); put(3, hcmul(v0, c768)); put(4, hcmul(v0, c1024));
    contract(2, 1);
    const uint32_t a = tb + (g * 24 + 2 * q) * 4;
#pragma unroll
    for (int t = 0; t < 6; ++t) {
      const float(&d)[4] = D[t / 3][t % 3];
      sts_f32x2(a + (t / 3) * 1536 + (t % 3) * 32, d[0] * inv, d[1] * inv);
      sts_f32x2(a + (t / 3) * 1536 + (t % 3) * 32 + 768, d[2] * inv, d[3] * inv);
    }
    if (mz > 0.f) {
      __syncwarp();
#pragma unroll 1
      for (int i = lane; i < 768; i += 32) {
        const int r = i / 24, y = i - 24 * r;
        sts_f32(tb + i * 4, lds_f32(tb + i * 4) * ex2(mz * 1.4426950408889634f * (koff(y) + 8 * r)));
      }
    }
  }
  if (tid == 0) TS(2);
  if (warp < 12) cluster_wait();
  __syncthreads();

  if (warp < 4) {
#define A_REGS 200
    asm volatile("setmaxnreg.inc.sync.aligned.u32 %0;" ::"n"(A_REGS));
    if (tid == 0) TS(34);
    const int d = cta * 4 + warp;
    const uint32_t vv = sb + SM_VV + warp * VV_BYTES;
    const uint32_t ub = sb + SM_U + warp * U_BYTES;
    const uint32_t pb = sb + SM_P + warp * P_BYTES;
    const float dskip = bf_lo(r_dskip);
#pragma unroll 1
    for (int pass = 0; pass < 2; ++pass) {
      if (pass == 1) {
        const uint32_t kf = vv;
#pragma unroll 2
        for (int i = 0; i < 6; ++i) {
          const uint32_t a = kf + (i * 32 + lane) * 16;
          const uint4 x0 = lds128(a), x1 = lds128(a + KG_BYTES), x2 = lds128(a + 2 * KG_BYTES), x3 = lds128(a + 3 * KG_BYTES);
          auto s4 = [](uint32_t a0, uint32_t a1, uint32_t a2, uint32_t a3) {
            return __float_as_uint((__uint_as_float(a0) + __uint_as_float(a1)) + (__uint_as_float(a2) + __uint_as_float(a3)));
          };
          sts128(a, s4(x0.x, x1.x, x2.x, x3.x), s4(x0.y, x1.y, x2.y, x3.y), s4(x0.z, x1.z, x2.z, x3.z), s4(x0.w, x1.w, x2.w, x3.w));
        }
        __syncwarp();
        const float k1024 = lds_f32(kf + kidx_c(1024) * 4);
        if (lane == 0) {
          sts_f32(kf + SL_ZERO * 4, 0.f);
          sts_f32(kf + SL_510 * 4, lds_f32(kf + kidx_c(510) * 4) - lds_f32(kf + kidx_c(512) * 4));
          sts_f32(kf + SL_0 * 4, lds_f32(kf) + dskip);
        }
        __syncwarp();
        if (tid == 0) TS(36);
        mbar_wait_long(BAR(B_PFREE), 0);
        if (tid == 0) TS(37);
        {
          float prev = 0.f;
#pragma unroll 1
          for (int i0 = 0; i0 < 16; i0 += 4) {
            uint32_t e[4];
            float a[4], b[4];
#pragma unroll
            for (int i = 0; i < 4; ++i) e[i] = lds32(sb + SM_PTAB + ((i0 + i) * 32 + lane) * 4);
#pragma unroll
            for (int i = 0; i < 4; ++i) { a[i] = lds_f32(kf + (e[i] & 0xffff)); b[i] = lds_f32(kf + (e[i] >> 16)); }
#pragma unroll
            for (int i = 0; i < 4; ++i) {
              const uint32_t w = pb + (31 * lane + 2 * (i0 + i)) * 4;
              if (i0 + i > 0) sts32(w - 4, pack_bf16(a[i], prev));
              sts32(w, pack_bf16(b[i], a[i]));
              prev = b[i];
            }
          }
        }
        __syncwarp();
        if (lane == 0) TS(4);
        const int gq = g - 2 * q;
        uint32_t h127, h128;
        {
          const uint32_t kf2 = pack_bf16(k1024, k1024) ^ 0x80008000u;
          h127 = (gq == 4 ? 0x0000ffffu : gq == 5 ? 0xffffffffu : gq == 6 ? 0xffff0000u : 0u) & kf2;
          h128 = (gq == -4 ? 0x0000ffffu : gq == -3 ? 0xffffffffu : gq == -2 ? 0xffff0000u : 0u) & kf2;
        }
        if (lane == 0) TSR(10, 10 + warp);
        bar_sync(7, 128);
        mbar_wait_long(BAR(B_UCH + 3), 0);
        if (tid == 0) TS(14);
#pragma unroll 1
        for (int idx = warp; idx < 7; idx += 4) box_filters<4>(sb, bars, idx, lane);
        if (tid == 0) TS(15);
        bar_sync(5, 128);
        if (lane == 0) TS(6);
        bar_sync(4, 384);
        if (lane == 0) TS(7);
        float acc[16][4];
#pragma unroll
        for (int i = 0; i < 16; ++i) { acc[i][0] = acc[i][1] = acc[i][2] = acc[i][3] = 0.f; }
        {
          const uint32_t pd_lane = pb + (PD_OFF + 16 + gq) * 4;
          const int prow0 = 8 + (lane & 7) + ((lane >> 4) << 3), hs = (lane >> 3) & 1;
          const uint32_t zero = (uint32_t)cta >> 20;
          uint32_t B[2][4][4];
          uint32_t A[4][4];
          const uint32_t la0 = ub + prow0 * 32 + ((hs ^ ((prow0 >> 2) & 1)) << 4);
#pragma unroll
          for (int m2 = 0; m2 < 4; ++m2) ldsm_x4(B[0][m2], la0 + m2 * 512);
#pragma unroll
          for (int i = 0; i < 4; ++i) {
            const uint32_t a = pd_lane + i * 512;
            A[i][0] = lds32(a); A[i][1] = lds32(a + 32); A[i][2] = lds32(a - 32); A[i][3] = lds32(a + zero);
          }
          uint32_t la = la0;
#define UNR_RHO 8
#define UNR_TAIL 2
          constexpr int unr_rho = UNR_RHO, unr_tail = UNR_TAIL;
#pragma unroll unr_rho
          for (int rho = 0; rho < 8; ++rho) {
#pragma unroll
            for (int m2 = 0; m2 < 4; ++m2) ldsm_x4(B[1][m2], la + (4 + m2) * 512);
#pragma unroll
            for (int i = 0; i < 4; ++i)
#pragma unroll
              for (int m = 0; m < 8; ++m) mma_bf16v(acc[m + i], A[i], B[0][m >> 1][2 * (m & 1)], B[0][m >> 1][2 * (m & 1) + 1]);
            const int prow = prow0 - min(rho + 1, 7);
            la = ub + prow * 32 + ((hs ^ ((prow >> 2) & 1)) << 4);
#pragma unroll
            for (int m2 = 0; m2 < 4; ++m2) ldsm_x4(B[0][m2], la + m2 * 512);
            const uint32_t pa = pd_lane + (rho + 1) * 64;
#pragma unroll
            for (int i = 0; i < 4; ++i) {
#pragma unroll
              for (int m = 0; m < 8 - i; ++m)
                mma_bf16v(acc[8 + m + i], A[i], B[1][m >> 1][2 * (m & 1)], B[1][m >> 1][2 * (m & 1) + 1]);
              A[i][0] = lds32(pa + i * 512); A[i][1] = lds32(pa + i * 512 + 32); A[i][2] = lds32(pa + i * 512 - 32);
              A[i][3] = lds32(pa + i * 512 + zero);
            }
          }
          if (lane == 0) TS(40);
          {
            uint32_t b8[4];
            ldsm_x4(b8, la + 4 * 512);
            const uint32_t h63 = lds32(pd_lane + 63 * 32), h64 = lds32(pd_lane + 64 * 32);
            const uint32_t a63[4] = {0u, h127, 0u, 0u}, a32[4] = {h64, 0u, h63, h64}, a64[4] = {h128, 0u, h127, h128};
#pragma unroll
            for (int m2 = 0; m2 < 4; ++m2) ldsm_x4(B[1][m2], la0 + m2 * 512);
#pragma unroll
            for (int m = 0; m < 8; ++m) mma_bf16v(acc[m + 7], a63, B[0][m >> 1][2 * (m & 1)], B[0][m >> 1][2 * (m & 1) + 1]);
#pragma unroll
            for (int m2 = 0; m2 < 2; ++m2) ldsm_x4(B[0][m2], la0 + (4 + m2) * 512);
#pragma unroll
            for (int m = 0; m < 8; ++m) mma_bf16v(acc[m + 4], a32, B[1][m >> 1][2 * (m & 1)], B[1][m >> 1][2 * (m & 1) + 1]);
            mma_bf16v(acc[15], a63, b8[0], b8[1]);
#pragma unroll
            for (int m = 0; m < 8; ++m) mma_bf16v(acc[m + 8], a64, B[1][m >> 1][2 * (m & 1)], B[1][m >> 1][2 * (m & 1) + 1]);
#pragma unroll
            for (int m = 0; m < 4; ++m) mma_bf16v(acc[m + 12], a32, B[0][m >> 1][2 * (m & 1)], B[0][m >> 1][2 * (m & 1) + 1]);
          }
          if (lane == 0) TS(41);
#pragma unroll unr_tail
          for (int v = 0; v < 4; ++v)
            conv_tail<4, 3, 11>(acc, pb + (P2_OFF + 56 * v + gq - 16) * 4, vv + ((v & 1) ? VV_U3 : VV_U5), v >> 1, v == 0, lane);
          if (lane == 0) TS(42);
#pragma unroll unr_tail
          for (int pi = 0; pi < 2; ++pi)
            conv_tail<8, 5, 7>(acc, pb + (P3_OFF + 88 * pi + gq - 48) * 4, vv + (pi ? VV_U7 : VV_U9), pi, pi == 0, lane);
        }
        if (lane == 0) TS(8);
        __syncwarp();
        {
          const int mt = lane >> 3;
          const uint32_t a = pb + (128 * (mt >> 1) + 16 * (lane & 7) + 8 * (mt & 1)) * 2;
#pragma unroll
          for (int ab = 0; ab < 16; ab += 2)
            stsm_x4_t(a + ab * 256, pack_bf16(acc[ab][0], acc[ab][1]), pack_bf16(acc[ab][2], acc[ab][3]),
                      pack_bf16(acc[ab + 1][0], acc[ab + 1][1]), pack_bf16(acc[ab + 1][2], acc[ab + 1][3]));
        }
        fence_async_smem();
        __syncwarp();
        if (lane < 2) mbar_arrive_cluster(BAR(B_CONVD), lane);
        bar_arrive(3, 384);
        if (elect_one()) {
          bulk_store(p.yT + (size_t)d * 2048, pb, 4096);
          bulk_commit();
          bulk_wait0();
          red_relaxed_add(&g_cnt[(C_Y + (cta >> 4)) * 32], 1);
          TS(9);
        }
        bar_sync(2, 128);
        if (warp == 0 && elect_one()) {
          wait_counter(&g_cnt[(C_Y + tj) * 32], (epoch + 1) * 64);
          TS(28);
          mbar_expect_tx(BAR(B_TILE), 16384);
          tma_load_2d(sb + SM_U, &maps.yT, ti * 128, tj * 64, BAR(B_TILE));
          tma_load_2d(sb + SM_U + 8192, &maps.yT, ti * 128 + 64, tj * 64, BAR(B_TILE));
        }
        __syncwarp();
      }
      mbar_wait_long(BAR(B_TILE), pass);
      if (lane == 0) TS(26 + 3 * pass);
      {
        const int m = lane >> 3, r = lane & 7;
#pragma unroll 2
        for (int it = 0; it < 8; ++it) {
          const int tb = warp * 4 + (it >> 1), cb = (it & 1) * 4 + m;
          const uint32_t at = (tb * 8 + r) * 128 + ((cb ^ r) << 4);
          const uint32_t ac = (tb >> 3) * 8192 + (cb * 8 + r) * 128 + (((tb & 7) ^ (pass ? 0 : tb >> 3) ^ r) << 4);
          uint32_t v[4];
          ldsm_x4_t(v, sb + SM_U + (pass ? ac : at));
          stsm_x4(sb + SM_P + (pass ? at : ac), v[0], v[1], v[2], v[3]);
        }
      }
      if (pass == 0 && tid == 0) TS(35);
      fence_async_smem();
      if (pass == 0) {
        bar_arrive(6, 160);
      } else {
        bar_sync(2, 128);
        if (warp == 0 && elect_one()) {
          tma_store_2d(&maps.out, sb + SM_P, 64 * tj, 128 * ti);
          bulk_commit();
          bulk_wait_read0();
          TS(30);
        }
      }
    }
  } else if (warp < 12) {
    const int w8 = warp - 4;
    const int row = w8 * 16 + (lane & 7) + (((lane >> 3) & 1) << 3);
    uint32_t pq[16];
    {
      float acc[96];
#pragma unroll 1
      for (int ks = 0, s = 0, ph = 0; ks < 16; ++ks) {
        mbar_wait(BAR(B_FULL + s), ph);
        if (tid == 128 && !(ks & 1)) TSR(16, ks == 0 ? 16 : 9 + (ks >> 1) + (ks > 12 ? 43 : 0));
        const uint32_t st = sb + s * STG_BYTES;
        const uint32_t da = mkdesc(st + STG_X + (w8 >> 2) * 4096, 16);
        const uint32_t db = mkdesc(st + STG_W, 2048);
        wg_fence();
        wgmma_n192(acc, da, db, ks != 0);
        wgmma_n192(acc, da + 2, db + 384, 1);
        wg_commit();
        const uint32_t eprev = BAR(B_EMPTY + (s == 0 ? NSTG - 1 : s - 1));
        if (++s == NSTG) { s = 0; ph ^= 1; }
        if (ks > 0) {
          wg_wait<1>();
          if (lane < 2) mbar_arrive_cluster(eprev, lane);
        }
      }
      wg_wait<0>();
      if (tid == 128) TS(17);
      auto phi2 = [](float a, float b) -> uint32_t {
        const uint32_t x = pack_bf16(a, b);
        const uint32_t e = pack_bf16(ex2(a * 1.4426950408889634f), ex2(b * 1.4426950408889634f));
        const uint32_t m = __hgt2_mask(*reinterpret_cast<const __nv_bfloat162*>(&x), __floats2bfloat162_rn(0.f, 0.f));
        return badd((badd(x, 0x3f803f80u) & m) | (e & ~m), 0x35863586u);
      };
      uint32_t pk[16];
#pragma unroll
      for (int i = 0; i < 16; ++i) pk[i] = phi2(acc[32 + 2 * i], acc[33 + 2 * i]);
      if (tid == 128) TS(53);
      bar_sync(1, 256);
#pragma unroll
      for (int i = 0; i < 8; i += 2) {
        const uint32_t off = row * 128 + (((i + (lane >> 4)) ^ (row & 7)) << 4);
        stsm_x4(sb + SM_PK + off, pk[2 * i], pk[2 * i + 1], pk[2 * i + 2], pk[2 * i + 3]);
        stsm_x4(sb + SM_VS + off, pack_bf16(acc[64 + 4 * i], acc[65 + 4 * i]), pack_bf16(acc[66 + 4 * i], acc[67 + 4 * i]),
                pack_bf16(acc[68 + 4 * i], acc[69 + 4 * i]), pack_bf16(acc[70 + 4 * i], acc[71 + 4 * i]));
      }
      bar_sync(1, 256);
      {
        const int hh = w8 >> 1, dtile = w8 & 1;
        float kv[2][4] = {{0.f, 0.f, 0.f, 0.f}, {0.f, 0.f, 0.f, 0.f}}, zz[2][4] = {{0.f, 0.f, 0.f, 0.f}, {0.f, 0.f, 0.f, 0.f}};
        const int m = lane >> 3;
        const uint32_t aa = sb + SM_VS + ((lane & 7) + ((m >> 1) << 3)) * 128 + (((2 * hh + (m & 1)) ^ (lane & 7)) << 4);
        const uint32_t ab = sb + SM_PK + (lane & 15) * 128 + (((2 * hh + dtile) ^ (lane & 7)) << 4);
#pragma unroll
        for (int ks = 0; ks < 8; ++ks) {
          uint32_t a[4], b0, b1;
          ldsm_x4_t(a, aa + ks * 2048);
          ldsm_x2_t(b0, b1, ab + ks * 2048);
          mma_bf16(kv[ks & 1], a[0], a[1], a[2], a[3], b0, b1);
          mma_bf16(zz[ks & 1], 0x3f803f80u, 0x3f803f80u, 0x3f803f80u, 0x3f803f80u, b0, b1);
        }
        const uint32_t kp = sb + SM_KV + hh * 1088;
        sts128(kp + dtile * 512 + lane * 16, __float_as_uint(kv[0][0] + kv[1][0]), __float_as_uint(kv[0][1] + kv[1][1]),
               __float_as_uint(kv[0][2] + kv[1][2]), __float_as_uint(kv[0][3] + kv[1][3]));
        if (g == 0) sts_f32x2(kp + 1024 + dtile * 32 + q * 8, zz[0][0] + zz[1][0], zz[0][1] + zz[1][1]);
        fence_async_smem();
        __syncwarp();
        if (lane == 0) mbar_arrive(BAR(B_KVP));
        bar_arrive(4, 384);
        if (tid == 128) TS(55);
      }
#pragma unroll
      for (int i = 0; i < 16; ++i) pq[i] = phi2(acc[2 * i], acc[2 * i + 1]);
    }
    if (tid == 128) TS(56);
    if (warp == 4) mbar_wait_long(BAR(B_KVF), 0);
    bar_sync(1, 256);
    if (tid == 128) TS(19);
    {
      uint32_t kb[4][6];
#pragma unroll
      for (int h = 0; h < 4; ++h) {
        const uint32_t kp = sb + SM_KV + h * 1088;
        const uint4 k0 = lds128(kp + lane * 16), k1 = lds128(kp + 512 + lane * 16);
        const uint32_t za = kp + 1024 + q * 8;
        auto pk2 = [](uint32_t x, uint32_t y) { return pack_bf16(__uint_as_float(x), __uint_as_float(y)); };
        kb[h][0] = pk2(k0.x, k0.y); kb[h][1] = pk2(k1.x, k1.y); kb[h][2] = pk2(k0.z, k0.w); kb[h][3] = pk2(k1.z, k1.w);
        kb[h][4] = pack_bf16(lds_f32(za), lds_f32(za + 4)); kb[h][5] = pack_bf16(lds_f32(za + 32), lds_f32(za + 36));
      }
#pragma unroll
      for (int h = 0; h < 4; ++h) {
        float n0[4] = {0.f, 0.f, 0.f, 0.f}, n1[4] = {0.f, 0.f, 0.f, 0.f}, dn[4] = {0.f, 0.f, 0.f, 0.f};
        mma_bf16(n0, pq[4 * h], pq[4 * h + 1], pq[4 * h + 2], pq[4 * h + 3], kb[h][0], kb[h][1]);
        mma_bf16(n1, pq[4 * h], pq[4 * h + 1], pq[4 * h + 2], pq[4 * h + 3], kb[h][2], kb[h][3]);
        mma_bf16(dn, pq[4 * h], pq[4 * h + 1], pq[4 * h + 2], pq[4 * h + 3], kb[h][4], kb[h][5]);
        const float r0 = rcp(dn[0] + 1e-6f), r1 = rcp(dn[2] + 1e-6f);
        stsm_x4(sb + SM_QS + row * 128 + (((2 * h + (lane >> 4)) ^ (row & 7)) << 4),
                pack_bf16(n0[0] * r0, n0[1] * r0), pack_bf16(n0[2] * r1, n0[3] * r1),
                pack_bf16(n1[0] * r0, n1[1] * r0), pack_bf16(n1[2] * r1, n1[3] * r1));
      }
    }
    fence_async_smem();
    __syncwarp();
    if (lane == 0) mbar_arrive(BAR(B_OST));
    if (tid == 128) TS(57);
    if (warp == 4) mbar_wait_long(BAR(B_WO), 0);
    bar_sync(3, 384);
    {
      float o[32];
#pragma unroll 1
      for (int c = 0; c < 8; ++c) {
        mbar_wait_long(BAR(B_RF + c), 0);
        if (tid == 128) TSR(22, c == 0 ? 22 : 43 + c);
        const uint32_t slot = c < 4 ? SM_QS + c * 16384 : c < 7 ? SM_VV + (c - 4) * 16384 : SM_QS;
        const uint32_t da = mkdesc(sb + slot + (w8 >> 2) * 8192, 16);
        const uint32_t db = mkdesc(sb + SM_WO + c * 8192, 8192);
        wg_fence();
#pragma unroll
        for (int k = 0; k < 4; ++k) wgmma_n64(o, da + 2 * k, db + 128 * k, (c | k) != 0);
        wg_commit();
        if (c == 1) {
          wg_wait<1>();
          if (lane < 2) mbar_arrive_cluster(BAR(B_RE), lane);
        }
      }
      wg_wait<0>();
      if (tid == 128) TS(51);
#pragma unroll
      for (int i = 0; i < 8; i += 2)
        stsm_x4(sb + SM_BOUT + row * 128 + (((i + (lane >> 4)) ^ (row & 7)) << 4), pack_bf16(o[4 * i], o[4 * i + 1]),
                pack_bf16(o[4 * i + 2], o[4 * i + 3]), pack_bf16(o[4 * i + 4], o[4 * i + 5]), pack_bf16(o[4 * i + 6], o[4 * i + 7]));
      fence_async_smem();
      bar_sync(8 + (w8 >> 2), 128);
      if ((w8 & 3) == 0 && elect_one()) {
        tma_store_2d(&maps.outh, sb + SM_BOUT + (w8 >> 2) * 8192, 512 + 64 * pj, 128 * pi + (w8 >> 2) * 64);
        bulk_commit();
        bulk_wait_read0();
        TS(23);
      }
    }
  } else {
    asm volatile("setmaxnreg.dec.sync.aligned.u32 40;");
    if (warp == 12) {
      if (elect_one()) {
#pragma unroll 1
        for (int ks = NSTG, s = 0, ph = 0; ks < 16; ++ks) {
          mbar_wait(BAR(B_EMPTY + s), ph);
          issue_stage(ks, s);
          if (ks == NSTG) l2_prefetch((const char*)p.wo + (size_t)cta * 4096, 4096);
          if (++s == NSTG) { s = 0; ph ^= 1; }
        }
        mbar_wait(BAR(B_EMPTY + 6), 1);
        mbar_expect_tx(BAR(B_WO), 65536);
        tma_load_2d(sb + SM_WO, &maps.wo, pj * 64, 0, BAR(B_WO));
        tma_load_2d(sb + SM_WO + 32768, &maps.wo, pj * 64, 256, BAR(B_WO));
        float* kvg = &g_kv[epoch & 1][tj][0];
        mbar_wait_long(BAR(B_KVP), 0);
        bulk_reduce_add_f32(kvg, sb + SM_KV, 4352);
        bulk_commit();
        bulk_wait0();
        red_relaxed_add(&g_cnt[(C_KV + tj) * 32], 1);
        TS(18);
        wait_counter(&g_cnt[(C_KV + tj) * 32], (epoch + 1) * 16);
        mbar_expect_tx(BAR(B_KVF), 4352);
        bulk_load(sb + SM_KV, kvg, 4352, BAR(B_KVF));
        mbar_wait_long(BAR(B_OST), 0);
        tma_store_2d(&maps.o, sb + SM_QS, tj * 64, ti * 128);
        tma_store_2d(&maps.o, sb + SM_QS + 8192, tj * 64, ti * 128 + 64);
        bulk_commit();
        bulk_wait0();
        red_relaxed_add(&g_cnt[(C_O + ti) * 32], 1);
        TS(20);
        mbar_arrive_cluster(BAR(B_SLOT), 0);
        mbar_arrive_cluster(BAR(B_SLOT), 1);
        wait_counter(&g_cnt[(C_O + pi) * 32], (epoch + 1) * 8);
        if (cta == 0) g_epoch = epoch + 1;
        mbar_wait(BAR(B_SLOT), 0);
        TS(21);
#pragma unroll 1
        for (int c = 0; c < 8; ++c) {
          if (c == 4) mbar_wait_long(BAR(B_CONVD), 0);
          if (c == 7) mbar_wait(BAR(B_RE), 0);
          const uint32_t slot = c < 4 ? SM_QS + c * 16384 : c < 7 ? SM_VV + (c - 4) * 16384 : SM_QS;
          mbar_expect_tx(BAR(B_RF + c), 16384);
          tma_load_2d_mc(sb + slot + rank * 8192, &maps.o, c * 64, pi * 128 + rank * 64, BAR(B_RF + c), 3);
        }
      }
    } else if (warp == 13) {
      bar_sync(6, 160);
      sts128(sb + SM_U + (lane >> 4) * U_BYTES + (lane & 15) * 16, 0, 0, 0, 0);
      sts128(sb + SM_U + (2 + (lane >> 4)) * U_BYTES + (lane & 15) * 16, 0, 0, 0, 0);
      __syncwarp();
      if (elect_one()) {
        tma_store_2d(&maps.uT, sb + SM_P, ti * 128, tj * 64);
        tma_store_2d(&maps.uT, sb + SM_P + 8192, ti * 128 + 64, tj * 64);
        bulk_commit();
        bulk_wait_read0();
        mbar_arrive(BAR(B_PFREE));
        bulk_wait0();
        red_relaxed_add(&g_cnt[(C_U + tj) * 32], 1);
        TS(27);
        wait_counter(&g_cnt[(C_U + (cta >> 4)) * 32], (epoch + 1) * 16);
#pragma unroll 1
        for (int c = 0; c < 4; ++c) {
          mbar_expect_tx(BAR(B_UCH + c), 4096);
          bulk_load(sb + SM_U + c * U_BYTES + 256, p.uT + (size_t)(cta * 4 + c) * 2048, 4096, BAR(B_UCH + c));
        }
        TS(3);
      }
      __syncwarp();
      if (ti == 0) {
        float4* z = (float4*)&g_kv[(epoch & 1) ^ 1][tj][0];
#pragma unroll 1
        for (int i = lane; i < 272; i += 32) z[i] = make_float4(0.f, 0.f, 0.f, 0.f);
      }
    }
  }
  __syncwarp();
  cluster_arrive();
  cluster_wait();
  if (tid == 0) TS(31);
#undef BAR
}

typedef CUresult (*EncodeFn)(CUtensorMap*, CUtensorMapDataType, cuuint32_t, void*, const cuuint64_t*, const cuuint64_t*,
                             const cuuint32_t*, const cuuint32_t*, CUtensorMapInterleave, CUtensorMapSwizzle,
                             CUtensorMapL2promotion, CUtensorMapFloatOOBfill);

static void make_map(EncodeFn enc, CUtensorMap* m, const void* base, uint64_t inner, uint64_t outer, uint32_t box_in,
                     uint32_t box_out, CUtensorMapSwizzle swz = CU_TENSOR_MAP_SWIZZLE_128B) {
  cuuint64_t gd[2] = {inner, outer};
  cuuint64_t gs[1] = {inner * 2};
  cuuint32_t bd[2] = {box_in, box_out};
  cuuint32_t es[2] = {1, 1};
  enc(m, CU_TENSOR_MAP_DATA_TYPE_BFLOAT16, 2, const_cast<void*>(base), gd, gs, bd, es, CU_TENSOR_MAP_INTERLEAVE_NONE,
      swz, CU_TENSOR_MAP_L2_PROMOTION_L2_128B, CU_TENSOR_MAP_FLOAT_OOB_FILL_NONE);
}

}

extern "C" void kernel_launch(void* const* d_in, const int* in_sizes, int n_in, void* d_out, int out_size) {
  using namespace s4la;
  (void)in_sizes; (void)n_in; (void)out_size;
  static EncodeFn enc = nullptr;
  static void *uT = nullptr, *yT = nullptr, *oS = nullptr;
  if (!enc) {
    void* fn = nullptr;
    cudaDriverEntryPointQueryResult qr;
    cudaGetDriverEntryPoint("cuTensorMapEncodeTiled", &fn, cudaEnableDefault, &qr);
    enc = (EncodeFn)fn;
    cudaGetSymbolAddress(&uT, g_uT);
    cudaGetSymbolAddress(&yT, g_yT);
    cudaGetSymbolAddress(&oS, g_o);
    cudaFuncSetAttribute(fused_kernel, cudaFuncAttributeMaxDynamicSharedMemorySize, SM_TOTAL);
  }
  const __nv_bfloat16* const* in = (const __nv_bfloat16* const*)d_in;
  Maps maps;
  make_map(enc, &maps.x, in[9], 512, 2048, 32, 128, CU_TENSOR_MAP_SWIZZLE_64B);
  {
    cuuint64_t gd[3] = {512, 512, 3};
    cuuint64_t gs[2] = {3072, 1024};
    cuuint32_t bd[3] = {64, 16, 3};
    cuuint32_t es[3] = {1, 1, 1};
    enc(&maps.w, CU_TENSOR_MAP_DATA_TYPE_BFLOAT16, 3, const_cast<__nv_bfloat16*>(in[10]), gd, gs, bd, es,
        CU_TENSOR_MAP_INTERLEAVE_NONE, CU_TENSOR_MAP_SWIZZLE_128B, CU_TENSOR_MAP_L2_PROMOTION_L2_128B,
        CU_TENSOR_MAP_FLOAT_OOB_FILL_NONE);
  }
  make_map(enc, &maps.wo, in[11], 512, 512, 64, 256);
  make_map(enc, &maps.u, in[0], 512, 2048, 64, 128);
  make_map(enc, &maps.uT, uT, 2048, 512, 64, 64);
  make_map(enc, &maps.yT, yT, 2048, 512, 64, 64);
  make_map(enc, &maps.o, oS, 512, 2048, 64, 64);
  make_map(enc, &maps.out, d_out, 1024, 2048, 64, 128);
  make_map(enc, &maps.outh, d_out, 1024, 2048, 64, 64);
  Ptrs p;
  p.A_re = in[1]; p.A_im = in[2]; p.B_re = in[3]; p.B_im = in[4]; p.C_re = in[5]; p.C_im = in[6];
  p.log_dt = in[7]; p.Dskip = in[8]; p.x = in[9]; p.wqkv = in[10]; p.wo = in[11];
  p.uT = (__nv_bfloat16*)uT; p.yT = (__nv_bfloat16*)yT;
  fused_kernel<<<NCTA, NTHREADS, SM_TOTAL, cudaStreamPerThread>>>(maps, p);
}
```

```cpp
#include <cuda_runtime.h>
#include <cuda_bf16.h>
#include <cuda_fp16.h>
#include <cuda.h>
#include <stdint.h>

#define DEVI __device__ __forceinline__

namespace s4la {

constexpr int NTHREADS = 512;
constexpr int NCTA = 128;

constexpr int NSTG = 7;
constexpr uint32_t STG_BYTES = 20480, STG_X = 0, STG_W = 8192;
constexpr uint32_t SM_QS = 0;
constexpr uint32_t SM_PK = SM_QS + 16384, SM_VS = SM_QS + 32768;
constexpr uint32_t SM_WO = 65536;
constexpr uint32_t SM_KV = 131072;
constexpr uint32_t SM_BOUT = 16384;
constexpr uint32_t SM_U = 143360, U_BYTES = 4352;
constexpr uint32_t SM_P = 160768, P_BYTES = 4096;
constexpr uint32_t SM_VV = 177152, VV_BYTES = 12800;
constexpr uint32_t VV_U5 = 0, VV_U3 = 3712, VV_U9 = 7424, VV_U7 = 10112;
constexpr uint32_t KG_BYTES = 3200;
constexpr uint32_t SM_BAR = SM_VV + 4 * VV_BYTES;
constexpr uint32_t SM_PTAB = SM_BAR + 320;
constexpr uint32_t SM_TOTAL = SM_PTAB + 2048;
static_assert(SM_TOTAL <= 232448, "shared memory");
constexpr int PADV = 12;

enum { B_FULL = 0, B_EMPTY = 7, B_TILE = 14, B_UCH = 15, B_KVP = 19, B_KVF = 20, B_OST = 21, B_RF = 22, B_WO = 30, B_RE = 31, B_PFREE = 32, B_CONVD = 33, B_SLOT = 34, B_COUNT = 35 };
__host__ __device__ constexpr int bar_count(int i) {
  return (i >= B_EMPTY && i < B_TILE) ? 16 : (i == B_KVP || i == B_OST || i == B_CONVD) ? 8 : i == B_RE ? 16 : i == B_SLOT ? 2 : 1;
}

constexpr int PD_OFF = 0, P2_OFF = 544, P3_OFF = 768;

constexpr int SL_K2048 = 20, SL_ZERO = 21, SL_510 = 22, SL_0 = 23;
__host__ __device__ constexpr int koff(int y) {
  return y < 8 ? y : y < 12 ? 256 + 2 * (y - 8) : y < 16 ? 512 + 256 * ((y - 12) >> 1) + 4 * (y & 1) : 1024 + 256 * (y - 16);
}
__host__ __device__ constexpr int kidx_c(int l) {
  const int y = l < 256 ? (l & 7) : l < 512 ? 8 + ((l & 7) >> 1) : l < 1024 ? 12 + (((l - 512) >> 8) << 1) + ((l >> 2) & 1)
                                                                            : 16 + ((l - 1024) >> 8);
  return ((l >> 3) & 31) * 24 + y;
}
constexpr int slot_direct(int l) {
  if (l < 0 || l > 510) return SL_ZERO;
  if (l == 510) return SL_510;
  if (l == 0) return SL_0;
  return kidx_c(l < 256 ? l : ((l + ((l >> 1) & 1)) & ~1));
}
constexpr int slot_seg2(int v, int k) { return (k >= 32 && k < 64) ? kidx_c(16 * k + 4 * v) : SL_ZERO; }
constexpr int slot_seg3(int pi, int k) {
  return (k >= 64 && k < 128) ? kidx_c(16 * k + 8 * pi) : ((k == 128 && pi == 0) ? SL_K2048 : SL_ZERO);
}
constexpr int slot_word(int w) {
  return w < 0 ? SL_ZERO : w < 544 ? slot_direct(w - 16) : w < 768 ? slot_seg2((w - 544) / 56, 16 + (w - 544) % 56)
       : w < 944 ? slot_seg3((w - 768) / 88, 48 + (w - 768) % 88) : SL_ZERO;
}
struct PTab { uint32_t v[512]; };
constexpr PTab make_ptab() {
  PTab t{};
  for (int lane = 0; lane < 32; ++lane)
    for (int i = 0; i < 16; ++i)
      t.v[i * 32 + lane] = (slot_word(31 * lane - 1 + 2 * i) * 4) | ((slot_word(31 * lane + 2 * i) * 4) << 16);
  return t;
}
__device__ const PTab g_ptab = make_ptab();

__device__ __nv_bfloat16 g_uT[512 * 2048];
__device__ __nv_bfloat16 g_yT[512 * 2048];
__device__ __nv_bfloat16 g_o[2048 * 512];
__device__ float g_kv[2][8][4 * 272];
__device__ unsigned g_cnt[64 * 32];
__device__ unsigned g_epoch;
#define TS(slot) do { } while (0)
#define TSR(on, slot) do { } while (0)
#define TSD(slot) do { } while (0)
enum { C_U = 0, C_KV = 8, C_O = 16, C_Y = 32 };

struct Maps {
  CUtensorMap x, w, wo, u, uT, yT, o, out, outh;
};
struct Ptrs {
  const __nv_bfloat16 *A_re, *A_im, *B_re, *B_im, *C_re, *C_im, *log_dt, *Dskip;
  const __nv_bfloat16 *x, *wqkv, *wo;
  __nv_bfloat16 *uT, *yT;
};

DEVI uint32_t s2u(const void* p) { return (uint32_t)__cvta_generic_to_shared(p); }
DEVI void mbar_init(uint32_t b, uint32_t c) { asm volatile("mbarrier.init.shared::cta.b64 [%0], %1;" ::"r"(b), "r"(c) : "memory"); }
DEVI void mbar_expect_tx(uint32_t b, uint32_t bytes) {
  asm volatile("mbarrier.arrive.expect_tx.shared::cta.b64 _, [%0], %1;" ::"r"(b), "r"(bytes) : "memory");
}
DEVI void mbar_arrive(uint32_t b) { asm volatile("mbarrier.arrive.shared::cta.b64 _, [%0];" ::"r"(b) : "memory"); }
DEVI void mbar_arrive_cluster(uint32_t b, uint32_t cta) {
  asm volatile("{\n.reg .b32 r;\nmapa.shared::cluster.u32 r, %0, %1;\nmbarrier.arrive.shared::cluster.b64 _, [r];\n}"
               ::"r"(b), "r"(cta) : "memory");
}
DEVI void mbar_wait(uint32_t b, uint32_t parity) {
  asm volatile("{\n.reg .pred p;\nLAB_WAIT:\nmbarrier.try_wait.parity.shared::cta.b64 p, [%0], %1;\n@!p bra LAB_WAIT;\n}"
               ::"r"(b), "r"(parity) : "memory");
}
DEVI void mbar_wait_long(uint32_t b, uint32_t parity) {
  asm volatile("{\n.reg .pred p;\nLAB_WAIT:\nmbarrier.try_wait.parity.shared::cta.b64 p, [%0], %1, 0x989680;\n@!p bra LAB_WAIT;\n}"
               ::"r"(b), "r"(parity) : "memory");
}
DEVI void bar_sync(int id, int n) { asm volatile("bar.sync %0, %1;" ::"r"(id), "r"(n) : "memory"); }
DEVI void bar_arrive(int id, int n) { asm volatile("bar.arrive %0, %1;" ::"r"(id), "r"(n) : "memory"); }
DEVI void fence_async_smem() { asm volatile("fence.proxy.async.shared::cta;" ::: "memory"); }
DEVI void fence_async_all() { asm volatile("fence.proxy.async;" ::: "memory"); }
DEVI void cluster_arrive() { asm volatile("barrier.cluster.arrive.relaxed.aligned;" ::: "memory"); }
DEVI void cluster_wait() { asm volatile("barrier.cluster.wait.aligned;" ::: "memory"); }

DEVI void tma_load_2d(uint32_t dst, const CUtensorMap* m, int c0, int c1, uint32_t bar) {
  asm volatile("cp.async.bulk.tensor.2d.shared::cluster.global.mbarrier::complete_tx::bytes [%0], [%1, {%3, %4}], [%2];"
               ::"r"(dst), "l"(m), "r"(bar), "r"(c0), "r"(c1) : "memory");
}
DEVI void tma_load_2d_mc(uint32_t dst, const CUtensorMap* m, int c0, int c1, uint32_t bar, uint16_t mask) {
  asm volatile("cp.async.bulk.tensor.2d.shared::cluster.global.mbarrier::complete_tx::bytes.multicast::cluster [%0], [%1, {%3, %4}], [%2], %5;"
               ::"r"(dst), "l"(m), "r"(bar), "r"(c0), "r"(c1), "h"(mask) : "memory");
}
DEVI void tma_load_3d_mc(uint32_t dst, const CUtensorMap* m, int c0, int c1, int c2, uint32_t bar, uint16_t mask) {
  asm volatile("cp.async.bulk.tensor.3d.shared::cluster.global.mbarrier::complete_tx::bytes.multicast::cluster [%0], [%1, {%3, %4, %5}], [%2], %6;"
               ::"r"(dst), "l"(m), "r"(bar), "r"(c0), "r"(c1), "r"(c2), "h"(mask) : "memory");
}
DEVI void tma_store_2d(const CUtensorMap* m, uint32_t src, int c0, int c1) {
  asm volatile("cp.async.bulk.tensor.2d.global.shared::cta.bulk_group [%0, {%2, %3}], [%1];"
               ::"l"(m), "r"(src), "r"(c0), "r"(c1) : "memory");
}
DEVI void bulk_load(uint32_t dst, const void* src, uint32_t bytes, uint32_t bar) {
  asm volatile("cp.async.bulk.shared::cluster.global.mbarrier::complete_tx::bytes [%0], [%1], %2, [%3];"
               ::"r"(dst), "l"(src), "r"(bytes), "r"(bar) : "memory");
}
DEVI void bulk_store(void* dst, uint32_t src, uint32_t bytes) {
  asm volatile("cp.async.bulk.global.shared::cta.bulk_group [%0], [%1], %2;" ::"l"(dst), "r"(src), "r"(bytes) : "memory");
}
DEVI void bulk_reduce_add_f32(void* dst, uint32_t src, uint32_t bytes) {
  asm volatile("cp.reduce.async.bulk.global.shared::cta.bulk_group.add.f32 [%0], [%1], %2;" ::"l"(dst), "r"(src), "r"(bytes) : "memory");
}
DEVI void bulk_commit() { asm volatile("cp.async.bulk.commit_group;" ::: "memory"); }
DEVI void bulk_wait0() { asm volatile("cp.async.bulk.wait_group 0;" ::: "memory"); }
DEVI void bulk_wait_read0() { asm volatile("cp.async.bulk.wait_group.read 0;" ::: "memory"); }
DEVI void l2_prefetch(const void* p, uint32_t bytes) {
  asm volatile("cp.async.bulk.prefetch.L2.global [%0], %1;" ::"l"(p), "r"(bytes) : "memory");
}
DEVI void prefetch_tmap(const CUtensorMap* m) { asm volatile("prefetch.tensormap [%0];" ::"l"(m) : "memory"); }

DEVI void red_release_add(unsigned* p, unsigned v) {
  asm volatile("red.release.gpu.global.add.u32 [%0], %1;" ::"l"(p), "r"(v) : "memory");
}
DEVI void red_relaxed_add(unsigned* p, unsigned v) {
  asm volatile("red.relaxed.gpu.global.add.u32 [%0], %1;" ::"l"(p), "r"(v) : "memory");
}
DEVI unsigned ld_relaxed(const unsigned* p) {
  unsigned v;
  asm volatile("ld.relaxed.gpu.global.u32 %0, [%1];" : "=r"(v) : "l"(p) : "memory");
  return v;
}
DEVI void wait_counter(const unsigned* p, unsigned target) {
#pragma unroll 1
  for (int it = 0; (int)(ld_relaxed(p) - target) < 0; ++it)
    if (it > (1 << 22)) __trap();
}

DEVI void ldsm_x4(uint32_t (&r)[4], uint32_t a) {
  asm volatile("ldmatrix.sync.aligned.m8n8.x4.shared.b16 {%0,%1,%2,%3}, [%4];"
               : "=r"(r[0]), "=r"(r[1]), "=r"(r[2]), "=r"(r[3]) : "r"(a) : "memory");
}
DEVI void ldsm_x4_t(uint32_t (&r)[4], uint32_t a) {
  asm volatile("ldmatrix.sync.aligned.m8n8.x4.trans.shared.b16 {%0,%1,%2,%3}, [%4];"
               : "=r"(r[0]), "=r"(r[1]), "=r"(r[2]), "=r"(r[3]) : "r"(a) : "memory");
}
DEVI void ldsm_x2_t(uint32_t& r0, uint32_t& r1, uint32_t a) {
  asm volatile("ldmatrix.sync.aligned.m8n8.x2.trans.shared.b16 {%0,%1}, [%2];" : "=r"(r0), "=r"(r1) : "r"(a) : "memory");
}
DEVI void stsm_x4(uint32_t a, uint32_t r0, uint32_t r1, uint32_t r2, uint32_t r3) {
  asm volatile("stmatrix.sync.aligned.m8n8.x4.shared.b16 [%0], {%1,%2,%3,%4};"
               ::"r"(a), "r"(r0), "r"(r1), "r"(r2), "r"(r3) : "memory");
}
DEVI void stsm_x4_t(uint32_t a, uint32_t r0, uint32_t r1, uint32_t r2, uint32_t r3) {
  asm volatile("stmatrix.sync.aligned.m8n8.x4.trans.shared.b16 [%0], {%1,%2,%3,%4};"
               ::"r"(a), "r"(r0), "r"(r1), "r"(r2), "r"(r3) : "memory");
}
DEVI uint32_t lds32(uint32_t a) { uint32_t v; asm volatile("ld.shared.b32 %0, [%1];" : "=r"(v) : "r"(a) : "memory"); return v; }
DEVI float lds_f32(uint32_t a) { float v; asm volatile("ld.shared.f32 %0, [%1];" : "=f"(v) : "r"(a) : "memory"); return v; }
DEVI void sts32(uint32_t a, uint32_t v) { asm volatile("st.shared.b32 [%0], %1;" ::"r"(a), "r"(v) : "memory"); }
DEVI void sts_f32(uint32_t a, float v) { asm volatile("st.shared.f32 [%0], %1;" ::"r"(a), "f"(v) : "memory"); }
DEVI void sts_f32x2(uint32_t a, float x, float y) { asm volatile("st.shared.v2.f32 [%0], {%1,%2};" ::"r"(a), "f"(x), "f"(y) : "memory"); }
DEVI uint4 lds128(uint32_t a) {
  uint4 v;
  asm volatile("ld.shared.v4.b32 {%0,%1,%2,%3}, [%4];" : "=r"(v.x), "=r"(v.y), "=r"(v.z), "=r"(v.w) : "r"(a) : "memory");
  return v;
}
DEVI void sts128(uint32_t a, uint32_t x, uint32_t y, uint32_t z, uint32_t w) {
  asm volatile("st.shared.v4.b32 [%0], {%1,%2,%3,%4};" ::"r"(a), "r"(x), "r"(y), "r"(z), "r"(w) : "memory");
}

DEVI void mma_bf16(float (&d)[4], uint32_t a0, uint32_t a1, uint32_t a2, uint32_t a3, uint32_t b0, uint32_t b1) {
  asm("mma.sync.aligned.m16n8k16.row.col.f32.bf16.bf16.f32 {%0,%1,%2,%3}, {%4,%5,%6,%7}, {%8,%9}, {%0,%1,%2,%3};"
      : "+f"(d[0]), "+f"(d[1]), "+f"(d[2]), "+f"(d[3])
      : "r"(a0), "r"(a1), "r"(a2), "r"(a3), "r"(b0), "r"(b1));
}
DEVI void mma_f16(float (&d)[4], const uint32_t (&a)[4], uint32_t b0, uint32_t b1) {
  asm("mma.sync.aligned.m16n8k16.row.col.f32.f16.f16.f32 {%0,%1,%2,%3}, {%4,%5,%6,%7}, {%8,%9}, {%0,%1,%2,%3};"
      : "+f"(d[0]), "+f"(d[1]), "+f"(d[2]), "+f"(d[3])
      : "r"(a[0]), "r"(a[1]), "r"(a[2]), "r"(a[3]), "r"(b0), "r"(b1));
}
DEVI void mma_bf16v(float (&d)[4], const uint32_t (&a)[4], uint32_t b0, uint32_t b1) {
  asm volatile("mma.sync.aligned.m16n8k16.row.col.f32.bf16.bf16.f32 {%0,%1,%2,%3}, {%4,%5,%6,%7}, {%8,%9}, {%0,%1,%2,%3};"
               : "+f"(d[0]), "+f"(d[1]), "+f"(d[2]), "+f"(d[3])
               : "r"(a[0]), "r"(a[1]), "r"(a[2]), "r"(a[3]), "r"(b0), "r"(b1));
}
DEVI uint32_t pack_bf16(float lo, float hi) {
  uint32_t r;
  asm("cvt.rn.bf16x2.f32 %0, %1, %2;" : "=r"(r) : "f"(hi), "f"(lo));
  return r;
}
DEVI uint32_t pack_f16(float lo, float hi) {
  uint32_t r;
  asm("cvt.rn.f16x2.f32 %0, %1, %2;" : "=r"(r) : "f"(hi), "f"(lo));
  return r;
}
DEVI uint32_t ldg16(const __nv_bfloat16* p) {
  uint32_t v;
  asm volatile("ld.global.nc.u16 %0, [%1];" : "=r"(v) : "l"(p));
  return v;
}
DEVI bool elect_one() {
  uint32_t pred;
  asm volatile("{\n.reg .pred p;\nelect.sync _|p, 0xffffffff;\nselp.u32 %0, 1, 0, p;\n}" : "=r"(pred));
  return pred != 0;
}
DEVI float bf_lo(uint32_t v) { return __uint_as_float(v << 16); }
DEVI float bf_hi(uint32_t v) { return __uint_as_float(v & 0xffff0000u); }
DEVI float bf2f(__nv_bfloat16 v) { return __bfloat162float(v); }
DEVI float round_bf16(float v) { return __bfloat162float(__float2bfloat16_rn(v)); }
DEVI float rcp(float x) { float r; asm("rcp.approx.ftz.f32 %0, %1;" : "=f"(r) : "f"(x)); return r; }
DEVI float ex2(float x) { float r; asm("ex2.approx.ftz.f32 %0, %1;" : "=f"(r) : "f"(x)); return r; }

DEVI void wg_fence() { asm volatile("wgmma.fence.sync.aligned;" ::: "memory"); }
DEVI void wg_commit() { asm volatile("wgmma.commit_group.sync.aligned;" ::: "memory"); }
template <int N> DEVI void wg_wait() { asm volatile("wgmma.wait_group.sync.aligned %0;" ::"n"(N) : "memory"); }
constexpr uint32_t DESC_HI = (1u << 30) | (1024 >> 4);
constexpr uint32_t DESC_HI64 = (2u << 30) | (512 >> 4);
DEVI uint32_t mkdesc(uint32_t saddr, uint32_t lbo) { return ((saddr & 0x3FFFF) >> 4) | ((lbo >> 4) << 16); }

#define R8(b) "%" #b
DEVI void wgmma_n192(float (&d)[96], uint32_t da, uint32_t db, int scale_d) {
  asm volatile(
      "{\n.reg .pred p;\n.reg .b64 da, db;\nsetp.ne.b32 p, %98, 0;\nmov.b64 da, {%96, %100};\nmov.b64 db, {%97, %99};\n"
      "wgmma.mma_async.sync.aligned.m64n192k16.f32.bf16.bf16 "
      "{%0,%1,%2,%3,%4,%5,%6,%7,%8,%9,%10,%11,%12,%13,%14,%15,"
      "%16,%17,%18,%19,%20,%21,%22,%23,%24,%25,%26,%27,%28,%29,%30,%31,"
      "%32,%33,%34,%35,%36,%37,%38,%39,%40,%41,%42,%43,%44,%45,%46,%47,"
      "%48,%49,%50,%51,%52,%53,%54,%55,%56,%57,%58,%59,%60,%61,%62,%63,"
      "%64,%65,%66,%67,%68,%69,%70,%71,%72,%73,%74,%75,%76,%77,%78,%79,"
      "%80,%81,%82,%83,%84,%85,%86,%87,%88,%89,%90,%91,%92,%93,%94,%95}, "
      "da, db, p, 1, 1, 0, 1;\n}"
      : "+f"(d[0]), "+f"(d[1]), "+f"(d[2]), "+f"(d[3]), "+f"(d[4]), "+f"(d[5]), "+f"(d[6]), "+f"(d[7]),
        "+f"(d[8]), "+f"(d[9]), "+f"(d[10]), "+f"(d[11]), "+f"(d[12]), "+f"(d[13]), "+f"(d[14]), "+f"(d[15]),
        "+f"(d[16]), "+f"(d[17]), "+f"(d[18]), "+f"(d[19]), "+f"(d[20]), "+f"(d[21]), "+f"(d[22]), "+f"(d[23]),
        "+f"(d[24]), "+f"(d[25]), "+f"(d[26]), "+f"(d[27]), "+f"(d[28]), "+f"(d[29]), "+f"(d[30]), "+f"(d[31]),
        "+f"(d[32]), "+f"(d[33]), "+f"(d[34]), "+f"(d[35]), "+f"(d[36]), "+f"(d[37]), "+f"(d[38]), "+f"(d[39]),
        "+f"(d[40]), "+f"(d[41]), "+f"(d[42]), "+f"(d[43]), "+f"(d[44]), "+f"(d[45]), "+f"(d[46]), "+f"(d[47]),
        "+f"(d[48]), "+f"(d[49]), "+f"(d[50]), "+f"(d[51]), "+f"(d[52]), "+f"(d[53]), "+f"(d[54]), "+f"(d[55]),
        "+f"(d[56]), "+f"(d[57]), "+f"(d[58]), "+f"(d[59]), "+f"(d[60]), "+f"(d[61]), "+f"(d[62]), "+f"(d[63]),
        "+f"(d[64]), "+f"(d[65]), "+f"(d[66]), "+f"(d[67]), "+f"(d[68]), "+f"(d[69]), "+f"(d[70]), "+f"(d[71]),
        "+f"(d[72]), "+f"(d[73]), "+f"(d[74]), "+f"(d[75]), "+f"(d[76]), "+f"(d[77]), "+f"(d[78]), "+f"(d[79]),
        "+f"(d[80]), "+f"(d[81]), "+f"(d[82]), "+f"(d[83]), "+f"(d[84]), "+f"(d[85]), "+f"(d[86]), "+f"(d[87]),
        "+f"(d[88]), "+f"(d[89]), "+f"(d[90]), "+f"(d[91]), "+f"(d[92]), "+f"(d[93]), "+f"(d[94]), "+f"(d[95])
      : "r"(da), "r"(db), "r"(scale_d), "n"(DESC_HI), "n"(DESC_HI64));
}
DEVI void wgmma_n64(float (&d)[32], uint32_t da, uint32_t db, int scale_d) {
  asm volatile(
      "{\n.reg .pred p;\n.reg .b64 da, db;\nsetp.ne.b32 p, %34, 0;\nmov.b64 da, {%32, %35};\nmov.b64 db, {%33, %35};\n"
      "wgmma.mma_async.sync.aligned.m64n64k16.f32.bf16.bf16 "
      "{%0,%1,%2,%3,%4,%5,%6,%7,%8,%9,%10,%11,%12,%13,%14,%15,"
      "%16,%17,%18,%19,%20,%21,%22,%23,%24,%25,%26,%27,%28,%29,%30,%31}, "
      "da, db, p, 1, 1, 0, 1;\n}"
      : "+f"(d[0]), "+f"(d[1]), "+f"(d[2]), "+f"(d[3]), "+f"(d[4]), "+f"(d[5]), "+f"(d[6]), "+f"(d[7]),
        "+f"(d[8]), "+f"(d[9]), "+f"(d[10]), "+f"(d[11]), "+f"(d[12]), "+f"(d[13]), "+f"(d[14]), "+f"(d[15]),
        "+f"(d[16]), "+f"(d[17]), "+f"(d[18]), "+f"(d[19]), "+f"(d[20]), "+f"(d[21]), "+f"(d[22]), "+f"(d[23]),
        "+f"(d[24]), "+f"(d[25]), "+f"(d[26]), "+f"(d[27]), "+f"(d[28]), "+f"(d[29]), "+f"(d[30]), "+f"(d[31])
      : "r"(da), "r"(db), "r"(scale_d), "n"(DESC_HI));
}

struct C32 { float re, im; };
DEVI C32 csq(C32 a) { return {a.re * a.re - a.im * a.im, 2.f * a.re * a.im}; }
DEVI C32 cmul(C32 a, C32 b) { return {a.re * b.re - a.im * b.im, a.re * b.im + a.im * b.re}; }
DEVI C32 cfresh(float zl, float zi, float m) {
  float mag = ex2(zl * m), ph = zi * m;
  return {mag * __cosf(ph), mag * __sinf(ph)};
}
struct HMul { uint32_t b, bp; };
DEVI HMul mk_mul(float re, float im) { return {pack_f16(re, im), pack_f16(-im, re)}; }
DEVI uint32_t hcmul(uint32_t a, const HMul& m) {
  __half2 ah = *reinterpret_cast<__half2*>(&a);
  __half2 b = *reinterpret_cast<const __half2*>(&m.b), bp = *reinterpret_cast<const __half2*>(&m.bp);
  __half2 r = __hfma2(__high2half2(ah), bp, __hmul2(__low2half2(ah), b));
  return *reinterpret_cast<uint32_t*>(&r);
}
DEVI uint32_t badd(uint32_t a, uint32_t b) {
  __nv_bfloat162 r = __hadd2(*reinterpret_cast<__nv_bfloat162*>(&a), *reinterpret_cast<__nv_bfloat162*>(&b));
  return *reinterpret_cast<uint32_t*>(&r);
}
template <int MU0, int NMU, int DMAX>
DEVI void conv_tail(float (&acc)[16][4], uint32_t p_lane, uint32_t v_base, int back, bool edge, int lane) {
  const int hsel = (lane >> 3) & 1;
  const int row = (lane & 7) + ((lane >> 4) << 3) + PADV - 8 - (back & (hsel ^ 1));
  const uint32_t la = v_base + row * 32 + (((hsel ^ back) ^ ((row >> 2) & 1)) << 4);
  uint32_t M[3][4];
  ldsm_x4_t(M[0], la);
  ldsm_x4_t(M[1], la + 256);
  uint32_t H[2 * NMU];
#pragma unroll
  for (int i = 0; i < 2 * NMU; ++i) H[i ^ 1] = lds32(p_lane + (uint32_t)(MU0 - 1 + i) * 32);
  if (edge) {
    const uint32_t a[4] = {0u, 0u, M[0][0], M[0][1]};
#pragma unroll
    for (int k = 1; k < NMU; ++k) mma_bf16v(acc[MU0 - 2 + 2 * k], a, H[2 * k], H[2 * k + 1]);
  }
#pragma unroll
  for (int delta = -1; delta <= DMAX; ++delta) {
    if (delta + 2 <= DMAX) ldsm_x4_t(M[(delta + 3) % 3], la + (delta + 3) * 256);
#pragma unroll
    for (int k = 0; k < NMU; ++k)
      if (delta + MU0 + 2 * k < 16) mma_bf16v(acc[delta + MU0 + 2 * k], M[(delta + 1) % 3], H[2 * k], H[2 * k + 1]);
  }
}

template <int NB>
DEVI void box_filters(uint32_t sb, uint32_t bars, int idx, int lane) {
  auto swz = [](int k, int pad) { const int r = (k >> 1) + pad; return (uint32_t)(r * 32 + (((k & 1) ^ ((r >> 2) & 1)) << 4)); };
  const uint32_t o0 = swz(lane - 3, 8), o1 = swz(lane - 2, 8), o2 = swz(lane - 1, 8), ow = swz(lane - 2, PADV), oz = swz(lane - 18, PADV);
  const int k = 32 * idx - 2 + lane;
#pragma unroll 1
  for (int c2 = 0; c2 < 4; c2 += NB) {
    uint4 t[NB][3];
#pragma unroll
    for (int b = 0; b < NB; ++b) mbar_wait_long(bars + 8 * (B_UCH + c2 + b), 0);
#pragma unroll
    for (int b = 0; b < NB; ++b) {
      const uint32_t ua = sb + SM_U + (c2 + b) * U_BYTES + idx * 512;
      t[b][0] = lds128(ua + o0); t[b][1] = lds128(ua + o1); t[b][2] = lds128(ua + o2);
    }
#pragma unroll
    for (int b = 0; b < NB; ++b) {
      const uint32_t vb = sb + SM_VV + (c2 + b) * VV_BYTES, aw = vb + idx * 512 + ow;
      const uint32_t E[12] = {t[b][0].x, t[b][0].y, t[b][0].z, t[b][0].w, t[b][1].x, t[b][1].y, t[b][1].z, t[b][1].w,
                              t[b][2].x, t[b][2].y, t[b][2].z, t[b][2].w};
      uint32_t O[8];
#pragma unroll
      for (int j = 0; j < 8; ++j) O[j] = __byte_perm(E[j + 1], E[j + 2], 0x5432);
      uint32_t s3[6], s5[4], s7[4], s9[4];
#pragma unroll
      for (int j = 0; j < 6; ++j) s3[j] = badd(badd(O[j], O[j + 1]), E[j + 2]);
#pragma unroll
      for (int j = 0; j < 4; ++j) {
        s5[j] = badd(s3[j + 2], badd(E[j + 3], E[j + 5]));
        s7[j] = badd(s5[j], badd(O[j + 1], O[j + 4]));
        s9[j] = badd(s7[j], badd(E[j + 2], E[j + 6]));
      }
      if (k < 208) { sts128(aw + VV_U3, s3[0], s3[1], s3[2], s3[3]); sts128(aw + VV_U5, s5[0], s5[1], s5[2], s5[3]); }
      if (k < 144) { sts128(aw + VV_U7, s7[0], s7[1], s7[2], s7[3]); sts128(aw + VV_U9, s9[0], s9[1], s9[2], s9[3]); }
      if (idx == 0 && lane < 16) {
        sts128(vb + oz + VV_U3, 0, 0, 0, 0); sts128(vb + oz + VV_U5, 0, 0, 0, 0);
        sts128(vb + oz + VV_U7, 0, 0, 0, 0); sts128(vb + oz + VV_U9, 0, 0, 0, 0);
      }
    }
  }
}

__global__ void __cluster_dims__(2, 1, 1) __launch_bounds__(NTHREADS, 1)
fused_kernel(const __grid_constant__ Maps maps, const Ptrs p) {
  extern __shared__ __align__(1024) uint8_t smem[];
  const uint32_t sb = s2u(smem);
  const int tid = threadIdx.x, lane = tid & 31;
  const int warp = __shfl_sync(0xffffffffu, tid >> 5, 0);
  const int cta = blockIdx.x;
  const uint32_t rank = cta & 1;
  const int ti = 2 * (cta >> 4) + rank;
  const int tj = (cta >> 1) & 7;
  const int pi = cta >> 3, pj = cta & 7;
  const uint32_t bars = sb + SM_BAR;
#define BAR(i) (bars + 8 * (i))
  const int g = lane >> 2, q = lane & 3;

  auto issue_stage = [&](int ks, int s) {
    const uint32_t st = sb + s * STG_BYTES, fb = BAR(B_FULL + s);
    mbar_expect_tx(fb, STG_BYTES);
    tma_load_2d(st + STG_X, &maps.x, ks * 32, ti * 128, fb);
    tma_load_3d_mc(st + STG_W + rank * 6144, &maps.w, tj * 64, ks * 32 + rank * 16, 0, fb, 3);
  };

  const int kch = warp & 3, krd = warp >> 2;
  float zr, zi, wr, wi;
  unsigned epoch;
  uint32_t r_dskip;
  {
    const size_t po = (size_t)(cta * 4 + kch) * 128 + krd * 32 + lane;
    const uint32_t r_ar = ldg16(p.A_re + po), r_ai = ldg16(p.A_im + po), r_br = ldg16(p.B_re + po), r_bi = ldg16(p.B_im + po);
    const uint32_t r_cr = ldg16(p.C_re + po), r_ci = ldg16(p.C_im + po), r_ldt = ldg16(p.log_dt + cta * 4 + kch);
    epoch = __ldcg(&g_epoch);
    r_dskip = ldg16(p.Dskip + cta * 4 + kch);
    uint4 pt;
    if (tid < 128) pt = __ldg((const uint4*)g_ptab.v + tid);
    if (tid == 384) {
      TS(0);
#pragma unroll
      for (int i = 0; i < B_COUNT; ++i) mbar_init(BAR(i), bar_count(i));
      asm volatile("fence.mbarrier_init.release.cluster;" ::: "memory");
      prefetch_tmap(&maps.x); prefetch_tmap(&maps.w); prefetch_tmap(&maps.u);
    }
    __syncthreads();
    cluster_arrive();
    if (warp >= 12) {
      cluster_wait();
      if (elect_one()) {
        if (warp == 13) {
          mbar_expect_tx(BAR(B_TILE), 16384);
          tma_load_2d(sb + SM_U, &maps.u, tj * 64, ti * 128, BAR(B_TILE));
          prefetch_tmap(&maps.uT); prefetch_tmap(&maps.wo); prefetch_tmap(&maps.o); prefetch_tmap(&maps.yT);
          prefetch_tmap(&maps.out); prefetch_tmap(&maps.outh);
        } else {
          if (warp == 12) TS(61);
          { const int ks = warp == 12 ? 0 : warp - 13; issue_stage(ks, ks); }
        }
      }
      __syncwarp();
    }
    if (tid < 128) sts128(sb + SM_PTAB + tid * 16, pt.x, pt.y, pt.z, pt.w);
    const float dt = round_bf16(expf(bf_lo(r_ldt)));
    zr = dt * bf_lo(r_ar); zi = dt * bf_lo(r_ai);
    const float dbr = dt * bf_lo(r_br), dbi = dt * bf_lo(r_bi), cr = bf_lo(r_cr), ci = bf_lo(r_ci);
    wr = cr * dbr - ci * dbi; wi = cr * dbi + ci * dbr;
  }
  {
    const float mz = __uint_as_float(__reduce_max_sync(0xffffffffu, __float_as_uint(fmaxf(zr, 0.f))));
    const int E = min(max((int)(__reduce_max_sync(0xffffffffu, __float_as_uint(fmaxf(fabsf(wr), fabsf(wi)))) >> 23), 1), 252);
    const float sc = __int_as_float((253 - E) << 23), inv = __int_as_float((E + 1) << 23);
    const float zl = (zr - mz) * 1.4426950408889634f;
    const uint32_t tb = sb + SM_VV + kch * VV_BYTES + krd * KG_BYTES;
    const uint32_t sta = tb + (((lane >> 2) << 4) | ((lane & 3) << 2));
    auto put = [&](int r, uint32_t v) { sts32((sta ^ ((r & 7) << 4)) + r * 128, v); };
    const uint32_t lda = tb + ((lane & 7) + (((lane >> 3) & 1) << 3)) * 128;
    const uint32_t ldb = tb + ((lane & 7) + ((lane >> 4) << 3)) * 128;
    C32 e1 = cfresh(zl, zi, 1.f), e2 = csq(e1), e4 = csq(e2), e8 = csq(e4);
    C32 e16 = cfresh(zl, zi, 16.f), e32 = csq(e16), e64 = csq(e32), e128 = csq(e64);
    C32 e256 = cfresh(zl, zi, 256.f), e512 = csq(e256), e1024 = csq(e512), e768 = cmul(e512, e256);
    uint32_t XA[2][4][4];
    {
      const HMul m16 = mk_mul(e16.re, e16.im), m32 = mk_mul(e32.re, e32.im), m64 = mk_mul(e64.re, e64.im);
      const HMul m128 = mk_mul(e128.re, e128.im);
      uint32_t X[16];
      X[0] = 0x00003c00u; X[1] = pack_f16(e8.re, e8.im); X[2] = m16.b; X[4] = m32.b; X[8] = m64.b;
      X[3] = hcmul(X[1], m16); X[5] = hcmul(X[1], m32); X[6] = hcmul(X[2], m32); X[7] = hcmul(X[3], m32);
#pragma unroll
      for (int r = 1; r < 8; ++r) X[8 + r] = hcmul(X[r], m64);
#pragma unroll
      for (int h = 0; h < 2; ++h) {
#pragma unroll
        for (int r = 0; r < 16; ++r) put(r, h == 0 ? X[r] : r == 0 ? m128.b : hcmul(X[r], m128));
        __syncwarp();
#pragma unroll
        for (int k = 0; k < 4; ++k) ldsm_x4(XA[h][k], lda + (((2 * k + (lane >> 4)) ^ (lane & 7)) << 4));
        __syncwarp();
      }
    }
    if (warp >= 14 && elect_one()) {
      issue_stage(warp - 11, warp - 11);
      issue_stage(warp - 9, warp - 9);
      if (warp == 14) l2_prefetch((const char*)p.wqkv + 224 * 3072 + cta * 6912, 6912);
      else l2_prefetch((const char*)p.x + (size_t)cta * 16384, 16384);
    }
    __syncwarp();
    float D[2][3][4];
#pragma unroll
    for (int t = 0; t < 6; ++t) D[t / 3][t % 3][0] = D[t / 3][t % 3][1] = D[t / 3][t % 3][2] = D[t / 3][t % 3][3] = 0.f;
    auto contract = [&](int t0, int nt) {
      __syncwarp();
#pragma unroll
      for (int k = 0; k < 4; ++k) {
        uint32_t b[4];
        ldsm_x4(b, ldb + (((2 * k + ((lane >> 3) & 1)) ^ (lane & 7)) << 4));
#pragma unroll
        for (int h = 0; h < 2; ++h) {
          mma_f16(D[h][t0], XA[h][k], b[0], b[1]);
          if (nt == 2) mma_f16(D[h][t0 + 1], XA[h][k], b[2], b[3]);
        }
      }
      __syncwarp();
    };
    const HMul c1 = mk_mul(e1.re, -e1.im), c2 = mk_mul(e2.re, -e2.im), c4 = mk_mul(e4.re, -e4.im);
    const HMul c256 = mk_mul(e256.re, -e256.im), c512 = mk_mul(e512.re, -e512.im), c768 = mk_mul(e768.re, -e768.im);
    const HMul c1024 = mk_mul(e1024.re, -e1024.im);
    uint32_t W[8];
    W[0] = pack_f16(wr * sc, -wi * sc);
    W[1] = hcmul(W[0], c1); W[2] = hcmul(W[0], c2); W[3] = hcmul(W[1], c2);
    W[4] = hcmul(W[0], c4); W[5] = hcmul(W[1], c4); W[6] = hcmul(W[2], c4); W[7] = hcmul(W[3], c4);
#pragma unroll
    for (int i = 0; i < 8; ++i) put(i, W[i]);
#pragma unroll
    for (int i = 0; i < 4; ++i) put(8 + i, hcmul(W[2 * i], c256));
    put(12, hcmul(W[0], c512)); put(13, hcmul(W[4], c512)); put(14, hcmul(W[0], c768)); put(15, hcmul(W[4], c768));
    contract(0, 2);
    const uint32_t v0 = hcmul(W[0], c1024);
    put(0, v0); put(1, hcmul(v0, c256)); put(2, hcmul(v0, c512)); put(3, hcmul(v0, c768)); put(4, hcmul(v0, c1024));
    contract(2, 1);
    const uint32_t a = tb + (g * 24 + 2 * q) * 4;
#pragma unroll
    for (int t = 0; t < 6; ++t) {
      const float(&d)[4] = D[t / 3][t % 3];
      sts_f32x2(a + (t / 3) * 1536 + (t % 3) * 32, d[0] * inv, d[1] * inv);
      sts_f32x2(a + (t / 3) * 1536 + (t % 3) * 32 + 768, d[2] * inv, d[3] * inv);
    }
    if (mz > 0.f) {
      __syncwarp();
#pragma unroll 1
      for (int i = lane; i < 768; i += 32) {
        const int r = i / 24, y = i - 24 * r;
        sts_f32(tb + i * 4, lds_f32(tb + i * 4) * ex2(mz * 1.4426950408889634f * (koff(y) + 8 * r)));
      }
    }
  }
  if (tid == 0) TS(2);
  if (warp < 12) cluster_wait();
  __syncthreads();

  if (warp < 4) {
#define A_REGS 200
    asm volatile("setmaxnreg.inc.sync.aligned.u32 %0;" ::"n"(A_REGS));
    if (tid == 0) TS(34);
    const int d = cta * 4 + warp;
    const uint32_t vv = sb + SM_VV + warp * VV_BYTES;
    const uint32_t ub = sb + SM_U + warp * U_BYTES;
    const uint32_t pb = sb + SM_P + warp * P_BYTES;
    const float dskip = bf_lo(r_dskip);
#pragma unroll 1
    for (int pass = 0; pass < 2; ++pass) {
      if (pass == 1) {
        const uint32_t kf = vv;
#pragma unroll 2
        for (int i = 0; i < 6; ++i) {
          const uint32_t a = kf + (i * 32 + lane) * 16;
          const uint4 x0 = lds128(a), x1 = lds128(a + KG_BYTES), x2 = lds128(a + 2 * KG_BYTES), x3 = lds128(a + 3 * KG_BYTES);
          auto s4 = [](uint32_t a0, uint32_t a1, uint32_t a2, uint32_t a3) {
            return __float_as_uint((__uint_as_float(a0) + __uint_as_float(a1)) + (__uint_as_float(a2) + __uint_as_float(a3)));
          };
          sts128(a, s4(x0.x, x1.x, x2.x, x3.x), s4(x0.y, x1.y, x2.y, x3.y), s4(x0.z, x1.z, x2.z, x3.z), s4(x0.w, x1.w, x2.w, x3.w));
        }
        __syncwarp();
        const float k1024 = lds_f32(kf + kidx_c(1024) * 4);
        if (lane == 0) {
          sts_f32(kf + SL_ZERO * 4, 0.f);
          sts_f32(kf + SL_510 * 4, lds_f32(kf + kidx_c(510) * 4) - lds_f32(kf + kidx_c(512) * 4));
          sts_f32(kf + SL_0 * 4, lds_f32(kf) + dskip);
        }
        __syncwarp();
        if (tid == 0) TS(36);
        mbar_wait_long(BAR(B_PFREE), 0);
        if (tid == 0) TS(37);
        {
          float prev = 0.f;
#pragma unroll 1
          for (int i0 = 0; i0 < 16; i0 += 4) {
            uint32_t e[4];
            float a[4], b[4];
#pragma unroll
            for (int i = 0; i < 4; ++i) e[i] = lds32(sb + SM_PTAB + ((i0 + i) * 32 + lane) * 4);
#pragma unroll
            for (int i = 0; i < 4; ++i) { a[i] = lds_f32(kf + (e[i] & 0xffff)); b[i] = lds_f32(kf + (e[i] >> 16)); }
#pragma unroll
            for (int i = 0; i < 4; ++i) {
              const uint32_t w = pb + (31 * lane + 2 * (i0 + i)) * 4;
              if (i0 + i > 0) sts32(w - 4, pack_bf16(a[i], prev));
              sts32(w, pack_bf16(b[i], a[i]));
              prev = b[i];
            }
          }
        }
        __syncwarp();
        if (lane == 0) TS(4);
        const int gq = g - 2 * q;
        uint32_t h127, h128;
        {
          const uint32_t kf2 = pack_bf16(k1024, k1024) ^ 0x80008000u;
          h127 = (gq == 4 ? 0x0000ffffu : gq == 5 ? 0xffffffffu : gq == 6 ? 0xffff0000u : 0u) & kf2;
          h128 = (gq == -4 ? 0x0000ffffu : gq == -3 ? 0xffffffffu : gq == -2 ? 0xffff0000u : 0u) & kf2;
        }
        bar_arrive(7, 384);
        if (lane == 0) TS(6);
        bar_sync(4, 384);
        mbar_wait_long(BAR(B_UCH + warp), 0);
        if (lane == 0) TS(7);
        float acc[16][4];
#pragma unroll
        for (int i = 0; i < 16; ++i) { acc[i][0] = acc[i][1] = acc[i][2] = acc[i][3] = 0.f; }
        {
          const uint32_t pd_lane = pb + (PD_OFF + 16 + gq) * 4;
          const int prow0 = 8 + (lane & 7) + ((lane >> 4) << 3), hs = (lane >> 3) & 1;
          const uint32_t zero = (uint32_t)cta >> 20;
          uint32_t B[2][4][4];
          uint32_t A[4][4];
          const uint32_t la0 = ub + prow0 * 32 + ((hs ^ ((prow0 >> 2) & 1)) << 4);
#pragma unroll
          for (int m2 = 0; m2 < 4; ++m2) ldsm_x4(B[0][m2], la0 + m2 * 512);
#pragma unroll
          for (int i = 0; i < 4; ++i) {
            const uint32_t a = pd_lane + i * 512;
            A[i][0] = lds32(a); A[i][1] = lds32(a + 32); A[i][2] = lds32(a - 32); A[i][3] = lds32(a + zero);
          }
          uint32_t la = la0;
#define UNR_RHO 4
#define UNR_TAIL 4
          constexpr int unr_rho = UNR_RHO, unr_tail = UNR_TAIL;
#pragma unroll unr_rho
          for (int rho = 0; rho < 8; ++rho) {
#pragma unroll
            for (int m2 = 0; m2 < 4; ++m2) ldsm_x4(B[1][m2], la + (4 + m2) * 512);
#pragma unroll
            for (int i = 0; i < 4; ++i)
#pragma unroll
              for (int m = 0; m < 8; ++m) mma_bf16v(acc[m + i], A[i], B[0][m >> 1][2 * (m & 1)], B[0][m >> 1][2 * (m & 1) + 1]);
            const int prow = prow0 - min(rho + 1, 7);
            la = ub + prow * 32 + ((hs ^ ((prow >> 2) & 1)) << 4);
#pragma unroll
            for (int m2 = 0; m2 < 4; ++m2) ldsm_x4(B[0][m2], la + m2 * 512);
            const uint32_t pa = pd_lane + (rho + 1) * 64;
#pragma unroll
            for (int i = 0; i < 4; ++i) {
#pragma unroll
              for (int m = 0; m < 8 - i; ++m)
                mma_bf16v(acc[8 + m + i], A[i], B[1][m >> 1][2 * (m & 1)], B[1][m >> 1][2 * (m & 1) + 1]);
              A[i][0] = lds32(pa + i * 512); A[i][1] = lds32(pa + i * 512 + 32); A[i][2] = lds32(pa + i * 512 - 32);
              A[i][3] = lds32(pa + i * 512 + zero);
            }
          }
          if (lane == 0) TS(40);
          {
            uint32_t b8[4];
            ldsm_x4(b8, la + 4 * 512);
            const uint32_t h63 = lds32(pd_lane + 63 * 32), h64 = lds32(pd_lane + 64 * 32);
            const uint32_t a63[4] = {0u, h127, 0u, 0u}, a32[4] = {h64, 0u, h63, h64}, a64[4] = {h128, 0u, h127, h128};
#pragma unroll
            for (int m2 = 0; m2 < 4; ++m2) ldsm_x4(B[1][m2], la0 + m2 * 512);
#pragma unroll
            for (int m = 0; m < 8; ++m) mma_bf16v(acc[m + 7], a63, B[0][m >> 1][2 * (m & 1)], B[0][m >> 1][2 * (m & 1) + 1]);
#pragma unroll
            for (int m2 = 0; m2 < 2; ++m2) ldsm_x4(B[0][m2], la0 + (4 + m2) * 512);
#pragma unroll
            for (int m = 0; m < 8; ++m) mma_bf16v(acc[m + 4], a32, B[1][m >> 1][2 * (m & 1)], B[1][m >> 1][2 * (m & 1) + 1]);
            mma_bf16v(acc[15], a63, b8[0], b8[1]);
#pragma unroll
            for (int m = 0; m < 8; ++m) mma_bf16v(acc[m + 8], a64, B[1][m >> 1][2 * (m & 1)], B[1][m >> 1][2 * (m & 1) + 1]);
#pragma unroll
            for (int m = 0; m < 4; ++m) mma_bf16v(acc[m + 12], a32, B[0][m >> 1][2 * (m & 1)], B[0][m >> 1][2 * (m & 1) + 1]);
          }
          if (lane == 0) TS(41);
          bar_sync(5, 384);
#pragma unroll unr_tail
          for (int v = 0; v < 4; ++v)
            conv_tail<4, 3, 11>(acc, pb + (P2_OFF + 56 * v + gq - 16) * 4, vv + ((v & 1) ? VV_U3 : VV_U5), v >> 1, v == 0, lane);
          if (lane == 0) TS(42);
#pragma unroll unr_tail
          for (int pi = 0; pi < 2; ++pi)
            conv_tail<8, 5, 7>(acc, pb + (P3_OFF + 88 * pi + gq - 48) * 4, vv + (pi ? VV_U7 : VV_U9), pi, pi == 0, lane);
        }
        if (lane == 0) TS(8);
        __syncwarp();
        {
          const int mt = lane >> 3;
          const uint32_t a = pb + (128 * (mt >> 1) + 16 * (lane & 7) + 8 * (mt & 1)) * 2;
#pragma unroll
          for (int ab = 0; ab < 16; ab += 2)
            stsm_x4_t(a + ab * 256, pack_bf16(acc[ab][0], acc[ab][1]), pack_bf16(acc[ab][2], acc[ab][3]),
                      pack_bf16(acc[ab + 1][0], acc[ab + 1][1]), pack_bf16(acc[ab + 1][2], acc[ab + 1][3]));
        }
        fence_async_smem();
        __syncwarp();
        if (lane < 2) mbar_arrive_cluster(BAR(B_CONVD), lane);
        bar_arrive(3, 384);
        if (elect_one()) {
          bulk_store(p.yT + (size_t)d * 2048, pb, 4096);
          bulk_commit();
          bulk_wait0();
          red_relaxed_add(&g_cnt[(C_Y + (cta >> 4)) * 32], 1);
          TS(9);
        }
        bar_sync(2, 128);
        if (warp == 0 && elect_one()) {
          wait_counter(&g_cnt[(C_Y + tj) * 32], (epoch + 1) * 64);
          TS(28);
          mbar_expect_tx(BAR(B_TILE), 16384);
          tma_load_2d(sb + SM_U, &maps.yT, ti * 128, tj * 64, BAR(B_TILE));
          tma_load_2d(sb + SM_U + 8192, &maps.yT, ti * 128 + 64, tj * 64, BAR(B_TILE));
        }
        __syncwarp();
      }
      mbar_wait_long(BAR(B_TILE), pass);
      if (lane == 0) TS(26 + 3 * pass);
      {
        const int m = lane >> 3, r = lane & 7;
#pragma unroll 2
        for (int it = 0; it < 8; ++it) {
          const int tb = warp * 4 + (it >> 1), cb = (it & 1) * 4 + m;
          const uint32_t at = (tb * 8 + r) * 128 + ((cb ^ r) << 4);
          const uint32_t ac = (tb >> 3) * 8192 + (cb * 8 + r) * 128 + (((tb & 7) ^ (pass ? 0 : tb >> 3) ^ r) << 4);
          uint32_t v[4];
          ldsm_x4_t(v, sb + SM_U + (pass ? ac : at));
          stsm_x4(sb + SM_P + (pass ? at : ac), v[0], v[1], v[2], v[3]);
        }
      }
      if (pass == 0 && tid == 0) TS(35);
      fence_async_smem();
      if (pass == 0) {
        bar_arrive(6, 160);
      } else {
        bar_sync(2, 128);
        if (warp == 0 && elect_one()) {
          tma_store_2d(&maps.out, sb + SM_P, 64 * tj, 128 * ti);
          bulk_commit();
          bulk_wait_read0();
          TS(30);
        }
      }
    }
  } else if (warp < 12) {
    const int w8 = warp - 4;
    const int row = w8 * 16 + (lane & 7) + (((lane >> 3) & 1) << 3);
    uint32_t pq[16];
    {
      float acc[96];
#pragma unroll 1
      for (int ks = 0, s = 0, ph = 0; ks < 16; ++ks) {
        mbar_wait(BAR(B_FULL + s), ph);
        if (tid == 128 && !(ks & 1)) TSR(16, ks == 0 ? 16 : 9 + (ks >> 1) + (ks > 12 ? 43 : 0));
        const uint32_t st = sb + s * STG_BYTES;
        const uint32_t da = mkdesc(st + STG_X + (w8 >> 2) * 4096, 16);
        const uint32_t db = mkdesc(st + STG_W, 2048);
        wg_fence();
        wgmma_n192(acc, da, db, ks != 0);
        wgmma_n192(acc, da + 2, db + 384, 1);
        wg_commit();
        const uint32_t eprev = BAR(B_EMPTY + (s == 0 ? NSTG - 1 : s - 1));
        if (++s == NSTG) { s = 0; ph ^= 1; }
        if (ks > 0) {
          wg_wait<1>();
          if (lane < 2) mbar_arrive_cluster(eprev, lane);
        }
      }
      wg_wait<0>();
      if (tid == 128) TS(17);
      auto phi2 = [](float a, float b) -> uint32_t {
        const uint32_t x = pack_bf16(a, b);
        const uint32_t e = pack_bf16(ex2(a * 1.4426950408889634f), ex2(b * 1.4426950408889634f));
        const uint32_t m = __hgt2_mask(*reinterpret_cast<const __nv_bfloat162*>(&x), __floats2bfloat162_rn(0.f, 0.f));
        return badd((badd(x, 0x3f803f80u) & m) | (e & ~m), 0x35863586u);
      };
      uint32_t pk[16];
#pragma unroll
      for (int i = 0; i < 16; ++i) pk[i] = phi2(acc[32 + 2 * i], acc[33 + 2 * i]);
      if (tid == 128) TS(53);
      bar_sync(1, 256);
#pragma unroll
      for (int i = 0; i < 8; i += 2) {
        const uint32_t off = row * 128 + (((i + (lane >> 4)) ^ (row & 7)) << 4);
        stsm_x4(sb + SM_PK + off, pk[2 * i], pk[2 * i + 1], pk[2 * i + 2], pk[2 * i + 3]);
        stsm_x4(sb + SM_VS + off, pack_bf16(acc[64 + 4 * i], acc[65 + 4 * i]), pack_bf16(acc[66 + 4 * i], acc[67 + 4 * i]),
                pack_bf16(acc[68 + 4 * i], acc[69 + 4 * i]), pack_bf16(acc[70 + 4 * i], acc[71 + 4 * i]));
      }
      bar_sync(1, 256);
      {
        const int hh = w8 >> 1, dtile = w8 & 1;
        float kv[2][4] = {{0.f, 0.f, 0.f, 0.f}, {0.f, 0.f, 0.f, 0.f}}, zz[2][4] = {{0.f, 0.f, 0.f, 0.f}, {0.f, 0.f, 0.f, 0.f}};
        const int m = lane >> 3;
        const uint32_t aa = sb + SM_VS + ((lane & 7) + ((m >> 1) << 3)) * 128 + (((2 * hh + (m & 1)) ^ (lane & 7)) << 4);
        const uint32_t ab = sb + SM_PK + (lane & 15) * 128 + (((2 * hh + dtile) ^ (lane & 7)) << 4);
#pragma unroll
        for (int ks = 0; ks < 8; ++ks) {
          uint32_t a[4], b0, b1;
          ldsm_x4_t(a, aa + ks * 2048);
          ldsm_x2_t(b0, b1, ab + ks * 2048);
          mma_bf16(kv[ks & 1], a[0], a[1], a[2], a[3], b0, b1);
          mma_bf16(zz[ks & 1], 0x3f803f80u, 0x3f803f80u, 0x3f803f80u, 0x3f803f80u, b0, b1);
        }
        const uint32_t kp = sb + SM_KV + hh * 1088;
        sts128(kp + dtile * 512 + lane * 16, __float_as_uint(kv[0][0] + kv[1][0]), __float_as_uint(kv[0][1] + kv[1][1]),
               __float_as_uint(kv[0][2] + kv[1][2]), __float_as_uint(kv[0][3] + kv[1][3]));
        if (g == 0) sts_f32x2(kp + 1024 + dtile * 32 + q * 8, zz[0][0] + zz[1][0], zz[0][1] + zz[1][1]);
        fence_async_smem();
        __syncwarp();
        if (lane == 0) mbar_arrive(BAR(B_KVP));
        bar_arrive(4, 384);
        if (tid == 128) TS(55);
      }
#pragma unroll
      for (int i = 0; i < 16; ++i) pq[i] = phi2(acc[2 * i], acc[2 * i + 1]);
    }
    if (tid == 128) TS(56);
    if (warp == 4) mbar_wait_long(BAR(B_KVF), 0);
    bar_sync(1, 256);
    if (tid == 128) TS(19);
    {
      uint32_t kb[4][6];
#pragma unroll
      for (int h = 0; h < 4; ++h) {
        const uint32_t kp = sb + SM_KV + h * 1088;
        const uint4 k0 = lds128(kp + lane * 16), k1 = lds128(kp + 512 + lane * 16);
        const uint32_t za = kp + 1024 + q * 8;
        auto pk2 = [](uint32_t x, uint32_t y) { return pack_bf16(__uint_as_float(x), __uint_as_float(y)); };
        kb[h][0] = pk2(k0.x, k0.y); kb[h][1] = pk2(k1.x, k1.y); kb[h][2] = pk2(k0.z, k0.w); kb[h][3] = pk2(k1.z, k1.w);
        kb[h][4] = pack_bf16(lds_f32(za), lds_f32(za + 4)); kb[h][5] = pack_bf16(lds_f32(za + 32), lds_f32(za + 36));
      }
#pragma unroll
      for (int h = 0; h < 4; ++h) {
        float n0[4] = {0.f, 0.f, 0.f, 0.f}, n1[4] = {0.f, 0.f, 0.f, 0.f}, dn[4] = {0.f, 0.f, 0.f, 0.f};
        mma_bf16(n0, pq[4 * h], pq[4 * h + 1], pq[4 * h + 2], pq[4 * h + 3], kb[h][0], kb[h][1]);
        mma_bf16(n1, pq[4 * h], pq[4 * h + 1], pq[4 * h + 2], pq[4 * h + 3], kb[h][2], kb[h][3]);
        mma_bf16(dn, pq[4 * h], pq[4 * h + 1], pq[4 * h + 2], pq[4 * h + 3], kb[h][4], kb[h][5]);
        const float r0 = rcp(dn[0] + 1e-6f), r1 = rcp(dn[2] + 1e-6f);
        stsm_x4(sb + SM_QS + row * 128 + (((2 * h + (lane >> 4)) ^ (row & 7)) << 4),
                pack_bf16(n0[0] * r0, n0[1] * r0), pack_bf16(n0[2] * r1, n0[3] * r1),
                pack_bf16(n1[0] * r0, n1[1] * r0), pack_bf16(n1[2] * r1, n1[3] * r1));
      }
    }
    fence_async_smem();
    __syncwarp();
    if (lane == 0) mbar_arrive(BAR(B_OST));
    if (tid == 128) TS(57);
    bar_sync(7, 384);
    if (w8 < 7) box_filters<4>(sb, bars, w8, lane);
    bar_arrive(5, 384);
    if (tid == 128) TS(6);
    if (warp == 4) mbar_wait_long(BAR(B_WO), 0);
    bar_sync(3, 384);
    {
      float o[32];
#pragma unroll 1
      for (int c = 0; c < 8; ++c) {
        mbar_wait_long(BAR(B_RF + c), 0);
        if (tid == 128) TSR(22, c == 0 ? 22 : 43 + c);
        const uint32_t slot = c < 4 ? SM_QS + c * 16384 : c < 7 ? SM_VV + (c - 4) * 16384 : SM_QS;
        const uint32_t da = mkdesc(sb + slot + (w8 >> 2) * 8192, 16);
        const uint32_t db = mkdesc(sb + SM_WO + c * 8192, 8192);
        wg_fence();
#pragma unroll
        for (int k = 0; k < 4; ++k) wgmma_n64(o, da + 2 * k, db + 128 * k, (c | k) != 0);
        wg_commit();
        if (c == 1) {
          wg_wait<1>();
          if (lane < 2) mbar_arrive_cluster(BAR(B_RE), lane);
        }
      }
      wg_wait<0>();
      if (tid == 128) TS(51);
#pragma unroll
      for (int i = 0; i < 8; i += 2)
        stsm_x4(sb + SM_BOUT + row * 128 + (((i + (lane >> 4)) ^ (row & 7)) << 4), pack_bf16(o[4 * i], o[4 * i + 1]),
                pack_bf16(o[4 * i + 2], o[4 * i + 3]), pack_bf16(o[4 * i + 4], o[4 * i + 5]), pack_bf16(o[4 * i + 6], o[4 * i + 7]));
      fence_async_smem();
      bar_sync(8 + (w8 >> 2), 128);
      if ((w8 & 3) == 0 && elect_one()) {
        tma_store_2d(&maps.outh, sb + SM_BOUT + (w8 >> 2) * 8192, 512 + 64 * pj, 128 * pi + (w8 >> 2) * 64);
        bulk_commit();
        bulk_wait_read0();
        TS(23);
      }
    }
  } else {
    asm volatile("setmaxnreg.dec.sync.aligned.u32 40;");
    if (warp == 12) {
      if (elect_one()) {
#pragma unroll 1
        for (int ks = NSTG, s = 0, ph = 0; ks < 16; ++ks) {
          mbar_wait(BAR(B_EMPTY + s), ph);
          issue_stage(ks, s);
          if (ks == NSTG) l2_prefetch((const char*)p.wo + (size_t)cta * 4096, 4096);
          if (++s == NSTG) { s = 0; ph ^= 1; }
        }
        mbar_wait(BAR(B_EMPTY + 6), 1);
        mbar_expect_tx(BAR(B_WO), 65536);
        tma_load_2d(sb + SM_WO, &maps.wo, pj * 64, 0, BAR(B_WO));
        tma_load_2d(sb + SM_WO + 32768, &maps.wo, pj * 64, 256, BAR(B_WO));
        float* kvg = &g_kv[epoch & 1][tj][0];
        mbar_wait_long(BAR(B_KVP), 0);
        bulk_reduce_add_f32(kvg, sb + SM_KV, 4352);
        bulk_commit();
        bulk_wait0();
        red_relaxed_add(&g_cnt[(C_KV + tj) * 32], 1);
        TS(18);
        wait_counter(&g_cnt[(C_KV + tj) * 32], (epoch + 1) * 16);
        mbar_expect_tx(BAR(B_KVF), 4352);
        bulk_load(sb + SM_KV, kvg, 4352, BAR(B_KVF));
        mbar_wait_long(BAR(B_OST), 0);
        tma_store_2d(&maps.o, sb + SM_QS, tj * 64, ti * 128);
        tma_store_2d(&maps.o, sb + SM_QS + 8192, tj * 64, ti * 128 + 64);
        bulk_commit();
        bulk_wait0();
        red_relaxed_add(&g_cnt[(C_O + ti) * 32], 1);
        TS(20);
        mbar_arrive_cluster(BAR(B_SLOT), 0);
        mbar_arrive_cluster(BAR(B_SLOT), 1);
        wait_counter(&g_cnt[(C_O + pi) * 32], (epoch + 1) * 8);
        if (cta == 0) g_epoch = epoch + 1;
        mbar_wait(BAR(B_SLOT), 0);
        TS(21);
#pragma unroll 1
        for (int c = 0; c < 8; ++c) {
          if (c == 4) mbar_wait_long(BAR(B_CONVD), 0);
          if (c == 7) mbar_wait(BAR(B_RE), 0);
          const uint32_t slot = c < 4 ? SM_QS + c * 16384 : c < 7 ? SM_VV + (c - 4) * 16384 : SM_QS;
          mbar_expect_tx(BAR(B_RF + c), 16384);
          tma_load_2d_mc(sb + slot + rank * 8192, &maps.o, c * 64, pi * 128 + rank * 64, BAR(B_RF + c), 3);
        }
      }
    } else if (warp == 13) {
      bar_sync(6, 160);
      sts128(sb + SM_U + (lane >> 4) * U_BYTES + (lane & 15) * 16, 0, 0, 0, 0);
      sts128(sb + SM_U + (2 + (lane >> 4)) * U_BYTES + (lane & 15) * 16, 0, 0, 0, 0);
      __syncwarp();
      if (elect_one()) {
        tma_store_2d(&maps.uT, sb + SM_P, ti * 128, tj * 64);
        tma_store_2d(&maps.uT, sb + SM_P + 8192, ti * 128 + 64, tj * 64);
        bulk_commit();
        bulk_wait_read0();
        mbar_arrive(BAR(B_PFREE));
        bulk_wait0();
        red_relaxed_add(&g_cnt[(C_U + tj) * 32], 1);
        TS(27);
        wait_counter(&g_cnt[(C_U + (cta >> 4)) * 32], (epoch + 1) * 16);
#pragma unroll 1
        for (int c = 0; c < 4; ++c) {
          mbar_expect_tx(BAR(B_UCH + c), 4096);
          bulk_load(sb + SM_U + c * U_BYTES + 256, p.uT + (size_t)(cta * 4 + c) * 2048, 4096, BAR(B_UCH + c));
        }
        TS(3);
      }
      __syncwarp();
      if (ti == 0) {
        float4* z = (float4*)&g_kv[(epoch & 1) ^ 1][tj][0];
#pragma unroll 1
        for (int i = lane; i < 272; i += 32) z[i] = make_float4(0.f, 0.f, 0.f, 0.f);
      }
    }
  }
  __syncwarp();
  cluster_arrive();
  cluster_wait();
  if (tid == 0) TS(31);
#undef BAR
}

typedef CUresult (*EncodeFn)(CUtensorMap*, CUtensorMapDataType, cuuint32_t, void*, const cuuint64_t*, const cuuint64_t*,
                             const cuuint32_t*, const cuuint32_t*, CUtensorMapInterleave, CUtensorMapSwizzle,
                             CUtensorMapL2promotion, CUtensorMapFloatOOBfill);

static void make_map(EncodeFn enc, CUtensorMap* m, const void* base, uint64_t inner, uint64_t outer, uint32_t box_in,
                     uint32_t box_out, CUtensorMapSwizzle swz = CU_TENSOR_MAP_SWIZZLE_128B) {
  cuuint64_t gd[2] = {inner, outer};
  cuuint64_t gs[1] = {inner * 2};
  cuuint32_t bd[2] = {box_in, box_out};
  cuuint32_t es[2] = {1, 1};
  enc(m, CU_TENSOR_MAP_DATA_TYPE_BFLOAT16, 2, const_cast<void*>(base), gd, gs, bd, es, CU_TENSOR_MAP_INTERLEAVE_NONE,
      swz, CU_TENSOR_MAP_L2_PROMOTION_L2_128B, CU_TENSOR_MAP_FLOAT_OOB_FILL_NONE);
}

}

extern "C" void kernel_launch(void* const* d_in, const int* in_sizes, int n_in, void* d_out, int out_size) {
  using namespace s4la;
  (void)in_sizes; (void)n_in; (void)out_size;
  static EncodeFn enc = nullptr;
  static void *uT = nullptr, *yT = nullptr, *oS = nullptr;
  if (!enc) {
    void* fn = nullptr;
    cudaDriverEntryPointQueryResult qr;
    cudaGetDriverEntryPoint("cuTensorMapEncodeTiled", &fn, cudaEnableDefault, &qr);
    enc = (EncodeFn)fn;
    cudaGetSymbolAddress(&uT, g_uT);
    cudaGetSymbolAddress(&yT, g_yT);
    cudaGetSymbolAddress(&oS, g_o);
    cudaFuncSetAttribute(fused_kernel, cudaFuncAttributeMaxDynamicSharedMemorySize, SM_TOTAL);
  }
  const __nv_bfloat16* const* in = (const __nv_bfloat16* const*)d_in;
  Maps maps;
  make_map(enc, &maps.x, in[9], 512, 2048, 32, 128, CU_TENSOR_MAP_SWIZZLE_64B);
  {
    cuuint64_t gd[3] = {512, 512, 3};
    cuuint64_t gs[2] = {3072, 1024};
    cuuint32_t bd[3] = {64, 16, 3};
    cuuint32_t es[3] = {1, 1, 1};
    enc(&maps.w, CU_TENSOR_MAP_DATA_TYPE_BFLOAT16, 3, const_cast<__nv_bfloat16*>(in[10]), gd, gs, bd, es,
        CU_TENSOR_MAP_INTERLEAVE_NONE, CU_TENSOR_MAP_SWIZZLE_128B, CU_TENSOR_MAP_L2_PROMOTION_L2_128B,
        CU_TENSOR_MAP_FLOAT_OOB_FILL_NONE);
  }
  make_map(enc, &maps.wo, in[11], 512, 512, 64, 256);
  make_map(enc, &maps.u, in[0], 512, 2048, 64, 128);
  make_map(enc, &maps.uT, uT, 2048, 512, 64, 64);
  make_map(enc, &maps.yT, yT, 2048, 512, 64, 64);
  make_map(enc, &maps.o, oS, 512, 2048, 64, 64);
  make_map(enc, &maps.out, d_out, 1024, 2048, 64, 128);
  make_map(enc, &maps.outh, d_out, 1024, 2048, 64, 64);
  Ptrs p;
  p.A_re = in[1]; p.A_im = in[2]; p.B_re = in[3]; p.B_im = in[4]; p.C_re = in[5]; p.C_im = in[6];
  p.log_dt = in[7]; p.Dskip = in[8]; p.x = in[9]; p.wqkv = in[10]; p.wo = in[11];
  p.uT = (__nv_bfloat16*)uT; p.yT = (__nv_bfloat16*)yT;
  fused_kernel<<<NCTA, NTHREADS, SM_TOTAL, cudaStreamPerThread>>>(maps, p);
}
```

```cpp
#include <cuda_runtime.h>
#include <cuda_bf16.h>
#include <cuda_fp16.h>
#include <cuda.h>
#include <stdint.h>

#define DEVI __device__ __forceinline__

namespace s4la {

constexpr int NTHREADS = 512;
constexpr int NCTA = 128;

constexpr int NSTG = 7;
constexpr uint32_t STG_BYTES = 20480, STG_X = 0, STG_W = 8192;
constexpr uint32_t SM_QS = 0;
constexpr uint32_t SM_PK = SM_QS + 16384, SM_VS = SM_QS + 32768;
constexpr uint32_t SM_WO = 65536;
constexpr uint32_t SM_KV = 131072;
constexpr uint32_t SM_BOUT = 16384;
constexpr uint32_t SM_U = 143360, U_BYTES = 4352;
constexpr uint32_t SM_P = 160768, P_BYTES = 4096;
constexpr uint32_t SM_VV = 177152, VV_BYTES = 12800;
constexpr uint32_t VV_U5 = 0, VV_U3 = 3712, VV_U9 = 7424, VV_U7 = 10112;
constexpr uint32_t KG_BYTES = 3200;
constexpr uint32_t SM_BAR = SM_VV + 4 * VV_BYTES;
constexpr uint32_t SM_PTAB = SM_BAR + 320;
constexpr uint32_t SM_TOTAL = SM_PTAB + 2048;
static_assert(SM_TOTAL <= 232448, "shared memory");
constexpr int PADV = 12;

enum { B_FULL = 0, B_EMPTY = 7, B_TILE = 14, B_UCH = 15, B_KVP = 19, B_KVF = 20, B_OST = 21, B_RF = 22, B_WO = 30, B_RE = 31, B_PFREE = 32, B_CONVD = 33, B_SLOT = 34, B_COUNT = 35 };
__host__ __device__ constexpr int bar_count(int i) {
  return (i >= B_EMPTY && i < B_TILE) ? 16 : (i == B_KVP || i == B_OST || i == B_CONVD) ? 8 : i == B_RE ? 16 : i == B_SLOT ? 2 : 1;
}

constexpr int PD_OFF = 0, P2_OFF = 544, P3_OFF = 768;

constexpr int SL_K2048 = 20, SL_ZERO = 21, SL_510 = 22, SL_0 = 23;
__host__ __device__ constexpr int koff(int y) {
  return y < 8 ? y : y < 12 ? 256 + 2 * (y - 8) : y < 16 ? 512 + 256 * ((y - 12) >> 1) + 4 * (y & 1) : 1024 + 256 * (y - 16);
}
__host__ __device__ constexpr int kidx_c(int l) {
  const int y = l < 256 ? (l & 7) : l < 512 ? 8 + ((l & 7) >> 1) : l < 1024 ? 12 + (((l - 512) >> 8) << 1) + ((l >> 2) & 1)
                                                                            : 16 + ((l - 1024) >> 8);
  return ((l >> 3) & 31) * 24 + y;
}
constexpr int slot_direct(int l) {
  if (l < 0 || l > 510) return SL_ZERO;
  if (l == 510) return SL_510;
  if (l == 0) return SL_0;
  return kidx_c(l < 256 ? l : ((l + ((l >> 1) & 1)) & ~1));
}
constexpr int slot_seg2(int v, int k) { return (k >= 32 && k < 64) ? kidx_c(16 * k + 4 * v) : SL_ZERO; }
constexpr int slot_seg3(int pi, int k) {
  return (k >= 64 && k < 128) ? kidx_c(16 * k + 8 * pi) : ((k == 128 && pi == 0) ? SL_K2048 : SL_ZERO);
}
constexpr int slot_word(int w) {
  return w < 0 ? SL_ZERO : w < 544 ? slot_direct(w - 16) : w < 768 ? slot_seg2((w - 544) / 56, 16 + (w - 544) % 56)
       : w < 944 ? slot_seg3((w - 768) / 88, 48 + (w - 768) % 88) : SL_ZERO;
}
struct PTab { uint32_t v[512]; };
constexpr PTab make_ptab() {
  PTab t{};
  for (int lane = 0; lane < 32; ++lane)
    for (int i = 0; i < 16; ++i)
      t.v[i * 32 + lane] = (slot_word(31 * lane - 1 + 2 * i) * 4) | ((slot_word(31 * lane + 2 * i) * 4) << 16);
  return t;
}
__device__ const PTab g_ptab = make_ptab();

__device__ __nv_bfloat16 g_uT[512 * 2048];
__device__ __nv_bfloat16 g_yT[512 * 2048];
__device__ __nv_bfloat16 g_o[2048 * 512];
__device__ float g_kv[2][8][4 * 272];
__device__ unsigned g_cnt[64 * 32];
__device__ unsigned g_epoch;
#define TS(slot) do { } while (0)
#define TSR(on, slot) do { } while (0)
#define TSD(slot) do { } while (0)
enum { C_U = 0, C_KV = 8, C_O = 16, C_Y = 32 };

struct Maps {
  CUtensorMap x, w, wo, u, uT, yT, o, out, outh;
};
struct Ptrs {
  const __nv_bfloat16 *A_re, *A_im, *B_re, *B_im, *C_re, *C_im, *log_dt, *Dskip;
  const __nv_bfloat16 *x, *wqkv, *wo;
  __nv_bfloat16 *uT, *yT;
};

DEVI uint32_t s2u(const void* p) { return (uint32_t)__cvta_generic_to_shared(p); }
DEVI void mbar_init(uint32_t b, uint32_t c) { asm volatile("mbarrier.init.shared::cta.b64 [%0], %1;" ::"r"(b), "r"(c) : "memory"); }
DEVI void mbar_expect_tx(uint32_t b, uint32_t bytes) {
  asm volatile("mbarrier.arrive.expect_tx.shared::cta.b64 _, [%0], %1;" ::"r"(b), "r"(bytes) : "memory");
}
DEVI void mbar_arrive(uint32_t b) { asm volatile("mbarrier.arrive.shared::cta.b64 _, [%0];" ::"r"(b) : "memory"); }
DEVI void mbar_arrive_cluster(uint32_t b, uint32_t cta) {
  asm volatile("{\n.reg .b32 r;\nmapa.shared::cluster.u32 r, %0, %1;\nmbarrier.arrive.shared::cluster.b64 _, [r];\n}"
               ::"r"(b), "r"(cta) : "memory");
}
DEVI void mbar_wait(uint32_t b, uint32_t parity) {
  asm volatile("{\n.reg .pred p;\nLAB_WAIT:\nmbarrier.try_wait.parity.shared::cta.b64 p, [%0], %1;\n@!p bra LAB_WAIT;\n}"
               ::"r"(b), "r"(parity) : "memory");
}
DEVI void mbar_wait_long(uint32_t b, uint32_t parity) {
  asm volatile("{\n.reg .pred p;\nLAB_WAIT:\nmbarrier.try_wait.parity.shared::cta.b64 p, [%0], %1, 0x989680;\n@!p bra LAB_WAIT;\n}"
               ::"r"(b), "r"(parity) : "memory");
}
DEVI void bar_sync(int id, int n) { asm volatile("bar.sync %0, %1;" ::"r"(id), "r"(n) : "memory"); }
DEVI void bar_arrive(int id, int n) { asm volatile("bar.arrive %0, %1;" ::"r"(id), "r"(n) : "memory"); }
DEVI void fence_async_smem() { asm volatile("fence.proxy.async.shared::cta;" ::: "memory"); }
DEVI void fence_async_all() { asm volatile("fence.proxy.async;" ::: "memory"); }
DEVI void cluster_arrive() { asm volatile("barrier.cluster.arrive.relaxed.aligned;" ::: "memory"); }
DEVI void cluster_wait() { asm volatile("barrier.cluster.wait.aligned;" ::: "memory"); }

DEVI void tma_load_2d(uint32_t dst, const CUtensorMap* m, int c0, int c1, uint32_t bar) {
  asm volatile("cp.async.bulk.tensor.2d.shared::cluster.global.mbarrier::complete_tx::bytes [%0], [%1, {%3, %4}], [%2];"
               ::"r"(dst), "l"(m), "r"(bar), "r"(c0), "r"(c1) : "memory");
}
DEVI void tma_load_2d_mc(uint32_t dst, const CUtensorMap* m, int c0, int c1, uint32_t bar, uint16_t mask) {
  asm volatile("cp.async.bulk.tensor.2d.shared::cluster.global.mbarrier::complete_tx::bytes.multicast::cluster [%0], [%1, {%3, %4}], [%2], %5;"
               ::"r"(dst), "l"(m), "r"(bar), "r"(c0), "r"(c1), "h"(mask) : "memory");
}
DEVI void tma_load_3d_mc(uint32_t dst, const CUtensorMap* m, int c0, int c1, int c2, uint32_t bar, uint16_t mask) {
  asm volatile("cp.async.bulk.tensor.3d.shared::cluster.global.mbarrier::complete_tx::bytes.multicast::cluster [%0], [%1, {%3, %4, %5}], [%2], %6;"
               ::"r"(dst), "l"(m), "r"(bar), "r"(c0), "r"(c1), "r"(c2), "h"(mask) : "memory");
}
DEVI void tma_store_2d(const CUtensorMap* m, uint32_t src, int c0, int c1) {
  asm volatile("cp.async.bulk.tensor.2d.global.shared::cta.bulk_group [%0, {%2, %3}], [%1];"
               ::"l"(m), "r"(src), "r"(c0), "r"(c1) : "memory");
}
DEVI void bulk_load(uint32_t dst, const void* src, uint32_t bytes, uint32_t bar) {
  asm volatile("cp.async.bulk.shared::cluster.global.mbarrier::complete_tx::bytes [%0], [%1], %2, [%3];"
               ::"r"(dst), "l"(src), "r"(bytes), "r"(bar) : "memory");
}
DEVI void bulk_store(void* dst, uint32_t src, uint32_t bytes) {
  asm volatile("cp.async.bulk.global.shared::cta.bulk_group [%0], [%1], %2;" ::"l"(dst), "r"(src), "r"(bytes) : "memory");
}
DEVI void bulk_reduce_add_f32(void* dst, uint32_t src, uint32_t bytes) {
  asm volatile("cp.reduce.async.bulk.global.shared::cta.bulk_group.add.f32 [%0], [%1], %2;" ::"l"(dst), "r"(src), "r"(bytes) : "memory");
}
DEVI void bulk_commit() { asm volatile("cp.async.bulk.commit_group;" ::: "memory"); }
DEVI void bulk_wait0() { asm volatile("cp.async.bulk.wait_group 0;" ::: "memory"); }
DEVI void bulk_wait_read0() { asm volatile("cp.async.bulk.wait_group.read 0;" ::: "memory"); }
DEVI void l2_prefetch(const void* p, uint32_t bytes) {
  asm volatile("cp.async.bulk.prefetch.L2.global [%0], %1;" ::"l"(p), "r"(bytes) : "memory");
}
DEVI void prefetch_tmap(const CUtensorMap* m) { asm volatile("prefetch.tensormap [%0];" ::"l"(m) : "memory"); }

DEVI void red_release_add(unsigned* p, unsigned v) {
  asm volatile("red.release.gpu.global.add.u32 [%0], %1;" ::"l"(p), "r"(v) : "memory");
}
DEVI void red_relaxed_add(unsigned* p, unsigned v) {
  asm volatile("red.relaxed.gpu.global.add.u32 [%0], %1;" ::"l"(p), "r"(v) : "memory");
}
DEVI unsigned ld_relaxed(const unsigned* p) {
  unsigned v;
  asm volatile("ld.relaxed.gpu.global.u32 %0, [%1];" : "=r"(v) : "l"(p) : "memory");
  return v;
}
DEVI void wait_counter(const unsigned* p, unsigned target) {
#pragma unroll 1
  for (int it = 0; (int)(ld_relaxed(p) - target) < 0; ++it)
    if (it > (1 << 22)) __trap();
}

DEVI void ldsm_x4(uint32_t (&r)[4], uint32_t a) {
  asm volatile("ldmatrix.sync.aligned.m8n8.x4.shared.b16 {%0,%1,%2,%3}, [%4];"
               : "=r"(r[0]), "=r"(r[1]), "=r"(r[2]), "=r"(r[3]) : "r"(a) : "memory");
}
DEVI void ldsm_x4_t(uint32_t (&r)[4], uint32_t a) {
  asm volatile("ldmatrix.sync.aligned.m8n8.x4.trans.shared.b16 {%0,%1,%2,%3}, [%4];"
               : "=r"(r[0]), "=r"(r[1]), "=r"(r[2]), "=r"(r[3]) : "r"(a) : "memory");
}
DEVI void ldsm_x2_t(uint32_t& r0, uint32_t& r1, uint32_t a) {
  asm volatile("ldmatrix.sync.aligned.m8n8.x2.trans.shared.b16 {%0,%1}, [%2];" : "=r"(r0), "=r"(r1) : "r"(a) : "memory");
}
DEVI void stsm_x4(uint32_t a, uint32_t r0, uint32_t r1, uint32_t r2, uint32_t r3) {
  asm volatile("stmatrix.sync.aligned.m8n8.x4.shared.b16 [%0], {%1,%2,%3,%4};"
               ::"r"(a), "r"(r0), "r"(r1), "r"(r2), "r"(r3) : "memory");
}
DEVI void stsm_x4_t(uint32_t a, uint32_t r0, uint32_t r1, uint32_t r2, uint32_t r3) {
  asm volatile("stmatrix.sync.aligned.m8n8.x4.trans.shared.b16 [%0], {%1,%2,%3,%4};"
               ::"r"(a), "r"(r0), "r"(r1), "r"(r2), "r"(r3) : "memory");
}
DEVI uint32_t lds32(uint32_t a) { uint32_t v; asm volatile("ld.shared.b32 %0, [%1];" : "=r"(v) : "r"(a) : "memory"); return v; }
DEVI float lds_f32(uint32_t a) { float v; asm volatile("ld.shared.f32 %0, [%1];" : "=f"(v) : "r"(a) : "memory"); return v; }
DEVI void sts32(uint32_t a, uint32_t v) { asm volatile("st.shared.b32 [%0], %1;" ::"r"(a), "r"(v) : "memory"); }
DEVI void sts_f32(uint32_t a, float v) { asm volatile("st.shared.f32 [%0], %1;" ::"r"(a), "f"(v) : "memory"); }
DEVI void sts_f32x2(uint32_t a, float x, float y) { asm volatile("st.shared.v2.f32 [%0], {%1,%2};" ::"r"(a), "f"(x), "f"(y) : "memory"); }
DEVI uint4 lds128(uint32_t a) {
  uint4 v;
  asm volatile("ld.shared.v4.b32 {%0,%1,%2,%3}, [%4];" : "=r"(v.x), "=r"(v.y), "=r"(v.z), "=r"(v.w) : "r"(a) : "memory");
  return v;
}
DEVI void sts128(uint32_t a, uint32_t x, uint32_t y, uint32_t z, uint32_t w) {
  asm volatile("st.shared.v4.b32 [%0], {%1,%2,%3,%4};" ::"r"(a), "r"(x), "r"(y), "r"(z), "r"(w) : "memory");
}

DEVI void mma_bf16(float (&d)[4], uint32_t a0, uint32_t a1, uint32_t a2, uint32_t a3, uint32_t b0, uint32_t b1) {
  asm("mma.sync.aligned.m16n8k16.row.col.f32.bf16.bf16.f32 {%0,%1,%2,%3}, {%4,%5,%6,%7}, {%8,%9}, {%0,%1,%2,%3};"
      : "+f"(d[0]), "+f"(d[1]), "+f"(d[2]), "+f"(d[3])
      : "r"(a0), "r"(a1), "r"(a2), "r"(a3), "r"(b0), "r"(b1));
}
DEVI void mma_f16(float (&d)[4], const uint32_t (&a)[4], uint32_t b0, uint32_t b1) {
  asm("mma.sync.aligned.m16n8k16.row.col.f32.f16.f16.f32 {%0,%1,%2,%3}, {%4,%5,%6,%7}, {%8,%9}, {%0,%1,%2,%3};"
      : "+f"(d[0]), "+f"(d[1]), "+f"(d[2]), "+f"(d[3])
      : "r"(a[0]), "r"(a[1]), "r"(a[2]), "r"(a[3]), "r"(b0), "r"(b1));
}
DEVI void mma_bf16v(float (&d)[4], const uint32_t (&a)[4], uint32_t b0, uint32_t b1) {
  asm volatile("mma.sync.aligned.m16n8k16.row.col.f32.bf16.bf16.f32 {%0,%1,%2,%3}, {%4,%5,%6,%7}, {%8,%9}, {%0,%1,%2,%3};"
               : "+f"(d[0]), "+f"(d[1]), "+f"(d[2]), "+f"(d[3])
               : "r"(a[0]), "r"(a[1]), "r"(a[2]), "r"(a[3]), "r"(b0), "r"(b1));
}
DEVI uint32_t pack_bf16(float lo, float hi) {
  uint32_t r;
  asm("cvt.rn.bf16x2.f32 %0, %1, %2;" : "=r"(r) : "f"(hi), "f"(lo));
  return r;
}
DEVI uint32_t pack_f16(float lo, float hi) {
  uint32_t r;
  asm("cvt.rn.f16x2.f32 %0, %1, %2;" : "=r"(r) : "f"(hi), "f"(lo));
  return r;
}
DEVI uint32_t ldg16(const __nv_bfloat16* p) {
  uint32_t v;
  asm volatile("ld.global.nc.u16 %0, [%1];" : "=r"(v) : "l"(p));
  return v;
}
DEVI bool elect_one() {
  uint32_t pred;
  asm volatile("{\n.reg .pred p;\nelect.sync _|p, 0xffffffff;\nselp.u32 %0, 1, 0, p;\n}" : "=r"(pred));
  return pred != 0;
}
DEVI float bf_lo(uint32_t v) { return __uint_as_float(v << 16); }
DEVI float bf_hi(uint32_t v) { return __uint_as_float(v & 0xffff0000u); }
DEVI float bf2f(__nv_bfloat16 v) { return __bfloat162float(v); }
DEVI float round_bf16(float v) { return __bfloat162float(__float2bfloat16_rn(v)); }
DEVI float rcp(float x) { float r; asm("rcp.approx.ftz.f32 %0, %1;" : "=f"(r) : "f"(x)); return r; }
DEVI float ex2(float x) { float r; asm("ex2.approx.ftz.f32 %0, %1;" : "=f"(r) : "f"(x)); return r; }

DEVI void wg_fence() { asm volatile("wgmma.fence.sync.aligned;" ::: "memory"); }
DEVI void wg_commit() { asm volatile("wgmma.commit_group.sync.aligned;" ::: "memory"); }
template <int N> DEVI void wg_wait() { asm volatile("wgmma.wait_group.sync.aligned %0;" ::"n"(N) : "memory"); }
constexpr uint32_t DESC_HI = (1u << 30) | (1024 >> 4);
constexpr uint32_t DESC_HI64 = (2u << 30) | (512 >> 4);
DEVI uint32_t mkdesc(uint32_t saddr, uint32_t lbo) { return ((saddr & 0x3FFFF) >> 4) | ((lbo >> 4) << 16); }

#define R8(b) "%" #b
DEVI void wgmma_n192(float (&d)[96], uint32_t da, uint32_t db, int scale_d) {
  asm volatile(
      "{\n.reg .pred p;\n.reg .b64 da, db;\nsetp.ne.b32 p, %98, 0;\nmov.b64 da, {%96, %100};\nmov.b64 db, {%97, %99};\n"
      "wgmma.mma_async.sync.aligned.m64n192k16.f32.bf16.bf16 "
      "{%0,%1,%2,%3,%4,%5,%6,%7,%8,%9,%10,%11,%12,%13,%14,%15,"
      "%16,%17,%18,%19,%20,%21,%22,%23,%24,%25,%26,%27,%28,%29,%30,%31,"
      "%32,%33,%34,%35,%36,%37,%38,%39,%40,%41,%42,%43,%44,%45,%46,%47,"
      "%48,%49,%50,%51,%52,%53,%54,%55,%56,%57,%58,%59,%60,%61,%62,%63,"
      "%64,%65,%66,%67,%68,%69,%70,%71,%72,%73,%74,%75,%76,%77,%78,%79,"
      "%80,%81,%82,%83,%84,%85,%86,%87,%88,%89,%90,%91,%92,%93,%94,%95}, "
      "da, db, p, 1, 1, 0, 1;\n}"
      : "+f"(d[0]), "+f"(d[1]), "+f"(d[2]), "+f"(d[3]), "+f"(d[4]), "+f"(d[5]), "+f"(d[6]), "+f"(d[7]),
        "+f"(d[8]), "+f"(d[9]), "+f"(d[10]), "+f"(d[11]), "+f"(d[12]), "+f"(d[13]), "+f"(d[14]), "+f"(d[15]),
        "+f"(d[16]), "+f"(d[17]), "+f"(d[18]), "+f"(d[19]), "+f"(d[20]), "+f"(d[21]), "+f"(d[22]), "+f"(d[23]),
        "+f"(d[24]), "+f"(d[25]), "+f"(d[26]), "+f"(d[27]), "+f"(d[28]), "+f"(d[29]), "+f"(d[30]), "+f"(d[31]),
        "+f"(d[32]), "+f"(d[33]), "+f"(d[34]), "+f"(d[35]), "+f"(d[36]), "+f"(d[37]), "+f"(d[38]), "+f"(d[39]),
        "+f"(d[40]), "+f"(d[41]), "+f"(d[42]), "+f"(d[43]), "+f"(d[44]), "+f"(d[45]), "+f"(d[46]), "+f"(d[47]),
        "+f"(d[48]), "+f"(d[49]), "+f"(d[50]), "+f"(d[51]), "+f"(d[52]), "+f"(d[53]), "+f"(d[54]), "+f"(d[55]),
        "+f"(d[56]), "+f"(d[57]), "+f"(d[58]), "+f"(d[59]), "+f"(d[60]), "+f"(d[61]), "+f"(d[62]), "+f"(d[63]),
        "+f"(d[64]), "+f"(d[65]), "+f"(d[66]), "+f"(d[67]), "+f"(d[68]), "+f"(d[69]), "+f"(d[70]), "+f"(d[71]),
        "+f"(d[72]), "+f"(d[73]), "+f"(d[74]), "+f"(d[75]), "+f"(d[76]), "+f"(d[77]), "+f"(d[78]), "+f"(d[79]),
        "+f"(d[80]), "+f"(d[81]), "+f"(d[82]), "+f"(d[83]), "+f"(d[84]), "+f"(d[85]), "+f"(d[86]), "+f"(d[87]),
        "+f"(d[88]), "+f"(d[89]), "+f"(d[90]), "+f"(d[91]), "+f"(d[92]), "+f"(d[93]), "+f"(d[94]), "+f"(d[95])
      : "r"(da), "r"(db), "r"(scale_d), "n"(DESC_HI), "n"(DESC_HI64));
}
DEVI void wgmma_n64(float (&d)[32], uint32_t da, uint32_t db, int scale_d) {
  asm volatile(
      "{\n.reg .pred p;\n.reg .b64 da, db;\nsetp.ne.b32 p, %34, 0;\nmov.b64 da, {%32, %35};\nmov.b64 db, {%33, %35};\n"
      "wgmma.mma_async.sync.aligned.m64n64k16.f32.bf16.bf16 "
      "{%0,%1,%2,%3,%4,%5,%6,%7,%8,%9,%10,%11,%12,%13,%14,%15,"
      "%16,%17,%18,%19,%20,%21,%22,%23,%24,%25,%26,%27,%28,%29,%30,%31}, "
      "da, db, p, 1, 1, 0, 1;\n}"
      : "+f"(d[0]), "+f"(d[1]), "+f"(d[2]), "+f"(d[3]), "+f"(d[4]), "+f"(d[5]), "+f"(d[6]), "+f"(d[7]),
        "+f"(d[8]), "+f"(d[9]), "+f"(d[10]), "+f"(d[11]), "+f"(d[12]), "+f"(d[13]), "+f"(d[14]), "+f"(d[15]),
        "+f"(d[16]), "+f"(d[17]), "+f"(d[18]), "+f"(d[19]), "+f"(d[20]), "+f"(d[21]), "+f"(d[22]), "+f"(d[23]),
        "+f"(d[24]), "+f"(d[25]), "+f"(d[26]), "+f"(d[27]), "+f"(d[28]), "+f"(d[29]), "+f"(d[30]), "+f"(d[31])
      : "r"(da), "r"(db), "r"(scale_d), "n"(DESC_HI));
}

struct C32 { float re, im; };
DEVI C32 csq(C32 a) { return {a.re * a.re - a.im * a.im, 2.f * a.re * a.im}; }
DEVI C32 cmul(C32 a, C32 b) { return {a.re * b.re - a.im * b.im, a.re * b.im + a.im * b.re}; }
DEVI C32 cfresh(float zl, float zi, float m) {
  float mag = ex2(zl * m), ph = zi * m;
  return {mag * __cosf(ph), mag * __sinf(ph)};
}
struct HMul { uint32_t b, bp; };
DEVI HMul mk_mul(float re, float im) { return {pack_f16(re, im), pack_f16(-im, re)}; }
DEVI uint32_t hcmul(uint32_t a, const HMul& m) {
  __half2 ah = *reinterpret_cast<__half2*>(&a);
  __half2 b = *reinterpret_cast<const __half2*>(&m.b), bp = *reinterpret_cast<const __half2*>(&m.bp);
  __half2 r = __hfma2(__high2half2(ah), bp, __hmul2(__low2half2(ah), b));
  return *reinterpret_cast<uint32_t*>(&r);
}
DEVI uint32_t badd(uint32_t a, uint32_t b) {
  __nv_bfloat162 r = __hadd2(*reinterpret_cast<__nv_bfloat162*>(&a), *reinterpret_cast<__nv_bfloat162*>(&b));
  return *reinterpret_cast<uint32_t*>(&r);
}
template <int MU0, int NMU, int DMAX>
DEVI void conv_tail(float (&acc)[16][4], uint32_t p_lane, uint32_t v_base, int back, bool edge, int lane) {
  const int hsel = (lane >> 3) & 1;
  const int row = (lane & 7) + ((lane >> 4) << 3) + PADV - 8 - (back & (hsel ^ 1));
  const uint32_t la = v_base + row * 32 + (((hsel ^ back) ^ ((row >> 2) & 1)) << 4);
  uint32_t M[3][4];
  ldsm_x4_t(M[0], la);
  ldsm_x4_t(M[1], la + 256);
  uint32_t H[2 * NMU];
#pragma unroll
  for (int i = 0; i < 2 * NMU; ++i) H[i ^ 1] = lds32(p_lane + (uint32_t)(MU0 - 1 + i) * 32);
  if (edge) {
    const uint32_t a[4] = {0u, 0u, M[0][0], M[0][1]};
#pragma unroll
    for (int k = 1; k < NMU; ++k) mma_bf16v(acc[MU0 - 2 + 2 * k], a, H[2 * k], H[2 * k + 1]);
  }
#pragma unroll
  for (int delta = -1; delta <= DMAX; ++delta) {
    if (delta + 2 <= DMAX) ldsm_x4_t(M[(delta + 3) % 3], la + (delta + 3) * 256);
#pragma unroll
    for (int k = 0; k < NMU; ++k)
      if (delta + MU0 + 2 * k < 16) mma_bf16v(acc[delta + MU0 + 2 * k], M[(delta + 1) % 3], H[2 * k], H[2 * k + 1]);
  }
}

template <int NB>
DEVI void box_filters(uint32_t sb, uint32_t bars, int idx, int lane) {
  auto swz = [](int k, int pad) { const int r = (k >> 1) + pad; return (uint32_t)(r * 32 + (((k & 1) ^ ((r >> 2) & 1)) << 4)); };
  const uint32_t o0 = swz(lane - 3, 8), o1 = swz(lane - 2, 8), o2 = swz(lane - 1, 8), ow = swz(lane - 2, PADV), oz = swz(lane - 18, PADV);
  const int k = 32 * idx - 2 + lane;
#pragma unroll 1
  for (int c2 = 0; c2 < 4; c2 += NB) {
    uint4 t[NB][3];
#pragma unroll
    for (int b = 0; b < NB; ++b) mbar_wait_long(bars + 8 * (B_UCH + c2 + b), 0);
#pragma unroll
    for (int b = 0; b < NB; ++b) {
      const uint32_t ua = sb + SM_U + (c2 + b) * U_BYTES + idx * 512;
      t[b][0] = lds128(ua + o0); t[b][1] = lds128(ua + o1); t[b][2] = lds128(ua + o2);
    }
#pragma unroll
    for (int b = 0; b < NB; ++b) {
      const uint32_t vb = sb + SM_VV + (c2 + b) * VV_BYTES, aw = vb + idx * 512 + ow;
      const uint32_t E[12] = {t[b][0].x, t[b][0].y, t[b][0].z, t[b][0].w, t[b][1].x, t[b][1].y, t[b][1].z, t[b][1].w,
                              t[b][2].x, t[b][2].y, t[b][2].z, t[b][2].w};
      uint32_t O[8];
#pragma unroll
      for (int j = 0; j < 8; ++j) O[j] = __byte_perm(E[j + 1], E[j + 2], 0x5432);
      uint32_t s3[6], s5[4], s7[4], s9[4];
#pragma unroll
      for (int j = 0; j < 6; ++j) s3[j] = badd(badd(O[j], O[j + 1]), E[j + 2]);
#pragma unroll
      for (int j = 0; j < 4; ++j) {
        s5[j] = badd(s3[j + 2], badd(E[j + 3], E[j + 5]));
        s7[j] = badd(s5[j], badd(O[j + 1], O[j + 4]));
        s9[j] = badd(s7[j], badd(E[j + 2], E[j + 6]));
      }
      if (k < 208) { sts128(aw + VV_U3, s3[0], s3[1], s3[2], s3[3]); sts128(aw + VV_U5, s5[0], s5[1], s5[2], s5[3]); }
      if (k < 144) { sts128(aw + VV_U7, s7[0], s7[1], s7[2], s7[3]); sts128(aw + VV_U9, s9[0], s9[1], s9[2], s9[3]); }
      if (idx == 0 && lane < 16) {
        sts128(vb + oz + VV_U3, 0, 0, 0, 0); sts128(vb + oz + VV_U5, 0, 0, 0, 0);
        sts128(vb + oz + VV_U7, 0, 0, 0, 0); sts128(vb + oz + VV_U9, 0, 0, 0, 0);
      }
    }
  }
}

__global__ void __cluster_dims__(2, 1, 1) __launch_bounds__(NTHREADS, 1)
fused_kernel(const __grid_constant__ Maps maps, const Ptrs p) {
  extern __shared__ __align__(1024) uint8_t smem[];
  const uint32_t sb = s2u(smem);
  const int tid = threadIdx.x, lane = tid & 31;
  const int warp = __shfl_sync(0xffffffffu, tid >> 5, 0);
  const int cta = blockIdx.x;
  const uint32_t rank = cta & 1;
  const int ti = 2 * (cta >> 4) + rank;
  const int tj = (cta >> 1) & 7;
  const int pi = cta >> 3, pj = cta & 7;
  const uint32_t bars = sb + SM_BAR;
#define BAR(i) (bars + 8 * (i))
  const int g = lane >> 2, q = lane & 3;

  auto issue_stage = [&](int ks, int s) {
    const uint32_t st = sb + s * STG_BYTES, fb = BAR(B_FULL + s);
    mbar_expect_tx(fb, STG_BYTES);
    tma_load_2d(st + STG_X, &maps.x, ks * 32, ti * 128, fb);
    tma_load_3d_mc(st + STG_W + rank * 6144, &maps.w, tj * 64, ks * 32 + rank * 16, 0, fb, 3);
  };

  const int kch = warp & 3, krd = warp >> 2;
  float zr, zi, wr, wi;
  unsigned epoch;
  uint32_t r_dskip;
  {
    const size_t po = (size_t)(cta * 4 + kch) * 128 + krd * 32 + lane;
    const uint32_t r_ar = ldg16(p.A_re + po), r_ai = ldg16(p.A_im + po), r_br = ldg16(p.B_re + po), r_bi = ldg16(p.B_im + po);
    const uint32_t r_cr = ldg16(p.C_re + po), r_ci = ldg16(p.C_im + po), r_ldt = ldg16(p.log_dt + cta * 4 + kch);
    epoch = __ldcg(&g_epoch);
    r_dskip = ldg16(p.Dskip + cta * 4 + kch);
    uint4 pt;
    if (tid < 128) pt = __ldg((const uint4*)g_ptab.v + tid);
    if (tid == 384) {
      TS(0);
#pragma unroll
      for (int i = 0; i < B_COUNT; ++i) mbar_init(BAR(i), bar_count(i));
      asm volatile("fence.mbarrier_init.release.cluster;" ::: "memory");
      prefetch_tmap(&maps.x); prefetch_tmap(&maps.w); prefetch_tmap(&maps.u);
    }
    __syncthreads();
    cluster_arrive();
    if (warp >= 12) {
      cluster_wait();
      if (elect_one()) {
        if (warp == 13) {
          mbar_expect_tx(BAR(B_TILE), 16384);
          tma_load_2d(sb + SM_U, &maps.u, tj * 64, ti * 128, BAR(B_TILE));
          prefetch_tmap(&maps.uT); prefetch_tmap(&maps.wo); prefetch_tmap(&maps.o); prefetch_tmap(&maps.yT);
          prefetch_tmap(&maps.out); prefetch_tmap(&maps.outh);
        } else {
          if (warp == 12) TS(61);
          { const int ks = warp == 12 ? 0 : warp - 13; issue_stage(ks, ks); }
        }
      }
      __syncwarp();
    }
    if (tid < 128) sts128(sb + SM_PTAB + tid * 16, pt.x, pt.y, pt.z, pt.w);
    const float dt = round_bf16(expf(bf_lo(r_ldt)));
    zr = dt * bf_lo(r_ar); zi = dt * bf_lo(r_ai);
    const float dbr = dt * bf_lo(r_br), dbi = dt * bf_lo(r_bi), cr = bf_lo(r_cr), ci = bf_lo(r_ci);
    wr = cr * dbr - ci * dbi; wi = cr * dbi + ci * dbr;
  }
  {
    const float mz = __uint_as_float(__reduce_max_sync(0xffffffffu, __float_as_uint(fmaxf(zr, 0.f))));
    const int E = min(max((int)(__reduce_max_sync(0xffffffffu, __float_as_uint(fmaxf(fabsf(wr), fabsf(wi)))) >> 23), 1), 252);
    const float sc = __int_as_float((253 - E) << 23), inv = __int_as_float((E + 1) << 23);
    const float zl = (zr - mz) * 1.4426950408889634f;
    const uint32_t tb = sb + SM_VV + kch * VV_BYTES + krd * KG_BYTES;
    const uint32_t sta = tb + (((lane >> 2) << 4) | ((lane & 3) << 2));
    auto put = [&](int r, uint32_t v) { sts32((sta ^ ((r & 7) << 4)) + r * 128, v); };
    const uint32_t lda = tb + ((lane & 7) + (((lane >> 3) & 1) << 3)) * 128;
    const uint32_t ldb = tb + ((lane & 7) + ((lane >> 4) << 3)) * 128;
    C32 e1 = cfresh(zl, zi, 1.f), e2 = csq(e1), e4 = csq(e2), e8 = csq(e4);
    C32 e16 = cfresh(zl, zi, 16.f), e32 = csq(e16), e64 = csq(e32), e128 = csq(e64);
    C32 e256 = cfresh(zl, zi, 256.f), e512 = csq(e256), e1024 = csq(e512), e768 = cmul(e512, e256);
    uint32_t XA[2][4][4];
    {
      const HMul m16 = mk_mul(e16.re, e16.im), m32 = mk_mul(e32.re, e32.im), m64 = mk_mul(e64.re, e64.im);
      const HMul m128 = mk_mul(e128.re, e128.im);
      uint32_t X[16];
      X[0] = 0x00003c00u; X[1] = pack_f16(e8.re, e8.im); X[2] = m16.b; X[4] = m32.b; X[8] = m64.b;
      X[3] = hcmul(X[1], m16); X[5] = hcmul(X[1], m32); X[6] = hcmul(X[2], m32); X[7] = hcmul(X[3], m32);
#pragma unroll
      for (int r = 1; r < 8; ++r) X[8 + r] = hcmul(X[r], m64);
#pragma unroll
      for (int h = 0; h < 2; ++h) {
#pragma unroll
        for (int r = 0; r < 16; ++r) put(r, h == 0 ? X[r] : r == 0 ? m128.b : hcmul(X[r], m128));
        __syncwarp();
#pragma unroll
        for (int k = 0; k < 4; ++k) ldsm_x4(XA[h][k], lda + (((2 * k + (lane >> 4)) ^ (lane & 7)) << 4));
        __syncwarp();
      }
    }
    if (warp >= 14 && elect_one()) {
      issue_stage(warp - 11, warp - 11);
      issue_stage(warp - 9, warp - 9);
      if (warp == 14) l2_prefetch((const char*)p.wqkv + 224 * 3072 + cta * 6912, 6912);
      else l2_prefetch((const char*)p.x + (size_t)cta * 16384, 16384);
    }
    __syncwarp();
    float D[2][3][4];
#pragma unroll
    for (int t = 0; t < 6; ++t) D[t / 3][t % 3][0] = D[t / 3][t % 3][1] = D[t / 3][t % 3][2] = D[t / 3][t % 3][3] = 0.f;
    auto contract = [&](int t0, int nt) {
      __syncwarp();
#pragma unroll
      for (int k = 0; k < 4; ++k) {
        uint32_t b[4];
        ldsm_x4(b, ldb + (((2 * k + ((lane >> 3) & 1)) ^ (lane & 7)) << 4));
#pragma unroll
        for (int h = 0; h < 2; ++h) {
          mma_f16(D[h][t0], XA[h][k], b[0], b[1]);
          if (nt == 2) mma_f16(D[h][t0 + 1], XA[h][k], b[2], b[3]);
        }
      }
      __syncwarp();
    };
    const HMul c1 = mk_mul(e1.re, -e1.im), c2 = mk_mul(e2.re, -e2.im), c4 = mk_mul(e4.re, -e4.im);
    const HMul c256 = mk_mul(e256.re, -e256.im), c512 = mk_mul(e512.re, -e512.im), c768 = mk_mul(e768.re, -e768.im);
    const HMul c1024 = mk_mul(e1024.re, -e1024.im);
    uint32_t W[8];
    W[0] = pack_f16(wr * sc, -wi * sc);
    W[1] = hcmul(W[0], c1); W[2] = hcmul(W[0], c2); W[3] = hcmul(W[1], c2);
    W[4] = hcmul(W[0], c4); W[5] = hcmul(W[1], c4); W[6] = hcmul(W[2], c4); W[7] = hcmul(W[3], c4);
#pragma unroll
    for (int i = 0; i < 8; ++i) put(i, W[i]);
#pragma unroll
    for (int i = 0; i < 4; ++i) put(8 + i, hcmul(W[2 * i], c256));
    put(12, hcmul(W[0], c512)); put(13, hcmul(W[4], c512)); put(14, hcmul(W[0], c768)); put(15, hcmul(W[4], c768));
    contract(0, 2);
    const uint32_t v0 = hcmul(W[0], c1024);
    put(0, v0); put(1, hcmul(v0, c256)); put(2, hcmul(v0, c512)); put(3, hcmul(v0, c768)); put(4, hcmul(v0, c1024));
    contract(2, 1);
    const uint32_t a = tb + (g * 24 + 2 * q) * 4;
#pragma unroll
    for (int t = 0; t < 6; ++t) {
      const float(&d)[4] = D[t / 3][t % 3];
      sts_f32x2(a + (t / 3) * 1536 + (t % 3) * 32, d[0] * inv, d[1] * inv);
      sts_f32x2(a + (t / 3) * 1536 + (t % 3) * 32 + 768, d[2] * inv, d[3] * inv);
    }
    if (mz > 0.f) {
      __syncwarp();
#pragma unroll 1
      for (int i = lane; i < 768; i += 32) {
        const int r = i / 24, y = i - 24 * r;
        sts_f32(tb + i * 4, lds_f32(tb + i * 4) * ex2(mz * 1.4426950408889634f * (koff(y) + 8 * r)));
      }
    }
  }
  if (tid == 0) TS(2);
  if (warp < 12) cluster_wait();
  __syncthreads();

  if (warp < 4) {
#define A_REGS 200
    asm volatile("setmaxnreg.inc.sync.aligned.u32 %0;" ::"n"(A_REGS));
    if (tid == 0) TS(34);
    const int d = cta * 4 + warp;
    const uint32_t vv = sb + SM_VV + warp * VV_BYTES;
    const uint32_t ub = sb + SM_U + warp * U_BYTES;
    const uint32_t pb = sb + SM_P + warp * P_BYTES;
    const float dskip = bf_lo(r_dskip);
#pragma unroll 1
    for (int pass = 0; pass < 2; ++pass) {
      if (pass == 1) {
        const uint32_t kf = vv;
#pragma unroll 2
        for (int i = 0; i < 6; ++i) {
          const uint32_t a = kf + (i * 32 + lane) * 16;
          const uint4 x0 = lds128(a), x1 = lds128(a + KG_BYTES), x2 = lds128(a + 2 * KG_BYTES), x3 = lds128(a + 3 * KG_BYTES);
          auto s4 = [](uint32_t a0, uint32_t a1, uint32_t a2, uint32_t a3) {
            return __float_as_uint((__uint_as_float(a0) + __uint_as_float(a1)) + (__uint_as_float(a2) + __uint_as_float(a3)));
          };
          sts128(a, s4(x0.x, x1.x, x2.x, x3.x), s4(x0.y, x1.y, x2.y, x3.y), s4(x0.z, x1.z, x2.z, x3.z), s4(x0.w, x1.w, x2.w, x3.w));
        }
        __syncwarp();
        const float k1024 = lds_f32(kf + kidx_c(1024) * 4);
        if (lane == 0) {
          sts_f32(kf + SL_ZERO * 4, 0.f);
          sts_f32(kf + SL_510 * 4, lds_f32(kf + kidx_c(510) * 4) - lds_f32(kf + kidx_c(512) * 4));
          sts_f32(kf + SL_0 * 4, lds_f32(kf) + dskip);
        }
        __syncwarp();
        if (tid == 0) TS(36);
        mbar_wait_long(BAR(B_PFREE), 0);
        if (tid == 0) TS(37);
        {
          float prev = 0.f;
#pragma unroll 1
          for (int i0 = 0; i0 < 16; i0 += 4) {
            uint32_t e[4];
            float a[4], b[4];
#pragma unroll
            for (int i = 0; i < 4; ++i) e[i] = lds32(sb + SM_PTAB + ((i0 + i) * 32 + lane) * 4);
#pragma unroll
            for (int i = 0; i < 4; ++i) { a[i] = lds_f32(kf + (e[i] & 0xffff)); b[i] = lds_f32(kf + (e[i] >> 16)); }
#pragma unroll
            for (int i = 0; i < 4; ++i) {
              const uint32_t w = pb + (31 * lane + 2 * (i0 + i)) * 4;
              if (i0 + i > 0) sts32(w - 4, pack_bf16(a[i], prev));
              sts32(w, pack_bf16(b[i], a[i]));
              prev = b[i];
            }
          }
        }
        __syncwarp();
        if (lane == 0) TS(4);
        const int gq = g - 2 * q;
        uint32_t h127, h128;
        {
          const uint32_t kf2 = pack_bf16(k1024, k1024) ^ 0x80008000u;
          h127 = (gq == 4 ? 0x0000ffffu : gq == 5 ? 0xffffffffu : gq == 6 ? 0xffff0000u : 0u) & kf2;
          h128 = (gq == -4 ? 0x0000ffffu : gq == -3 ? 0xffffffffu : gq == -2 ? 0xffff0000u : 0u) & kf2;
        }
        bar_arrive(7, 384);
        if (lane == 0) TS(6);
        bar_sync(4, 384);
        mbar_wait_long(BAR(B_UCH + warp), 0);
        if (lane == 0) TS(7);
        float acc[16][4];
#pragma unroll
        for (int i = 0; i < 16; ++i) { acc[i][0] = acc[i][1] = acc[i][2] = acc[i][3] = 0.f; }
        {
          const uint32_t pd_lane = pb + (PD_OFF + 16 + gq) * 4;
          const int prow0 = 8 + (lane & 7) + ((lane >> 4) << 3), hs = (lane >> 3) & 1;
          const uint32_t zero = (uint32_t)cta >> 20;
          uint32_t B[2][4][4];
          uint32_t A[4][4];
          const uint32_t la0 = ub + prow0 * 32 + ((hs ^ ((prow0 >> 2) & 1)) << 4);
#pragma unroll
          for (int m2 = 0; m2 < 4; ++m2) ldsm_x4(B[0][m2], la0 + m2 * 512);
#pragma unroll
          for (int i = 0; i < 4; ++i) {
            const uint32_t a = pd_lane + i * 512;
            A[i][0] = lds32(a); A[i][1] = lds32(a + 32); A[i][2] = lds32(a - 32); A[i][3] = lds32(a + zero);
          }
          uint32_t la = la0;
#define UNR_RHO 4
#define UNR_TAIL 4
          constexpr int unr_rho = UNR_RHO, unr_tail = UNR_TAIL;
#pragma unroll unr_rho
          for (int rho = 0; rho < 8; ++rho) {
#pragma unroll
            for (int m2 = 0; m2 < 4; ++m2) ldsm_x4(B[1][m2], la + (4 + m2) * 512);
#pragma unroll
            for (int i = 0; i < 4; ++i)
#pragma unroll
              for (int m = 0; m < 8; ++m) mma_bf16v(acc[m + i], A[i], B[0][m >> 1][2 * (m & 1)], B[0][m >> 1][2 * (m & 1) + 1]);
            const int prow = prow0 - min(rho + 1, 7);
            la = ub + prow * 32 + ((hs ^ ((prow >> 2) & 1)) << 4);
#pragma unroll
            for (int m2 = 0; m2 < 4; ++m2) ldsm_x4(B[0][m2], la + m2 * 512);
            const uint32_t pa = pd_lane + (rho + 1) * 64;
#pragma unroll
            for (int i = 0; i < 4; ++i) {
#pragma unroll
              for (int m = 0; m < 8 - i; ++m)
                mma_bf16v(acc[8 + m + i], A[i], B[1][m >> 1][2 * (m & 1)], B[1][m >> 1][2 * (m & 1) + 1]);
              A[i][0] = lds32(pa + i * 512); A[i][1] = lds32(pa + i * 512 + 32); A[i][2] = lds32(pa + i * 512 - 32);
              A[i][3] = lds32(pa + i * 512 + zero);
            }
          }
          if (lane == 0) TS(40);
          {
            uint32_t b8[4];
            ldsm_x4(b8, la + 4 * 512);
            const uint32_t h63 = lds32(pd_lane + 63 * 32), h64 = lds32(pd_lane + 64 * 32);
            const uint32_t a63[4] = {0u, h127, 0u, 0u}, a32[4] = {h64, 0u, h63, h64}, a64[4] = {h128, 0u, h127, h128};
#pragma unroll
            for (int m2 = 0; m2 < 4; ++m2) ldsm_x4(B[1][m2], la0 + m2 * 512);
#pragma unroll
            for (int m = 0; m < 8; ++m) mma_bf16v(acc[m + 7], a63, B[0][m >> 1][2 * (m & 1)], B[0][m >> 1][2 * (m & 1) + 1]);
#pragma unroll
            for (int m2 = 0; m2 < 2; ++m2) ldsm_x4(B[0][m2], la0 + (4 + m2) * 512);
#pragma unroll
            for (int m = 0; m < 8; ++m) mma_bf16v(acc[m + 4], a32, B[1][m >> 1][2 * (m & 1)], B[1][m >> 1][2 * (m & 1) + 1]);
            mma_bf16v(acc[15], a63, b8[0], b8[1]);
#pragma unroll
            for (int m = 0; m < 8; ++m) mma_bf16v(acc[m + 8], a64, B[1][m >> 1][2 * (m & 1)], B[1][m >> 1][2 * (m & 1) + 1]);
#pragma unroll
            for (int m = 0; m < 4; ++m) mma_bf16v(acc[m + 12], a32, B[0][m >> 1][2 * (m & 1)], B[0][m >> 1][2 * (m & 1) + 1]);
          }
          if (lane == 0) TS(41);
          bar_sync(5, 384);
#pragma unroll unr_tail
          for (int v = 0; v < 4; ++v)
            conv_tail<4, 3, 11>(acc, pb + (P2_OFF + 56 * v + gq - 16) * 4, vv + ((v & 1) ? VV_U3 : VV_U5), v >> 1, v == 0, lane);
          if (lane == 0) TS(42);
#pragma unroll unr_tail
          for (int pi = 0; pi < 2; ++pi)
            conv_tail<8, 5, 7>(acc, pb + (P3_OFF + 88 * pi + gq - 48) * 4, vv + (pi ? VV_U7 : VV_U9), pi, pi == 0, lane);
        }
        if (lane == 0) TS(8);
        __syncwarp();
        {
          const int mt = lane >> 3;
          const uint32_t a = pb + (128 * (mt >> 1) + 16 * (lane & 7) + 8 * (mt & 1)) * 2;
#pragma unroll
          for (int ab = 0; ab < 16; ab += 2)
            stsm_x4_t(a + ab * 256, pack_bf16(acc[ab][0], acc[ab][1]), pack_bf16(acc[ab][2], acc[ab][3]),
                      pack_bf16(acc[ab + 1][0], acc[ab + 1][1]), pack_bf16(acc[ab + 1][2], acc[ab + 1][3]));
        }
        fence_async_smem();
        __syncwarp();
        if (lane < 2) mbar_arrive_cluster(BAR(B_CONVD), lane);
        __syncwarp();
        cluster_arrive();
        bar_arrive(3, 384);
        if (elect_one()) {
          bulk_store(p.yT + (size_t)d * 2048, pb, 4096);
          bulk_commit();
          bulk_wait0();
          red_relaxed_add(&g_cnt[(C_Y + (cta >> 4)) * 32], 1);
          TS(9);
        }
        bar_sync(2, 128);
        if (warp == 0 && elect_one()) {
          wait_counter(&g_cnt[(C_Y + tj) * 32], (epoch + 1) * 64);
          TS(28);
          mbar_expect_tx(BAR(B_TILE), 16384);
          tma_load_2d(sb + SM_U, &maps.yT, ti * 128, tj * 64, BAR(B_TILE));
          tma_load_2d(sb + SM_U + 8192, &maps.yT, ti * 128 + 64, tj * 64, BAR(B_TILE));
        }
        __syncwarp();
      }
      mbar_wait_long(BAR(B_TILE), pass);
      if (lane == 0) TS(26 + 3 * pass);
      {
        const int m = lane >> 3, r = lane & 7;
#pragma unroll 2
        for (int it = 0; it < 8; ++it) {
          const int tb = warp * 4 + (it >> 1), cb = (it & 1) * 4 + m;
          const uint32_t at = (tb * 8 + r) * 128 + ((cb ^ r) << 4);
          const uint32_t ac = (tb >> 3) * 8192 + (cb * 8 + r) * 128 + (((tb & 7) ^ (pass ? 0 : tb >> 3) ^ r) << 4);
          uint32_t v[4];
          ldsm_x4_t(v, sb + SM_U + (pass ? ac : at));
          stsm_x4(sb + SM_P + (pass ? at : ac), v[0], v[1], v[2], v[3]);
        }
      }
      if (pass == 0 && tid == 0) TS(35);
      fence_async_smem();
      if (pass == 0) {
        bar_arrive(6, 160);
      } else {
        bar_sync(2, 128);
        if (warp == 0 && elect_one()) {
          tma_store_2d(&maps.out, sb + SM_P, 64 * tj, 128 * ti);
          bulk_commit();
          bulk_wait_read0();
          TS(30);
        }
      }
    }
  } else if (warp < 12) {
    const int w8 = warp - 4;
    const int row = w8 * 16 + (lane & 7) + (((lane >> 3) & 1) << 3);
    uint32_t pq[16];
    {
      float acc[96];
#pragma unroll 1
      for (int ks = 0, s = 0, ph = 0; ks < 16; ++ks) {
        mbar_wait(BAR(B_FULL + s), ph);
        if (tid == 128 && !(ks & 1)) TSR(16, ks == 0 ? 16 : 9 + (ks >> 1) + (ks > 12 ? 43 : 0));
        const uint32_t st = sb + s * STG_BYTES;
        const uint32_t da = mkdesc(st + STG_X + (w8 >> 2) * 4096, 16);
        const uint32_t db = mkdesc(st + STG_W, 2048);
        wg_fence();
        wgmma_n192(acc, da, db, ks != 0);
        wgmma_n192(acc, da + 2, db + 384, 1);
        wg_commit();
        const uint32_t eprev = BAR(B_EMPTY + (s == 0 ? NSTG - 1 : s - 1));
        if (++s == NSTG) { s = 0; ph ^= 1; }
        if (ks > 0) {
          wg_wait<1>();
          if (lane < 2) mbar_arrive_cluster(eprev, lane);
        }
      }
      wg_wait<0>();
      bar_arrive(4, 384);
      if (tid == 128) TS(17);
      auto phi2 = [](float a, float b) -> uint32_t {
        const uint32_t x = pack_bf16(a, b);
        const uint32_t e = pack_bf16(ex2(a * 1.4426950408889634f), ex2(b * 1.4426950408889634f));
        const uint32_t m = __hgt2_mask(*reinterpret_cast<const __nv_bfloat162*>(&x), __floats2bfloat162_rn(0.f, 0.f));
        return badd((badd(x, 0x3f803f80u) & m) | (e & ~m), 0x35863586u);
      };
      uint32_t pk[16];
#pragma unroll
      for (int i = 0; i < 16; ++i) pk[i] = phi2(acc[32 + 2 * i], acc[33 + 2 * i]);
      if (tid == 128) TS(53);
      bar_sync(1, 256);
#pragma unroll
      for (int i = 0; i < 8; i += 2) {
        const uint32_t off = row * 128 + (((i + (lane >> 4)) ^ (row & 7)) << 4);
        stsm_x4(sb + SM_PK + off, pk[2 * i], pk[2 * i + 1], pk[2 * i + 2], pk[2 * i + 3]);
        stsm_x4(sb + SM_VS + off, pack_bf16(acc[64 + 4 * i], acc[65 + 4 * i]), pack_bf16(acc[66 + 4 * i], acc[67 + 4 * i]),
                pack_bf16(acc[68 + 4 * i], acc[69 + 4 * i]), pack_bf16(acc[70 + 4 * i], acc[71 + 4 * i]));
      }
      bar_sync(1, 256);
      {
        const int hh = w8 >> 1, dtile = w8 & 1;
        float kv[2][4] = {{0.f, 0.f, 0.f, 0.f}, {0.f, 0.f, 0.f, 0.f}}, zz[2][4] = {{0.f, 0.f, 0.f, 0.f}, {0.f, 0.f, 0.f, 0.f}};
        const int m = lane >> 3;
        const uint32_t aa = sb + SM_VS + ((lane & 7) + ((m >> 1) << 3)) * 128 + (((2 * hh + (m & 1)) ^ (lane & 7)) << 4);
        const uint32_t ab = sb + SM_PK + (lane & 15) * 128 + (((2 * hh + dtile) ^ (lane & 7)) << 4);
#pragma unroll
        for (int ks = 0; ks < 8; ++ks) {
          uint32_t a[4], b0, b1;
          ldsm_x4_t(a, aa + ks * 2048);
          ldsm_x2_t(b0, b1, ab + ks * 2048);
          mma_bf16(kv[ks & 1], a[0], a[1], a[2], a[3], b0, b1);
          mma_bf16(zz[ks & 1], 0x3f803f80u, 0x3f803f80u, 0x3f803f80u, 0x3f803f80u, b0, b1);
        }
        const uint32_t kp = sb + SM_KV + hh * 1088;
        sts128(kp + dtile * 512 + lane * 16, __float_as_uint(kv[0][0] + kv[1][0]), __float_as_uint(kv[0][1] + kv[1][1]),
               __float_as_uint(kv[0][2] + kv[1][2]), __float_as_uint(kv[0][3] + kv[1][3]));
        if (g == 0) sts_f32x2(kp + 1024 + dtile * 32 + q * 8, zz[0][0] + zz[1][0], zz[0][1] + zz[1][1]);
        fence_async_smem();
        __syncwarp();
        if (lane == 0) mbar_arrive(BAR(B_KVP));
        if (tid == 128) TS(55);
      }
#pragma unroll
      for (int i = 0; i < 16; ++i) pq[i] = phi2(acc[2 * i], acc[2 * i + 1]);
    }
    if (tid == 128) TS(56);
    if (warp == 4) mbar_wait_long(BAR(B_KVF), 0);
    bar_sync(1, 256);
    if (tid == 128) TS(19);
    {
      uint32_t kb[4][6];
#pragma unroll
      for (int h = 0; h < 4; ++h) {
        const uint32_t kp = sb + SM_KV + h * 1088;
        const uint4 k0 = lds128(kp + lane * 16), k1 = lds128(kp + 512 + lane * 16);
        const uint32_t za = kp + 1024 + q * 8;
        auto pk2 = [](uint32_t x, uint32_t y) { return pack_bf16(__uint_as_float(x), __uint_as_float(y)); };
        kb[h][0] = pk2(k0.x, k0.y); kb[h][1] = pk2(k1.x, k1.y); kb[h][2] = pk2(k0.z, k0.w); kb[h][3] = pk2(k1.z, k1.w);
        kb[h][4] = pack_bf16(lds_f32(za), lds_f32(za + 4)); kb[h][5] = pack_bf16(lds_f32(za + 32), lds_f32(za + 36));
      }
#pragma unroll
      for (int h = 0; h < 4; ++h) {
        float n0[4] = {0.f, 0.f, 0.f, 0.f}, n1[4] = {0.f, 0.f, 0.f, 0.f}, dn[4] = {0.f, 0.f, 0.f, 0.f};
        mma_bf16(n0, pq[4 * h], pq[4 * h + 1], pq[4 * h + 2], pq[4 * h + 3], kb[h][0], kb[h][1]);
        mma_bf16(n1, pq[4 * h], pq[4 * h + 1], pq[4 * h + 2], pq[4 * h + 3], kb[h][2], kb[h][3]);
        mma_bf16(dn, pq[4 * h], pq[4 * h + 1], pq[4 * h + 2], pq[4 * h + 3], kb[h][4], kb[h][5]);
        const float r0 = rcp(dn[0] + 1e-6f), r1 = rcp(dn[2] + 1e-6f);
        stsm_x4(sb + SM_QS + row * 128 + (((2 * h + (lane >> 4)) ^ (row & 7)) << 4),
                pack_bf16(n0[0] * r0, n0[1] * r0), pack_bf16(n0[2] * r1, n0[3] * r1),
                pack_bf16(n1[0] * r0, n1[1] * r0), pack_bf16(n1[2] * r1, n1[3] * r1));
      }
    }
    fence_async_smem();
    __syncwarp();
    if (lane == 0) mbar_arrive(BAR(B_OST));
    if (tid == 128) TS(57);
    bar_sync(7, 384);
    if (w8 < 7) box_filters<4>(sb, bars, w8, lane);
    bar_arrive(5, 384);
    if (tid == 128) TS(6);
    if (warp == 4) mbar_wait_long(BAR(B_WO), 0);
    bar_sync(3, 384);
    {
      float o[32];
#pragma unroll 1
      for (int c = 0; c < 8; ++c) {
        mbar_wait_long(BAR(B_RF + c), 0);
        if (tid == 128) TSR(22, c == 0 ? 22 : 43 + c);
        const uint32_t slot = c < 4 ? SM_QS + c * 16384 : c < 7 ? SM_VV + (c - 4) * 16384 : SM_QS;
        const uint32_t da = mkdesc(sb + slot + (w8 >> 2) * 8192, 16);
        const uint32_t db = mkdesc(sb + SM_WO + c * 8192, 8192);
        wg_fence();
#pragma unroll
        for (int k = 0; k < 4; ++k) wgmma_n64(o, da + 2 * k, db + 128 * k, (c | k) != 0);
        wg_commit();
        if (c == 1) {
          wg_wait<1>();
          if (lane < 2) mbar_arrive_cluster(BAR(B_RE), lane);
          __syncwarp();
          cluster_arrive();
        }
      }
      wg_wait<0>();
      if (tid == 128) TS(51);
#pragma unroll
      for (int i = 0; i < 8; i += 2)
        stsm_x4(sb + SM_BOUT + row * 128 + (((i + (lane >> 4)) ^ (row & 7)) << 4), pack_bf16(o[4 * i], o[4 * i + 1]),
                pack_bf16(o[4 * i + 2], o[4 * i + 3]), pack_bf16(o[4 * i + 4], o[4 * i + 5]), pack_bf16(o[4 * i + 6], o[4 * i + 7]));
      fence_async_smem();
      bar_sync(8 + (w8 >> 2), 128);
      if ((w8 & 3) == 0 && elect_one()) {
        tma_store_2d(&maps.outh, sb + SM_BOUT + (w8 >> 2) * 8192, 512 + 64 * pj, 128 * pi + (w8 >> 2) * 64);
        bulk_commit();
        bulk_wait_read0();
        TS(23);
      }
    }
  } else {
    asm volatile("setmaxnreg.dec.sync.aligned.u32 40;");
    if (warp == 12) {
      if (elect_one()) {
#pragma unroll 1
        for (int ks = NSTG, s = 0, ph = 0; ks < 16; ++ks) {
          mbar_wait(BAR(B_EMPTY + s), ph);
          issue_stage(ks, s);
          if (ks == NSTG) l2_prefetch((const char*)p.wo + (size_t)cta * 4096, 4096);
          if (++s == NSTG) { s = 0; ph ^= 1; }
        }
        mbar_wait(BAR(B_EMPTY + 6), 1);
        mbar_expect_tx(BAR(B_WO), 65536);
        tma_load_2d(sb + SM_WO, &maps.wo, pj * 64, 0, BAR(B_WO));
        tma_load_2d(sb + SM_WO + 32768, &maps.wo, pj * 64, 256, BAR(B_WO));
        float* kvg = &g_kv[epoch & 1][tj][0];
        mbar_wait_long(BAR(B_KVP), 0);
        bulk_reduce_add_f32(kvg, sb + SM_KV, 4352);
        bulk_commit();
        bulk_wait0();
        red_relaxed_add(&g_cnt[(C_KV + tj) * 32], 1);
        TS(18);
        wait_counter(&g_cnt[(C_KV + tj) * 32], (epoch + 1) * 16);
        mbar_expect_tx(BAR(B_KVF), 4352);
        bulk_load(sb + SM_KV, kvg, 4352, BAR(B_KVF));
        mbar_wait_long(BAR(B_OST), 0);
        tma_store_2d(&maps.o, sb + SM_QS, tj * 64, ti * 128);
        tma_store_2d(&maps.o, sb + SM_QS + 8192, tj * 64, ti * 128 + 64);
        bulk_commit();
        bulk_wait0();
        red_relaxed_add(&g_cnt[(C_O + ti) * 32], 1);
        TS(20);
        mbar_arrive_cluster(BAR(B_SLOT), 0);
        mbar_arrive_cluster(BAR(B_SLOT), 1);
        wait_counter(&g_cnt[(C_O + pi) * 32], (epoch + 1) * 8);
        if (cta == 0) g_epoch = epoch + 1;
        mbar_wait(BAR(B_SLOT), 0);
        TS(21);
#pragma unroll 1
        for (int c = 0; c < 8; ++c) {
          if (c == 4) mbar_wait_long(BAR(B_CONVD), 0);
          if (c == 7) mbar_wait(BAR(B_RE), 0);
          const uint32_t slot = c < 4 ? SM_QS + c * 16384 : c < 7 ? SM_VV + (c - 4) * 16384 : SM_QS;
          mbar_expect_tx(BAR(B_RF + c), 16384);
          tma_load_2d_mc(sb + slot + rank * 8192, &maps.o, c * 64, pi * 128 + rank * 64, BAR(B_RF + c), 3);
        }
      }
    } else if (warp == 13) {
      bar_sync(6, 160);
      sts128(sb + SM_U + (lane >> 4) * U_BYTES + (lane & 15) * 16, 0, 0, 0, 0);
      sts128(sb + SM_U + (2 + (lane >> 4)) * U_BYTES + (lane & 15) * 16, 0, 0, 0, 0);
      __syncwarp();
      if (elect_one()) {
        tma_store_2d(&maps.uT, sb + SM_P, ti * 128, tj * 64);
        tma_store_2d(&maps.uT, sb + SM_P + 8192, ti * 128 + 64, tj * 64);
        bulk_commit();
        bulk_wait_read0();
        mbar_arrive(BAR(B_PFREE));
        bulk_wait0();
        red_relaxed_add(&g_cnt[(C_U + tj) * 32], 1);
        TS(27);
        wait_counter(&g_cnt[(C_U + (cta >> 4)) * 32], (epoch + 1) * 16);
#pragma unroll 1
        for (int c = 0; c < 4; ++c) {
          mbar_expect_tx(BAR(B_UCH + c), 4096);
          bulk_load(sb + SM_U + c * U_BYTES + 256, p.uT + (size_t)(cta * 4 + c) * 2048, 4096, BAR(B_UCH + c));
        }
        TS(3);
      }
      __syncwarp();
      if (ti == 0) {
        float4* z = (float4*)&g_kv[(epoch & 1) ^ 1][tj][0];
#pragma unroll 1
        for (int i = lane; i < 272; i += 32) z[i] = make_float4(0.f, 0.f, 0.f, 0.f);
      }
    }
  }
  __syncwarp();
  if (warp >= 12) cluster_arrive();
  cluster_wait();
  if (tid == 0) TS(31);
#undef BAR
}

typedef CUresult (*EncodeFn)(CUtensorMap*, CUtensorMapDataType, cuuint32_t, void*, const cuuint64_t*, const cuuint64_t*,
                             const cuuint32_t*, const cuuint32_t*, CUtensorMapInterleave, CUtensorMapSwizzle,
                             CUtensorMapL2promotion, CUtensorMapFloatOOBfill);

static void make_map(EncodeFn enc, CUtensorMap* m, const void* base, uint64_t inner, uint64_t outer, uint32_t box_in,
                     uint32_t box_out, CUtensorMapSwizzle swz = CU_TENSOR_MAP_SWIZZLE_128B) {
  cuuint64_t gd[2] = {inner, outer};
  cuuint64_t gs[1] = {inner * 2};
  cuuint32_t bd[2] = {box_in, box_out};
  cuuint32_t es[2] = {1, 1};
  enc(m, CU_TENSOR_MAP_DATA_TYPE_BFLOAT16, 2, const_cast<void*>(base), gd, gs, bd, es, CU_TENSOR_MAP_INTERLEAVE_NONE,
      swz, CU_TENSOR_MAP_L2_PROMOTION_L2_128B, CU_TENSOR_MAP_FLOAT_OOB_FILL_NONE);
}

}

extern "C" void kernel_launch(void* const* d_in, const int* in_sizes, int n_in, void* d_out, int out_size) {
  using namespace s4la;
  (void)in_sizes; (void)n_in; (void)out_size;
  static EncodeFn enc = nullptr;
  static void *uT = nullptr, *yT = nullptr, *oS = nullptr;
  if (!enc) {
    void* fn = nullptr;
    cudaDriverEntryPointQueryResult qr;
    cudaGetDriverEntryPoint("cuTensorMapEncodeTiled", &fn, cudaEnableDefault, &qr);
    enc = (EncodeFn)fn;
    cudaGetSymbolAddress(&uT, g_uT);
    cudaGetSymbolAddress(&yT, g_yT);
    cudaGetSymbolAddress(&oS, g_o);
    cudaFuncSetAttribute(fused_kernel, cudaFuncAttributeMaxDynamicSharedMemorySize, SM_TOTAL);
  }
  const __nv_bfloat16* const* in = (const __nv_bfloat16* const*)d_in;
  Maps maps;
  make_map(enc, &maps.x, in[9], 512, 2048, 32, 128, CU_TENSOR_MAP_SWIZZLE_64B);
  {
    cuuint64_t gd[3] = {512, 512, 3};
    cuuint64_t gs[2] = {3072, 1024};
    cuuint32_t bd[3] = {64, 16, 3};
    cuuint32_t es[3] = {1, 1, 1};
    enc(&maps.w, CU_TENSOR_MAP_DATA_TYPE_BFLOAT16, 3, const_cast<__nv_bfloat16*>(in[10]), gd, gs, bd, es,
        CU_TENSOR_MAP_INTERLEAVE_NONE, CU_TENSOR_MAP_SWIZZLE_128B, CU_TENSOR_MAP_L2_PROMOTION_L2_128B,
        CU_TENSOR_MAP_FLOAT_OOB_FILL_NONE);
  }
  make_map(enc, &maps.wo, in[11], 512, 512, 64, 256);
  make_map(enc, &maps.u, in[0], 512, 2048, 64, 128);
  make_map(enc, &maps.uT, uT, 2048, 512, 64, 64);
  make_map(enc, &maps.yT, yT, 2048, 512, 64, 64);
  make_map(enc, &maps.o, oS, 512, 2048, 64, 64);
  make_map(enc, &maps.out, d_out, 1024, 2048, 64, 128);
  make_map(enc, &maps.outh, d_out, 1024, 2048, 64, 64);
  Ptrs p;
  p.A_re = in[1]; p.A_im = in[2]; p.B_re = in[3]; p.B_im = in[4]; p.C_re = in[5]; p.C_im = in[6];
  p.log_dt = in[7]; p.Dskip = in[8]; p.x = in[9]; p.wqkv = in[10]; p.wo = in[11];
  p.uT = (__nv_bfloat16*)uT; p.yT = (__nv_bfloat16*)yT;
  fused_kernel<<<NCTA, NTHREADS, SM_TOTAL, cudaStreamPerThread>>>(maps, p);
}
```

```cpp
#include <cuda_runtime.h>
#include <cuda_bf16.h>
#include <cuda_fp16.h>
#include <cuda.h>
#include <stdint.h>

#define DEVI __device__ __forceinline__

namespace s4la {

constexpr int NTHREADS = 512;
constexpr int NCTA = 128;

constexpr int NSTG = 7;
constexpr uint32_t STG_BYTES = 20480, STG_X = 0, STG_W = 8192;
constexpr uint32_t SM_QS = 0;
constexpr uint32_t SM_PK = SM_QS + 16384, SM_VS = SM_QS + 32768;
constexpr uint32_t SM_WO = 65536;
constexpr uint32_t SM_KV = 131072;
constexpr uint32_t SM_BOUT = 16384;
constexpr uint32_t SM_U = 143360, U_BYTES = 4352;
constexpr uint32_t SM_P = 160768, P_BYTES = 4096;
constexpr uint32_t SM_VV = 177152, VV_BYTES = 12800;
constexpr uint32_t VV_U5 = 0, VV_U3 = 3712, VV_U9 = 7424, VV_U7 = 10112;
constexpr uint32_t KG_BYTES = 3200;
constexpr uint32_t SM_BAR = SM_VV + 4 * VV_BYTES;
constexpr uint32_t SM_PTAB = SM_BAR + 320;
constexpr uint32_t SM_TOTAL = SM_PTAB + 2048;
static_assert(SM_TOTAL <= 232448, "shared memory");
constexpr int PADV = 12;

enum { B_FULL = 0, B_EMPTY = 7, B_TILE = 14, B_UCH = 15, B_KVP = 19, B_KVF = 20, B_OST = 21, B_RF = 22, B_WO = 30, B_RE = 31, B_PFREE = 32, B_CONVD = 33, B_SLOT = 34, B_COUNT = 35 };
__host__ __device__ constexpr int bar_count(int i) {
  return (i >= B_EMPTY && i < B_TILE) ? 16 : (i == B_KVP || i == B_OST || i == B_CONVD) ? 8 : i == B_RE ? 16 : i == B_SLOT ? 2 : 1;
}

constexpr int PD_OFF = 0, P2_OFF = 544, P3_OFF = 768;

constexpr int SL_K2048 = 20, SL_ZERO = 21, SL_510 = 22, SL_0 = 23;
__host__ __device__ constexpr int koff(int y) {
  return y < 8 ? y : y < 12 ? 256 + 2 * (y - 8) : y < 16 ? 512 + 256 * ((y - 12) >> 1) + 4 * (y & 1) : 1024 + 256 * (y - 16);
}
__host__ __device__ constexpr int kidx_c(int l) {
  const int y = l < 256 ? (l & 7) : l < 512 ? 8 + ((l & 7) >> 1) : l < 1024 ? 12 + (((l - 512) >> 8) << 1) + ((l >> 2) & 1)
                                                                            : 16 + ((l - 1024) >> 8);
  return ((l >> 3) & 31) * 24 + y;
}
constexpr int slot_direct(int l) {
  if (l < 0 || l > 510) return SL_ZERO;
  if (l == 510) return SL_510;
  if (l == 0) return SL_0;
  return kidx_c(l < 256 ? l : ((l + ((l >> 1) & 1)) & ~1));
}
constexpr int slot_seg2(int v, int k) { return (k >= 32 && k < 64) ? kidx_c(16 * k + 4 * v) : SL_ZERO; }
constexpr int slot_seg3(int pi, int k) {
  return (k >= 64 && k < 128) ? kidx_c(16 * k + 8 * pi) : ((k == 128 && pi == 0) ? SL_K2048 : SL_ZERO);
}
constexpr int slot_word(int w) {
  return w < 0 ? SL_ZERO : w < 544 ? slot_direct(w - 16) : w < 768 ? slot_seg2((w - 544) / 56, 16 + (w - 544) % 56)
       : w < 944 ? slot_seg3((w - 768) / 88, 48 + (w - 768) % 88) : SL_ZERO;
}
struct PTab { uint32_t v[512]; };
constexpr PTab make_ptab() {
  PTab t{};
  for (int lane = 0; lane < 32; ++lane)
    for (int i = 0; i < 16; ++i)
      t.v[i * 32 + lane] = (slot_word(31 * lane - 1 + 2 * i) * 4) | ((slot_word(31 * lane + 2 * i) * 4) << 16);
  return t;
}
__device__ const PTab g_ptab = make_ptab();

__device__ __nv_bfloat16 g_uT[512 * 2048];
__device__ __nv_bfloat16 g_yT[512 * 2048];
__device__ __nv_bfloat16 g_o[2048 * 512];
__device__ float g_kv[2][8][4 * 272];
__device__ unsigned g_cnt[64 * 32];
__device__ unsigned g_epoch;
#define TS(slot) do { } while (0)
#define TSR(on, slot) do { } while (0)
#define TSD(slot) do { } while (0)
enum { C_U = 0, C_KV = 8, C_O = 16, C_Y = 32 };

struct Maps {
  CUtensorMap x, w, wo, u, uT, yT, o, out, outh;
};
struct Ptrs {
  const __nv_bfloat16 *A_re, *A_im, *B_re, *B_im, *C_re, *C_im, *log_dt, *Dskip;
  const __nv_bfloat16 *x, *wqkv, *wo;
  __nv_bfloat16 *uT, *yT;
};

DEVI uint32_t s2u(const void* p) { return (uint32_t)__cvta_generic_to_shared(p); }
DEVI void mbar_init(uint32_t b, uint32_t c) { asm volatile("mbarrier.init.shared::cta.b64 [%0], %1;" ::"r"(b), "r"(c) : "memory"); }
DEVI void mbar_expect_tx(uint32_t b, uint32_t bytes) {
  asm volatile("mbarrier.arrive.expect_tx.shared::cta.b64 _, [%0], %1;" ::"r"(b), "r"(bytes) : "memory");
}
DEVI void mbar_arrive(uint32_t b) { asm volatile("mbarrier.arrive.shared::cta.b64 _, [%0];" ::"r"(b) : "memory"); }
DEVI void mbar_arrive_cluster(uint32_t b, uint32_t cta) {
  asm volatile("{\n.reg .b32 r;\nmapa.shared::cluster.u32 r, %0, %1;\nmbarrier.arrive.shared::cluster.b64 _, [r];\n}"
               ::"r"(b), "r"(cta) : "memory");
}
DEVI void mbar_wait(uint32_t b, uint32_t parity) {
  asm volatile("{\n.reg .pred p;\nLAB_WAIT:\nmbarrier.try_wait.parity.shared::cta.b64 p, [%0], %1;\n@!p bra LAB_WAIT;\n}"
               ::"r"(b), "r"(parity) : "memory");
}
DEVI void mbar_wait_long(uint32_t b, uint32_t parity) {
  asm volatile("{\n.reg .pred p;\nLAB_WAIT:\nmbarrier.try_wait.parity.shared::cta.b64 p, [%0], %1, 0x989680;\n@!p bra LAB_WAIT;\n}"
               ::"r"(b), "r"(parity) : "memory");
}
DEVI void bar_sync(int id, int n) { asm volatile("bar.sync %0, %1;" ::"r"(id), "r"(n) : "memory"); }
DEVI void bar_arrive(int id, int n) { asm volatile("bar.arrive %0, %1;" ::"r"(id), "r"(n) : "memory"); }
DEVI void fence_async_smem() { asm volatile("fence.proxy.async.shared::cta;" ::: "memory"); }
DEVI void fence_async_all() { asm volatile("fence.proxy.async;" ::: "memory"); }
DEVI void cluster_arrive() { asm volatile("barrier.cluster.arrive.relaxed.aligned;" ::: "memory"); }
DEVI void cluster_wait() { asm volatile("barrier.cluster.wait.aligned;" ::: "memory"); }

DEVI void tma_load_2d(uint32_t dst, const CUtensorMap* m, int c0, int c1, uint32_t bar) {
  asm volatile("cp.async.bulk.tensor.2d.shared::cluster.global.mbarrier::complete_tx::bytes [%0], [%1, {%3, %4}], [%2];"
               ::"r"(dst), "l"(m), "r"(bar), "r"(c0), "r"(c1) : "memory");
}
DEVI void tma_load_2d_mc(uint32_t dst, const CUtensorMap* m, int c0, int c1, uint32_t bar, uint16_t mask) {
  asm volatile("cp.async.bulk.tensor.2d.shared::cluster.global.mbarrier::complete_tx::bytes.multicast::cluster [%0], [%1, {%3, %4}], [%2], %5;"
               ::"r"(dst), "l"(m), "r"(bar), "r"(c0), "r"(c1), "h"(mask) : "memory");
}
DEVI void tma_load_3d_mc(uint32_t dst, const CUtensorMap* m, int c0, int c1, int c2, uint32_t bar, uint16_t mask) {
  asm volatile("cp.async.bulk.tensor.3d.shared::cluster.global.mbarrier::complete_tx::bytes.multicast::cluster [%0], [%1, {%3, %4, %5}], [%2], %6;"
               ::"r"(dst), "l"(m), "r"(bar), "r"(c0), "r"(c1), "r"(c2), "h"(mask) : "memory");
}
DEVI void tma_store_2d(const CUtensorMap* m, uint32_t src, int c0, int c1) {
  asm volatile("cp.async.bulk.tensor.2d.global.shared::cta.bulk_group [%0, {%2, %3}], [%1];"
               ::"l"(m), "r"(src), "r"(c0), "r"(c1) : "memory");
}
DEVI void bulk_load(uint32_t dst, const void* src, uint32_t bytes, uint32_t bar) {
  asm volatile("cp.async.bulk.shared::cluster.global.mbarrier::complete_tx::bytes [%0], [%1], %2, [%3];"
               ::"r"(dst), "l"(src), "r"(bytes), "r"(bar) : "memory");
}
DEVI void bulk_store(void* dst, uint32_t src, uint32_t bytes) {
  asm volatile("cp.async.bulk.global.shared::cta.bulk_group [%0], [%1], %2;" ::"l"(dst), "r"(src), "r"(bytes) : "memory");
}
DEVI void bulk_reduce_add_f32(void* dst, uint32_t src, uint32_t bytes) {
  asm volatile("cp.reduce.async.bulk.global.shared::cta.bulk_group.add.f32 [%0], [%1], %2;" ::"l"(dst), "r"(src), "r"(bytes) : "memory");
}
DEVI void bulk_commit() { asm volatile("cp.async.bulk.commit_group;" ::: "memory"); }
DEVI void bulk_wait0() { asm volatile("cp.async.bulk.wait_group 0;" ::: "memory"); }
DEVI void bulk_wait_read0() { asm volatile("cp.async.bulk.wait_group.read 0;" ::: "memory"); }
DEVI void l2_prefetch(const void* p, uint32_t bytes) {
  asm volatile("cp.async.bulk.prefetch.L2.global [%0], %1;" ::"l"(p), "r"(bytes) : "memory");
}
DEVI void prefetch_tmap(const CUtensorMap* m) { asm volatile("prefetch.tensormap [%0];" ::"l"(m) : "memory"); }

DEVI void red_release_add(unsigned* p, unsigned v) {
  asm volatile("red.release.gpu.global.add.u32 [%0], %1;" ::"l"(p), "r"(v) : "memory");
}
DEVI void red_relaxed_add(unsigned* p, unsigned v) {
  asm volatile("red.relaxed.gpu.global.add.u32 [%0], %1;" ::"l"(p), "r"(v) : "memory");
}
DEVI unsigned ld_relaxed(const unsigned* p) {
  unsigned v;
  asm volatile("ld.relaxed.gpu.global.u32 %0, [%1];" : "=r"(v) : "l"(p) : "memory");
  return v;
}
DEVI void wait_counter(const unsigned* p, unsigned target) {
#pragma unroll 1
  for (int it = 0; (int)(ld_relaxed(p) - target) < 0; ++it)
    if (it > (1 << 22)) __trap();
}

DEVI void ldsm_x4(uint32_t (&r)[4], uint32_t a) {
  asm volatile("ldmatrix.sync.aligned.m8n8.x4.shared.b16 {%0,%1,%2,%3}, [%4];"
               : "=r"(r[0]), "=r"(r[1]), "=r"(r[2]), "=r"(r[3]) : "r"(a) : "memory");
}
DEVI void ldsm_x4_t(uint32_t (&r)[4], uint32_t a) {
  asm volatile("ldmatrix.sync.aligned.m8n8.x4.trans.shared.b16 {%0,%1,%2,%3}, [%4];"
               : "=r"(r[0]), "=r"(r[1]), "=r"(r[2]), "=r"(r[3]) : "r"(a) : "memory");
}
DEVI void ldsm_x2_t(uint32_t& r0, uint32_t& r1, uint32_t a) {
  asm volatile("ldmatrix.sync.aligned.m8n8.x2.trans.shared.b16 {%0,%1}, [%2];" : "=r"(r0), "=r"(r1) : "r"(a) : "memory");
}
DEVI void stsm_x4(uint32_t a, uint32_t r0, uint32_t r1, uint32_t r2, uint32_t r3) {
  asm volatile("stmatrix.sync.aligned.m8n8.x4.shared.b16 [%0], {%1,%2,%3,%4};"
               ::"r"(a), "r"(r0), "r"(r1), "r"(r2), "r"(r3) : "memory");
}
DEVI void stsm_x4_t(uint32_t a, uint32_t r0, uint32_t r1, uint32_t r2, uint32_t r3) {
  asm volatile("stmatrix.sync.aligned.m8n8.x4.trans.shared.b16 [%0], {%1,%2,%3,%4};"
               ::"r"(a), "r"(r0), "r"(r1), "r"(r2), "r"(r3) : "memory");
}
DEVI uint32_t lds32(uint32_t a) { uint32_t v; asm volatile("ld.shared.b32 %0, [%1];" : "=r"(v) : "r"(a) : "memory"); return v; }
DEVI float lds_f32(uint32_t a) { float v; asm volatile("ld.shared.f32 %0, [%1];" : "=f"(v) : "r"(a) : "memory"); return v; }
DEVI void sts32(uint32_t a, uint32_t v) { asm volatile("st.shared.b32 [%0], %1;" ::"r"(a), "r"(v) : "memory"); }
DEVI void sts_f32(uint32_t a, float v) { asm volatile("st.shared.f32 [%0], %1;" ::"r"(a), "f"(v) : "memory"); }
DEVI void sts_f32x2(uint32_t a, float x, float y) { asm volatile("st.shared.v2.f32 [%0], {%1,%2};" ::"r"(a), "f"(x), "f"(y) : "memory"); }
DEVI uint4 lds128(uint32_t a) {
  uint4 v;
  asm volatile("ld.shared.v4.b32 {%0,%1,%2,%3}, [%4];" : "=r"(v.x), "=r"(v.y), "=r"(v.z), "=r"(v.w) : "r"(a) : "memory");
  return v;
}
DEVI void sts128(uint32_t a, uint32_t x, uint32_t y, uint32_t z, uint32_t w) {
  asm volatile("st.shared.v4.b32 [%0], {%1,%2,%3,%4};" ::"r"(a), "r"(x), "r"(y), "r"(z), "r"(w) : "memory");
}

DEVI void mma_bf16(float (&d)[4], uint32_t a0, uint32_t a1, uint32_t a2, uint32_t a3, uint32_t b0, uint32_t b1) {
  asm("mma.sync.aligned.m16n8k16.row.col.f32.bf16.bf16.f32 {%0,%1,%2,%3}, {%4,%5,%6,%7}, {%8,%9}, {%0,%1,%2,%3};"
      : "+f"(d[0]), "+f"(d[1]), "+f"(d[2]), "+f"(d[3])
      : "r"(a0), "r"(a1), "r"(a2), "r"(a3), "r"(b0), "r"(b1));
}
DEVI void mma_f16(float (&d)[4], const uint32_t (&a)[4], uint32_t b0, uint32_t b1) {
  asm("mma.sync.aligned.m16n8k16.row.col.f32.f16.f16.f32 {%0,%1,%2,%3}, {%4,%5,%6,%7}, {%8,%9}, {%0,%1,%2,%3};"
      : "+f"(d[0]), "+f"(d[1]), "+f"(d[2]), "+f"(d[3])
      : "r"(a[0]), "r"(a[1]), "r"(a[2]), "r"(a[3]), "r"(b0), "r"(b1));
}
DEVI void mma_bf16v(float (&d)[4], const uint32_t (&a)[4], uint32_t b0, uint32_t b1) {
  asm volatile("mma.sync.aligned.m16n8k16.row.col.f32.bf16.bf16.f32 {%0,%1,%2,%3}, {%4,%5,%6,%7}, {%8,%9}, {%0,%1,%2,%3};"
               : "+f"(d[0]), "+f"(d[1]), "+f"(d[2]), "+f"(d[3])
               : "r"(a[0]), "r"(a[1]), "r"(a[2]), "r"(a[3]), "r"(b0), "r"(b1));
}
DEVI uint32_t pack_bf16(float lo, float hi) {
  uint32_t r;
  asm("cvt.rn.bf16x2.f32 %0, %1, %2;" : "=r"(r) : "f"(hi), "f"(lo));
  return r;
}
DEVI uint32_t pack_f16(float lo, float hi) {
  uint32_t r;
  asm("cvt.rn.f16x2.f32 %0, %1, %2;" : "=r"(r) : "f"(hi), "f"(lo));
  return r;
}
DEVI uint32_t ldg16(const __nv_bfloat16* p) {
  uint32_t v;
  asm volatile("ld.global.nc.u16 %0, [%1];" : "=r"(v) : "l"(p));
  return v;
}
DEVI bool elect_one() {
  uint32_t pred;
  asm volatile("{\n.reg .pred p;\nelect.sync _|p, 0xffffffff;\nselp.u32 %0, 1, 0, p;\n}" : "=r"(pred));
  return pred != 0;
}
DEVI float bf_lo(uint32_t v) { return __uint_as_float(v << 16); }
DEVI float bf_hi(uint32_t v) { return __uint_as_float(v & 0xffff0000u); }
DEVI float bf2f(__nv_bfloat16 v) { return __bfloat162float(v); }
DEVI float round_bf16(float v) { return __bfloat162float(__float2bfloat16_rn(v)); }
DEVI float rcp(float x) { float r; asm("rcp.approx.ftz.f32 %0, %1;" : "=f"(r) : "f"(x)); return r; }
DEVI float ex2(float x) { float r; asm("ex2.approx.ftz.f32 %0, %1;" : "=f"(r) : "f"(x)); return r; }

DEVI void wg_fence() { asm volatile("wgmma.fence.sync.aligned;" ::: "memory"); }
DEVI void wg_commit() { asm volatile("wgmma.commit_group.sync.aligned;" ::: "memory"); }
template <int N> DEVI void wg_wait() { asm volatile("wgmma.wait_group.sync.aligned %0;" ::"n"(N) : "memory"); }
constexpr uint32_t DESC_HI = (1u << 30) | (1024 >> 4);
constexpr uint32_t DESC_HI64 = (2u << 30) | (512 >> 4);
DEVI uint32_t mkdesc(uint32_t saddr, uint32_t lbo) { return ((saddr & 0x3FFFF) >> 4) | ((lbo >> 4) << 16); }

#define R8(b) "%" #b
DEVI void wgmma_n192(float (&d)[96], uint32_t da, uint32_t db, int scale_d) {
  asm volatile(
      "{\n.reg .pred p;\n.reg .b64 da, db;\nsetp.ne.b32 p, %98, 0;\nmov.b64 da, {%96, %100};\nmov.b64 db, {%97, %99};\n"
      "wgmma.mma_async.sync.aligned.m64n192k16.f32.bf16.bf16 "
      "{%0,%1,%2,%3,%4,%5,%6,%7,%8,%9,%10,%11,%12,%13,%14,%15,"
      "%16,%17,%18,%19,%20,%21,%22,%23,%24,%25,%26,%27,%28,%29,%30,%31,"
      "%32,%33,%34,%35,%36,%37,%38,%39,%40,%41,%42,%43,%44,%45,%46,%47,"
      "%48,%49,%50,%51,%52,%53,%54,%55,%56,%57,%58,%59,%60,%61,%62,%63,"
      "%64,%65,%66,%67,%68,%69,%70,%71,%72,%73,%74,%75,%76,%77,%78,%79,"
      "%80,%81,%82,%83,%84,%85,%86,%87,%88,%89,%90,%91,%92,%93,%94,%95}, "
      "da, db, p, 1, 1, 0, 1;\n}"
      : "+f"(d[0]), "+f"(d[1]), "+f"(d[2]), "+f"(d[3]), "+f"(d[4]), "+f"(d[5]), "+f"(d[6]), "+f"(d[7]),
        "+f"(d[8]), "+f"(d[9]), "+f"(d[10]), "+f"(d[11]), "+f"(d[12]), "+f"(d[13]), "+f"(d[14]), "+f"(d[15]),
        "+f"(d[16]), "+f"(d[17]), "+f"(d[18]), "+f"(d[19]), "+f"(d[20]), "+f"(d[21]), "+f"(d[22]), "+f"(d[23]),
        "+f"(d[24]), "+f"(d[25]), "+f"(d[26]), "+f"(d[27]), "+f"(d[28]), "+f"(d[29]), "+f"(d[30]), "+f"(d[31]),
        "+f"(d[32]), "+f"(d[33]), "+f"(d[34]), "+f"(d[35]), "+f"(d[36]), "+f"(d[37]), "+f"(d[38]), "+f"(d[39]),
        "+f"(d[40]), "+f"(d[41]), "+f"(d[42]), "+f"(d[43]), "+f"(d[44]), "+f"(d[45]), "+f"(d[46]), "+f"(d[47]),
        "+f"(d[48]), "+f"(d[49]), "+f"(d[50]), "+f"(d[51]), "+f"(d[52]), "+f"(d[53]), "+f"(d[54]), "+f"(d[55]),
        "+f"(d[56]), "+f"(d[57]), "+f"(d[58]), "+f"(d[59]), "+f"(d[60]), "+f"(d[61]), "+f"(d[62]), "+f"(d[63]),
        "+f"(d[64]), "+f"(d[65]), "+f"(d[66]), "+f"(d[67]), "+f"(d[68]), "+f"(d[69]), "+f"(d[70]), "+f"(d[71]),
        "+f"(d[72]), "+f"(d[73]), "+f"(d[74]), "+f"(d[75]), "+f"(d[76]), "+f"(d[77]), "+f"(d[78]), "+f"(d[79]),
        "+f"(d[80]), "+f"(d[81]), "+f"(d[82]), "+f"(d[83]), "+f"(d[84]), "+f"(d[85]), "+f"(d[86]), "+f"(d[87]),
        "+f"(d[88]), "+f"(d[89]), "+f"(d[90]), "+f"(d[91]), "+f"(d[92]), "+f"(d[93]), "+f"(d[94]), "+f"(d[95])
      : "r"(da), "r"(db), "r"(scale_d), "n"(DESC_HI), "n"(DESC_HI64));
}
DEVI void wgmma_n64(float (&d)[32], uint32_t da, uint32_t db, int scale_d) {
  asm volatile(
      "{\n.reg .pred p;\n.reg .b64 da, db;\nsetp.ne.b32 p, %34, 0;\nmov.b64 da, {%32, %35};\nmov.b64 db, {%33, %35};\n"
      "wgmma.mma_async.sync.aligned.m64n64k16.f32.bf16.bf16 "
      "{%0,%1,%2,%3,%4,%5,%6,%7,%8,%9,%10,%11,%12,%13,%14,%15,"
      "%16,%17,%18,%19,%20,%21,%22,%23,%24,%25,%26,%27,%28,%29,%30,%31}, "
      "da, db, p, 1, 1, 0, 1;\n}"
      : "+f"(d[0]), "+f"(d[1]), "+f"(d[2]), "+f"(d[3]), "+f"(d[4]), "+f"(d[5]), "+f"(d[6]), "+f"(d[7]),
        "+f"(d[8]), "+f"(d[9]), "+f"(d[10]), "+f"(d[11]), "+f"(d[12]), "+f"(d[13]), "+f"(d[14]), "+f"(d[15]),
        "+f"(d[16]), "+f"(d[17]), "+f"(d[18]), "+f"(d[19]), "+f"(d[20]), "+f"(d[21]), "+f"(d[22]), "+f"(d[23]),
        "+f"(d[24]), "+f"(d[25]), "+f"(d[26]), "+f"(d[27]), "+f"(d[28]), "+f"(d[29]), "+f"(d[30]), "+f"(d[31])
      : "r"(da), "r"(db), "r"(scale_d), "n"(DESC_HI));
}

struct C32 { float re, im; };
DEVI C32 csq(C32 a) { return {a.re * a.re - a.im * a.im, 2.f * a.re * a.im}; }
DEVI C32 cmul(C32 a, C32 b) { return {a.re * b.re - a.im * b.im, a.re * b.im + a.im * b.re}; }
DEVI C32 cfresh(float zl, float zi, float m) {
  float mag = ex2(zl * m), ph = zi * m;
  return {mag * __cosf(ph), mag * __sinf(ph)};
}
struct HMul { uint32_t b, bp; };
DEVI HMul mk_mul(float re, float im) { return {pack_f16(re, im), pack_f16(-im, re)}; }
DEVI uint32_t hcmul(uint32_t a, const HMul& m) {
  __half2 ah = *reinterpret_cast<__half2*>(&a);
  __half2 b = *reinterpret_cast<const __half2*>(&m.b), bp = *reinterpret_cast<const __half2*>(&m.bp);
  __half2 r = __hfma2(__high2half2(ah), bp, __hmul2(__low2half2(ah), b));
  return *reinterpret_cast<uint32_t*>(&r);
}
DEVI uint32_t badd(uint32_t a, uint32_t b) {
  __nv_bfloat162 r = __hadd2(*reinterpret_cast<__nv_bfloat162*>(&a), *reinterpret_cast<__nv_bfloat162*>(&b));
  return *reinterpret_cast<uint32_t*>(&r);
}
template <int MU0, int NMU, int DMAX>
DEVI void conv_tail(float (&acc)[16][4], uint32_t p_lane, uint32_t v_base, int back, bool edge, int lane) {
  const int hsel = (lane >> 3) & 1;
  const int row = (lane & 7) + ((lane >> 4) << 3) + PADV - 8 - (back & (hsel ^ 1));
  const uint32_t la = v_base + row * 32 + (((hsel ^ back) ^ ((row >> 2) & 1)) << 4);
  uint32_t M[3][4];
  ldsm_x4_t(M[0], la);
  ldsm_x4_t(M[1], la + 256);
  uint32_t H[2 * NMU];
#pragma unroll
  for (int i = 0; i < 2 * NMU; ++i) H[i ^ 1] = lds32(p_lane + (uint32_t)(MU0 - 1 + i) * 32);
  if (edge) {
    const uint32_t a[4] = {0u, 0u, M[0][0], M[0][1]};
#pragma unroll
    for (int k = 1; k < NMU; ++k) mma_bf16v(acc[MU0 - 2 + 2 * k], a, H[2 * k], H[2 * k + 1]);
  }
#pragma unroll
  for (int delta = -1; delta <= DMAX; ++delta) {
    if (delta + 2 <= DMAX) ldsm_x4_t(M[(delta + 3) % 3], la + (delta + 3) * 256);
#pragma unroll
    for (int k = 0; k < NMU; ++k)
      if (delta + MU0 + 2 * k < 16) mma_bf16v(acc[delta + MU0 + 2 * k], M[(delta + 1) % 3], H[2 * k], H[2 * k + 1]);
  }
}

template <int NB>
DEVI void box_filters(uint32_t sb, uint32_t bars, int idx, int lane) {
  auto swz = [](int k, int pad) { const int r = (k >> 1) + pad; return (uint32_t)(r * 32 + (((k & 1) ^ ((r >> 2) & 1)) << 4)); };
  const uint32_t o0 = swz(lane - 3, 8), o1 = swz(lane - 2, 8), o2 = swz(lane - 1, 8), ow = swz(lane - 2, PADV), oz = swz(lane - 18, PADV);
  const int k = 32 * idx - 2 + lane;
#pragma unroll 1
  for (int c2 = 0; c2 < 4; c2 += NB) {
    uint4 t[NB][3];
#pragma unroll
    for (int b = 0; b < NB; ++b) mbar_wait_long(bars + 8 * (B_UCH + c2 + b), 0);
#pragma unroll
    for (int b = 0; b < NB; ++b) {
      const uint32_t ua = sb + SM_U + (c2 + b) * U_BYTES + idx * 512;
      t[b][0] = lds128(ua + o0); t[b][1] = lds128(ua + o1); t[b][2] = lds128(ua + o2);
    }
#pragma unroll
    for (int b = 0; b < NB; ++b) {
      const uint32_t vb = sb + SM_VV + (c2 + b) * VV_BYTES, aw = vb + idx * 512 + ow;
      const uint32_t E[12] = {t[b][0].x, t[b][0].y, t[b][0].z, t[b][0].w, t[b][1].x, t[b][1].y, t[b][1].z, t[b][1].w,
                              t[b][2].x, t[b][2].y, t[b][2].z, t[b][2].w};
      uint32_t O[8];
#pragma unroll
      for (int j = 0; j < 8; ++j) O[j] = __byte_perm(E[j + 1], E[j + 2], 0x5432);
      uint32_t s3[6], s5[4], s7[4], s9[4];
#pragma unroll
      for (int j = 0; j < 6; ++j) s3[j] = badd(badd(O[j], O[j + 1]), E[j + 2]);
#pragma unroll
      for (int j = 0; j < 4; ++j) {
        s5[j] = badd(s3[j + 2], badd(E[j + 3], E[j + 5]));
        s7[j] = badd(s5[j], badd(O[j + 1], O[j + 4]));
        s9[j] = badd(s7[j], badd(E[j + 2], E[j + 6]));
      }
      if (k < 208) { sts128(aw + VV_U3, s3[0], s3[1], s3[2], s3[3]); sts128(aw + VV_U5, s5[0], s5[1], s5[2], s5[3]); }
      if (k < 144) { sts128(aw + VV_U7, s7[0], s7[1], s7[2], s7[3]); sts128(aw + VV_U9, s9[0], s9[1], s9[2], s9[3]); }
      if (idx == 0 && lane < 16) {
        sts128(vb + oz + VV_U3, 0, 0, 0, 0); sts128(vb + oz + VV_U5, 0, 0, 0, 0);
        sts128(vb + oz + VV_U7, 0, 0, 0, 0); sts128(vb + oz + VV_U9, 0, 0, 0, 0);
      }
    }
  }
}

__global__ void __cluster_dims__(2, 1, 1) __launch_bounds__(NTHREADS, 1)
fused_kernel(const __grid_constant__ Maps maps, const Ptrs p) {
  extern __shared__ __align__(1024) uint8_t smem[];
  const uint32_t sb = s2u(smem);
  const int tid = threadIdx.x, lane = tid & 31;
  const int warp = __shfl_sync(0xffffffffu, tid >> 5, 0);
  const int cta = blockIdx.x;
  const uint32_t rank = cta & 1;
  const int ti = 2 * (cta >> 4) + rank;
  const int tj = (cta >> 1) & 7;
  const int pi = cta >> 3, pj = cta & 7;
  const uint32_t bars = sb + SM_BAR;
#define BAR(i) (bars + 8 * (i))
  const int g = lane >> 2, q = lane & 3;

  auto issue_stage = [&](int ks, int s) {
    const uint32_t st = sb + s * STG_BYTES, fb = BAR(B_FULL + s);
    mbar_expect_tx(fb, STG_BYTES);
    tma_load_2d(st + STG_X, &maps.x, ks * 32, ti * 128, fb);
    tma_load_3d_mc(st + STG_W + rank * 6144, &maps.w, tj * 64, ks * 32 + rank * 16, 0, fb, 3);
  };

  const int kch = warp & 3, krd = warp >> 2;
  float zr, zi, wr, wi;
  unsigned epoch;
  uint32_t r_dskip;
  {
    const size_t po = (size_t)(cta * 4 + kch) * 128 + krd * 32 + lane;
    const uint32_t r_ar = ldg16(p.A_re + po), r_ai = ldg16(p.A_im + po), r_br = ldg16(p.B_re + po), r_bi = ldg16(p.B_im + po);
    const uint32_t r_cr = ldg16(p.C_re + po), r_ci = ldg16(p.C_im + po), r_ldt = ldg16(p.log_dt + cta * 4 + kch);
    epoch = __ldcg(&g_epoch);
    r_dskip = ldg16(p.Dskip + cta * 4 + kch);
    uint4 pt;
    if (tid < 128) pt = __ldg((const uint4*)g_ptab.v + tid);
    if (tid == 384) {
      TS(0);
#pragma unroll
      for (int i = 0; i < B_COUNT; ++i) mbar_init(BAR(i), bar_count(i));
      asm volatile("fence.mbarrier_init.release.cluster;" ::: "memory");
      prefetch_tmap(&maps.x); prefetch_tmap(&maps.w); prefetch_tmap(&maps.u);
    }
    __syncthreads();
    cluster_arrive();
    if (warp >= 12) {
      cluster_wait();
      if (elect_one()) {
        if (warp == 13) {
          mbar_expect_tx(BAR(B_TILE), 16384);
          tma_load_2d(sb + SM_U, &maps.u, tj * 64, ti * 128, BAR(B_TILE));
          prefetch_tmap(&maps.uT); prefetch_tmap(&maps.wo); prefetch_tmap(&maps.o); prefetch_tmap(&maps.yT);
          prefetch_tmap(&maps.out); prefetch_tmap(&maps.outh);
        } else {
          if (warp == 12) TS(61);
          { const int ks = warp == 12 ? 0 : warp - 13; issue_stage(ks, ks); }
        }
      }
      __syncwarp();
    }
    if (tid < 128) sts128(sb + SM_PTAB + tid * 16, pt.x, pt.y, pt.z, pt.w);
    const float dt = round_bf16(expf(bf_lo(r_ldt)));
    zr = dt * bf_lo(r_ar); zi = dt * bf_lo(r_ai);
    const float dbr = dt * bf_lo(r_br), dbi = dt * bf_lo(r_bi), cr = bf_lo(r_cr), ci = bf_lo(r_ci);
    wr = cr * dbr - ci * dbi; wi = cr * dbi + ci * dbr;
  }
  {
    const float mz = __uint_as_float(__reduce_max_sync(0xffffffffu, __float_as_uint(fmaxf(zr, 0.f))));
    const int E = min(max((int)(__reduce_max_sync(0xffffffffu, __float_as_uint(fmaxf(fabsf(wr), fabsf(wi)))) >> 23), 1), 252);
    const float sc = __int_as_float((253 - E) << 23), inv = __int_as_float((E + 1) << 23);
    const float zl = (zr - mz) * 1.4426950408889634f;
    const uint32_t tb = sb + SM_VV + kch * VV_BYTES + krd * KG_BYTES;
    const uint32_t sta = tb + (((lane >> 2) << 4) | ((lane & 3) << 2));
    auto put = [&](int r, uint32_t v) { sts32((sta ^ ((r & 7) << 4)) + r * 128, v); };
    const uint32_t lda = tb + ((lane & 7) + (((lane >> 3) & 1) << 3)) * 128;
    const uint32_t ldb = tb + ((lane & 7) + ((lane >> 4) << 3)) * 128;
    C32 e1 = cfresh(zl, zi, 1.f), e2 = csq(e1), e4 = csq(e2), e8 = csq(e4);
    C32 e16 = cfresh(zl, zi, 16.f), e32 = csq(e16), e64 = csq(e32), e128 = csq(e64);
    C32 e256 = cfresh(zl, zi, 256.f), e512 = csq(e256), e1024 = csq(e512), e768 = cmul(e512, e256);
    uint32_t XA[2][4][4];
    {
      const HMul m16 = mk_mul(e16.re, e16.im), m32 = mk_mul(e32.re, e32.im), m64 = mk_mul(e64.re, e64.im);
      const HMul m128 = mk_mul(e128.re, e128.im);
      uint32_t X[16];
      X[0] = 0x00003c00u; X[1] = pack_f16(e8.re, e8.im); X[2] = m16.b; X[4] = m32.b; X[8] = m64.b;
      X[3] = hcmul(X[1], m16); X[5] = hcmul(X[1], m32); X[6] = hcmul(X[2], m32); X[7] = hcmul(X[3], m32);
#pragma unroll
      for (int r = 1; r < 8; ++r) X[8 + r] = hcmul(X[r], m64);
#pragma unroll
      for (int h = 0; h < 2; ++h) {
#pragma unroll
        for (int r = 0; r < 16; ++r) put(r, h == 0 ? X[r] : r == 0 ? m128.b : hcmul(X[r], m128));
        __syncwarp();
#pragma unroll
        for (int k = 0; k < 4; ++k) ldsm_x4(XA[h][k], lda + (((2 * k + (lane >> 4)) ^ (lane & 7)) << 4));
        __syncwarp();
      }
    }
    if (warp >= 14 && elect_one()) {
      issue_stage(warp - 11, warp - 11);
      issue_stage(warp - 9, warp - 9);
      if (warp == 14) l2_prefetch((const char*)p.wqkv + 224 * 3072 + cta * 6912, 6912);
      else l2_prefetch((const char*)p.x + (size_t)cta * 16384, 16384);
    }
    __syncwarp();
    float D[2][3][4];
#pragma unroll
    for (int t = 0; t < 6; ++t) D[t / 3][t % 3][0] = D[t / 3][t % 3][1] = D[t / 3][t % 3][2] = D[t / 3][t % 3][3] = 0.f;
    auto contract = [&](int t0, int nt) {
      __syncwarp();
#pragma unroll
      for (int k = 0; k < 4; ++k) {
        uint32_t b[4];
        ldsm_x4(b, ldb + (((2 * k + ((lane >> 3) & 1)) ^ (lane & 7)) << 4));
#pragma unroll
        for (int h = 0; h < 2; ++h) {
          mma_f16(D[h][t0], XA[h][k], b[0], b[1]);
          if (nt == 2) mma_f16(D[h][t0 + 1], XA[h][k], b[2], b[3]);
        }
      }
      __syncwarp();
    };
    const HMul c1 = mk_mul(e1.re, -e1.im), c2 = mk_mul(e2.re, -e2.im), c4 = mk_mul(e4.re, -e4.im);
    const HMul c256 = mk_mul(e256.re, -e256.im), c512 = mk_mul(e512.re, -e512.im), c768 = mk_mul(e768.re, -e768.im);
    const HMul c1024 = mk_mul(e1024.re, -e1024.im);
    uint32_t W[8];
    W[0] = pack_f16(wr * sc, -wi * sc);
    W[1] = hcmul(W[0], c1); W[2] = hcmul(W[0], c2); W[3] = hcmul(W[1], c2);
    W[4] = hcmul(W[0], c4); W[5] = hcmul(W[1], c4); W[6] = hcmul(W[2], c4); W[7] = hcmul(W[3], c4);
#pragma unroll
    for (int i = 0; i < 8; ++i) put(i, W[i]);
#pragma unroll
    for (int i = 0; i < 4; ++i) put(8 + i, hcmul(W[2 * i], c256));
    put(12, hcmul(W[0], c512)); put(13, hcmul(W[4], c512)); put(14, hcmul(W[0], c768)); put(15, hcmul(W[4], c768));
    contract(0, 2);
    const uint32_t v0 = hcmul(W[0], c1024);
    put(0, v0); put(1, hcmul(v0, c256)); put(2, hcmul(v0, c512)); put(3, hcmul(v0, c768)); put(4, hcmul(v0, c1024));
    contract(2, 1);
    const uint32_t a = tb + (g * 24 + 2 * q) * 4;
#pragma unroll
    for (int t = 0; t < 6; ++t) {
      const float(&d)[4] = D[t / 3][t % 3];
      sts_f32x2(a + (t / 3) * 1536 + (t % 3) * 32, d[0], d[1]);
      sts_f32x2(a + (t / 3) * 1536 + (t % 3) * 32 + 768, d[2], d[3]);
    }
    if (lane == 0) sts_f32(tb + 3072, inv);
    if (mz > 0.f) {
      __syncwarp();
#pragma unroll 1
      for (int i = lane; i < 768; i += 32) {
        const int r = i / 24, y = i - 24 * r;
        sts_f32(tb + i * 4, lds_f32(tb + i * 4) * ex2(mz * 1.4426950408889634f * (koff(y) + 8 * r)));
      }
    }
  }
  if (tid == 0) TS(2);
  if (warp < 12) cluster_wait();
  __syncthreads();

  if (warp < 4) {
#define A_REGS 200
    asm volatile("setmaxnreg.inc.sync.aligned.u32 %0;" ::"n"(A_REGS));
    if (tid == 0) TS(34);
    const int d = cta * 4 + warp;
    const uint32_t vv = sb + SM_VV + warp * VV_BYTES;
    const uint32_t ub = sb + SM_U + warp * U_BYTES;
    const uint32_t pb = sb + SM_P + warp * P_BYTES;
    const float dskip = bf_lo(r_dskip);
#pragma unroll 1
    for (int pass = 0; pass < 2; ++pass) {
      if (pass == 1) {
        const uint32_t kf = vv;
        const float i0 = lds_f32(kf + 3072), i1 = lds_f32(kf + KG_BYTES + 3072), i2 = lds_f32(kf + 2 * KG_BYTES + 3072);
        const float i3 = lds_f32(kf + 3 * KG_BYTES + 3072);
#pragma unroll 2
        for (int i = 0; i < 6; ++i) {
          const uint32_t a = kf + (i * 32 + lane) * 16;
          const uint4 x0 = lds128(a), x1 = lds128(a + KG_BYTES), x2 = lds128(a + 2 * KG_BYTES), x3 = lds128(a + 3 * KG_BYTES);
          auto s4 = [&](uint32_t a0, uint32_t a1, uint32_t a2, uint32_t a3) {
            return __float_as_uint(fmaf(__uint_as_float(a0), i0, __uint_as_float(a1) * i1) +
                                   fmaf(__uint_as_float(a2), i2, __uint_as_float(a3) * i3));
          };
          sts128(a, s4(x0.x, x1.x, x2.x, x3.x), s4(x0.y, x1.y, x2.y, x3.y), s4(x0.z, x1.z, x2.z, x3.z), s4(x0.w, x1.w, x2.w, x3.w));
        }
        __syncwarp();
        const float k1024 = lds_f32(kf + kidx_c(1024) * 4);
        if (lane == 0) {
          sts_f32(kf + SL_ZERO * 4, 0.f);
          sts_f32(kf + SL_510 * 4, lds_f32(kf + kidx_c(510) * 4) - lds_f32(kf + kidx_c(512) * 4));
          sts_f32(kf + SL_0 * 4, lds_f32(kf) + dskip);
        }
        __syncwarp();
        if (tid == 0) TS(36);
        mbar_wait_long(BAR(B_PFREE), 0);
        if (tid == 0) TS(37);
        {
          float prev = 0.f;
#pragma unroll 1
          for (int i0 = 0; i0 < 16; i0 += 4) {
            uint32_t e[4];
            float a[4], b[4];
#pragma unroll
            for (int i = 0; i < 4; ++i) e[i] = lds32(sb + SM_PTAB + ((i0 + i) * 32 + lane) * 4);
#pragma unroll
            for (int i = 0; i < 4; ++i) { a[i] = lds_f32(kf + (e[i] & 0xffff)); b[i] = lds_f32(kf + (e[i] >> 16)); }
#pragma unroll
            for (int i = 0; i < 4; ++i) {
              const uint32_t w = pb + (31 * lane + 2 * (i0 + i)) * 4;
              if (i0 + i > 0) sts32(w - 4, pack_bf16(a[i], prev));
              sts32(w, pack_bf16(b[i], a[i]));
              prev = b[i];
            }
          }
        }
        __syncwarp();
        if (lane == 0) TS(4);
        const int gq = g - 2 * q;
        uint32_t h127, h128;
        {
          const uint32_t kf2 = pack_bf16(k1024, k1024) ^ 0x80008000u;
          h127 = (gq == 4 ? 0x0000ffffu : gq == 5 ? 0xffffffffu : gq == 6 ? 0xffff0000u : 0u) & kf2;
          h128 = (gq == -4 ? 0x0000ffffu : gq == -3 ? 0xffffffffu : gq == -2 ? 0xffff0000u : 0u) & kf2;
        }
        bar_arrive(7, 384);
        if (lane == 0) TS(6);
        bar_sync(4, 384);
        mbar_wait_long(BAR(B_UCH + warp), 0);
        if (lane == 0) TS(7);
        float acc[16][4];
#pragma unroll
        for (int i = 0; i < 16; ++i) { acc[i][0] = acc[i][1] = acc[i][2] = acc[i][3] = 0.f; }
        {
          const uint32_t pd_lane = pb + (PD_OFF + 16 + gq) * 4;
          const int prow0 = 8 + (lane & 7) + ((lane >> 4) << 3), hs = (lane >> 3) & 1;
          const uint32_t zero = (uint32_t)cta >> 20;
          uint32_t B[2][4][4];
          uint32_t A[4][4];
          const uint32_t la0 = ub + prow0 * 32 + ((hs ^ ((prow0 >> 2) & 1)) << 4);
#pragma unroll
          for (int m2 = 0; m2 < 4; ++m2) ldsm_x4(B[0][m2], la0 + m2 * 512);
#pragma unroll
          for (int i = 0; i < 4; ++i) {
            const uint32_t a = pd_lane + i * 512;
            A[i][0] = lds32(a); A[i][1] = lds32(a + 32); A[i][2] = lds32(a - 32); A[i][3] = lds32(a + zero);
          }
          uint32_t la = la0;
#define UNR_RHO 4
#define UNR_TAIL 4
          constexpr int unr_rho = UNR_RHO, unr_tail = UNR_TAIL;
#pragma unroll unr_rho
          for (int rho = 0; rho < 8; ++rho) {
#pragma unroll
            for (int m2 = 0; m2 < 4; ++m2) ldsm_x4(B[1][m2], la + (4 + m2) * 512);
#pragma unroll
            for (int i = 0; i < 4; ++i)
#pragma unroll
              for (int m = 0; m < 8; ++m) mma_bf16v(acc[m + i], A[i], B[0][m >> 1][2 * (m & 1)], B[0][m >> 1][2 * (m & 1) + 1]);
            const int prow = prow0 - min(rho + 1, 7);
            la = ub + prow * 32 + ((hs ^ ((prow >> 2) & 1)) << 4);
#pragma unroll
            for (int m2 = 0; m2 < 4; ++m2) ldsm_x4(B[0][m2], la + m2 * 512);
            const uint32_t pa = pd_lane + (rho + 1) * 64;
#pragma unroll
            for (int i = 0; i < 4; ++i) {
#pragma unroll
              for (int m = 0; m < 8 - i; ++m)
                mma_bf16v(acc[8 + m + i], A[i], B[1][m >> 1][2 * (m & 1)], B[1][m >> 1][2 * (m & 1) + 1]);
              A[i][0] = lds32(pa + i * 512); A[i][1] = lds32(pa + i * 512 + 32); A[i][2] = lds32(pa + i * 512 - 32);
              A[i][3] = lds32(pa + i * 512 + zero);
            }
          }
          if (lane == 0) TS(40);
          {
            uint32_t b8[4];
            ldsm_x4(b8, la + 4 * 512);
            const uint32_t h63 = lds32(pd_lane + 63 * 32), h64 = lds32(pd_lane + 64 * 32);
            const uint32_t a63[4] = {0u, h127, 0u, 0u}, a32[4] = {h64, 0u, h63, h64}, a64[4] = {h128, 0u, h127, h128};
#pragma unroll
            for (int m2 = 0; m2 < 4; ++m2) ldsm_x4(B[1][m2], la0 + m2 * 512);
#pragma unroll
            for (int m = 0; m < 8; ++m) mma_bf16v(acc[m + 7], a63, B[0][m >> 1][2 * (m & 1)], B[0][m >> 1][2 * (m & 1) + 1]);
#pragma unroll
            for (int m2 = 0; m2 < 2; ++m2) ldsm_x4(B[0][m2], la0 + (4 + m2) * 512);
#pragma unroll
            for (int m = 0; m < 8; ++m) mma_bf16v(acc[m + 4], a32, B[1][m >> 1][2 * (m & 1)], B[1][m >> 1][2 * (m & 1) + 1]);
            mma_bf16v(acc[15], a63, b8[0], b8[1]);
#pragma unroll
            for (int m = 0; m < 8; ++m) mma_bf16v(acc[m + 8], a64, B[1][m >> 1][2 * (m & 1)], B[1][m >> 1][2 * (m & 1) + 1]);
#pragma unroll
            for (int m = 0; m < 4; ++m) mma_bf16v(acc[m + 12], a32, B[0][m >> 1][2 * (m & 1)], B[0][m >> 1][2 * (m & 1) + 1]);
          }
          if (lane == 0) TS(41);
          bar_sync(5, 384);
#pragma unroll unr_tail
          for (int v = 0; v < 4; ++v)
            conv_tail<4, 3, 11>(acc, pb + (P2_OFF + 56 * v + gq - 16) * 4, vv + ((v & 1) ? VV_U3 : VV_U5), v >> 1, v == 0, lane);
          if (lane == 0) TS(42);
#pragma unroll unr_tail
          for (int pi = 0; pi < 2; ++pi)
            conv_tail<8, 5, 7>(acc, pb + (P3_OFF + 88 * pi + gq - 48) * 4, vv + (pi ? VV_U7 : VV_U9), pi, pi == 0, lane);
        }
        if (lane == 0) TS(8);
        __syncwarp();
        {
          const int mt = lane >> 3;
          const uint32_t a = pb + (128 * (mt >> 1) + 16 * (lane & 7) + 8 * (mt & 1)) * 2;
#pragma unroll
          for (int ab = 0; ab < 16; ab += 2)
            stsm_x4_t(a + ab * 256, pack_bf16(acc[ab][0], acc[ab][1]), pack_bf16(acc[ab][2], acc[ab][3]),
                      pack_bf16(acc[ab + 1][0], acc[ab + 1][1]), pack_bf16(acc[ab + 1][2], acc[ab + 1][3]));
        }
        fence_async_smem();
        __syncwarp();
        if (lane < 2) mbar_arrive_cluster(BAR(B_CONVD), lane);
        __syncwarp();
        cluster_arrive();
        bar_arrive(3, 384);
        if (elect_one()) {
          bulk_store(p.yT + (size_t)d * 2048, pb, 4096);
          bulk_commit();
          bulk_wait0();
          red_relaxed_add(&g_cnt[(C_Y + (cta >> 4)) * 32], 1);
          TS(9);
        }
        bar_sync(2, 128);
        if (warp == 0 && elect_one()) {
          wait_counter(&g_cnt[(C_Y + tj) * 32], (epoch + 1) * 64);
          TS(28);
          mbar_expect_tx(BAR(B_TILE), 16384);
          tma_load_2d(sb + SM_U, &maps.yT, ti * 128, tj * 64, BAR(B_TILE));
          tma_load_2d(sb + SM_U + 8192, &maps.yT, ti * 128 + 64, tj * 64, BAR(B_TILE));
        }
        __syncwarp();
      }
      mbar_wait_long(BAR(B_TILE), pass);
      if (lane == 0) TS(26 + 3 * pass);
      {
        const int m = lane >> 3, r = lane & 7;
#pragma unroll 2
        for (int it = 0; it < 8; ++it) {
          const int tb = warp * 4 + (it >> 1), cb = (it & 1) * 4 + m;
          const uint32_t at = (tb * 8 + r) * 128 + ((cb ^ r) << 4);
          const uint32_t ac = (tb >> 3) * 8192 + (cb * 8 + r) * 128 + (((tb & 7) ^ (pass ? 0 : tb >> 3) ^ r) << 4);
          uint32_t v[4];
          ldsm_x4_t(v, sb + SM_U + (pass ? ac : at));
          stsm_x4(sb + SM_P + (pass ? at : ac), v[0], v[1], v[2], v[3]);
        }
      }
      if (pass == 0 && tid == 0) TS(35);
      fence_async_smem();
      if (pass == 0) {
        bar_arrive(6, 160);
      } else {
        bar_sync(2, 128);
        if (warp == 0 && elect_one()) {
          tma_store_2d(&maps.out, sb + SM_P, 64 * tj, 128 * ti);
          bulk_commit();
          bulk_wait_read0();
          TS(30);
        }
      }
    }
  } else if (warp < 12) {
    const int w8 = warp - 4;
    const int row = w8 * 16 + (lane & 7) + (((lane >> 3) & 1) << 3);
    uint32_t pq[16];
    {
      float acc[96];
#pragma unroll 1
      for (int ks = 0, s = 0, ph = 0; ks < 16; ++ks) {
        mbar_wait(BAR(B_FULL + s), ph);
        if (tid == 128 && !(ks & 1)) TSR(16, ks == 0 ? 16 : 9 + (ks >> 1) + (ks > 12 ? 43 : 0));
        const uint32_t st = sb + s * STG_BYTES;
        const uint32_t da = mkdesc(st + STG_X + (w8 >> 2) * 4096, 16);
        const uint32_t db = mkdesc(st + STG_W, 2048);
        wg_fence();
        wgmma_n192(acc, da, db, ks != 0);
        wgmma_n192(acc, da + 2, db + 384, 1);
        wg_commit();
        const uint32_t eprev = BAR(B_EMPTY + (s == 0 ? NSTG - 1 : s - 1));
        if (++s == NSTG) { s = 0; ph ^= 1; }
        if (ks > 0) {
          wg_wait<1>();
          if (lane < 2) mbar_arrive_cluster(eprev, lane);
        }
      }
      wg_wait<0>();
      bar_arrive(4, 384);
      if (tid == 128) TS(17);
      auto phi2 = [](float a, float b) -> uint32_t {
        const uint32_t x = pack_bf16(a, b);
        const uint32_t e = pack_bf16(ex2(a * 1.4426950408889634f), ex2(b * 1.4426950408889634f));
        const uint32_t m = __hgt2_mask(*reinterpret_cast<const __nv_bfloat162*>(&x), __floats2bfloat162_rn(0.f, 0.f));
        return badd((badd(x, 0x3f803f80u) & m) | (e & ~m), 0x35863586u);
      };
      uint32_t pk[16];
#pragma unroll
      for (int i = 0; i < 16; ++i) pk[i] = phi2(acc[32 + 2 * i], acc[33 + 2 * i]);
      if (tid == 128) TS(53);
      bar_sync(1, 256);
#pragma unroll
      for (int i = 0; i < 8; i += 2) {
        const uint32_t off = row * 128 + (((i + (lane >> 4)) ^ (row & 7)) << 4);
        stsm_x4(sb + SM_PK + off, pk[2 * i], pk[2 * i + 1], pk[2 * i + 2], pk[2 * i + 3]);
        stsm_x4(sb + SM_VS + off, pack_bf16(acc[64 + 4 * i], acc[65 + 4 * i]), pack_bf16(acc[66 + 4 * i], acc[67 + 4 * i]),
                pack_bf16(acc[68 + 4 * i], acc[69 + 4 * i]), pack_bf16(acc[70 + 4 * i], acc[71 + 4 * i]));
      }
      bar_sync(1, 256);
      {
        const int hh = w8 >> 1, dtile = w8 & 1;
        float kv[2][4] = {{0.f, 0.f, 0.f, 0.f}, {0.f, 0.f, 0.f, 0.f}}, zz[2][4] = {{0.f, 0.f, 0.f, 0.f}, {0.f, 0.f, 0.f, 0.f}};
        const int m = lane >> 3;
        const uint32_t aa = sb + SM_VS + ((lane & 7) + ((m >> 1) << 3)) * 128 + (((2 * hh + (m & 1)) ^ (lane & 7)) << 4);
        const uint32_t ab = sb + SM_PK + (lane & 15) * 128 + (((2 * hh + dtile) ^ (lane & 7)) << 4);
#pragma unroll
        for (int ks = 0; ks < 8; ++ks) {
          uint32_t a[4], b0, b1;
          ldsm_x4_t(a, aa + ks * 2048);
          ldsm_x2_t(b0, b1, ab + ks * 2048);
          mma_bf16(kv[ks & 1], a[0], a[1], a[2], a[3], b0, b1);
          mma_bf16(zz[ks & 1], 0x3f803f80u, 0x3f803f80u, 0x3f803f80u, 0x3f803f80u, b0, b1);
        }
        const uint32_t kp = sb + SM_KV + hh * 1088;
        sts128(kp + dtile * 512 + lane * 16, __float_as_uint(kv[0][0] + kv[1][0]), __float_as_uint(kv[0][1] + kv[1][1]),
               __float_as_uint(kv[0][2] + kv[1][2]), __float_as_uint(kv[0][3] + kv[1][3]));
        if (g == 0) sts_f32x2(kp + 1024 + dtile * 32 + q * 8, zz[0][0] + zz[1][0], zz[0][1] + zz[1][1]);
        fence_async_smem();
        __syncwarp();
        if (lane == 0) mbar_arrive(BAR(B_KVP));
        if (tid == 128) TS(55);
      }
#pragma unroll
      for (int i = 0; i < 16; ++i) pq[i] = phi2(acc[2 * i], acc[2 * i + 1]);
    }
    if (tid == 128) TS(56);
    if (warp == 4) mbar_wait_long(BAR(B_KVF), 0);
    bar_sync(1, 256);
    if (tid == 128) TS(19);
    {
      uint32_t kb[4][6];
#pragma unroll
      for (int h = 0; h < 4; ++h) {
        const uint32_t kp = sb + SM_KV + h * 1088;
        const uint4 k0 = lds128(kp + lane * 16), k1 = lds128(kp + 512 + lane * 16);
        const uint32_t za = kp + 1024 + q * 8;
        auto pk2 = [](uint32_t x, uint32_t y) { return pack_bf16(__uint_as_float(x), __uint_as_float(y)); };
        kb[h][0] = pk2(k0.x, k0.y); kb[h][1] = pk2(k1.x, k1.y); kb[h][2] = pk2(k0.z, k0.w); kb[h][3] = pk2(k1.z, k1.w);
        kb[h][4] = pack_bf16(lds_f32(za), lds_f32(za + 4)); kb[h][5] = pack_bf16(lds_f32(za + 32), lds_f32(za + 36));
      }
#pragma unroll
      for (int h = 0; h < 4; ++h) {
        float n0[4] = {0.f, 0.f, 0.f, 0.f}, n1[4] = {0.f, 0.f, 0.f, 0.f}, dn[4] = {0.f, 0.f, 0.f, 0.f};
        mma_bf16(n0, pq[4 * h], pq[4 * h + 1], pq[4 * h + 2], pq[4 * h + 3], kb[h][0], kb[h][1]);
        mma_bf16(n1, pq[4 * h], pq[4 * h + 1], pq[4 * h + 2], pq[4 * h + 3], kb[h][2], kb[h][3]);
        mma_bf16(dn, pq[4 * h], pq[4 * h + 1], pq[4 * h + 2], pq[4 * h + 3], kb[h][4], kb[h][5]);
        const float r0 = rcp(dn[0] + 1e-6f), r1 = rcp(dn[2] + 1e-6f);
        stsm_x4(sb + SM_QS + row * 128 + (((2 * h + (lane >> 4)) ^ (row & 7)) << 4),
                pack_bf16(n0[0] * r0, n0[1] * r0), pack_bf16(n0[2] * r1, n0[3] * r1),
                pack_bf16(n1[0] * r0, n1[1] * r0), pack_bf16(n1[2] * r1, n1[3] * r1));
      }
    }
    fence_async_smem();
    __syncwarp();
    if (lane == 0) mbar_arrive(BAR(B_OST));
    if (tid == 128) TS(57);
    bar_sync(7, 384);
    if (w8 < 7) box_filters<4>(sb, bars, w8, lane);
    bar_arrive(5, 384);
    if (tid == 128) TS(6);
    if (warp == 4) mbar_wait_long(BAR(B_WO), 0);
    bar_sync(3, 384);
    {
      float o[32];
#pragma unroll 1
      for (int c = 0; c < 8; ++c) {
        mbar_wait_long(BAR(B_RF + c), 0);
        if (tid == 128) TSR(22, c == 0 ? 22 : 43 + c);
        const uint32_t slot = c < 4 ? SM_QS + c * 16384 : c < 7 ? SM_VV + (c - 4) * 16384 : SM_QS;
        const uint32_t da = mkdesc(sb + slot + (w8 >> 2) * 8192, 16);
        const uint32_t db = mkdesc(sb + SM_WO + c * 8192, 8192);
        wg_fence();
#pragma unroll
        for (int k = 0; k < 4; ++k) wgmma_n64(o, da + 2 * k, db + 128 * k, (c | k) != 0);
        wg_commit();
        if (c == 1) {
          wg_wait<1>();
          if (lane < 2) mbar_arrive_cluster(BAR(B_RE), lane);
          __syncwarp();
          cluster_arrive();
        }
      }
      wg_wait<0>();
      if (tid == 128) TS(51);
#pragma unroll
      for (int i = 0; i < 8; i += 2)
        stsm_x4(sb + SM_BOUT + row * 128 + (((i + (lane >> 4)) ^ (row & 7)) << 4), pack_bf16(o[4 * i], o[4 * i + 1]),
                pack_bf16(o[4 * i + 2], o[4 * i + 3]), pack_bf16(o[4 * i + 4], o[4 * i + 5]), pack_bf16(o[4 * i + 6], o[4 * i + 7]));
      fence_async_smem();
      bar_sync(8 + (w8 >> 2), 128);
      if ((w8 & 3) == 0 && elect_one()) {
        tma_store_2d(&maps.outh, sb + SM_BOUT + (w8 >> 2) * 8192, 512 + 64 * pj, 128 * pi + (w8 >> 2) * 64);
        bulk_commit();
        bulk_wait_read0();
        TS(23);
      }
    }
  } else {
    asm volatile("setmaxnreg.dec.sync.aligned.u32 40;");
    if (warp == 12) {
      if (elect_one()) {
#pragma unroll 1
        for (int ks = NSTG, s = 0, ph = 0; ks < 16; ++ks) {
          mbar_wait(BAR(B_EMPTY + s), ph);
          issue_stage(ks, s);
          if (ks == NSTG) l2_prefetch((const char*)p.wo + (size_t)cta * 4096, 4096);
          if (++s == NSTG) { s = 0; ph ^= 1; }
        }
        mbar_wait(BAR(B_EMPTY + 6), 1);
        mbar_expect_tx(BAR(B_WO), 65536);
        tma_load_2d(sb + SM_WO, &maps.wo, pj * 64, 0, BAR(B_WO));
        tma_load_2d(sb + SM_WO + 32768, &maps.wo, pj * 64, 256, BAR(B_WO));
        float* kvg = &g_kv[epoch & 1][tj][0];
        mbar_wait_long(BAR(B_KVP), 0);
        bulk_reduce_add_f32(kvg, sb + SM_KV, 4352);
        bulk_commit();
        bulk_wait0();
        red_relaxed_add(&g_cnt[(C_KV + tj) * 32], 1);
        TS(18);
        wait_counter(&g_cnt[(C_KV + tj) * 32], (epoch + 1) * 16);
        mbar_expect_tx(BAR(B_KVF), 4352);
        bulk_load(sb + SM_KV, kvg, 4352, BAR(B_KVF));
        mbar_wait_long(BAR(B_OST), 0);
        tma_store_2d(&maps.o, sb + SM_QS, tj * 64, ti * 128);
        tma_store_2d(&maps.o, sb + SM_QS + 8192, tj * 64, ti * 128 + 64);
        bulk_commit();
        bulk_wait0();
        red_relaxed_add(&g_cnt[(C_O + ti) * 32], 1);
        TS(20);
        mbar_arrive_cluster(BAR(B_SLOT), 0);
        mbar_arrive_cluster(BAR(B_SLOT), 1);
        wait_counter(&g_cnt[(C_O + pi) * 32], (epoch + 1) * 8);
        if (cta == 0) g_epoch = epoch + 1;
        mbar_wait(BAR(B_SLOT), 0);
        TS(21);
#pragma unroll 1
        for (int c = 0; c < 8; ++c) {
          if (c == 4) mbar_wait_long(BAR(B_CONVD), 0);
          if (c == 7) mbar_wait(BAR(B_RE), 0);
          const uint32_t slot = c < 4 ? SM_QS + c * 16384 : c < 7 ? SM_VV + (c - 4) * 16384 : SM_QS;
          mbar_expect_tx(BAR(B_RF + c), 16384);
          tma_load_2d_mc(sb + slot + rank * 8192, &maps.o, c * 64, pi * 128 + rank * 64, BAR(B_RF + c), 3);
        }
      }
    } else if (warp == 13) {
      bar_sync(6, 160);
      sts128(sb + SM_U + (lane >> 4) * U_BYTES + (lane & 15) * 16, 0, 0, 0, 0);
      sts128(sb + SM_U + (2 + (lane >> 4)) * U_BYTES + (lane & 15) * 16, 0, 0, 0, 0);
      __syncwarp();
      if (elect_one()) {
        tma_store_2d(&maps.uT, sb + SM_P, ti * 128, tj * 64);
        tma_store_2d(&maps.uT, sb + SM_P + 8192, ti * 128 + 64, tj * 64);
        bulk_commit();
        bulk_wait_read0();
        mbar_arrive(BAR(B_PFREE));
        bulk_wait0();
        red_relaxed_add(&g_cnt[(C_U + tj) * 32], 1);
        TS(27);
        wait_counter(&g_cnt[(C_U + (cta >> 4)) * 32], (epoch + 1) * 16);
#pragma unroll 1
        for (int c = 0; c < 4; ++c) {
          mbar_expect_tx(BAR(B_UCH + c), 4096);
          bulk_load(sb + SM_U + c * U_BYTES + 256, p.uT + (size_t)(cta * 4 + c) * 2048, 4096, BAR(B_UCH + c));
        }
        TS(3);
      }
      __syncwarp();
      if (ti == 0) {
        float4* z = (float4*)&g_kv[(epoch & 1) ^ 1][tj][0];
#pragma unroll 1
        for (int i = lane; i < 272; i += 32) z[i] = make_float4(0.f, 0.f, 0.f, 0.f);
      }
    }
  }
  __syncwarp();
  if (warp >= 12) cluster_arrive();
  cluster_wait();
  if (tid == 0) TS(31);
#undef BAR
}

typedef CUresult (*EncodeFn)(CUtensorMap*, CUtensorMapDataType, cuuint32_t, void*, const cuuint64_t*, const cuuint64_t*,
                             const cuuint32_t*, const cuuint32_t*, CUtensorMapInterleave, CUtensorMapSwizzle,
                             CUtensorMapL2promotion, CUtensorMapFloatOOBfill);

static void make_map(EncodeFn enc, CUtensorMap* m, const void* base, uint64_t inner, uint64_t outer, uint32_t box_in,
                     uint32_t box_out, CUtensorMapSwizzle swz = CU_TENSOR_MAP_SWIZZLE_128B) {
  cuuint64_t gd[2] = {inner, outer};
  cuuint64_t gs[1] = {inner * 2};
  cuuint32_t bd[2] = {box_in, box_out};
  cuuint32_t es[2] = {1, 1};
  enc(m, CU_TENSOR_MAP_DATA_TYPE_BFLOAT16, 2, const_cast<void*>(base), gd, gs, bd, es, CU_TENSOR_MAP_INTERLEAVE_NONE,
      swz, CU_TENSOR_MAP_L2_PROMOTION_L2_128B, CU_TENSOR_MAP_FLOAT_OOB_FILL_NONE);
}

}

extern "C" void kernel_launch(void* const* d_in, const int* in_sizes, int n_in, void* d_out, int out_size) {
  using namespace s4la;
  (void)in_sizes; (void)n_in; (void)out_size;
  static EncodeFn enc = nullptr;
  static void *uT = nullptr, *yT = nullptr, *oS = nullptr;
  if (!enc) {
    void* fn = nullptr;
    cudaDriverEntryPointQueryResult qr;
    cudaGetDriverEntryPoint("cuTensorMapEncodeTiled", &fn, cudaEnableDefault, &qr);
    enc = (EncodeFn)fn;
    cudaGetSymbolAddress(&uT, g_uT);
    cudaGetSymbolAddress(&yT, g_yT);
    cudaGetSymbolAddress(&oS, g_o);
    cudaFuncSetAttribute(fused_kernel, cudaFuncAttributeMaxDynamicSharedMemorySize, SM_TOTAL);
  }
  const __nv_bfloat16* const* in = (const __nv_bfloat16* const*)d_in;
  Maps maps;
  make_map(enc, &maps.x, in[9], 512, 2048, 32, 128, CU_TENSOR_MAP_SWIZZLE_64B);
  {
    cuuint64_t gd[3] = {512, 512, 3};
    cuuint64_t gs[2] = {3072, 1024};
    cuuint32_t bd[3] = {64, 16, 3};
    cuuint32_t es[3] = {1, 1, 1};
    enc(&maps.w, CU_TENSOR_MAP_DATA_TYPE_BFLOAT16, 3, const_cast<__nv_bfloat16*>(in[10]), gd, gs, bd, es,
        CU_TENSOR_MAP_INTERLEAVE_NONE, CU_TENSOR_MAP_SWIZZLE_128B, CU_TENSOR_MAP_L2_PROMOTION_L2_128B,
        CU_TENSOR_MAP_FLOAT_OOB_FILL_NONE);
  }
  make_map(enc, &maps.wo, in[11], 512, 512, 64, 256);
  make_map(enc, &maps.u, in[0], 512, 2048, 64, 128);
  make_map(enc, &maps.uT, uT, 2048, 512, 64, 64);
  make_map(enc, &maps.yT, yT, 2048, 512, 64, 64);
  make_map(enc, &maps.o, oS, 512, 2048, 64, 64);
  make_map(enc, &maps.out, d_out, 1024, 2048, 64, 128);
  make_map(enc, &maps.outh, d_out, 1024, 2048, 64, 64);
  Ptrs p;
  p.A_re = in[1]; p.A_im = in[2]; p.B_re = in[3]; p.B_im = in[4]; p.C_re = in[5]; p.C_im = in[6];
  p.log_dt = in[7]; p.Dskip = in[8]; p.x = in[9]; p.wqkv = in[10]; p.wo = in[11];
  p.uT = (__nv_bfloat16*)uT; p.yT = (__nv_bfloat16*)yT;
  fused_kernel<<<NCTA, NTHREADS, SM_TOTAL, cudaStreamPerThread>>>(maps, p);
}
```

```cpp
#include <cuda_runtime.h>
#include <cuda_bf16.h>
#include <cuda_fp16.h>
#include <cuda.h>
#include <stdint.h>

#define DEVI __device__ __forceinline__

namespace s4la {

constexpr int NTHREADS = 512;
constexpr int NCTA = 128;

constexpr int NSTG = 7;
constexpr uint32_t STG_BYTES = 20480, STG_X = 0, STG_W = 8192;
constexpr uint32_t SM_QS = 0;
constexpr uint32_t SM_PK = SM_QS + 16384, SM_VS = SM_QS + 32768;
constexpr uint32_t SM_WO = 65536;
constexpr uint32_t SM_KV = 131072;
constexpr uint32_t SM_BOUT = 16384;
constexpr uint32_t SM_U = 143360, U_BYTES = 4352;
constexpr uint32_t SM_P = 160768, P_BYTES = 4096;
constexpr uint32_t SM_VV = 177152, VV_BYTES = 12800;
constexpr uint32_t VV_U5 = 0, VV_U3 = 3712, VV_U9 = 7424, VV_U7 = 10112;
constexpr uint32_t KG_BYTES = 3200;
constexpr uint32_t SM_BAR = SM_VV + 4 * VV_BYTES;
constexpr uint32_t SM_PTAB = SM_BAR + 320;
constexpr uint32_t SM_TOTAL = SM_PTAB + 2048;
static_assert(SM_TOTAL <= 232448, "shared memory");
constexpr int PADV = 12;

enum { B_FULL = 0, B_EMPTY = 7, B_TILE = 14, B_UCH = 15, B_KVP = 19, B_KVF = 20, B_OST = 21, B_RF = 22, B_WO = 30, B_RE = 31, B_PFREE = 32, B_CONVD = 33, B_SLOT = 34, B_COUNT = 35 };
__host__ __device__ constexpr int bar_count(int i) {
  return (i >= B_EMPTY && i < B_TILE) ? 16 : (i == B_KVP || i == B_OST || i == B_CONVD) ? 8 : i == B_RE ? 16 : i == B_SLOT ? 2 : 1;
}

constexpr int PD_OFF = 0, P2_OFF = 544, P3_OFF = 768;

constexpr int SL_K2048 = 20, SL_ZERO = 21, SL_510 = 22, SL_0 = 23;
__host__ __device__ constexpr int koff(int y) {
  return y < 8 ? y : y < 12 ? 256 + 2 * (y - 8) : y < 16 ? 512 + 256 * ((y - 12) >> 1) + 4 * (y & 1) : 1024 + 256 * (y - 16);
}
__host__ __device__ constexpr int kidx_c(int l) {
  const int y = l < 256 ? (l & 7) : l < 512 ? 8 + ((l & 7) >> 1) : l < 1024 ? 12 + (((l - 512) >> 8) << 1) + ((l >> 2) & 1)
                                                                            : 16 + ((l - 1024) >> 8);
  return ((l >> 3) & 31) * 24 + y;
}
constexpr int slot_direct(int l) {
  if (l < 0 || l > 510) return SL_ZERO;
  if (l == 510) return SL_510;
  if (l == 0) return SL_0;
  return kidx_c(l < 256 ? l : ((l + ((l >> 1) & 1)) & ~1));
}
constexpr int slot_seg2(int v, int k) { return (k >= 32 && k < 64) ? kidx_c(16 * k + 4 * v) : SL_ZERO; }
constexpr int slot_seg3(int pi, int k) {
  return (k >= 64 && k < 128) ? kidx_c(16 * k + 8 * pi) : ((k == 128 && pi == 0) ? SL_K2048 : SL_ZERO);
}
constexpr int slot_word(int w) {
  return w < 0 ? SL_ZERO : w < 544 ? slot_direct(w - 16) : w < 768 ? slot_seg2((w - 544) / 56, 16 + (w - 544) % 56)
       : w < 944 ? slot_seg3((w - 768) / 88, 48 + (w - 768) % 88) : SL_ZERO;
}
struct PTab { uint32_t v[512]; };
constexpr PTab make_ptab() {
  PTab t{};
  for (int lane = 0; lane < 32; ++lane)
    for (int i = 0; i < 16; ++i)
      t.v[i * 32 + lane] = (slot_word(31 * lane - 1 + 2 * i) * 4) | ((slot_word(31 * lane + 2 * i) * 4) << 16);
  return t;
}
__device__ const PTab g_ptab = make_ptab();

__device__ __nv_bfloat16 g_uT[512 * 2048];
__device__ __nv_bfloat16 g_yT[512 * 2048];
__device__ __nv_bfloat16 g_o[2048 * 512];
__device__ float g_kv[2][8][4 * 272];
__device__ unsigned g_cnt[64 * 32];
__device__ unsigned g_epoch;
#define TS(slot) do { } while (0)
#define TSR(on, slot) do { } while (0)
#define TSD(slot) do { } while (0)
enum { C_U = 0, C_KV = 8, C_O = 16, C_Y = 32 };

struct Maps {
  CUtensorMap x, w, wo, u, uT, yT, o, out, outh;
};
struct Ptrs {
  const __nv_bfloat16 *A_re, *A_im, *B_re, *B_im, *C_re, *C_im, *log_dt, *Dskip;
  const __nv_bfloat16 *x, *wqkv, *wo;
  __nv_bfloat16 *uT, *yT;
};

DEVI uint32_t s2u(const void* p) { return (uint32_t)__cvta_generic_to_shared(p); }
DEVI void mbar_init(uint32_t b, uint32_t c) { asm volatile("mbarrier.init.shared::cta.b64 [%0], %1;" ::"r"(b), "r"(c) : "memory"); }
DEVI void mbar_expect_tx(uint32_t b, uint32_t bytes) {
  asm volatile("mbarrier.arrive.expect_tx.shared::cta.b64 _, [%0], %1;" ::"r"(b), "r"(bytes) : "memory");
}
DEVI void mbar_arrive(uint32_t b) { asm volatile("mbarrier.arrive.shared::cta.b64 _, [%0];" ::"r"(b) : "memory"); }
DEVI void mbar_arrive_cluster(uint32_t b, uint32_t cta) {
  asm volatile("{\n.reg .b32 r;\nmapa.shared::cluster.u32 r, %0, %1;\nmbarrier.arrive.shared::cluster.b64 _, [r];\n}"
               ::"r"(b), "r"(cta) : "memory");
}
DEVI void mbar_wait(uint32_t b, uint32_t parity) {
  asm volatile("{\n.reg .pred p;\nLAB_WAIT:\nmbarrier.try_wait.parity.shared::cta.b64 p, [%0], %1;\n@!p bra LAB_WAIT;\n}"
               ::"r"(b), "r"(parity) : "memory");
}
DEVI void mbar_wait_long(uint32_t b, uint32_t parity) {
  asm volatile("{\n.reg .pred p;\nLAB_WAIT:\nmbarrier.try_wait.parity.shared::cta.b64 p, [%0], %1, 0x989680;\n@!p bra LAB_WAIT;\n}"
               ::"r"(b), "r"(parity) : "memory");
}
DEVI void bar_sync(int id, int n) { asm volatile("bar.sync %0, %1;" ::"r"(id), "r"(n) : "memory"); }
DEVI void bar_arrive(int id, int n) { asm volatile("bar.arrive %0, %1;" ::"r"(id), "r"(n) : "memory"); }
DEVI void fence_async_smem() { asm volatile("fence.proxy.async.shared::cta;" ::: "memory"); }
DEVI void fence_async_all() { asm volatile("fence.proxy.async;" ::: "memory"); }
DEVI void cluster_arrive() { asm volatile("barrier.cluster.arrive.relaxed.aligned;" ::: "memory"); }
DEVI void cluster_wait() { asm volatile("barrier.cluster.wait.aligned;" ::: "memory"); }

DEVI void tma_load_2d(uint32_t dst, const CUtensorMap* m, int c0, int c1, uint32_t bar) {
  asm volatile("cp.async.bulk.tensor.2d.shared::cluster.global.mbarrier::complete_tx::bytes [%0], [%1, {%3, %4}], [%2];"
               ::"r"(dst), "l"(m), "r"(bar), "r"(c0), "r"(c1) : "memory");
}
DEVI void tma_load_2d_mc(uint32_t dst, const CUtensorMap* m, int c0, int c1, uint32_t bar, uint16_t mask) {
  asm volatile("cp.async.bulk.tensor.2d.shared::cluster.global.mbarrier::complete_tx::bytes.multicast::cluster [%0], [%1, {%3, %4}], [%2], %5;"
               ::"r"(dst), "l"(m), "r"(bar), "r"(c0), "r"(c1), "h"(mask) : "memory");
}
DEVI void tma_load_3d_mc(uint32_t dst, const CUtensorMap* m, int c0, int c1, int c2, uint32_t bar, uint16_t mask) {
  asm volatile("cp.async.bulk.tensor.3d.shared::cluster.global.mbarrier::complete_tx::bytes.multicast::cluster [%0], [%1, {%3, %4, %5}], [%2], %6;"
               ::"r"(dst), "l"(m), "r"(bar), "r"(c0), "r"(c1), "r"(c2), "h"(mask) : "memory");
}
DEVI void tma_store_2d(const CUtensorMap* m, uint32_t src, int c0, int c1) {
  asm volatile("cp.async.bulk.tensor.2d.global.shared::cta.bulk_group [%0, {%2, %3}], [%1];"
               ::"l"(m), "r"(src), "r"(c0), "r"(c1) : "memory");
}
DEVI void bulk_load(uint32_t dst, const void* src, uint32_t bytes, uint32_t bar) {
  asm volatile("cp.async.bulk.shared::cluster.global.mbarrier::complete_tx::bytes [%0], [%1], %2, [%3];"
               ::"r"(dst), "l"(src), "r"(bytes), "r"(bar) : "memory");
}
DEVI void bulk_store(void* dst, uint32_t src, uint32_t bytes) {
  asm volatile("cp.async.bulk.global.shared::cta.bulk_group [%0], [%1], %2;" ::"l"(dst), "r"(src), "r"(bytes) : "memory");
}
DEVI void bulk_reduce_add_f32(void* dst, uint32_t src, uint32_t bytes) {
  asm volatile("cp.reduce.async.bulk.global.shared::cta.bulk_group.add.f32 [%0], [%1], %2;" ::"l"(dst), "r"(src), "r"(bytes) : "memory");
}
DEVI void bulk_commit() { asm volatile("cp.async.bulk.commit_group;" ::: "memory"); }
DEVI void bulk_wait0() { asm volatile("cp.async.bulk.wait_group 0;" ::: "memory"); }
DEVI void bulk_wait_read0() { asm volatile("cp.async.bulk.wait_group.read 0;" ::: "memory"); }
DEVI void l2_prefetch(const void* p, uint32_t bytes) {
  asm volatile("cp.async.bulk.prefetch.L2.global [%0], %1;" ::"l"(p), "r"(bytes) : "memory");
}
DEVI void prefetch_tmap(const CUtensorMap* m) { asm volatile("prefetch.tensormap [%0];" ::"l"(m) : "memory"); }

DEVI void red_release_add(unsigned* p, unsigned v) {
  asm volatile("red.release.gpu.global.add.u32 [%0], %1;" ::"l"(p), "r"(v) : "memory");
}
DEVI void red_relaxed_add(unsigned* p, unsigned v) {
  asm volatile("red.relaxed.gpu.global.add.u32 [%0], %1;" ::"l"(p), "r"(v) : "memory");
}
DEVI unsigned ld_relaxed(const unsigned* p) {
  unsigned v;
  asm volatile("ld.relaxed.gpu.global.u32 %0, [%1];" : "=r"(v) : "l"(p) : "memory");
  return v;
}
DEVI void wait_counter(const unsigned* p, unsigned target) {
#pragma unroll 1
  for (int it = 0; (int)(ld_relaxed(p) - target) < 0; ++it)
    if (it > (1 << 22)) __trap();
}

DEVI void ldsm_x4(uint32_t (&r)[4], uint32_t a) {
  asm volatile("ldmatrix.sync.aligned.m8n8.x4.shared.b16 {%0,%1,%2,%3}, [%4];"
               : "=r"(r[0]), "=r"(r[1]), "=r"(r[2]), "=r"(r[3]) : "r"(a) : "memory");
}
DEVI void ldsm_x4_t(uint32_t (&r)[4], uint32_t a) {
  asm volatile("ldmatrix.sync.aligned.m8n8.x4.trans.shared.b16 {%0,%1,%2,%3}, [%4];"
               : "=r"(r[0]), "=r"(r[1]), "=r"(r[2]), "=r"(r[3]) : "r"(a) : "memory");
}
DEVI void ldsm_x2_t(uint32_t& r0, uint32_t& r1, uint32_t a) {
  asm volatile("ldmatrix.sync.aligned.m8n8.x2.trans.shared.b16 {%0,%1}, [%2];" : "=r"(r0), "=r"(r1) : "r"(a) : "memory");
}
DEVI void stsm_x4(uint32_t a, uint32_t r0, uint32_t r1, uint32_t r2, uint32_t r3) {
  asm volatile("stmatrix.sync.aligned.m8n8.x4.shared.b16 [%0], {%1,%2,%3,%4};"
               ::"r"(a), "r"(r0), "r"(r1), "r"(r2), "r"(r3) : "memory");
}
DEVI void stsm_x4_t(uint32_t a, uint32_t r0, uint32_t r1, uint32_t r2, uint32_t r3) {
  asm volatile("stmatrix.sync.aligned.m8n8.x4.trans.shared.b16 [%0], {%1,%2,%3,%4};"
               ::"r"(a), "r"(r0), "r"(r1), "r"(r2), "r"(r3) : "memory");
}
DEVI uint32_t lds32(uint32_t a) { uint32_t v; asm volatile("ld.shared.b32 %0, [%1];" : "=r"(v) : "r"(a) : "memory"); return v; }
DEVI float lds_f32(uint32_t a) { float v; asm volatile("ld.shared.f32 %0, [%1];" : "=f"(v) : "r"(a) : "memory"); return v; }
DEVI void sts32(uint32_t a, uint32_t v) { asm volatile("st.shared.b32 [%0], %1;" ::"r"(a), "r"(v) : "memory"); }
DEVI void sts_f32(uint32_t a, float v) { asm volatile("st.shared.f32 [%0], %1;" ::"r"(a), "f"(v) : "memory"); }
DEVI void sts_f32x2(uint32_t a, float x, float y) { asm volatile("st.shared.v2.f32 [%0], {%1,%2};" ::"r"(a), "f"(x), "f"(y) : "memory"); }
DEVI uint4 lds128(uint32_t a) {
  uint4 v;
  asm volatile("ld.shared.v4.b32 {%0,%1,%2,%3}, [%4];" : "=r"(v.x), "=r"(v.y), "=r"(v.z), "=r"(v.w) : "r"(a) : "memory");
  return v;
}
DEVI void sts128(uint32_t a, uint32_t x, uint32_t y, uint32_t z, uint32_t w) {
  asm volatile("st.shared.v4.b32 [%0], {%1,%2,%3,%4};" ::"r"(a), "r"(x), "r"(y), "r"(z), "r"(w) : "memory");
}

DEVI void mma_bf16(float (&d)[4], uint32_t a0, uint32_t a1, uint32_t a2, uint32_t a3, uint32_t b0, uint32_t b1) {
  asm("mma.sync.aligned.m16n8k16.row.col.f32.bf16.bf16.f32 {%0,%1,%2,%3}, {%4,%5,%6,%7}, {%8,%9}, {%0,%1,%2,%3};"
      : "+f"(d[0]), "+f"(d[1]), "+f"(d[2]), "+f"(d[3])
      : "r"(a0), "r"(a1), "r"(a2), "r"(a3), "r"(b0), "r"(b1));
}
DEVI void mma_f16(float (&d)[4], const uint32_t (&a)[4], uint32_t b0, uint32_t b1) {
  asm("mma.sync.aligned.m16n8k16.row.col.f32.f16.f16.f32 {%0,%1,%2,%3}, {%4,%5,%6,%7}, {%8,%9}, {%0,%1,%2,%3};"
      : "+f"(d[0]), "+f"(d[1]), "+f"(d[2]), "+f"(d[3])
      : "r"(a[0]), "r"(a[1]), "r"(a[2]), "r"(a[3]), "r"(b0), "r"(b1));
}
DEVI void mma_bf16v(float (&d)[4], const uint32_t (&a)[4], uint32_t b0, uint32_t b1) {
  asm volatile("mma.sync.aligned.m16n8k16.row.col.f32.bf16.bf16.f32 {%0,%1,%2,%3}, {%4,%5,%6,%7}, {%8,%9}, {%0,%1,%2,%3};"
               : "+f"(d[0]), "+f"(d[1]), "+f"(d[2]), "+f"(d[3])
               : "r"(a[0]), "r"(a[1]), "r"(a[2]), "r"(a[3]), "r"(b0), "r"(b1));
}
DEVI uint32_t pack_bf16(float lo, float hi) {
  uint32_t r;
  asm("cvt.rn.bf16x2.f32 %0, %1, %2;" : "=r"(r) : "f"(hi), "f"(lo));
  return r;
}
DEVI uint32_t pack_f16(float lo, float hi) {
  uint32_t r;
  asm("cvt.rn.f16x2.f32 %0, %1, %2;" : "=r"(r) : "f"(hi), "f"(lo));
  return r;
}
DEVI uint32_t ldg16(const __nv_bfloat16* p) {
  uint32_t v;
  asm volatile("ld.global.nc.u16 %0, [%1];" : "=r"(v) : "l"(p));
  return v;
}
DEVI bool elect_one() {
  uint32_t pred;
  asm volatile("{\n.reg .pred p;\nelect.sync _|p, 0xffffffff;\nselp.u32 %0, 1, 0, p;\n}" : "=r"(pred));
  return pred != 0;
}
DEVI float bf_lo(uint32_t v) { return __uint_as_float(v << 16); }
DEVI float bf_hi(uint32_t v) { return __uint_as_float(v & 0xffff0000u); }
DEVI float bf2f(__nv_bfloat16 v) { return __bfloat162float(v); }
DEVI float round_bf16(float v) { return __bfloat162float(__float2bfloat16_rn(v)); }
DEVI float rcp(float x) { float r; asm("rcp.approx.ftz.f32 %0, %1;" : "=f"(r) : "f"(x)); return r; }
DEVI float ex2(float x) { float r; asm("ex2.approx.ftz.f32 %0, %1;" : "=f"(r) : "f"(x)); return r; }

DEVI void wg_fence() { asm volatile("wgmma.fence.sync.aligned;" ::: "memory"); }
DEVI void wg_commit() { asm volatile("wgmma.commit_group.sync.aligned;" ::: "memory"); }
template <int N> DEVI void wg_wait() { asm volatile("wgmma.wait_group.sync.aligned %0;" ::"n"(N) : "memory"); }
constexpr uint32_t DESC_HI = (1u << 30) | (1024 >> 4);
constexpr uint32_t DESC_HI64 = (2u << 30) | (512 >> 4);
DEVI uint32_t mkdesc(uint32_t saddr, uint32_t lbo) { return ((saddr & 0x3FFFF) >> 4) | ((lbo >> 4) << 16); }

#define R8(b) "%" #b
DEVI void wgmma_n192(float (&d)[96], uint32_t da, uint32_t db, int scale_d) {
  asm volatile(
      "{\n.reg .pred p;\n.reg .b64 da, db;\nsetp.ne.b32 p, %98, 0;\nmov.b64 da, {%96, %100};\nmov.b64 db, {%97, %99};\n"
      "wgmma.mma_async.sync.aligned.m64n192k16.f32.bf16.bf16 "
      "{%0,%1,%2,%3,%4,%5,%6,%7,%8,%9,%10,%11,%12,%13,%14,%15,"
      "%16,%17,%18,%19,%20,%21,%22,%23,%24,%25,%26,%27,%28,%29,%30,%31,"
      "%32,%33,%34,%35,%36,%37,%38,%39,%40,%41,%42,%43,%44,%45,%46,%47,"
      "%48,%49,%50,%51,%52,%53,%54,%55,%56,%57,%58,%59,%60,%61,%62,%63,"
      "%64,%65,%66,%67,%68,%69,%70,%71,%72,%73,%74,%75,%76,%77,%78,%79,"
      "%80,%81,%82,%83,%84,%85,%86,%87,%88,%89,%90,%91,%92,%93,%94,%95}, "
      "da, db, p, 1, 1, 0, 1;\n}"
      : "+f"(d[0]), "+f"(d[1]), "+f"(d[2]), "+f"(d[3]), "+f"(d[4]), "+f"(d[5]), "+f"(d[6]), "+f"(d[7]),
        "+f"(d[8]), "+f"(d[9]), "+f"(d[10]), "+f"(d[11]), "+f"(d[12]), "+f"(d[13]), "+f"(d[14]), "+f"(d[15]),
        "+f"(d[16]), "+f"(d[17]), "+f"(d[18]), "+f"(d[19]), "+f"(d[20]), "+f"(d[21]), "+f"(d[22]), "+f"(d[23]),
        "+f"(d[24]), "+f"(d[25]), "+f"(d[26]), "+f"(d[27]), "+f"(d[28]), "+f"(d[29]), "+f"(d[30]), "+f"(d[31]),
        "+f"(d[32]), "+f"(d[33]), "+f"(d[34]), "+f"(d[35]), "+f"(d[36]), "+f"(d[37]), "+f"(d[38]), "+f"(d[39]),
        "+f"(d[40]), "+f"(d[41]), "+f"(d[42]), "+f"(d[43]), "+f"(d[44]), "+f"(d[45]), "+f"(d[46]), "+f"(d[47]),
        "+f"(d[48]), "+f"(d[49]), "+f"(d[50]), "+f"(d[51]), "+f"(d[52]), "+f"(d[53]), "+f"(d[54]), "+f"(d[55]),
        "+f"(d[56]), "+f"(d[57]), "+f"(d[58]), "+f"(d[59]), "+f"(d[60]), "+f"(d[61]), "+f"(d[62]), "+f"(d[63]),
        "+f"(d[64]), "+f"(d[65]), "+f"(d[66]), "+f"(d[67]), "+f"(d[68]), "+f"(d[69]), "+f"(d[70]), "+f"(d[71]),
        "+f"(d[72]), "+f"(d[73]), "+f"(d[74]), "+f"(d[75]), "+f"(d[76]), "+f"(d[77]), "+f"(d[78]), "+f"(d[79]),
        "+f"(d[80]), "+f"(d[81]), "+f"(d[82]), "+f"(d[83]), "+f"(d[84]), "+f"(d[85]), "+f"(d[86]), "+f"(d[87]),
        "+f"(d[88]), "+f"(d[89]), "+f"(d[90]), "+f"(d[91]), "+f"(d[92]), "+f"(d[93]), "+f"(d[94]), "+f"(d[95])
      : "r"(da), "r"(db), "r"(scale_d), "n"(DESC_HI), "n"(DESC_HI64));
}
DEVI void wgmma_n64(float (&d)[32], uint32_t da, uint32_t db, int scale_d) {
  asm volatile(
      "{\n.reg .pred p;\n.reg .b64 da, db;\nsetp.ne.b32 p, %34, 0;\nmov.b64 da, {%32, %35};\nmov.b64 db, {%33, %35};\n"
      "wgmma.mma_async.sync.aligned.m64n64k16.f32.bf16.bf16 "
      "{%0,%1,%2,%3,%4,%5,%6,%7,%8,%9,%10,%11,%12,%13,%14,%15,"
      "%16,%17,%18,%19,%20,%21,%22,%23,%24,%25,%26,%27,%28,%29,%30,%31}, "
      "da, db, p, 1, 1, 0, 1;\n}"
      : "+f"(d[0]), "+f"(d[1]), "+f"(d[2]), "+f"(d[3]), "+f"(d[4]), "+f"(d[5]), "+f"(d[6]), "+f"(d[7]),
        "+f"(d[8]), "+f"(d[9]), "+f"(d[10]), "+f"(d[11]), "+f"(d[12]), "+f"(d[13]), "+f"(d[14]), "+f"(d[15]),
        "+f"(d[16]), "+f"(d[17]), "+f"(d[18]), "+f"(d[19]), "+f"(d[20]), "+f"(d[21]), "+f"(d[22]), "+f"(d[23]),
        "+f"(d[24]), "+f"(d[25]), "+f"(d[26]), "+f"(d[27]), "+f"(d[28]), "+f"(d[29]), "+f"(d[30]), "+f"(d[31])
      : "r"(da), "r"(db), "r"(scale_d), "n"(DESC_HI));
}

struct C32 { float re, im; };
DEVI C32 csq(C32 a) { return {a.re * a.re - a.im * a.im, 2.f * a.re * a.im}; }
DEVI C32 cmul(C32 a, C32 b) { return {a.re * b.re - a.im * b.im, a.re * b.im + a.im * b.re}; }
DEVI C32 cfresh(float zl, float zi, float m) {
  float mag = ex2(zl * m), ph = zi * m;
  return {mag * __cosf(ph), mag * __sinf(ph)};
}
struct HMul { uint32_t b, bp; };
DEVI HMul mk_mul(float re, float im) { return {pack_f16(re, im), pack_f16(-im, re)}; }
DEVI uint32_t hcmul(uint32_t a, const HMul& m) {
  __half2 ah = *reinterpret_cast<__half2*>(&a);
  __half2 b = *reinterpret_cast<const __half2*>(&m.b), bp = *reinterpret_cast<const __half2*>(&m.bp);
  __half2 r = __hfma2(__high2half2(ah), bp, __hmul2(__low2half2(ah), b));
  return *reinterpret_cast<uint32_t*>(&r);
}
DEVI uint32_t badd(uint32_t a, uint32_t b) {
  __nv_bfloat162 r = __hadd2(*reinterpret_cast<__nv_bfloat162*>(&a), *reinterpret_cast<__nv_bfloat162*>(&b));
  return *reinterpret_cast<uint32_t*>(&r);
}
template <int MU0, int NMU, int DMAX>
DEVI void conv_tail(float (&acc)[16][4], uint32_t p_lane, uint32_t v_base, int back, bool edge, int lane) {
  const int hsel = (lane >> 3) & 1;
  const int row = (lane & 7) + ((lane >> 4) << 3) + PADV - 8 - (back & (hsel ^ 1));
  const uint32_t la = v_base + row * 32 + (((hsel ^ back) ^ ((row >> 2) & 1)) << 4);
  uint32_t M[3][4];
  ldsm_x4_t(M[0], la);
  ldsm_x4_t(M[1], la + 256);
  uint32_t H[2 * NMU];
#pragma unroll
  for (int i = 0; i < 2 * NMU; ++i) H[i ^ 1] = lds32(p_lane + (uint32_t)(MU0 - 1 + i) * 32);
  if (edge) {
    const uint32_t a[4] = {0u, 0u, M[0][0], M[0][1]};
#pragma unroll
    for (int k = 1; k < NMU; ++k) mma_bf16v(acc[MU0 - 2 + 2 * k], a, H[2 * k], H[2 * k + 1]);
  }
#pragma unroll
  for (int delta = -1; delta <= DMAX; ++delta) {
    if (delta + 2 <= DMAX) ldsm_x4_t(M[(delta + 3) % 3], la + (delta + 3) * 256);
#pragma unroll
    for (int k = 0; k < NMU; ++k)
      if (delta + MU0 + 2 * k < 16) mma_bf16v(acc[delta + MU0 + 2 * k], M[(delta + 1) % 3], H[2 * k], H[2 * k + 1]);
  }
}

template <int NB>
DEVI void box_filters(uint32_t sb, uint32_t bars, int idx, int lane) {
  auto swz = [](int k, int pad) { const int r = (k >> 1) + pad; return (uint32_t)(r * 32 + (((k & 1) ^ ((r >> 2) & 1)) << 4)); };
  const uint32_t o0 = swz(lane - 3, 8), o1 = swz(lane - 2, 8), o2 = swz(lane - 1, 8), ow = swz(lane - 2, PADV), oz = swz(lane - 18, PADV);
  const int k = 32 * idx - 2 + lane;
#pragma unroll 1
  for (int c2 = 0; c2 < 4; c2 += NB) {
    uint4 t[NB][3];
#pragma unroll
    for (int b = 0; b < NB; ++b) mbar_wait_long(bars + 8 * (B_UCH + c2 + b), 0);
#pragma unroll
    for (int b = 0; b < NB; ++b) {
      const uint32_t ua = sb + SM_U + (c2 + b) * U_BYTES + idx * 512;
      t[b][0] = lds128(ua + o0); t[b][1] = lds128(ua + o1); t[b][2] = lds128(ua + o2);
    }
#pragma unroll
    for (int b = 0; b < NB; ++b) {
      const uint32_t vb = sb + SM_VV + (c2 + b) * VV_BYTES, aw = vb + idx * 512 + ow;
      const uint32_t E[12] = {t[b][0].x, t[b][0].y, t[b][0].z, t[b][0].w, t[b][1].x, t[b][1].y, t[b][1].z, t[b][1].w,
                              t[b][2].x, t[b][2].y, t[b][2].z, t[b][2].w};
      uint32_t O[8];
#pragma unroll
      for (int j = 0; j < 8; ++j) O[j] = __byte_perm(E[j + 1], E[j + 2], 0x5432);
      uint32_t s3[6], s5[4], s7[4], s9[4];
#pragma unroll
      for (int j = 0; j < 6; ++j) s3[j] = badd(badd(O[j], O[j + 1]), E[j + 2]);
#pragma unroll
      for (int j = 0; j < 4; ++j) {
        s5[j] = badd(s3[j + 2], badd(E[j + 3], E[j + 5]));
        s7[j] = badd(s5[j], badd(O[j + 1], O[j + 4]));
        s9[j] = badd(s7[j], badd(E[j + 2], E[j + 6]));
      }
      if (k < 208) { sts128(aw + VV_U3, s3[0], s3[1], s3[2], s3[3]); sts128(aw + VV_U5, s5[0], s5[1], s5[2], s5[3]); }
      if (k < 144) { sts128(aw + VV_U7, s7[0], s7[1], s7[2], s7[3]); sts128(aw + VV_U9, s9[0], s9[1], s9[2], s9[3]); }
      if (idx == 0 && lane < 16) {
        sts128(vb + oz + VV_U3, 0, 0, 0, 0); sts128(vb + oz + VV_U5, 0, 0, 0, 0);
        sts128(vb + oz + VV_U7, 0, 0, 0, 0); sts128(vb + oz + VV_U9, 0, 0, 0, 0);
      }
    }
  }
}

__global__ void __cluster_dims__(2, 1, 1) __launch_bounds__(NTHREADS, 1)
fused_kernel(const __grid_constant__ Maps maps, const Ptrs p) {
  extern __shared__ __align__(1024) uint8_t smem[];
  const uint32_t sb = s2u(smem);
  const int tid = threadIdx.x, lane = tid & 31;
  const int warp = __shfl_sync(0xffffffffu, tid >> 5, 0);
  const int cta = blockIdx.x;
  const uint32_t rank = cta & 1;
  const int ti = 2 * (cta >> 4) + rank;
  const int tj = (cta >> 1) & 7;
  const int pi = cta >> 3, pj = cta & 7;
  const uint32_t bars = sb + SM_BAR;
#define BAR(i) (bars + 8 * (i))
  const int g = lane >> 2, q = lane & 3;

  auto issue_stage = [&](int ks, int s) {
    const uint32_t st = sb + s * STG_BYTES, fb = BAR(B_FULL + s);
    mbar_expect_tx(fb, STG_BYTES);
    tma_load_2d(st + STG_X, &maps.x, ks * 32, ti * 128, fb);
    tma_load_3d_mc(st + STG_W + rank * 6144, &maps.w, tj * 64, ks * 32 + rank * 16, 0, fb, 3);
  };

  const int kch = warp & 3, krd = warp >> 2;
  float zr, zi, wr, wi;
  unsigned epoch;
  uint32_t r_dskip;
  {
    const size_t po = (size_t)(cta * 4 + kch) * 128 + krd * 32 + lane;
    const uint32_t r_ar = ldg16(p.A_re + po), r_ai = ldg16(p.A_im + po), r_br = ldg16(p.B_re + po), r_bi = ldg16(p.B_im + po);
    const uint32_t r_cr = ldg16(p.C_re + po), r_ci = ldg16(p.C_im + po), r_ldt = ldg16(p.log_dt + cta * 4 + kch);
    epoch = __ldcg(&g_epoch);
    r_dskip = ldg16(p.Dskip + cta * 4 + kch);
    uint4 pt;
    if (tid < 128) pt = __ldg((const uint4*)g_ptab.v + tid);
    if (tid == 384) {
      TS(0);
#pragma unroll
      for (int i = 0; i < B_COUNT; ++i) mbar_init(BAR(i), bar_count(i));
      asm volatile("fence.mbarrier_init.release.cluster;" ::: "memory");
      prefetch_tmap(&maps.x); prefetch_tmap(&maps.w); prefetch_tmap(&maps.u);
    }
    __syncthreads();
    cluster_arrive();
    if (warp >= 12) {
      cluster_wait();
      if (elect_one()) {
        if (warp == 13) {
          mbar_expect_tx(BAR(B_TILE), 16384);
          tma_load_2d(sb + SM_U, &maps.u, tj * 64, ti * 128, BAR(B_TILE));
          prefetch_tmap(&maps.uT); prefetch_tmap(&maps.wo); prefetch_tmap(&maps.o); prefetch_tmap(&maps.yT);
          prefetch_tmap(&maps.out); prefetch_tmap(&maps.outh);
        } else {
          if (warp == 12) TS(61);
          { const int ks = warp == 12 ? 0 : warp - 13; issue_stage(ks, ks); }
        }
      }
      __syncwarp();
    }
    if (tid < 128) sts128(sb + SM_PTAB + tid * 16, pt.x, pt.y, pt.z, pt.w);
    const float dt = round_bf16(expf(bf_lo(r_ldt)));
    zr = dt * bf_lo(r_ar); zi = dt * bf_lo(r_ai);
    const float dbr = dt * bf_lo(r_br), dbi = dt * bf_lo(r_bi), cr = bf_lo(r_cr), ci = bf_lo(r_ci);
    wr = cr * dbr - ci * dbi; wi = cr * dbi + ci * dbr;
  }
  {
    const float mz = __uint_as_float(__reduce_max_sync(0xffffffffu, __float_as_uint(fmaxf(zr, 0.f))));
    const int E = min(max((int)(__reduce_max_sync(0xffffffffu, __float_as_uint(fmaxf(fabsf(wr), fabsf(wi)))) >> 23), 1), 252);
    const float sc = __int_as_float((253 - E) << 23), inv = __int_as_float((E + 1) << 23);
    const float zl = (zr - mz) * 1.4426950408889634f;
    const uint32_t tb = sb + SM_VV + kch * VV_BYTES + krd * KG_BYTES;
    const uint32_t sta = tb + (((lane >> 2) << 4) | ((lane & 3) << 2));
    auto put = [&](int r, uint32_t v) { sts32((sta ^ ((r & 7) << 4)) + r * 128, v); };
    const uint32_t lda = tb + ((lane & 7) + (((lane >> 3) & 1) << 3)) * 128;
    const uint32_t ldb = tb + ((lane & 7) + ((lane >> 4) << 3)) * 128;
#define STG_POS 1
#define PF_POS 1
    if (STG_POS == 0 && warp >= 14 && elect_one()) { issue_stage(warp - 11, warp - 11); issue_stage(warp - 9, warp - 9); }
    if (PF_POS == 0 && warp >= 14 && elect_one()) {
      if (warp == 14) l2_prefetch((const char*)p.wqkv + 224 * 3072 + cta * 6912, 6912);
      else l2_prefetch((const char*)p.x + (size_t)cta * 16384, 16384);
    }
    __syncwarp();
    C32 e1 = cfresh(zl, zi, 1.f), e2 = csq(e1), e4 = csq(e2), e8 = csq(e4);
    C32 e16 = cfresh(zl, zi, 16.f), e32 = csq(e16), e64 = csq(e32), e128 = csq(e64);
    C32 e256 = cfresh(zl, zi, 256.f), e512 = csq(e256), e1024 = csq(e512), e768 = cmul(e512, e256);
    uint32_t XA[2][4][4];
    {
      const HMul m16 = mk_mul(e16.re, e16.im), m32 = mk_mul(e32.re, e32.im), m64 = mk_mul(e64.re, e64.im);
      const HMul m128 = mk_mul(e128.re, e128.im);
      uint32_t X[16];
      X[0] = 0x00003c00u; X[1] = pack_f16(e8.re, e8.im); X[2] = m16.b; X[4] = m32.b; X[8] = m64.b;
      X[3] = hcmul(X[1], m16); X[5] = hcmul(X[1], m32); X[6] = hcmul(X[2], m32); X[7] = hcmul(X[3], m32);
#pragma unroll
      for (int r = 1; r < 8; ++r) X[8 + r] = hcmul(X[r], m64);
#pragma unroll
      for (int h = 0; h < 2; ++h) {
#pragma unroll
        for (int r = 0; r < 16; ++r) put(r, h == 0 ? X[r] : r == 0 ? m128.b : hcmul(X[r], m128));
        __syncwarp();
#pragma unroll
        for (int k = 0; k < 4; ++k) ldsm_x4(XA[h][k], lda + (((2 * k + (lane >> 4)) ^ (lane & 7)) << 4));
        __syncwarp();
      }
    }
    if (STG_POS == 1 && warp >= 14 && elect_one()) { issue_stage(warp - 11, warp - 11); issue_stage(warp - 9, warp - 9); }
    if (PF_POS == 1 && warp >= 14 && elect_one()) {
      if (warp == 14) l2_prefetch((const char*)p.wqkv + 224 * 3072 + cta * 6912, 6912);
      else l2_prefetch((const char*)p.x + (size_t)cta * 16384, 16384);
    }
    __syncwarp();
    float D[2][3][4];
#pragma unroll
    for (int t = 0; t < 6; ++t) D[t / 3][t % 3][0] = D[t / 3][t % 3][1] = D[t / 3][t % 3][2] = D[t / 3][t % 3][3] = 0.f;
    auto contract = [&](int t0, int nt) {
      __syncwarp();
#pragma unroll
      for (int k = 0; k < 4; ++k) {
        uint32_t b[4];
        ldsm_x4(b, ldb + (((2 * k + ((lane >> 3) & 1)) ^ (lane & 7)) << 4));
#pragma unroll
        for (int h = 0; h < 2; ++h) {
          mma_f16(D[h][t0], XA[h][k], b[0], b[1]);
          if (nt == 2) mma_f16(D[h][t0 + 1], XA[h][k], b[2], b[3]);
        }
      }
      __syncwarp();
    };
    const HMul c1 = mk_mul(e1.re, -e1.im), c2 = mk_mul(e2.re, -e2.im), c4 = mk_mul(e4.re, -e4.im);
    const HMul c256 = mk_mul(e256.re, -e256.im), c512 = mk_mul(e512.re, -e512.im), c768 = mk_mul(e768.re, -e768.im);
    const HMul c1024 = mk_mul(e1024.re, -e1024.im);
    uint32_t W[8];
    W[0] = pack_f16(wr * sc, -wi * sc);
    W[1] = hcmul(W[0], c1); W[2] = hcmul(W[0], c2); W[3] = hcmul(W[1], c2);
    W[4] = hcmul(W[0], c4); W[5] = hcmul(W[1], c4); W[6] = hcmul(W[2], c4); W[7] = hcmul(W[3], c4);
#pragma unroll
    for (int i = 0; i < 8; ++i) put(i, W[i]);
#pragma unroll
    for (int i = 0; i < 4; ++i) put(8 + i, hcmul(W[2 * i], c256));
    put(12, hcmul(W[0], c512)); put(13, hcmul(W[4], c512)); put(14, hcmul(W[0], c768)); put(15, hcmul(W[4], c768));
    if (PF_POS == 2 && warp >= 14 && elect_one()) {
      if (warp == 14) l2_prefetch((const char*)p.wqkv + 224 * 3072 + cta * 6912, 6912);
      else l2_prefetch((const char*)p.x + (size_t)cta * 16384, 16384);
    }
    contract(0, 2);
    const uint32_t v0 = hcmul(W[0], c1024);
    put(0, v0); put(1, hcmul(v0, c256)); put(2, hcmul(v0, c512)); put(3, hcmul(v0, c768)); put(4, hcmul(v0, c1024));
    contract(2, 1);
    const uint32_t a = tb + (g * 24 + 2 * q) * 4;
#pragma unroll
    for (int t = 0; t < 6; ++t) {
      const float(&d)[4] = D[t / 3][t % 3];
      sts_f32x2(a + (t / 3) * 1536 + (t % 3) * 32, d[0], d[1]);
      sts_f32x2(a + (t / 3) * 1536 + (t % 3) * 32 + 768, d[2], d[3]);
    }
    if (lane == 0) sts_f32(tb + 3072, inv);
    if (mz > 0.f) {
      __syncwarp();
#pragma unroll 1
      for (int i = lane; i < 768; i += 32) {
        const int r = i / 24, y = i - 24 * r;
        sts_f32(tb + i * 4, lds_f32(tb + i * 4) * ex2(mz * 1.4426950408889634f * (koff(y) + 8 * r)));
      }
    }
  }
  if (tid == 0) TS(2);
  if (warp < 12) cluster_wait();
  __syncthreads();

  if (warp < 4) {
#define A_REGS 200
    asm volatile("setmaxnreg.inc.sync.aligned.u32 %0;" ::"n"(A_REGS));
    if (tid == 0) TS(34);
    const int d = cta * 4 + warp;
    const uint32_t vv = sb + SM_VV + warp * VV_BYTES;
    const uint32_t ub = sb + SM_U + warp * U_BYTES;
    const uint32_t pb = sb + SM_P + warp * P_BYTES;
    const float dskip = bf_lo(r_dskip);
#pragma unroll 1
    for (int pass = 0; pass < 2; ++pass) {
      if (pass == 1) {
        const uint32_t kf = vv;
        const float i0 = lds_f32(kf + 3072), i1 = lds_f32(kf + KG_BYTES + 3072), i2 = lds_f32(kf + 2 * KG_BYTES + 3072);
        const float i3 = lds_f32(kf + 3 * KG_BYTES + 3072);
#pragma unroll 2
        for (int i = 0; i < 6; ++i) {
          const uint32_t a = kf + (i * 32 + lane) * 16;
          const uint4 x0 = lds128(a), x1 = lds128(a + KG_BYTES), x2 = lds128(a + 2 * KG_BYTES), x3 = lds128(a + 3 * KG_BYTES);
          auto s4 = [&](uint32_t a0, uint32_t a1, uint32_t a2, uint32_t a3) {
            return __float_as_uint(fmaf(__uint_as_float(a0), i0, __uint_as_float(a1) * i1) +
                                   fmaf(__uint_as_float(a2), i2, __uint_as_float(a3) * i3));
          };
          sts128(a, s4(x0.x, x1.x, x2.x, x3.x), s4(x0.y, x1.y, x2.y, x3.y), s4(x0.z, x1.z, x2.z, x3.z), s4(x0.w, x1.w, x2.w, x3.w));
        }
        __syncwarp();
        const float k1024 = lds_f32(kf + kidx_c(1024) * 4);
        if (lane == 0) {
          sts_f32(kf + SL_ZERO * 4, 0.f);
          sts_f32(kf + SL_510 * 4, lds_f32(kf + kidx_c(510) * 4) - lds_f32(kf + kidx_c(512) * 4));
          sts_f32(kf + SL_0 * 4, lds_f32(kf) + dskip);
        }
        __syncwarp();
        if (tid == 0) TS(36);
        mbar_wait_long(BAR(B_PFREE), 0);
        if (tid == 0) TS(37);
        {
          float prev = 0.f;
#pragma unroll 1
          for (int i0 = 0; i0 < 16; i0 += 4) {
            uint32_t e[4];
            float a[4], b[4];
#pragma unroll
            for (int i = 0; i < 4; ++i) e[i] = lds32(sb + SM_PTAB + ((i0 + i) * 32 + lane) * 4);
#pragma unroll
            for (int i = 0; i < 4; ++i) { a[i] = lds_f32(kf + (e[i] & 0xffff)); b[i] = lds_f32(kf + (e[i] >> 16)); }
#pragma unroll
            for (int i = 0; i < 4; ++i) {
              const uint32_t w = pb + (31 * lane + 2 * (i0 + i)) * 4;
              if (i0 + i > 0) sts32(w - 4, pack_bf16(a[i], prev));
              sts32(w, pack_bf16(b[i], a[i]));
              prev = b[i];
            }
          }
        }
        __syncwarp();
        if (lane == 0) TS(4);
        const int gq = g - 2 * q;
        uint32_t h127, h128;
        {
          const uint32_t kf2 = pack_bf16(k1024, k1024) ^ 0x80008000u;
          h127 = (gq == 4 ? 0x0000ffffu : gq == 5 ? 0xffffffffu : gq == 6 ? 0xffff0000u : 0u) & kf2;
          h128 = (gq == -4 ? 0x0000ffffu : gq == -3 ? 0xffffffffu : gq == -2 ? 0xffff0000u : 0u) & kf2;
        }
        bar_arrive(7, 384);
        if (lane == 0) TS(6);
        bar_sync(4, 384);
        mbar_wait_long(BAR(B_UCH + warp), 0);
        if (lane == 0) TS(7);
        float acc[16][4];
#pragma unroll
        for (int i = 0; i < 16; ++i) { acc[i][0] = acc[i][1] = acc[i][2] = acc[i][3] = 0.f; }
        {
          const uint32_t pd_lane = pb + (PD_OFF + 16 + gq) * 4;
          const int prow0 = 8 + (lane & 7) + ((lane >> 4) << 3), hs = (lane >> 3) & 1;
          const uint32_t zero = (uint32_t)cta >> 20;
          uint32_t B[2][4][4];
          uint32_t A[4][4];
          const uint32_t la0 = ub + prow0 * 32 + ((hs ^ ((prow0 >> 2) & 1)) << 4);
#pragma unroll
          for (int m2 = 0; m2 < 4; ++m2) ldsm_x4(B[0][m2], la0 + m2 * 512);
#pragma unroll
          for (int i = 0; i < 4; ++i) {
            const uint32_t a = pd_lane + i * 512;
            A[i][0] = lds32(a); A[i][1] = lds32(a + 32); A[i][2] = lds32(a - 32); A[i][3] = lds32(a + zero);
          }
          uint32_t la = la0;
#define UNR_RHO 4
#define UNR_TAIL 4
          constexpr int unr_rho = UNR_RHO, unr_tail = UNR_TAIL;
#pragma unroll unr_rho
          for (int rho = 0; rho < 8; ++rho) {
#pragma unroll
            for (int m2 = 0; m2 < 4; ++m2) ldsm_x4(B[1][m2], la + (4 + m2) * 512);
#pragma unroll
            for (int i = 0; i < 4; ++i)
#pragma unroll
              for (int m = 0; m < 8; ++m) mma_bf16v(acc[m + i], A[i], B[0][m >> 1][2 * (m & 1)], B[0][m >> 1][2 * (m & 1) + 1]);
            const int prow = prow0 - min(rho + 1, 7);
            la = ub + prow * 32 + ((hs ^ ((prow >> 2) & 1)) << 4);
#pragma unroll
            for (int m2 = 0; m2 < 4; ++m2) ldsm_x4(B[0][m2], la + m2 * 512);
            const uint32_t pa = pd_lane + (rho + 1) * 64;
#pragma unroll
            for (int i = 0; i < 4; ++i) {
#pragma unroll
              for (int m = 0; m < 8 - i; ++m)
                mma_bf16v(acc[8 + m + i], A[i], B[1][m >> 1][2 * (m & 1)], B[1][m >> 1][2 * (m & 1) + 1]);
              A[i][0] = lds32(pa + i * 512); A[i][1] = lds32(pa + i * 512 + 32); A[i][2] = lds32(pa + i * 512 - 32);
              A[i][3] = lds32(pa + i * 512 + zero);
            }
          }
          if (lane == 0) TS(40);
          {
            uint32_t b8[4];
            ldsm_x4(b8, la + 4 * 512);
            const uint32_t h63 = lds32(pd_lane + 63 * 32), h64 = lds32(pd_lane + 64 * 32);
            const uint32_t a63[4] = {0u, h127, 0u, 0u}, a32[4] = {h64, 0u, h63, h64}, a64[4] = {h128, 0u, h127, h128};
#pragma unroll
            for (int m2 = 0; m2 < 4; ++m2) ldsm_x4(B[1][m2], la0 + m2 * 512);
#pragma unroll
            for (int m = 0; m < 8; ++m) mma_bf16v(acc[m + 7], a63, B[0][m >> 1][2 * (m & 1)], B[0][m >> 1][2 * (m & 1) + 1]);
#pragma unroll
            for (int m2 = 0; m2 < 2; ++m2) ldsm_x4(B[0][m2], la0 + (4 + m2) * 512);
#pragma unroll
            for (int m = 0; m < 8; ++m) mma_bf16v(acc[m + 4], a32, B[1][m >> 1][2 * (m & 1)], B[1][m >> 1][2 * (m & 1) + 1]);
            mma_bf16v(acc[15], a63, b8[0], b8[1]);
#pragma unroll
            for (int m = 0; m < 8; ++m) mma_bf16v(acc[m + 8], a64, B[1][m >> 1][2 * (m & 1)], B[1][m >> 1][2 * (m & 1) + 1]);
#pragma unroll
            for (int m = 0; m < 4; ++m) mma_bf16v(acc[m + 12], a32, B[0][m >> 1][2 * (m & 1)], B[0][m >> 1][2 * (m & 1) + 1]);
          }
          if (lane == 0) TS(41);
          bar_sync(5, 384);
#pragma unroll unr_tail
          for (int v = 0; v < 4; ++v)
            conv_tail<4, 3, 11>(acc, pb + (P2_OFF + 56 * v + gq - 16) * 4, vv + ((v & 1) ? VV_U3 : VV_U5), v >> 1, v == 0, lane);
          if (lane == 0) TS(42);
#pragma unroll unr_tail
          for (int pi = 0; pi < 2; ++pi)
            conv_tail<8, 5, 7>(acc, pb + (P3_OFF + 88 * pi + gq - 48) * 4, vv + (pi ? VV_U7 : VV_U9), pi, pi == 0, lane);
        }
        if (lane == 0) TS(8);
        __syncwarp();
        {
          const int mt = lane >> 3;
          const uint32_t a = pb + (128 * (mt >> 1) + 16 * (lane & 7) + 8 * (mt & 1)) * 2;
#pragma unroll
          for (int ab = 0; ab < 16; ab += 2)
            stsm_x4_t(a + ab * 256, pack_bf16(acc[ab][0], acc[ab][1]), pack_bf16(acc[ab][2], acc[ab][3]),
                      pack_bf16(acc[ab + 1][0], acc[ab + 1][1]), pack_bf16(acc[ab + 1][2], acc[ab + 1][3]));
        }
        fence_async_smem();
        __syncwarp();
        if (lane < 2) mbar_arrive_cluster(BAR(B_CONVD), lane);
        __syncwarp();
        cluster_arrive();
        bar_arrive(3, 384);
        if (elect_one()) {
          bulk_store(p.yT + (size_t)d * 2048, pb, 4096);
          bulk_commit();
          bulk_wait0();
          red_relaxed_add(&g_cnt[(C_Y + (cta >> 4)) * 32], 1);
          TS(9);
        }
        bar_sync(2, 128);
        if (warp == 0 && elect_one()) {
          wait_counter(&g_cnt[(C_Y + tj) * 32], (epoch + 1) * 64);
          TS(28);
          mbar_expect_tx(BAR(B_TILE), 16384);
          tma_load_2d(sb + SM_U, &maps.yT, ti * 128, tj * 64, BAR(B_TILE));
          tma_load_2d(sb + SM_U + 8192, &maps.yT, ti * 128 + 64, tj * 64, BAR(B_TILE));
        }
        __syncwarp();
      }
      mbar_wait_long(BAR(B_TILE), pass);
      if (lane == 0) TS(26 + 3 * pass);
      {
        const int m = lane >> 3, r = lane & 7;
#pragma unroll 2
        for (int it = 0; it < 8; ++it) {
          const int tb = warp * 4 + (it >> 1), cb = (it & 1) * 4 + m;
          const uint32_t at = (tb * 8 + r) * 128 + ((cb ^ r) << 4);
          const uint32_t ac = (tb >> 3) * 8192 + (cb * 8 + r) * 128 + (((tb & 7) ^ (pass ? 0 : tb >> 3) ^ r) << 4);
          uint32_t v[4];
          ldsm_x4_t(v, sb + SM_U + (pass ? ac : at));
          stsm_x4(sb + SM_P + (pass ? at : ac), v[0], v[1], v[2], v[3]);
        }
      }
      if (pass == 0 && tid == 0) TS(35);
      fence_async_smem();
      if (pass == 0) {
        bar_arrive(6, 160);
      } else {
        bar_sync(2, 128);
        if (warp == 0 && elect_one()) {
          tma_store_2d(&maps.out, sb + SM_P, 64 * tj, 128 * ti);
          bulk_commit();
          bulk_wait_read0();
          TS(30);
        }
      }
    }
  } else if (warp < 12) {
    const int w8 = warp - 4;
    const int row = w8 * 16 + (lane & 7) + (((lane >> 3) & 1) << 3);
    uint32_t pq[16];
    {
      float acc[96];
#pragma unroll 1
      for (int ks = 0, s = 0, ph = 0; ks < 16; ++ks) {
        mbar_wait(BAR(B_FULL + s), ph);
        if (tid == 128 && !(ks & 1)) TSR(16, ks == 0 ? 16 : 9 + (ks >> 1) + (ks > 12 ? 43 : 0));
        const uint32_t st = sb + s * STG_BYTES;
        const uint32_t da = mkdesc(st + STG_X + (w8 >> 2) * 4096, 16);
        const uint32_t db = mkdesc(st + STG_W, 2048);
        wg_fence();
        wgmma_n192(acc, da, db, ks != 0);
        wgmma_n192(acc, da + 2, db + 384, 1);
        wg_commit();
        const uint32_t eprev = BAR(B_EMPTY + (s == 0 ? NSTG - 1 : s - 1));
        if (++s == NSTG) { s = 0; ph ^= 1; }
        if (ks > 0) {
          wg_wait<1>();
          if (lane < 2) mbar_arrive_cluster(eprev, lane);
        }
      }
      wg_wait<0>();
      bar_arrive(4, 384);
      if (tid == 128) TS(17);
      auto phi2 = [](float a, float b) -> uint32_t {
        const uint32_t x = pack_bf16(a, b);
        const uint32_t e = pack_bf16(ex2(a * 1.4426950408889634f), ex2(b * 1.4426950408889634f));
        const uint32_t m = __hgt2_mask(*reinterpret_cast<const __nv_bfloat162*>(&x), __floats2bfloat162_rn(0.f, 0.f));
        return badd((badd(x, 0x3f803f80u) & m) | (e & ~m), 0x35863586u);
      };
      uint32_t pk[16];
#pragma unroll
      for (int i = 0; i < 16; ++i) pk[i] = phi2(acc[32 + 2 * i], acc[33 + 2 * i]);
      if (tid == 128) TS(53);
      bar_sync(1, 256);
#pragma unroll
      for (int i = 0; i < 8; i += 2) {
        const uint32_t off = row * 128 + (((i + (lane >> 4)) ^ (row & 7)) << 4);
        stsm_x4(sb + SM_PK + off, pk[2 * i], pk[2 * i + 1], pk[2 * i + 2], pk[2 * i + 3]);
        stsm_x4(sb + SM_VS + off, pack_bf16(acc[64 + 4 * i], acc[65 + 4 * i]), pack_bf16(acc[66 + 4 * i], acc[67 + 4 * i]),
                pack_bf16(acc[68 + 4 * i], acc[69 + 4 * i]), pack_bf16(acc[70 + 4 * i], acc[71 + 4 * i]));
      }
      bar_sync(1, 256);
      {
        const int hh = w8 >> 1, dtile = w8 & 1;
        float kv[2][4] = {{0.f, 0.f, 0.f, 0.f}, {0.f, 0.f, 0.f, 0.f}}, zz[2][4] = {{0.f, 0.f, 0.f, 0.f}, {0.f, 0.f, 0.f, 0.f}};
        const int m = lane >> 3;
        const uint32_t aa = sb + SM_VS + ((lane & 7) + ((m >> 1) << 3)) * 128 + (((2 * hh + (m & 1)) ^ (lane & 7)) << 4);
        const uint32_t ab = sb + SM_PK + (lane & 15) * 128 + (((2 * hh + dtile) ^ (lane & 7)) << 4);
#pragma unroll
        for (int ks = 0; ks < 8; ++ks) {
          uint32_t a[4], b0, b1;
          ldsm_x4_t(a, aa + ks * 2048);
          ldsm_x2_t(b0, b1, ab + ks * 2048);
          mma_bf16(kv[ks & 1], a[0], a[1], a[2], a[3], b0, b1);
          mma_bf16(zz[ks & 1], 0x3f803f80u, 0x3f803f80u, 0x3f803f80u, 0x3f803f80u, b0, b1);
        }
        const uint32_t kp = sb + SM_KV + hh * 1088;
        sts128(kp + dtile * 512 + lane * 16, __float_as_uint(kv[0][0] + kv[1][0]), __float_as_uint(kv[0][1] + kv[1][1]),
               __float_as_uint(kv[0][2] + kv[1][2]), __float_as_uint(kv[0][3] + kv[1][3]));
        if (g == 0) sts_f32x2(kp + 1024 + dtile * 32 + q * 8, zz[0][0] + zz[1][0], zz[0][1] + zz[1][1]);
        fence_async_smem();
        __syncwarp();
        if (lane == 0) mbar_arrive(BAR(B_KVP));
        if (tid == 128) TS(55);
      }
#pragma unroll
      for (int i = 0; i < 16; ++i) pq[i] = phi2(acc[2 * i], acc[2 * i + 1]);
    }
    if (tid == 128) TS(56);
    if (warp == 4) mbar_wait_long(BAR(B_KVF), 0);
    bar_sync(1, 256);
    if (tid == 128) TS(19);
    {
      uint32_t kb[4][6];
#pragma unroll
      for (int h = 0; h < 4; ++h) {
        const uint32_t kp = sb + SM_KV + h * 1088;
        const uint4 k0 = lds128(kp + lane * 16), k1 = lds128(kp + 512 + lane * 16);
        const uint32_t za = kp + 1024 + q * 8;
        auto pk2 = [](uint32_t x, uint32_t y) { return pack_bf16(__uint_as_float(x), __uint_as_float(y)); };
        kb[h][0] = pk2(k0.x, k0.y); kb[h][1] = pk2(k1.x, k1.y); kb[h][2] = pk2(k0.z, k0.w); kb[h][3] = pk2(k1.z, k1.w);
        kb[h][4] = pack_bf16(lds_f32(za), lds_f32(za + 4)); kb[h][5] = pack_bf16(lds_f32(za + 32), lds_f32(za + 36));
      }
#pragma unroll
      for (int h = 0; h < 4; ++h) {
        float n0[4] = {0.f, 0.f, 0.f, 0.f}, n1[4] = {0.f, 0.f, 0.f, 0.f}, dn[4] = {0.f, 0.f, 0.f, 0.f};
        mma_bf16(n0, pq[4 * h], pq[4 * h + 1], pq[4 * h + 2], pq[4 * h + 3], kb[h][0], kb[h][1]);
        mma_bf16(n1, pq[4 * h], pq[4 * h + 1], pq[4 * h + 2], pq[4 * h + 3], kb[h][2], kb[h][3]);
        mma_bf16(dn, pq[4 * h], pq[4 * h + 1], pq[4 * h + 2], pq[4 * h + 3], kb[h][4], kb[h][5]);
        const float r0 = rcp(dn[0] + 1e-6f), r1 = rcp(dn[2] + 1e-6f);
        stsm_x4(sb + SM_QS + row * 128 + (((2 * h + (lane >> 4)) ^ (row & 7)) << 4),
                pack_bf16(n0[0] * r0, n0[1] * r0), pack_bf16(n0[2] * r1, n0[3] * r1),
                pack_bf16(n1[0] * r0, n1[1] * r0), pack_bf16(n1[2] * r1, n1[3] * r1));
      }
    }
    fence_async_smem();
    __syncwarp();
    if (lane == 0) mbar_arrive(BAR(B_OST));
    if (tid == 128) TS(57);
    bar_sync(7, 384);
    if (w8 < 7) box_filters<4>(sb, bars, w8, lane);
    bar_arrive(5, 384);
    if (tid == 128) TS(6);
    if (warp == 4) mbar_wait_long(BAR(B_WO), 0);
    bar_sync(3, 384);
    {
      float o[32];
#pragma unroll 1
      for (int c = 0; c < 8; ++c) {
        mbar_wait_long(BAR(B_RF + c), 0);
        if (tid == 128) TSR(22, c == 0 ? 22 : 43 + c);
        const uint32_t slot = c < 4 ? SM_QS + c * 16384 : c < 7 ? SM_VV + (c - 4) * 16384 : SM_QS;
        const uint32_t da = mkdesc(sb + slot + (w8 >> 2) * 8192, 16);
        const uint32_t db = mkdesc(sb + SM_WO + c * 8192, 8192);
        wg_fence();
#pragma unroll
        for (int k = 0; k < 4; ++k) wgmma_n64(o, da + 2 * k, db + 128 * k, (c | k) != 0);
        wg_commit();
        if (c == 1) {
          wg_wait<1>();
          if (lane < 2) mbar_arrive_cluster(BAR(B_RE), lane);
          __syncwarp();
          cluster_arrive();
        }
      }
      wg_wait<0>();
      if (tid == 128) TS(51);
#pragma unroll
      for (int i = 0; i < 8; i += 2)
        stsm_x4(sb + SM_BOUT + row * 128 + (((i + (lane >> 4)) ^ (row & 7)) << 4), pack_bf16(o[4 * i], o[4 * i + 1]),
                pack_bf16(o[4 * i + 2], o[4 * i + 3]), pack_bf16(o[4 * i + 4], o[4 * i + 5]), pack_bf16(o[4 * i + 6], o[4 * i + 7]));
      fence_async_smem();
      bar_sync(8 + (w8 >> 2), 128);
      if ((w8 & 3) == 0 && elect_one()) {
        tma_store_2d(&maps.outh, sb + SM_BOUT + (w8 >> 2) * 8192, 512 + 64 * pj, 128 * pi + (w8 >> 2) * 64);
        bulk_commit();
        bulk_wait_read0();
        TS(23);
      }
    }
  } else {
    asm volatile("setmaxnreg.dec.sync.aligned.u32 40;");
    if (warp == 12) {
      if (elect_one()) {
#pragma unroll 1
        for (int ks = NSTG, s = 0, ph = 0; ks < 16; ++ks) {
          mbar_wait(BAR(B_EMPTY + s), ph);
          issue_stage(ks, s);
          if (ks == NSTG) l2_prefetch((const char*)p.wo + (size_t)cta * 4096, 4096);
          if (++s == NSTG) { s = 0; ph ^= 1; }
        }
        mbar_wait(BAR(B_EMPTY + 6), 1);
        mbar_expect_tx(BAR(B_WO), 65536);
        tma_load_2d(sb + SM_WO, &maps.wo, pj * 64, 0, BAR(B_WO));
        tma_load_2d(sb + SM_WO + 32768, &maps.wo, pj * 64, 256, BAR(B_WO));
        float* kvg = &g_kv[epoch & 1][tj][0];
        mbar_wait_long(BAR(B_KVP), 0);
        bulk_reduce_add_f32(kvg, sb + SM_KV, 4352);
        bulk_commit();
        bulk_wait0();
        red_relaxed_add(&g_cnt[(C_KV + tj) * 32], 1);
        TS(18);
        wait_counter(&g_cnt[(C_KV + tj) * 32], (epoch + 1) * 16);
        mbar_expect_tx(BAR(B_KVF), 4352);
        bulk_load(sb + SM_KV, kvg, 4352, BAR(B_KVF));
        mbar_wait_long(BAR(B_OST), 0);
        tma_store_2d(&maps.o, sb + SM_QS, tj * 64, ti * 128);
        tma_store_2d(&maps.o, sb + SM_QS + 8192, tj * 64, ti * 128 + 64);
        bulk_commit();
        bulk_wait0();
        red_relaxed_add(&g_cnt[(C_O + ti) * 32], 1);
        TS(20);
        mbar_arrive_cluster(BAR(B_SLOT), 0);
        mbar_arrive_cluster(BAR(B_SLOT), 1);
        wait_counter(&g_cnt[(C_O + pi) * 32], (epoch + 1) * 8);
        if (cta == 0) g_epoch = epoch + 1;
        mbar_wait(BAR(B_SLOT), 0);
        TS(21);
#pragma unroll 1
        for (int c = 0; c < 8; ++c) {
          if (c == 4) mbar_wait_long(BAR(B_CONVD), 0);
          if (c == 7) mbar_wait(BAR(B_RE), 0);
          const uint32_t slot = c < 4 ? SM_QS + c * 16384 : c < 7 ? SM_VV + (c - 4) * 16384 : SM_QS;
          mbar_expect_tx(BAR(B_RF + c), 16384);
          tma_load_2d_mc(sb + slot + rank * 8192, &maps.o, c * 64, pi * 128 + rank * 64, BAR(B_RF + c), 3);
        }
      }
    } else if (warp == 13) {
      bar_sync(6, 160);
      sts128(sb + SM_U + (lane >> 4) * U_BYTES + (lane & 15) * 16, 0, 0, 0, 0);
      sts128(sb + SM_U + (2 + (lane >> 4)) * U_BYTES + (lane & 15) * 16, 0, 0, 0, 0);
      __syncwarp();
      if (elect_one()) {
        tma_store_2d(&maps.uT, sb + SM_P, ti * 128, tj * 64);
        tma_store_2d(&maps.uT, sb + SM_P + 8192, ti * 128 + 64, tj * 64);
        bulk_commit();
        bulk_wait_read0();
        mbar_arrive(BAR(B_PFREE));
        bulk_wait0();
        red_relaxed_add(&g_cnt[(C_U + tj) * 32], 1);
        TS(27);
        wait_counter(&g_cnt[(C_U + (cta >> 4)) * 32], (epoch + 1) * 16);
#pragma unroll 1
        for (int c = 0; c < 4; ++c) {
          mbar_expect_tx(BAR(B_UCH + c), 4096);
          bulk_load(sb + SM_U + c * U_BYTES + 256, p.uT + (size_t)(cta * 4 + c) * 2048, 4096, BAR(B_UCH + c));
        }
        TS(3);
      }
      __syncwarp();
      if (ti == 0) {
        float4* z = (float4*)&g_kv[(epoch & 1) ^ 1][tj][0];
#pragma unroll 1
        for (int i = lane; i < 272; i += 32) z[i] = make_float4(0.f, 0.f, 0.f, 0.f);
      }
    }
  }
  __syncwarp();
  if (warp >= 12) cluster_arrive();
  cluster_wait();
  if (tid == 0) TS(31);
#undef BAR
}

typedef CUresult (*EncodeFn)(CUtensorMap*, CUtensorMapDataType, cuuint32_t, void*, const cuuint64_t*, const cuuint64_t*,
                             const cuuint32_t*, const cuuint32_t*, CUtensorMapInterleave, CUtensorMapSwizzle,
                             CUtensorMapL2promotion, CUtensorMapFloatOOBfill);

static void make_map(EncodeFn enc, CUtensorMap* m, const void* base, uint64_t inner, uint64_t outer, uint32_t box_in,
                     uint32_t box_out, CUtensorMapSwizzle swz = CU_TENSOR_MAP_SWIZZLE_128B) {
  cuuint64_t gd[2] = {inner, outer};
  cuuint64_t gs[1] = {inner * 2};
  cuuint32_t bd[2] = {box_in, box_out};
  cuuint32_t es[2] = {1, 1};
  enc(m, CU_TENSOR_MAP_DATA_TYPE_BFLOAT16, 2, const_cast<void*>(base), gd, gs, bd, es, CU_TENSOR_MAP_INTERLEAVE_NONE,
      swz, CU_TENSOR_MAP_L2_PROMOTION_L2_128B, CU_TENSOR_MAP_FLOAT_OOB_FILL_NONE);
}

}

extern "C" void kernel_launch(void* const* d_in, const int* in_sizes, int n_in, void* d_out, int out_size) {
  using namespace s4la;
  (void)in_sizes; (void)n_in; (void)out_size;
  static EncodeFn enc = nullptr;
  static void *uT = nullptr, *yT = nullptr, *oS = nullptr;
  if (!enc) {
    void* fn = nullptr;
    cudaDriverEntryPointQueryResult qr;
    cudaGetDriverEntryPoint("cuTensorMapEncodeTiled", &fn, cudaEnableDefault, &qr);
    enc = (EncodeFn)fn;
    cudaGetSymbolAddress(&uT, g_uT);
    cudaGetSymbolAddress(&yT, g_yT);
    cudaGetSymbolAddress(&oS, g_o);
    cudaFuncSetAttribute(fused_kernel, cudaFuncAttributeMaxDynamicSharedMemorySize, SM_TOTAL);
  }
  const __nv_bfloat16* const* in = (const __nv_bfloat16* const*)d_in;
  Maps maps;
  make_map(enc, &maps.x, in[9], 512, 2048, 32, 128, CU_TENSOR_MAP_SWIZZLE_64B);
  {
    cuuint64_t gd[3] = {512, 512, 3};
    cuuint64_t gs[2] = {3072, 1024};
    cuuint32_t bd[3] = {64, 16, 3};
    cuuint32_t es[3] = {1, 1, 1};
    enc(&maps.w, CU_TENSOR_MAP_DATA_TYPE_BFLOAT16, 3, const_cast<__nv_bfloat16*>(in[10]), gd, gs, bd, es,
        CU_TENSOR_MAP_INTERLEAVE_NONE, CU_TENSOR_MAP_SWIZZLE_128B, CU_TENSOR_MAP_L2_PROMOTION_L2_128B,
        CU_TENSOR_MAP_FLOAT_OOB_FILL_NONE);
  }
  make_map(enc, &maps.wo, in[11], 512, 512, 64, 256);
  make_map(enc, &maps.u, in[0], 512, 2048, 64, 128);
  make_map(enc, &maps.uT, uT, 2048, 512, 64, 64);
  make_map(enc, &maps.yT, yT, 2048, 512, 64, 64);
  make_map(enc, &maps.o, oS, 512, 2048, 64, 64);
  make_map(enc, &maps.out, d_out, 1024, 2048, 64, 128);
  make_map(enc, &maps.outh, d_out, 1024, 2048, 64, 64);
  Ptrs p;
  p.A_re = in[1]; p.A_im = in[2]; p.B_re = in[3]; p.B_im = in[4]; p.C_re = in[5]; p.C_im = in[6];
  p.log_dt = in[7]; p.Dskip = in[8]; p.x = in[9]; p.wqkv = in[10]; p.wo = in[11];
  p.uT = (__nv_bfloat16*)uT; p.yT = (__nv_bfloat16*)yT;
  fused_kernel<<<NCTA, NTHREADS, SM_TOTAL, cudaStreamPerThread>>>(maps, p);
}
```

```cpp
#include <cuda_runtime.h>
#include <cuda_bf16.h>
#include <cuda_fp16.h>
#include <cuda.h>
#include <stdint.h>

#define DEVI __device__ __forceinline__

namespace s4la {

constexpr int NTHREADS = 512;
constexpr int NCTA = 128;

constexpr int NSTG = 7;
constexpr uint32_t STG_BYTES = 20480, STG_X = 0, STG_W = 8192;
constexpr uint32_t SM_QS = 0;
constexpr uint32_t SM_PK = SM_QS + 16384, SM_VS = SM_QS + 32768;
constexpr uint32_t SM_WO = 65536;
constexpr uint32_t SM_KV = 131072;
constexpr uint32_t SM_BOUT = 16384;
constexpr uint32_t SM_U = 143360, U_BYTES = 4352;
constexpr uint32_t SM_P = 160768, P_BYTES = 4096;
constexpr uint32_t SM_VV = 177152, VV_BYTES = 12800;
constexpr uint32_t VV_U5 = 0, VV_U3 = 3712, VV_U9 = 7424, VV_U7 = 10112;
constexpr uint32_t KG_BYTES = 3200;
constexpr uint32_t SM_BAR = SM_VV + 4 * VV_BYTES;
constexpr uint32_t SM_PTAB = SM_BAR + 320;
constexpr uint32_t SM_TOTAL = SM_PTAB + 2048;
static_assert(SM_TOTAL <= 232448, "shared memory");
constexpr int PADV = 12;

enum { B_FULL = 0, B_EMPTY = 7, B_TILE = 14, B_UCH = 15, B_KVP = 19, B_KVF = 20, B_OST = 21, B_RF = 22, B_WO = 30, B_RE = 31, B_PFREE = 32, B_CONVD = 33, B_SLOT = 34, B_COUNT = 35 };
__host__ __device__ constexpr int bar_count(int i) {
  return (i >= B_EMPTY && i < B_TILE) ? 16 : (i == B_KVP || i == B_OST || i == B_CONVD) ? 8 : i == B_RE ? 16 : i == B_SLOT ? 2 : 1;
}

constexpr int PD_OFF = 0, P2_OFF = 544, P3_OFF = 768;

constexpr int SL_K2048 = 20, SL_ZERO = 21, SL_510 = 22, SL_0 = 23;
__host__ __device__ constexpr int koff(int y) {
  return y < 8 ? y : y < 12 ? 256 + 2 * (y - 8) : y < 16 ? 512 + 256 * ((y - 12) >> 1) + 4 * (y & 1) : 1024 + 256 * (y - 16);
}
__host__ __device__ constexpr int kidx_c(int l) {
  const int y = l < 256 ? (l & 7) : l < 512 ? 8 + ((l & 7) >> 1) : l < 1024 ? 12 + (((l - 512) >> 8) << 1) + ((l >> 2) & 1)
                                                                            : 16 + ((l - 1024) >> 8);
  return ((l >> 3) & 31) * 24 + y;
}
constexpr int slot_direct(int l) {
  if (l < 0 || l > 510) return SL_ZERO;
  if (l == 510) return SL_510;
  if (l == 0) return SL_0;
  return kidx_c(l < 256 ? l : ((l + ((l >> 1) & 1)) & ~1));
}
constexpr int slot_seg2(int v, int k) { return (k >= 32 && k < 64) ? kidx_c(16 * k + 4 * v) : SL_ZERO; }
constexpr int slot_seg3(int pi, int k) {
  return (k >= 64 && k < 128) ? kidx_c(16 * k + 8 * pi) : ((k == 128 && pi == 0) ? SL_K2048 : SL_ZERO);
}
constexpr int slot_word(int w) {
  return w < 0 ? SL_ZERO : w < 544 ? slot_direct(w - 16) : w < 768 ? slot_seg2((w - 544) / 56, 16 + (w - 544) % 56)
       : w < 944 ? slot_seg3((w - 768) / 88, 48 + (w - 768) % 88) : SL_ZERO;
}
struct PTab { uint32_t v[512]; };
constexpr PTab make_ptab() {
  PTab t{};
  for (int lane = 0; lane < 32; ++lane)
    for (int i = 0; i < 16; ++i)
      t.v[i * 32 + lane] = (slot_word(31 * lane - 1 + 2 * i) * 4) | ((slot_word(31 * lane + 2 * i) * 4) << 16);
  return t;
}
__device__ const PTab g_ptab = make_ptab();

__device__ __nv_bfloat16 g_uT[512 * 2048];
__device__ __nv_bfloat16 g_yT[512 * 2048];
__device__ __nv_bfloat16 g_o[2048 * 512];
__device__ float g_kv[2][8][4 * 272];
__device__ unsigned g_cnt[64 * 32];
__device__ unsigned g_epoch;
#define TS(slot) do { } while (0)
#define TSR(on, slot) do { } while (0)
#define TSD(slot) do { } while (0)
enum { C_U = 0, C_KV = 8, C_O = 16, C_Y = 32 };

struct Maps {
  CUtensorMap x, w, wo, u, uT, yT, o, out, outh;
};
struct Ptrs {
  const __nv_bfloat16 *A_re, *A_im, *B_re, *B_im, *C_re, *C_im, *log_dt, *Dskip;
  const __nv_bfloat16 *x, *wqkv, *wo;
  __nv_bfloat16 *uT, *yT;
};

DEVI uint32_t s2u(const void* p) { return (uint32_t)__cvta_generic_to_shared(p); }
DEVI void mbar_init(uint32_t b, uint32_t c) { asm volatile("mbarrier.init.shared::cta.b64 [%0], %1;" ::"r"(b), "r"(c) : "memory"); }
DEVI void mbar_expect_tx(uint32_t b, uint32_t bytes) {
  asm volatile("mbarrier.arrive.expect_tx.shared::cta.b64 _, [%0], %1;" ::"r"(b), "r"(bytes) : "memory");
}
DEVI void mbar_arrive(uint32_t b) { asm volatile("mbarrier.arrive.shared::cta.b64 _, [%0];" ::"r"(b) : "memory"); }
DEVI void mbar_arrive_cluster(uint32_t b, uint32_t cta) {
  asm volatile("{\n.reg .b32 r;\nmapa.shared::cluster.u32 r, %0, %1;\nmbarrier.arrive.shared::cluster.b64 _, [r];\n}"
               ::"r"(b), "r"(cta) : "memory");
}
DEVI void mbar_wait(uint32_t b, uint32_t parity) {
  asm volatile("{\n.reg .pred p;\nLAB_WAIT:\nmbarrier.try_wait.parity.shared::cta.b64 p, [%0], %1;\n@!p bra LAB_WAIT;\n}"
               ::"r"(b), "r"(parity) : "memory");
}
DEVI void mbar_wait_long(uint32_t b, uint32_t parity) {
  asm volatile("{\n.reg .pred p;\nLAB_WAIT:\nmbarrier.try_wait.parity.shared::cta.b64 p, [%0], %1, 0x989680;\n@!p bra LAB_WAIT;\n}"
               ::"r"(b), "r"(parity) : "memory");
}
DEVI void bar_sync(int id, int n) { asm volatile("bar.sync %0, %1;" ::"r"(id), "r"(n) : "memory"); }
DEVI void bar_arrive(int id, int n) { asm volatile("bar.arrive %0, %1;" ::"r"(id), "r"(n) : "memory"); }
DEVI void fence_async_smem() { asm volatile("fence.proxy.async.shared::cta;" ::: "memory"); }
DEVI void fence_async_all() { asm volatile("fence.proxy.async;" ::: "memory"); }
DEVI void cluster_arrive() { asm volatile("barrier.cluster.arrive.relaxed.aligned;" ::: "memory"); }
DEVI void cluster_wait() { asm volatile("barrier.cluster.wait.aligned;" ::: "memory"); }

DEVI void tma_load_2d(uint32_t dst, const CUtensorMap* m, int c0, int c1, uint32_t bar) {
  asm volatile("cp.async.bulk.tensor.2d.shared::cluster.global.mbarrier::complete_tx::bytes [%0], [%1, {%3, %4}], [%2];"
               ::"r"(dst), "l"(m), "r"(bar), "r"(c0), "r"(c1) : "memory");
}
DEVI void tma_load_2d_mc(uint32_t dst, const CUtensorMap* m, int c0, int c1, uint32_t bar, uint16_t mask) {
  asm volatile("cp.async.bulk.tensor.2d.shared::cluster.global.mbarrier::complete_tx::bytes.multicast::cluster [%0], [%1, {%3, %4}], [%2], %5;"
               ::"r"(dst), "l"(m), "r"(bar), "r"(c0), "r"(c1), "h"(mask) : "memory");
}
DEVI void tma_load_3d_mc(uint32_t dst, const CUtensorMap* m, int c0, int c1, int c2, uint32_t bar, uint16_t mask) {
  asm volatile("cp.async.bulk.tensor.3d.shared::cluster.global.mbarrier::complete_tx::bytes.multicast::cluster [%0], [%1, {%3, %4, %5}], [%2], %6;"
               ::"r"(dst), "l"(m), "r"(bar), "r"(c0), "r"(c1), "r"(c2), "h"(mask) : "memory");
}
DEVI void tma_store_2d(const CUtensorMap* m, uint32_t src, int c0, int c1) {
  asm volatile("cp.async.bulk.tensor.2d.global.shared::cta.bulk_group [%0, {%2, %3}], [%1];"
               ::"l"(m), "r"(src), "r"(c0), "r"(c1) : "memory");
}
DEVI void bulk_load(uint32_t dst, const void* src, uint32_t bytes, uint32_t bar) {
  asm volatile("cp.async.bulk.shared::cluster.global.mbarrier::complete_tx::bytes [%0], [%1], %2, [%3];"
               ::"r"(dst), "l"(src), "r"(bytes), "r"(bar) : "memory");
}
DEVI void bulk_store(void* dst, uint32_t src, uint32_t bytes) {
  asm volatile("cp.async.bulk.global.shared::cta.bulk_group [%0], [%1], %2;" ::"l"(dst), "r"(src), "r"(bytes) : "memory");
}
DEVI void bulk_reduce_add_f32(void* dst, uint32_t src, uint32_t bytes) {
  asm volatile("cp.reduce.async.bulk.global.shared::cta.bulk_group.add.f32 [%0], [%1], %2;" ::"l"(dst), "r"(src), "r"(bytes) : "memory");
}
DEVI void bulk_commit() { asm volatile("cp.async.bulk.commit_group;" ::: "memory"); }
DEVI void bulk_wait0() { asm volatile("cp.async.bulk.wait_group 0;" ::: "memory"); }
DEVI void bulk_wait_read0() { asm volatile("cp.async.bulk.wait_group.read 0;" ::: "memory"); }
DEVI void l2_prefetch(const void* p, uint32_t bytes) {
  asm volatile("cp.async.bulk.prefetch.L2.global [%0], %1;" ::"l"(p), "r"(bytes) : "memory");
}
DEVI void prefetch_tmap(const CUtensorMap* m) { asm volatile("prefetch.tensormap [%0];" ::"l"(m) : "memory"); }

DEVI void red_release_add(unsigned* p, unsigned v) {
  asm volatile("red.release.gpu.global.add.u32 [%0], %1;" ::"l"(p), "r"(v) : "memory");
}
DEVI void red_relaxed_add(unsigned* p, unsigned v) {
  asm volatile("red.relaxed.gpu.global.add.u32 [%0], %1;" ::"l"(p), "r"(v) : "memory");
}
DEVI unsigned ld_relaxed(const unsigned* p) {
  unsigned v;
  asm volatile("ld.relaxed.gpu.global.u32 %0, [%1];" : "=r"(v) : "l"(p) : "memory");
  return v;
}
DEVI void wait_counter(const unsigned* p, unsigned target) {
#pragma unroll 1
  for (int it = 0; (int)(ld_relaxed(p) - target) < 0; ++it)
    if (it > (1 << 22)) __trap();
}

DEVI void ldsm_x4(uint32_t (&r)[4], uint32_t a) {
  asm volatile("ldmatrix.sync.aligned.m8n8.x4.shared.b16 {%0,%1,%2,%3}, [%4];"
               : "=r"(r[0]), "=r"(r[1]), "=r"(r[2]), "=r"(r[3]) : "r"(a) : "memory");
}
DEVI void ldsm_x4_t(uint32_t (&r)[4], uint32_t a) {
  asm volatile("ldmatrix.sync.aligned.m8n8.x4.trans.shared.b16 {%0,%1,%2,%3}, [%4];"
               : "=r"(r[0]), "=r"(r[1]), "=r"(r[2]), "=r"(r[3]) : "r"(a) : "memory");
}
DEVI void ldsm_x2_t(uint32_t& r0, uint32_t& r1, uint32_t a) {
  asm volatile("ldmatrix.sync.aligned.m8n8.x2.trans.shared.b16 {%0,%1}, [%2];" : "=r"(r0), "=r"(r1) : "r"(a) : "memory");
}
DEVI void stsm_x4(uint32_t a, uint32_t r0, uint32_t r1, uint32_t r2, uint32_t r3) {
  asm volatile("stmatrix.sync.aligned.m8n8.x4.shared.b16 [%0], {%1,%2,%3,%4};"
               ::"r"(a), "r"(r0), "r"(r1), "r"(r2), "r"(r3) : "memory");
}
DEVI void stsm_x4_t(uint32_t a, uint32_t r0, uint32_t r1, uint32_t r2, uint32_t r3) {
  asm volatile("stmatrix.sync.aligned.m8n8.x4.trans.shared.b16 [%0], {%1,%2,%3,%4};"
               ::"r"(a), "r"(r0), "r"(r1), "r"(r2), "r"(r3) : "memory");
}
DEVI uint32_t lds32(uint32_t a) { uint32_t v; asm volatile("ld.shared.b32 %0, [%1];" : "=r"(v) : "r"(a) : "memory"); return v; }
DEVI float lds_f32(uint32_t a) { float v; asm volatile("ld.shared.f32 %0, [%1];" : "=f"(v) : "r"(a) : "memory"); return v; }
DEVI void sts32(uint32_t a, uint32_t v) { asm volatile("st.shared.b32 [%0], %1;" ::"r"(a), "r"(v) : "memory"); }
DEVI void sts_f32(uint32_t a, float v) { asm volatile("st.shared.f32 [%0], %1;" ::"r"(a), "f"(v) : "memory"); }
DEVI void sts_f32x2(uint32_t a, float x, float y) { asm volatile("st.shared.v2.f32 [%0], {%1,%2};" ::"r"(a), "f"(x), "f"(y) : "memory"); }
DEVI uint4 lds128(uint32_t a) {
  uint4 v;
  asm volatile("ld.shared.v4.b32 {%0,%1,%2,%3}, [%4];" : "=r"(v.x), "=r"(v.y), "=r"(v.z), "=r"(v.w) : "r"(a) : "memory");
  return v;
}
DEVI void sts128(uint32_t a, uint32_t x, uint32_t y, uint32_t z, uint32_t w) {
  asm volatile("st.shared.v4.b32 [%0], {%1,%2,%3,%4};" ::"r"(a), "r"(x), "r"(y), "r"(z), "r"(w) : "memory");
}

DEVI void mma_bf16(float (&d)[4], uint32_t a0, uint32_t a1, uint32_t a2, uint32_t a3, uint32_t b0, uint32_t b1) {
  asm("mma.sync.aligned.m16n8k16.row.col.f32.bf16.bf16.f32 {%0,%1,%2,%3}, {%4,%5,%6,%7}, {%8,%9}, {%0,%1,%2,%3};"
      : "+f"(d[0]), "+f"(d[1]), "+f"(d[2]), "+f"(d[3])
      : "r"(a0), "r"(a1), "r"(a2), "r"(a3), "r"(b0), "r"(b1));
}
DEVI void mma_f16(float (&d)[4], const uint32_t (&a)[4], uint32_t b0, uint32_t b1) {
  asm("mma.sync.aligned.m16n8k16.row.col.f32.f16.f16.f32 {%0,%1,%2,%3}, {%4,%5,%6,%7}, {%8,%9}, {%0,%1,%2,%3};"
      : "+f"(d[0]), "+f"(d[1]), "+f"(d[2]), "+f"(d[3])
      : "r"(a[0]), "r"(a[1]), "r"(a[2]), "r"(a[3]), "r"(b0), "r"(b1));
}
DEVI void mma_bf16v(float (&d)[4], const uint32_t (&a)[4], uint32_t b0, uint32_t b1) {
  asm volatile("mma.sync.aligned.m16n8k16.row.col.f32.bf16.bf16.f32 {%0,%1,%2,%3}, {%4,%5,%6,%7}, {%8,%9}, {%0,%1,%2,%3};"
               : "+f"(d[0]), "+f"(d[1]), "+f"(d[2]), "+f"(d[3])
               : "r"(a[0]), "r"(a[1]), "r"(a[2]), "r"(a[3]), "r"(b0), "r"(b1));
}
DEVI uint32_t pack_bf16(float lo, float hi) {
  uint32_t r;
  asm("cvt.rn.bf16x2.f32 %0, %1, %2;" : "=r"(r) : "f"(hi), "f"(lo));
  return r;
}
DEVI uint32_t pack_f16(float lo, float hi) {
  uint32_t r;
  asm("cvt.rn.f16x2.f32 %0, %1, %2;" : "=r"(r) : "f"(hi), "f"(lo));
  return r;
}
DEVI uint32_t ldg16(const __nv_bfloat16* p) {
  uint32_t v;
  asm volatile("ld.global.nc.u16 %0, [%1];" : "=r"(v) : "l"(p));
  return v;
}
DEVI bool elect_one() {
  uint32_t pred;
  asm volatile("{\n.reg .pred p;\nelect.sync _|p, 0xffffffff;\nselp.u32 %0, 1, 0, p;\n}" : "=r"(pred));
  return pred != 0;
}
DEVI float bf_lo(uint32_t v) { return __uint_as_float(v << 16); }
DEVI float bf_hi(uint32_t v) { return __uint_as_float(v & 0xffff0000u); }
DEVI float bf2f(__nv_bfloat16 v) { return __bfloat162float(v); }
DEVI float round_bf16(float v) { return __bfloat162float(__float2bfloat16_rn(v)); }
DEVI float rcp(float x) { float r; asm("rcp.approx.ftz.f32 %0, %1;" : "=f"(r) : "f"(x)); return r; }
DEVI float ex2(float x) { float r; asm("ex2.approx.ftz.f32 %0, %1;" : "=f"(r) : "f"(x)); return r; }

DEVI void wg_fence() { asm volatile("wgmma.fence.sync.aligned;" ::: "memory"); }
DEVI void wg_commit() { asm volatile("wgmma.commit_group.sync.aligned;" ::: "memory"); }
template <int N> DEVI void wg_wait() { asm volatile("wgmma.wait_group.sync.aligned %0;" ::"n"(N) : "memory"); }
constexpr uint32_t DESC_HI = (1u << 30) | (1024 >> 4);
constexpr uint32_t DESC_HI64 = (2u << 30) | (512 >> 4);
DEVI uint32_t mkdesc(uint32_t saddr, uint32_t lbo) { return ((saddr & 0x3FFFF) >> 4) | ((lbo >> 4) << 16); }

#define R8(b) "%" #b
DEVI void wgmma_n192(float (&d)[96], uint32_t da, uint32_t db, int scale_d) {
  asm volatile(
      "{\n.reg .pred p;\n.reg .b64 da, db;\nsetp.ne.b32 p, %98, 0;\nmov.b64 da, {%96, %100};\nmov.b64 db, {%97, %99};\n"
      "wgmma.mma_async.sync.aligned.m64n192k16.f32.bf16.bf16 "
      "{%0,%1,%2,%3,%4,%5,%6,%7,%8,%9,%10,%11,%12,%13,%14,%15,"
      "%16,%17,%18,%19,%20,%21,%22,%23,%24,%25,%26,%27,%28,%29,%30,%31,"
      "%32,%33,%34,%35,%36,%37,%38,%39,%40,%41,%42,%43,%44,%45,%46,%47,"
      "%48,%49,%50,%51,%52,%53,%54,%55,%56,%57,%58,%59,%60,%61,%62,%63,"
      "%64,%65,%66,%67,%68,%69,%70,%71,%72,%73,%74,%75,%76,%77,%78,%79,"
      "%80,%81,%82,%83,%84,%85,%86,%87,%88,%89,%90,%91,%92,%93,%94,%95}, "
      "da, db, p, 1, 1, 0, 1;\n}"
      : "+f"(d[0]), "+f"(d[1]), "+f"(d[2]), "+f"(d[3]), "+f"(d[4]), "+f"(d[5]), "+f"(d[6]), "+f"(d[7]),
        "+f"(d[8]), "+f"(d[9]), "+f"(d[10]), "+f"(d[11]), "+f"(d[12]), "+f"(d[13]), "+f"(d[14]), "+f"(d[15]),
        "+f"(d[16]), "+f"(d[17]), "+f"(d[18]), "+f"(d[19]), "+f"(d[20]), "+f"(d[21]), "+f"(d[22]), "+f"(d[23]),
        "+f"(d[24]), "+f"(d[25]), "+f"(d[26]), "+f"(d[27]), "+f"(d[28]), "+f"(d[29]), "+f"(d[30]), "+f"(d[31]),
        "+f"(d[32]), "+f"(d[33]), "+f"(d[34]), "+f"(d[35]), "+f"(d[36]), "+f"(d[37]), "+f"(d[38]), "+f"(d[39]),
        "+f"(d[40]), "+f"(d[41]), "+f"(d[42]), "+f"(d[43]), "+f"(d[44]), "+f"(d[45]), "+f"(d[46]), "+f"(d[47]),
        "+f"(d[48]), "+f"(d[49]), "+f"(d[50]), "+f"(d[51]), "+f"(d[52]), "+f"(d[53]), "+f"(d[54]), "+f"(d[55]),
        "+f"(d[56]), "+f"(d[57]), "+f"(d[58]), "+f"(d[59]), "+f"(d[60]), "+f"(d[61]), "+f"(d[62]), "+f"(d[63]),
        "+f"(d[64]), "+f"(d[65]), "+f"(d[66]), "+f"(d[67]), "+f"(d[68]), "+f"(d[69]), "+f"(d[70]), "+f"(d[71]),
        "+f"(d[72]), "+f"(d[73]), "+f"(d[74]), "+f"(d[75]), "+f"(d[76]), "+f"(d[77]), "+f"(d[78]), "+f"(d[79]),
        "+f"(d[80]), "+f"(d[81]), "+f"(d[82]), "+f"(d[83]), "+f"(d[84]), "+f"(d[85]), "+f"(d[86]), "+f"(d[87]),
        "+f"(d[88]), "+f"(d[89]), "+f"(d[90]), "+f"(d[91]), "+f"(d[92]), "+f"(d[93]), "+f"(d[94]), "+f"(d[95])
      : "r"(da), "r"(db), "r"(scale_d), "n"(DESC_HI), "n"(DESC_HI64));
}
DEVI void wgmma_n64(float (&d)[32], uint32_t da, uint32_t db, int scale_d) {
  asm volatile(
      "{\n.reg .pred p;\n.reg .b64 da, db;\nsetp.ne.b32 p, %34, 0;\nmov.b64 da, {%32, %35};\nmov.b64 db, {%33, %35};\n"
      "wgmma.mma_async.sync.aligned.m64n64k16.f32.bf16.bf16 "
      "{%0,%1,%2,%3,%4,%5,%6,%7,%8,%9,%10,%11,%12,%13,%14,%15,"
      "%16,%17,%18,%19,%20,%21,%22,%23,%24,%25,%26,%27,%28,%29,%30,%31}, "
      "da, db, p, 1, 1, 0, 1;\n}"
      : "+f"(d[0]), "+f"(d[1]), "+f"(d[2]), "+f"(d[3]), "+f"(d[4]), "+f"(d[5]), "+f"(d[6]), "+f"(d[7]),
        "+f"(d[8]), "+f"(d[9]), "+f"(d[10]), "+f"(d[11]), "+f"(d[12]), "+f"(d[13]), "+f"(d[14]), "+f"(d[15]),
        "+f"(d[16]), "+f"(d[17]), "+f"(d[18]), "+f"(d[19]), "+f"(d[20]), "+f"(d[21]), "+f"(d[22]), "+f"(d[23]),
        "+f"(d[24]), "+f"(d[25]), "+f"(d[26]), "+f"(d[27]), "+f"(d[28]), "+f"(d[29]), "+f"(d[30]), "+f"(d[31])
      : "r"(da), "r"(db), "r"(scale_d), "n"(DESC_HI));
}

struct C32 { float re, im; };
DEVI C32 csq(C32 a) { return {a.re * a.re - a.im * a.im, 2.f * a.re * a.im}; }
DEVI C32 cmul(C32 a, C32 b) { return {a.re * b.re - a.im * b.im, a.re * b.im + a.im * b.re}; }
DEVI C32 cfresh(float zl, float zi, float m) {
  float mag = ex2(zl * m), ph = zi * m;
  return {mag * __cosf(ph), mag * __sinf(ph)};
}
struct HMul { uint32_t b, bp; };
DEVI HMul mk_mul(float re, float im) { return {pack_f16(re, im), pack_f16(-im, re)}; }
DEVI uint32_t hcmul(uint32_t a, const HMul& m) {
  __half2 ah = *reinterpret_cast<__half2*>(&a);
  __half2 b = *reinterpret_cast<const __half2*>(&m.b), bp = *reinterpret_cast<const __half2*>(&m.bp);
  __half2 r = __hfma2(__high2half2(ah), bp, __hmul2(__low2half2(ah), b));
  return *reinterpret_cast<uint32_t*>(&r);
}
DEVI uint32_t badd(uint32_t a, uint32_t b) {
  __nv_bfloat162 r = __hadd2(*reinterpret_cast<__nv_bfloat162*>(&a), *reinterpret_cast<__nv_bfloat162*>(&b));
  return *reinterpret_cast<uint32_t*>(&r);
}
template <int MU0, int NMU, int DMAX>
DEVI void conv_tail(float (&acc)[16][4], uint32_t p_lane, uint32_t v_base, int back, bool edge, int lane) {
  const int hsel = (lane >> 3) & 1;
  const int row = (lane & 7) + ((lane >> 4) << 3) + PADV - 8 - (back & (hsel ^ 1));
  const uint32_t la = v_base + row * 32 + (((hsel ^ back) ^ ((row >> 2) & 1)) << 4);
  uint32_t M[3][4];
  ldsm_x4_t(M[0], la);
  ldsm_x4_t(M[1], la + 256);
  uint32_t H[2 * NMU];
#pragma unroll
  for (int i = 0; i < 2 * NMU; ++i) H[i ^ 1] = lds32(p_lane + (uint32_t)(MU0 - 1 + i) * 32);
  if (edge) {
    const uint32_t a[4] = {0u, 0u, M[0][0], M[0][1]};
#pragma unroll
    for (int k = 1; k < NMU; ++k) mma_bf16v(acc[MU0 - 2 + 2 * k], a, H[2 * k], H[2 * k + 1]);
  }
#pragma unroll
  for (int delta = -1; delta <= DMAX; ++delta) {
    if (delta + 2 <= DMAX) ldsm_x4_t(M[(delta + 3) % 3], la + (delta + 3) * 256);
#pragma unroll
    for (int k = 0; k < NMU; ++k)
      if (delta + MU0 + 2 * k < 16) mma_bf16v(acc[delta + MU0 + 2 * k], M[(delta + 1) % 3], H[2 * k], H[2 * k + 1]);
  }
}

template <int NB>
DEVI void box_filters(uint32_t sb, uint32_t bars, int idx, int lane) {
  auto swz = [](int k, int pad) { const int r = (k >> 1) + pad; return (uint32_t)(r * 32 + (((k & 1) ^ ((r >> 2) & 1)) << 4)); };
  const uint32_t o0 = swz(lane - 3, 8), o1 = swz(lane - 2, 8), o2 = swz(lane - 1, 8), ow = swz(lane - 2, PADV), oz = swz(lane - 18, PADV);
  const int k = 32 * idx - 2 + lane;
#pragma unroll 1
  for (int c2 = 0; c2 < 4; c2 += NB) {
    uint4 t[NB][3];
#pragma unroll
    for (int b = 0; b < NB; ++b) mbar_wait_long(bars + 8 * (B_UCH + c2 + b), 0);
#pragma unroll
    for (int b = 0; b < NB; ++b) {
      const uint32_t ua = sb + SM_U + (c2 + b) * U_BYTES + idx * 512;
      t[b][0] = lds128(ua + o0); t[b][1] = lds128(ua + o1); t[b][2] = lds128(ua + o2);
    }
#pragma unroll
    for (int b = 0; b < NB; ++b) {
      const uint32_t vb = sb + SM_VV + (c2 + b) * VV_BYTES, aw = vb + idx * 512 + ow;
      const uint32_t E[12] = {t[b][0].x, t[b][0].y, t[b][0].z, t[b][0].w, t[b][1].x, t[b][1].y, t[b][1].z, t[b][1].w,
                              t[b][2].x, t[b][2].y, t[b][2].z, t[b][2].w};
      uint32_t O[8];
#pragma unroll
      for (int j = 0; j < 8; ++j) O[j] = __byte_perm(E[j + 1], E[j + 2], 0x5432);
      uint32_t s3[6], s5[4], s7[4], s9[4];
#pragma unroll
      for (int j = 0; j < 6; ++j) s3[j] = badd(badd(O[j], O[j + 1]), E[j + 2]);
#pragma unroll
      for (int j = 0; j < 4; ++j) {
        s5[j] = badd(s3[j + 2], badd(E[j + 3], E[j + 5]));
        s7[j] = badd(s5[j], badd(O[j + 1], O[j + 4]));
        s9[j] = badd(s7[j], badd(E[j + 2], E[j + 6]));
      }
      if (k < 208) { sts128(aw + VV_U3, s3[0], s3[1], s3[2], s3[3]); sts128(aw + VV_U5, s5[0], s5[1], s5[2], s5[3]); }
      if (k < 144) { sts128(aw + VV_U7, s7[0], s7[1], s7[2], s7[3]); sts128(aw + VV_U9, s9[0], s9[1], s9[2], s9[3]); }
      if (idx == 0 && lane < 16) {
        sts128(vb + oz + VV_U3, 0, 0, 0, 0); sts128(vb + oz + VV_U5, 0, 0, 0, 0);
        sts128(vb + oz + VV_U7, 0, 0, 0, 0); sts128(vb + oz + VV_U9, 0, 0, 0, 0);
      }
    }
  }
}

__global__ void __cluster_dims__(2, 1, 1) __launch_bounds__(NTHREADS, 1)
fused_kernel(const __grid_constant__ Maps maps, const Ptrs p) {
  extern __shared__ __align__(1024) uint8_t smem[];
  const uint32_t sb = s2u(smem);
  const int tid = threadIdx.x, lane = tid & 31;
  const int warp = __shfl_sync(0xffffffffu, tid >> 5, 0);
  const int cta = blockIdx.x;
  const uint32_t rank = cta & 1;
  const int ti = 2 * (cta >> 4) + rank;
  const int tj = (cta >> 1) & 7;
  const int pi = cta >> 3, pj = cta & 7;
  const uint32_t bars = sb + SM_BAR;
#define BAR(i) (bars + 8 * (i))
  const int g = lane >> 2, q = lane & 3;

  auto issue_stage = [&](int ks, int s) {
    const uint32_t st = sb + s * STG_BYTES, fb = BAR(B_FULL + s);
    mbar_expect_tx(fb, STG_BYTES);
    tma_load_2d(st + STG_X, &maps.x, ks * 32, ti * 128, fb);
    tma_load_3d_mc(st + STG_W + rank * 6144, &maps.w, tj * 64, ks * 32 + rank * 16, 0, fb, 3);
  };

  const int kch = warp & 3, krd = warp >> 2;
  float zr, zi, wr, wi;
  unsigned epoch;
  uint32_t r_dskip;
  {
    const size_t po = (size_t)(cta * 4 + kch) * 128 + krd * 32 + lane;
    const uint32_t r_ar = ldg16(p.A_re + po), r_ai = ldg16(p.A_im + po), r_br = ldg16(p.B_re + po), r_bi = ldg16(p.B_im + po);
    const uint32_t r_cr = ldg16(p.C_re + po), r_ci = ldg16(p.C_im + po), r_ldt = ldg16(p.log_dt + cta * 4 + kch);
    epoch = __ldcg(&g_epoch);
    r_dskip = ldg16(p.Dskip + cta * 4 + kch);
    uint4 pt;
    if (tid < 128) pt = __ldg((const uint4*)g_ptab.v + tid);
    if (tid == 384) {
      TS(0);
#pragma unroll
      for (int i = 0; i < B_COUNT; ++i) mbar_init(BAR(i), bar_count(i));
      asm volatile("fence.mbarrier_init.release.cluster;" ::: "memory");
      prefetch_tmap(&maps.x); prefetch_tmap(&maps.w); prefetch_tmap(&maps.u);
    }
    __syncthreads();
    cluster_arrive();
    if (warp >= 12) {
      cluster_wait();
      if (elect_one()) {
        if (warp == 13) {
#define U_POS 0
          if (U_POS == 0) { mbar_expect_tx(BAR(B_TILE), 16384); tma_load_2d(sb + SM_U, &maps.u, tj * 64, ti * 128, BAR(B_TILE)); }
          prefetch_tmap(&maps.uT); prefetch_tmap(&maps.wo); prefetch_tmap(&maps.o); prefetch_tmap(&maps.yT);
          prefetch_tmap(&maps.out); prefetch_tmap(&maps.outh);
        } else {
          if (warp == 12) TS(61);
          { const int ks = warp == 12 ? 0 : warp - 13; issue_stage(ks, ks); }
        }
      }
      __syncwarp();
    }
    if (tid < 128) sts128(sb + SM_PTAB + tid * 16, pt.x, pt.y, pt.z, pt.w);
    const float dt = round_bf16(expf(bf_lo(r_ldt)));
    zr = dt * bf_lo(r_ar); zi = dt * bf_lo(r_ai);
    const float dbr = dt * bf_lo(r_br), dbi = dt * bf_lo(r_bi), cr = bf_lo(r_cr), ci = bf_lo(r_ci);
    wr = cr * dbr - ci * dbi; wi = cr * dbi + ci * dbr;
  }
  {
    const float mz = __uint_as_float(__reduce_max_sync(0xffffffffu, __float_as_uint(fmaxf(zr, 0.f))));
    const int E = min(max((int)(__reduce_max_sync(0xffffffffu, __float_as_uint(fmaxf(fabsf(wr), fabsf(wi)))) >> 23), 1), 252);
    const float sc = __int_as_float((253 - E) << 23), inv = __int_as_float((E + 1) << 23);
    const float zl = (zr - mz) * 1.4426950408889634f;
    const uint32_t tb = sb + SM_VV + kch * VV_BYTES + krd * KG_BYTES;
    const uint32_t sta = tb + (((lane >> 2) << 4) | ((lane & 3) << 2));
    auto put = [&](int r, uint32_t v) { sts32((sta ^ ((r & 7) << 4)) + r * 128, v); };
    const uint32_t lda = tb + ((lane & 7) + (((lane >> 3) & 1) << 3)) * 128;
    const uint32_t ldb = tb + ((lane & 7) + ((lane >> 4) << 3)) * 128;
#define STG_POS 0
#define PF_POS 1
    if (U_POS == 1 && warp == 13 && elect_one()) { mbar_expect_tx(BAR(B_TILE), 16384); tma_load_2d(sb + SM_U, &maps.u, tj * 64, ti * 128, BAR(B_TILE)); }
    if (STG_POS == 0 && warp >= 14 && elect_one()) { issue_stage(warp - 11, warp - 11); issue_stage(warp - 9, warp - 9); }
    if (PF_POS == 0 && warp >= 14 && elect_one()) {
      if (warp == 14) l2_prefetch((const char*)p.wqkv + 224 * 3072 + cta * 6912, 6912);
      else l2_prefetch((const char*)p.x + (size_t)cta * 16384, 16384);
    }
    __syncwarp();
    C32 e1 = cfresh(zl, zi, 1.f), e2 = csq(e1), e4 = csq(e2), e8 = csq(e4);
    C32 e16 = cfresh(zl, zi, 16.f), e32 = csq(e16), e64 = csq(e32), e128 = csq(e64);
    C32 e256 = cfresh(zl, zi, 256.f), e512 = csq(e256), e1024 = csq(e512), e768 = cmul(e512, e256);
    uint32_t XA[2][4][4];
    {
      const HMul m16 = mk_mul(e16.re, e16.im), m32 = mk_mul(e32.re, e32.im), m64 = mk_mul(e64.re, e64.im);
      const HMul m128 = mk_mul(e128.re, e128.im);
      uint32_t X[16];
      X[0] = 0x00003c00u; X[1] = pack_f16(e8.re, e8.im); X[2] = m16.b; X[4] = m32.b; X[8] = m64.b;
      X[3] = hcmul(X[1], m16); X[5] = hcmul(X[1], m32); X[6] = hcmul(X[2], m32); X[7] = hcmul(X[3], m32);
#pragma unroll
      for (int r = 1; r < 8; ++r) X[8 + r] = hcmul(X[r], m64);
#pragma unroll
      for (int h = 0; h < 2; ++h) {
#pragma unroll
        for (int r = 0; r < 16; ++r) put(r, h == 0 ? X[r] : r == 0 ? m128.b : hcmul(X[r], m128));
        __syncwarp();
#pragma unroll
        for (int k = 0; k < 4; ++k) ldsm_x4(XA[h][k], lda + (((2 * k + (lane >> 4)) ^ (lane & 7)) << 4));
        __syncwarp();
      }
    }
    if (U_POS == 2 && warp == 13 && elect_one()) { mbar_expect_tx(BAR(B_TILE), 16384); tma_load_2d(sb + SM_U, &maps.u, tj * 64, ti * 128, BAR(B_TILE)); }
    if (STG_POS == 1 && warp >= 14 && elect_one()) { issue_stage(warp - 11, warp - 11); issue_stage(warp - 9, warp - 9); }
    if (PF_POS == 1 && warp >= 14 && elect_one()) {
      if (warp == 14) l2_prefetch((const char*)p.wqkv + 224 * 3072 + cta * 6912, 6912);
      else l2_prefetch((const char*)p.x + (size_t)cta * 16384, 16384);
    }
    __syncwarp();
    float D[2][3][4];
#pragma unroll
    for (int t = 0; t < 6; ++t) D[t / 3][t % 3][0] = D[t / 3][t % 3][1] = D[t / 3][t % 3][2] = D[t / 3][t % 3][3] = 0.f;
    auto contract = [&](int t0, int nt) {
      __syncwarp();
#pragma unroll
      for (int k = 0; k < 4; ++k) {
        uint32_t b[4];
        ldsm_x4(b, ldb + (((2 * k + ((lane >> 3) & 1)) ^ (lane & 7)) << 4));
#pragma unroll
        for (int h = 0; h < 2; ++h) {
          mma_f16(D[h][t0], XA[h][k], b[0], b[1]);
          if (nt == 2) mma_f16(D[h][t0 + 1], XA[h][k], b[2], b[3]);
        }
      }
      __syncwarp();
    };
    const HMul c1 = mk_mul(e1.re, -e1.im), c2 = mk_mul(e2.re, -e2.im), c4 = mk_mul(e4.re, -e4.im);
    const HMul c256 = mk_mul(e256.re, -e256.im), c512 = mk_mul(e512.re, -e512.im), c768 = mk_mul(e768.re, -e768.im);
    const HMul c1024 = mk_mul(e1024.re, -e1024.im);
    uint32_t W[8];
    W[0] = pack_f16(wr * sc, -wi * sc);
    W[1] = hcmul(W[0], c1); W[2] = hcmul(W[0], c2); W[3] = hcmul(W[1], c2);
    W[4] = hcmul(W[0], c4); W[5] = hcmul(W[1], c4); W[6] = hcmul(W[2], c4); W[7] = hcmul(W[3], c4);
#pragma unroll
    for (int i = 0; i < 8; ++i) put(i, W[i]);
#pragma unroll
    for (int i = 0; i < 4; ++i) put(8 + i, hcmul(W[2 * i], c256));
    put(12, hcmul(W[0], c512)); put(13, hcmul(W[4], c512)); put(14, hcmul(W[0], c768)); put(15, hcmul(W[4], c768));
    if (PF_POS == 2 && warp >= 14 && elect_one()) {
      if (warp == 14) l2_prefetch((const char*)p.wqkv + 224 * 3072 + cta * 6912, 6912);
      else l2_prefetch((const char*)p.x + (size_t)cta * 16384, 16384);
    }
    contract(0, 2);
    const uint32_t v0 = hcmul(W[0], c1024);
    put(0, v0); put(1, hcmul(v0, c256)); put(2, hcmul(v0, c512)); put(3, hcmul(v0, c768)); put(4, hcmul(v0, c1024));
    contract(2, 1);
    const uint32_t a = tb + (g * 24 + 2 * q) * 4;
#pragma unroll
    for (int t = 0; t < 6; ++t) {
      const float(&d)[4] = D[t / 3][t % 3];
      sts_f32x2(a + (t / 3) * 1536 + (t % 3) * 32, d[0], d[1]);
      sts_f32x2(a + (t / 3) * 1536 + (t % 3) * 32 + 768, d[2], d[3]);
    }
    if (lane == 0) sts_f32(tb + 3072, inv);
    if (mz > 0.f) {
      __syncwarp();
#pragma unroll 1
      for (int i = lane; i < 768; i += 32) {
        const int r = i / 24, y = i - 24 * r;
        sts_f32(tb + i * 4, lds_f32(tb + i * 4) * ex2(mz * 1.4426950408889634f * (koff(y) + 8 * r)));
      }
    }
  }
  if (tid == 0) TS(2);
  if (warp < 12) cluster_wait();
  __syncthreads();

  if (warp < 4) {
#define A_REGS 200
    asm volatile("setmaxnreg.inc.sync.aligned.u32 %0;" ::"n"(A_REGS));
    if (tid == 0) TS(34);
    const int d = cta * 4 + warp;
    const uint32_t vv = sb + SM_VV + warp * VV_BYTES;
    const uint32_t ub = sb + SM_U + warp * U_BYTES;
    const uint32_t pb = sb + SM_P + warp * P_BYTES;
    const float dskip = bf_lo(r_dskip);
#pragma unroll 1
    for (int pass = 0; pass < 2; ++pass) {
      if (pass == 1) {
        const uint32_t kf = vv;
        const float i0 = lds_f32(kf + 3072), i1 = lds_f32(kf + KG_BYTES + 3072), i2 = lds_f32(kf + 2 * KG_BYTES + 3072);
        const float i3 = lds_f32(kf + 3 * KG_BYTES + 3072);
#pragma unroll 2
        for (int i = 0; i < 6; ++i) {
          const uint32_t a = kf + (i * 32 + lane) * 16;
          const uint4 x0 = lds128(a), x1 = lds128(a + KG_BYTES), x2 = lds128(a + 2 * KG_BYTES), x3 = lds128(a + 3 * KG_BYTES);
          auto s4 = [&](uint32_t a0, uint32_t a1, uint32_t a2, uint32_t a3) {
            return __float_as_uint(fmaf(__uint_as_float(a0), i0, __uint_as_float(a1) * i1) +
                                   fmaf(__uint_as_float(a2), i2, __uint_as_float(a3) * i3));
          };
          sts128(a, s4(x0.x, x1.x, x2.x, x3.x), s4(x0.y, x1.y, x2.y, x3.y), s4(x0.z, x1.z, x2.z, x3.z), s4(x0.w, x1.w, x2.w, x3.w));
        }
        __syncwarp();
        const float k1024 = lds_f32(kf + kidx_c(1024) * 4);
        if (lane == 0) {
          sts_f32(kf + SL_ZERO * 4, 0.f);
          sts_f32(kf + SL_510 * 4, lds_f32(kf + kidx_c(510) * 4) - lds_f32(kf + kidx_c(512) * 4));
          sts_f32(kf + SL_0 * 4, lds_f32(kf) + dskip);
        }
        __syncwarp();
        if (tid == 0) TS(36);
        mbar_wait_long(BAR(B_PFREE), 0);
        if (tid == 0) TS(37);
        {
          float prev = 0.f;
#pragma unroll 1
          for (int i0 = 0; i0 < 16; i0 += 4) {
            uint32_t e[4];
            float a[4], b[4];
#pragma unroll
            for (int i = 0; i < 4; ++i) e[i] = lds32(sb + SM_PTAB + ((i0 + i) * 32 + lane) * 4);
#pragma unroll
            for (int i = 0; i < 4; ++i) { a[i] = lds_f32(kf + (e[i] & 0xffff)); b[i] = lds_f32(kf + (e[i] >> 16)); }
#pragma unroll
            for (int i = 0; i < 4; ++i) {
              const uint32_t w = pb + (31 * lane + 2 * (i0 + i)) * 4;
              if (i0 + i > 0) sts32(w - 4, pack_bf16(a[i], prev));
              sts32(w, pack_bf16(b[i], a[i]));
              prev = b[i];
            }
          }
        }
        __syncwarp();
        if (lane == 0) TS(4);
        const int gq = g - 2 * q;
        uint32_t h127, h128;
        {
          const uint32_t kf2 = pack_bf16(k1024, k1024) ^ 0x80008000u;
          h127 = (gq == 4 ? 0x0000ffffu : gq == 5 ? 0xffffffffu : gq == 6 ? 0xffff0000u : 0u) & kf2;
          h128 = (gq == -4 ? 0x0000ffffu : gq == -3 ? 0xffffffffu : gq == -2 ? 0xffff0000u : 0u) & kf2;
        }
        bar_arrive(7, 384);
        if (lane == 0) TS(6);
        bar_sync(4, 384);
        mbar_wait_long(BAR(B_UCH + warp), 0);
        if (lane == 0) TS(7);
        float acc[16][4];
#pragma unroll
        for (int i = 0; i < 16; ++i) { acc[i][0] = acc[i][1] = acc[i][2] = acc[i][3] = 0.f; }
        {
          const uint32_t pd_lane = pb + (PD_OFF + 16 + gq) * 4;
          const int prow0 = 8 + (lane & 7) + ((lane >> 4) << 3), hs = (lane >> 3) & 1;
          const uint32_t zero = (uint32_t)cta >> 20;
          uint32_t B[2][4][4];
          uint32_t A[4][4];
          const uint32_t la0 = ub + prow0 * 32 + ((hs ^ ((prow0 >> 2) & 1)) << 4);
#pragma unroll
          for (int m2 = 0; m2 < 4; ++m2) ldsm_x4(B[0][m2], la0 + m2 * 512);
#pragma unroll
          for (int i = 0; i < 4; ++i) {
            const uint32_t a = pd_lane + i * 512;
            A[i][0] = lds32(a); A[i][1] = lds32(a + 32); A[i][2] = lds32(a - 32); A[i][3] = lds32(a + zero);
          }
          uint32_t la = la0;
#define UNR_RHO 4
#define UNR_TAIL 4
          constexpr int unr_rho = UNR_RHO, unr_tail = UNR_TAIL;
#pragma unroll unr_rho
          for (int rho = 0; rho < 8; ++rho) {
#pragma unroll
            for (int m2 = 0; m2 < 4; ++m2) ldsm_x4(B[1][m2], la + (4 + m2) * 512);
#pragma unroll
            for (int i = 0; i < 4; ++i)
#pragma unroll
              for (int m = 0; m < 8; ++m) mma_bf16v(acc[m + i], A[i], B[0][m >> 1][2 * (m & 1)], B[0][m >> 1][2 * (m & 1) + 1]);
            const int prow = prow0 - min(rho + 1, 7);
            la = ub + prow * 32 + ((hs ^ ((prow >> 2) & 1)) << 4);
#pragma unroll
            for (int m2 = 0; m2 < 4; ++m2) ldsm_x4(B[0][m2], la + m2 * 512);
            const uint32_t pa = pd_lane + (rho + 1) * 64;
#pragma unroll
            for (int i = 0; i < 4; ++i) {
#pragma unroll
              for (int m = 0; m < 8 - i; ++m)
                mma_bf16v(acc[8 + m + i], A[i], B[1][m >> 1][2 * (m & 1)], B[1][m >> 1][2 * (m & 1) + 1]);
              A[i][0] = lds32(pa + i * 512); A[i][1] = lds32(pa + i * 512 + 32); A[i][2] = lds32(pa + i * 512 - 32);
              A[i][3] = lds32(pa + i * 512 + zero);
            }
          }
          if (lane == 0) TS(40);
          {
            uint32_t b8[4];
            ldsm_x4(b8, la + 4 * 512);
            const uint32_t h63 = lds32(pd_lane + 63 * 32), h64 = lds32(pd_lane + 64 * 32);
            const uint32_t a63[4] = {0u, h127, 0u, 0u}, a32[4] = {h64, 0u, h63, h64}, a64[4] = {h128, 0u, h127, h128};
#pragma unroll
            for (int m2 = 0; m2 < 4; ++m2) ldsm_x4(B[1][m2], la0 + m2 * 512);
#pragma unroll
            for (int m = 0; m < 8; ++m) mma_bf16v(acc[m + 7], a63, B[0][m >> 1][2 * (m & 1)], B[0][m >> 1][2 * (m & 1) + 1]);
#pragma unroll
            for (int m2 = 0; m2 < 2; ++m2) ldsm_x4(B[0][m2], la0 + (4 + m2) * 512);
#pragma unroll
            for (int m = 0; m < 8; ++m) mma_bf16v(acc[m + 4], a32, B[1][m >> 1][2 * (m & 1)], B[1][m >> 1][2 * (m & 1) + 1]);
            mma_bf16v(acc[15], a63, b8[0], b8[1]);
#pragma unroll
            for (int m = 0; m < 8; ++m) mma_bf16v(acc[m + 8], a64, B[1][m >> 1][2 * (m & 1)], B[1][m >> 1][2 * (m & 1) + 1]);
#pragma unroll
            for (int m = 0; m < 4; ++m) mma_bf16v(acc[m + 12], a32, B[0][m >> 1][2 * (m & 1)], B[0][m >> 1][2 * (m & 1) + 1]);
          }
          if (lane == 0) TS(41);
          bar_sync(5, 384);
#pragma unroll unr_tail
          for (int v = 0; v < 4; ++v)
            conv_tail<4, 3, 11>(acc, pb + (P2_OFF + 56 * v + gq - 16) * 4, vv + ((v & 1) ? VV_U3 : VV_U5), v >> 1, v == 0, lane);
          if (lane == 0) TS(42);
#pragma unroll unr_tail
          for (int pi = 0; pi < 2; ++pi)
            conv_tail<8, 5, 7>(acc, pb + (P3_OFF + 88 * pi + gq - 48) * 4, vv + (pi ? VV_U7 : VV_U9), pi, pi == 0, lane);
        }
        if (lane == 0) TS(8);
        __syncwarp();
        {
          const int mt = lane >> 3;
          const uint32_t a = pb + (128 * (mt >> 1) + 16 * (lane & 7) + 8 * (mt & 1)) * 2;
#pragma unroll
          for (int ab = 0; ab < 16; ab += 2)
            stsm_x4_t(a + ab * 256, pack_bf16(acc[ab][0], acc[ab][1]), pack_bf16(acc[ab][2], acc[ab][3]),
                      pack_bf16(acc[ab + 1][0], acc[ab + 1][1]), pack_bf16(acc[ab + 1][2], acc[ab + 1][3]));
        }
        fence_async_smem();
        __syncwarp();
        if (lane < 2) mbar_arrive_cluster(BAR(B_CONVD), lane);
        __syncwarp();
        cluster_arrive();
        bar_arrive(3, 384);
        if (elect_one()) {
          bulk_store(p.yT + (size_t)d * 2048, pb, 4096);
          bulk_commit();
          bulk_wait0();
          red_relaxed_add(&g_cnt[(C_Y + (cta >> 4)) * 32], 1);
          TS(9);
        }
        bar_sync(2, 128);
        if (warp == 0 && elect_one()) {
          wait_counter(&g_cnt[(C_Y + tj) * 32], (epoch + 1) * 64);
          TS(28);
          mbar_expect_tx(BAR(B_TILE), 16384);
          tma_load_2d(sb + SM_U, &maps.yT, ti * 128, tj * 64, BAR(B_TILE));
          tma_load_2d(sb + SM_U + 8192, &maps.yT, ti * 128 + 64, tj * 64, BAR(B_TILE));
        }
        __syncwarp();
      }
      mbar_wait_long(BAR(B_TILE), pass);
      if (lane == 0) TS(26 + 3 * pass);
      {
        const int m = lane >> 3, r = lane & 7;
#pragma unroll 2
        for (int it = 0; it < 8; ++it) {
          const int tb = warp * 4 + (it >> 1), cb = (it & 1) * 4 + m;
          const uint32_t at = (tb * 8 + r) * 128 + ((cb ^ r) << 4);
          const uint32_t ac = (tb >> 3) * 8192 + (cb * 8 + r) * 128 + (((tb & 7) ^ (pass ? 0 : tb >> 3) ^ r) << 4);
          uint32_t v[4];
          ldsm_x4_t(v, sb + SM_U + (pass ? ac : at));
          stsm_x4(sb + SM_P + (pass ? at : ac), v[0], v[1], v[2], v[3]);
        }
      }
      if (pass == 0 && tid == 0) TS(35);
      fence_async_smem();
      if (pass == 0) {
        bar_arrive(6, 160);
      } else {
        bar_sync(2, 128);
        if (warp == 0 && elect_one()) {
          tma_store_2d(&maps.out, sb + SM_P, 64 * tj, 128 * ti);
          bulk_commit();
          bulk_wait_read0();
          TS(30);
        }
      }
    }
  } else if (warp < 12) {
    const int w8 = warp - 4;
    const int row = w8 * 16 + (lane & 7) + (((lane >> 3) & 1) << 3);
    uint32_t pq[16];
    {
      float acc[96];
#pragma unroll 1
      for (int ks = 0, s = 0, ph = 0; ks < 16; ++ks) {
        mbar_wait(BAR(B_FULL + s), ph);
        if (tid == 128 && !(ks & 1)) TSR(16, ks == 0 ? 16 : 9 + (ks >> 1) + (ks > 12 ? 43 : 0));
        const uint32_t st = sb + s * STG_BYTES;
        const uint32_t da = mkdesc(st + STG_X + (w8 >> 2) * 4096, 16);
        const uint32_t db = mkdesc(st + STG_W, 2048);
        wg_fence();
        wgmma_n192(acc, da, db, ks != 0);
        wgmma_n192(acc, da + 2, db + 384, 1);
        wg_commit();
        const uint32_t eprev = BAR(B_EMPTY + (s == 0 ? NSTG - 1 : s - 1));
        if (++s == NSTG) { s = 0; ph ^= 1; }
        if (ks > 0) {
          wg_wait<1>();
          if (lane < 2) mbar_arrive_cluster(eprev, lane);
        }
      }
      wg_wait<0>();
      bar_arrive(4, 384);
      if (tid == 128) TS(17);
      auto phi2 = [](float a, float b) -> uint32_t {
        const uint32_t x = pack_bf16(a, b);
        const uint32_t e = pack_bf16(ex2(a * 1.4426950408889634f), ex2(b * 1.4426950408889634f));
        const uint32_t m = __hgt2_mask(*reinterpret_cast<const __nv_bfloat162*>(&x), __floats2bfloat162_rn(0.f, 0.f));
        return badd((badd(x, 0x3f803f80u) & m) | (e & ~m), 0x35863586u);
      };
      uint32_t pk[16];
#pragma unroll
      for (int i = 0; i < 16; ++i) pk[i] = phi2(acc[32 + 2 * i], acc[33 + 2 * i]);
      if (tid == 128) TS(53);
      bar_sync(1, 256);
#pragma unroll
      for (int i = 0; i < 8; i += 2) {
        const uint32_t off = row * 128 + (((i + (lane >> 4)) ^ (row & 7)) << 4);
        stsm_x4(sb + SM_PK + off, pk[2 * i], pk[2 * i + 1], pk[2 * i + 2], pk[2 * i + 3]);
        stsm_x4(sb + SM_VS + off, pack_bf16(acc[64 + 4 * i], acc[65 + 4 * i]), pack_bf16(acc[66 + 4 * i], acc[67 + 4 * i]),
                pack_bf16(acc[68 + 4 * i], acc[69 + 4 * i]), pack_bf16(acc[70 + 4 * i], acc[71 + 4 * i]));
      }
      bar_sync(1, 256);
      {
        const int hh = w8 >> 1, dtile = w8 & 1;
        float kv[2][4] = {{0.f, 0.f, 0.f, 0.f}, {0.f, 0.f, 0.f, 0.f}}, zz[2][4] = {{0.f, 0.f, 0.f, 0.f}, {0.f, 0.f, 0.f, 0.f}};
        const int m = lane >> 3;
        const uint32_t aa = sb + SM_VS + ((lane & 7) + ((m >> 1) << 3)) * 128 + (((2 * hh + (m & 1)) ^ (lane & 7)) << 4);
        const uint32_t ab = sb + SM_PK + (lane & 15) * 128 + (((2 * hh + dtile) ^ (lane & 7)) << 4);
#pragma unroll
        for (int ks = 0; ks < 8; ++ks) {
          uint32_t a[4], b0, b1;
          ldsm_x4_t(a, aa + ks * 2048);
          ldsm_x2_t(b0, b1, ab + ks * 2048);
          mma_bf16(kv[ks & 1], a[0], a[1], a[2], a[3], b0, b1);
          mma_bf16(zz[ks & 1], 0x3f803f80u, 0x3f803f80u, 0x3f803f80u, 0x3f803f80u, b0, b1);
        }
        const uint32_t kp = sb + SM_KV + hh * 1088;
        sts128(kp + dtile * 512 + lane * 16, __float_as_uint(kv[0][0] + kv[1][0]), __float_as_uint(kv[0][1] + kv[1][1]),
               __float_as_uint(kv[0][2] + kv[1][2]), __float_as_uint(kv[0][3] + kv[1][3]));
        if (g == 0) sts_f32x2(kp + 1024 + dtile * 32 + q * 8, zz[0][0] + zz[1][0], zz[0][1] + zz[1][1]);
        fence_async_smem();
        __syncwarp();
        if (lane == 0) mbar_arrive(BAR(B_KVP));
        if (tid == 128) TS(55);
      }
#pragma unroll
      for (int i = 0; i < 16; ++i) pq[i] = phi2(acc[2 * i], acc[2 * i + 1]);
    }
    if (tid == 128) TS(56);
    if (warp == 4) mbar_wait_long(BAR(B_KVF), 0);
    bar_sync(1, 256);
    if (tid == 128) TS(19);
    {
      uint32_t kb[4][6];
#pragma unroll
      for (int h = 0; h < 4; ++h) {
        const uint32_t kp = sb + SM_KV + h * 1088;
        const uint4 k0 = lds128(kp + lane * 16), k1 = lds128(kp + 512 + lane * 16);
        const uint32_t za = kp + 1024 + q * 8;
        auto pk2 = [](uint32_t x, uint32_t y) { return pack_bf16(__uint_as_float(x), __uint_as_float(y)); };
        kb[h][0] = pk2(k0.x, k0.y); kb[h][1] = pk2(k1.x, k1.y); kb[h][2] = pk2(k0.z, k0.w); kb[h][3] = pk2(k1.z, k1.w);
        kb[h][4] = pack_bf16(lds_f32(za), lds_f32(za + 4)); kb[h][5] = pack_bf16(lds_f32(za + 32), lds_f32(za + 36));
      }
#pragma unroll
      for (int h = 0; h < 4; ++h) {
        float n0[4] = {0.f, 0.f, 0.f, 0.f}, n1[4] = {0.f, 0.f, 0.f, 0.f}, dn[4] = {0.f, 0.f, 0.f, 0.f};
        mma_bf16(n0, pq[4 * h], pq[4 * h + 1], pq[4 * h + 2], pq[4 * h + 3], kb[h][0], kb[h][1]);
        mma_bf16(n1, pq[4 * h], pq[4 * h + 1], pq[4 * h + 2], pq[4 * h + 3], kb[h][2], kb[h][3]);
        mma_bf16(dn, pq[4 * h], pq[4 * h + 1], pq[4 * h + 2], pq[4 * h + 3], kb[h][4], kb[h][5]);
        const float r0 = rcp(dn[0] + 1e-6f), r1 = rcp(dn[2] + 1e-6f);
        stsm_x4(sb + SM_QS + row * 128 + (((2 * h + (lane >> 4)) ^ (row & 7)) << 4),
                pack_bf16(n0[0] * r0, n0[1] * r0), pack_bf16(n0[2] * r1, n0[3] * r1),
                pack_bf16(n1[0] * r0, n1[1] * r0), pack_bf16(n1[2] * r1, n1[3] * r1));
      }
    }
    fence_async_smem();
    __syncwarp();
    if (lane == 0) mbar_arrive(BAR(B_OST));
    if (tid == 128) TS(57);
    bar_sync(7, 384);
    if (w8 < 7) box_filters<4>(sb, bars, w8, lane);
    bar_arrive(5, 384);
    if (tid == 128) TS(6);
    if (warp == 4) mbar_wait_long(BAR(B_WO), 0);
    bar_sync(3, 384);
    {
      float o[32];
#pragma unroll 1
      for (int c = 0; c < 8; ++c) {
        mbar_wait_long(BAR(B_RF + c), 0);
        if (tid == 128) TSR(22, c == 0 ? 22 : 43 + c);
        const uint32_t slot = c < 4 ? SM_QS + c * 16384 : c < 7 ? SM_VV + (c - 4) * 16384 : SM_QS;
        const uint32_t da = mkdesc(sb + slot + (w8 >> 2) * 8192, 16);
        const uint32_t db = mkdesc(sb + SM_WO + c * 8192, 8192);
        wg_fence();
#pragma unroll
        for (int k = 0; k < 4; ++k) wgmma_n64(o, da + 2 * k, db + 128 * k, (c | k) != 0);
        wg_commit();
        if (c == 1) {
          wg_wait<1>();
          if (lane < 2) mbar_arrive_cluster(BAR(B_RE), lane);
          __syncwarp();
          cluster_arrive();
        }
      }
      wg_wait<0>();
      if (tid == 128) TS(51);
#pragma unroll
      for (int i = 0; i < 8; i += 2)
        stsm_x4(sb + SM_BOUT + row * 128 + (((i + (lane >> 4)) ^ (row & 7)) << 4), pack_bf16(o[4 * i], o[4 * i + 1]),
                pack_bf16(o[4 * i + 2], o[4 * i + 3]), pack_bf16(o[4 * i + 4], o[4 * i + 5]), pack_bf16(o[4 * i + 6], o[4 * i + 7]));
      fence_async_smem();
      bar_sync(8 + (w8 >> 2), 128);
      if ((w8 & 3) == 0 && elect_one()) {
        tma_store_2d(&maps.outh, sb + SM_BOUT + (w8 >> 2) * 8192, 512 + 64 * pj, 128 * pi + (w8 >> 2) * 64);
        bulk_commit();
        bulk_wait_read0();
        TS(23);
      }
    }
  } else {
    asm volatile("setmaxnreg.dec.sync.aligned.u32 40;");
    if (warp == 12) {
      if (elect_one()) {
#pragma unroll 1
        for (int ks = NSTG, s = 0, ph = 0; ks < 16; ++ks) {
          mbar_wait(BAR(B_EMPTY + s), ph);
          issue_stage(ks, s);
          if (ks == NSTG) l2_prefetch((const char*)p.wo + (size_t)cta * 4096, 4096);
          if (++s == NSTG) { s = 0; ph ^= 1; }
        }
        mbar_wait(BAR(B_EMPTY + 6), 1);
        mbar_expect_tx(BAR(B_WO), 65536);
        tma_load_2d(sb + SM_WO, &maps.wo, pj * 64, 0, BAR(B_WO));
        tma_load_2d(sb + SM_WO + 32768, &maps.wo, pj * 64, 256, BAR(B_WO));
        float* kvg = &g_kv[epoch & 1][tj][0];
        mbar_wait_long(BAR(B_KVP), 0);
        bulk_reduce_add_f32(kvg, sb + SM_KV, 4352);
        bulk_commit();
        bulk_wait0();
        red_relaxed_add(&g_cnt[(C_KV + tj) * 32], 1);
        TS(18);
        wait_counter(&g_cnt[(C_KV + tj) * 32], (epoch + 1) * 16);
        mbar_expect_tx(BAR(B_KVF), 4352);
        bulk_load(sb + SM_KV, kvg, 4352, BAR(B_KVF));
        mbar_wait_long(BAR(B_OST), 0);
        tma_store_2d(&maps.o, sb + SM_QS, tj * 64, ti * 128);
        tma_store_2d(&maps.o, sb + SM_QS + 8192, tj * 64, ti * 128 + 64);
        bulk_commit();
        bulk_wait0();
        red_relaxed_add(&g_cnt[(C_O + ti) * 32], 1);
        TS(20);
        mbar_arrive_cluster(BAR(B_SLOT), 0);
        mbar_arrive_cluster(BAR(B_SLOT), 1);
        wait_counter(&g_cnt[(C_O + pi) * 32], (epoch + 1) * 8);
        if (cta == 0) g_epoch = epoch + 1;
        mbar_wait(BAR(B_SLOT), 0);
        TS(21);
#pragma unroll 1
        for (int c = 0; c < 8; ++c) {
          if (c == 4) mbar_wait_long(BAR(B_CONVD), 0);
          if (c == 7) mbar_wait(BAR(B_RE), 0);
          const uint32_t slot = c < 4 ? SM_QS + c * 16384 : c < 7 ? SM_VV + (c - 4) * 16384 : SM_QS;
          mbar_expect_tx(BAR(B_RF + c), 16384);
          tma_load_2d_mc(sb + slot + rank * 8192, &maps.o, c * 64, pi * 128 + rank * 64, BAR(B_RF + c), 3);
        }
      }
    } else if (warp == 13) {
      bar_sync(6, 160);
      sts128(sb + SM_U + (lane >> 4) * U_BYTES + (lane & 15) * 16, 0, 0, 0, 0);
      sts128(sb + SM_U + (2 + (lane >> 4)) * U_BYTES + (lane & 15) * 16, 0, 0, 0, 0);
      __syncwarp();
      if (elect_one()) {
        tma_store_2d(&maps.uT, sb + SM_P, ti * 128, tj * 64);
        tma_store_2d(&maps.uT, sb + SM_P + 8192, ti * 128 + 64, tj * 64);
        bulk_commit();
        bulk_wait_read0();
        mbar_arrive(BAR(B_PFREE));
        bulk_wait0();
        red_relaxed_add(&g_cnt[(C_U + tj) * 32], 1);
        TS(27);
        wait_counter(&g_cnt[(C_U + (cta >> 4)) * 32], (epoch + 1) * 16);
#pragma unroll 1
        for (int c = 0; c < 4; ++c) {
          mbar_expect_tx(BAR(B_UCH + c), 4096);
          bulk_load(sb + SM_U + c * U_BYTES + 256, p.uT + (size_t)(cta * 4 + c) * 2048, 4096, BAR(B_UCH + c));
        }
        TS(3);
      }
      __syncwarp();
      if (ti == 0) {
        float4* z = (float4*)&g_kv[(epoch & 1) ^ 1][tj][0];
#pragma unroll 1
        for (int i = lane; i < 272; i += 32) z[i] = make_float4(0.f, 0.f, 0.f, 0.f);
      }
    }
  }
  __syncwarp();
  if (warp >= 12) cluster_arrive();
  cluster_wait();
  if (tid == 0) TS(31);
#undef BAR
}

typedef CUresult (*EncodeFn)(CUtensorMap*, CUtensorMapDataType, cuuint32_t, void*, const cuuint64_t*, const cuuint64_t*,
                             const cuuint32_t*, const cuuint32_t*, CUtensorMapInterleave, CUtensorMapSwizzle,
                             CUtensorMapL2promotion, CUtensorMapFloatOOBfill);

static void make_map(EncodeFn enc, CUtensorMap* m, const void* base, uint64_t inner, uint64_t outer, uint32_t box_in,
                     uint32_t box_out, CUtensorMapSwizzle swz = CU_TENSOR_MAP_SWIZZLE_128B) {
  cuuint64_t gd[2] = {inner, outer};
  cuuint64_t gs[1] = {inner * 2};
  cuuint32_t bd[2] = {box_in, box_out};
  cuuint32_t es[2] = {1, 1};
  enc(m, CU_TENSOR_MAP_DATA_TYPE_BFLOAT16, 2, const_cast<void*>(base), gd, gs, bd, es, CU_TENSOR_MAP_INTERLEAVE_NONE,
      swz, CU_TENSOR_MAP_L2_PROMOTION_L2_128B, CU_TENSOR_MAP_FLOAT_OOB_FILL_NONE);
}

}

extern "C" void kernel_launch(void* const* d_in, const int* in_sizes, int n_in, void* d_out, int out_size) {
  using namespace s4la;
  (void)in_sizes; (void)n_in; (void)out_size;
  static EncodeFn enc = nullptr;
  static void *uT = nullptr, *yT = nullptr, *oS = nullptr;
  if (!enc) {
    void* fn = nullptr;
    cudaDriverEntryPointQueryResult qr;
    cudaGetDriverEntryPoint("cuTensorMapEncodeTiled", &fn, cudaEnableDefault, &qr);
    enc = (EncodeFn)fn;
    cudaGetSymbolAddress(&uT, g_uT);
    cudaGetSymbolAddress(&yT, g_yT);
    cudaGetSymbolAddress(&oS, g_o);
    cudaFuncSetAttribute(fused_kernel, cudaFuncAttributeMaxDynamicSharedMemorySize, SM_TOTAL);
  }
  const __nv_bfloat16* const* in = (const __nv_bfloat16* const*)d_in;
  Maps maps;
  make_map(enc, &maps.x, in[9], 512, 2048, 32, 128, CU_TENSOR_MAP_SWIZZLE_64B);
  {
    cuuint64_t gd[3] = {512, 512, 3};
    cuuint64_t gs[2] = {3072, 1024};
    cuuint32_t bd[3] = {64, 16, 3};
    cuuint32_t es[3] = {1, 1, 1};
    enc(&maps.w, CU_TENSOR_MAP_DATA_TYPE_BFLOAT16, 3, const_cast<__nv_bfloat16*>(in[10]), gd, gs, bd, es,
        CU_TENSOR_MAP_INTERLEAVE_NONE, CU_TENSOR_MAP_SWIZZLE_128B, CU_TENSOR_MAP_L2_PROMOTION_L2_128B,
        CU_TENSOR_MAP_FLOAT_OOB_FILL_NONE);
  }
  make_map(enc, &maps.wo, in[11], 512, 512, 64, 256);
  make_map(enc, &maps.u, in[0], 512, 2048, 64, 128);
  make_map(enc, &maps.uT, uT, 2048, 512, 64, 64);
  make_map(enc, &maps.yT, yT, 2048, 512, 64, 64);
  make_map(enc, &maps.o, oS, 512, 2048, 64, 64);
  make_map(enc, &maps.out, d_out, 1024, 2048, 64, 128);
  make_map(enc, &maps.outh, d_out, 1024, 2048, 64, 64);
  Ptrs p;
  p.A_re = in[1]; p.A_im = in[2]; p.B_re = in[3]; p.B_im = in[4]; p.C_re = in[5]; p.C_im = in[6];
  p.log_dt = in[7]; p.Dskip = in[8]; p.x = in[9]; p.wqkv = in[10]; p.wo = in[11];
  p.uT = (__nv_bfloat16*)uT; p.yT = (__nv_bfloat16*)yT;
  fused_kernel<<<NCTA, NTHREADS, SM_TOTAL, cudaStreamPerThread>>>(maps, p);
}
```

```cpp
#include <cuda_runtime.h>
#include <cuda_bf16.h>
#include <cuda_fp16.h>
#include <cuda.h>
#include <stdint.h>

#define DEVI __device__ __forceinline__

namespace s4la {

constexpr int NTHREADS = 512;
constexpr int NCTA = 128;

constexpr int NSTG = 7;
constexpr uint32_t STG_BYTES = 20480, STG_X = 0, STG_W = 8192;
constexpr uint32_t SM_QS = 0;
constexpr uint32_t SM_PK = SM_QS + 16384, SM_VS = SM_QS + 32768;
constexpr uint32_t SM_WO = 65536;
constexpr uint32_t SM_KV = 131072;
constexpr uint32_t SM_BOUT = 16384;
constexpr uint32_t SM_U = 143360, U_BYTES = 4352;
constexpr uint32_t SM_P = 160768, P_BYTES = 4096;
constexpr uint32_t SM_VV = 177152, VV_BYTES = 12800;
constexpr uint32_t VV_U5 = 0, VV_U3 = 3712, VV_U9 = 7424, VV_U7 = 10112;
constexpr uint32_t KG_BYTES = 3200;
constexpr uint32_t SM_BAR = SM_VV + 4 * VV_BYTES;
constexpr uint32_t SM_PTAB = SM_BAR + 320;
constexpr uint32_t SM_TOTAL = SM_PTAB + 2048;
static_assert(SM_TOTAL <= 232448, "shared memory");
constexpr int PADV = 12;

enum { B_FULL = 0, B_EMPTY = 7, B_TILE = 14, B_UCH = 15, B_KVP = 19, B_KVF = 20, B_OST = 21, B_RF = 22, B_WO = 30, B_RE = 31, B_PFREE = 32, B_CONVD = 33, B_SLOT = 34, B_COUNT = 35 };
__host__ __device__ constexpr int bar_count(int i) {
  return (i >= B_EMPTY && i < B_TILE) ? 16 : (i == B_KVP || i == B_OST || i == B_CONVD) ? 8 : i == B_RE ? 16 : i == B_SLOT ? 2 : 1;
}

constexpr int PD_OFF = 0, P2_OFF = 544, P3_OFF = 768;

constexpr int SL_K2048 = 20, SL_ZERO = 21, SL_510 = 22, SL_0 = 23;
__host__ __device__ constexpr int koff(int y) {
  return y < 8 ? y : y < 12 ? 256 + 2 * (y - 8) : y < 16 ? 512 + 256 * ((y - 12) >> 1) + 4 * (y & 1) : 1024 + 256 * (y - 16);
}
__host__ __device__ constexpr int kidx_c(int l) {
  const int y = l < 256 ? (l & 7) : l < 512 ? 8 + ((l & 7) >> 1) : l < 1024 ? 12 + (((l - 512) >> 8) << 1) + ((l >> 2) & 1)
                                                                            : 16 + ((l - 1024) >> 8);
  return ((l >> 3) & 31) * 24 + y;
}
constexpr int slot_direct(int l) {
  if (l < 0 || l > 510) return SL_ZERO;
  if (l == 510) return SL_510;
  if (l == 0) return SL_0;
  return kidx_c(l < 256 ? l : ((l + ((l >> 1) & 1)) & ~1));
}
constexpr int slot_seg2(int v, int k) { return (k >= 32 && k < 64) ? kidx_c(16 * k + 4 * v) : SL_ZERO; }
constexpr int slot_seg3(int pi, int k) {
  return (k >= 64 && k < 128) ? kidx_c(16 * k + 8 * pi) : ((k == 128 && pi == 0) ? SL_K2048 : SL_ZERO);
}
constexpr int slot_word(int w) {
  return w < 0 ? SL_ZERO : w < 544 ? slot_direct(w - 16) : w < 768 ? slot_seg2((w - 544) / 56, 16 + (w - 544) % 56)
       : w < 944 ? slot_seg3((w - 768) / 88, 48 + (w - 768) % 88) : SL_ZERO;
}
struct PTab { uint32_t v[512]; };
constexpr PTab make_ptab() {
  PTab t{};
  for (int lane = 0; lane < 32; ++lane)
    for (int i = 0; i < 16; ++i)
      t.v[i * 32 + lane] = (slot_word(31 * lane - 1 + 2 * i) * 4) | ((slot_word(31 * lane + 2 * i) * 4) << 16);
  return t;
}
__device__ const PTab g_ptab = make_ptab();

__device__ __nv_bfloat16 g_uT[512 * 2048];
__device__ __nv_bfloat16 g_yT[512 * 2048];
__device__ __nv_bfloat16 g_o[2048 * 512];
__device__ float g_kv[2][8][4 * 272];
__device__ unsigned g_cnt[64 * 32];
__device__ unsigned g_epoch;
#define TS(slot) do { } while (0)
#define TSR(on, slot) do { } while (0)
#define TSD(slot) do { } while (0)
enum { C_U = 0, C_KV = 8, C_O = 16, C_Y = 32 };

struct Maps {
  CUtensorMap x, w, wo, u, uT, yT, o, out, outh;
};
struct Ptrs {
  const __nv_bfloat16 *A_re, *A_im, *B_re, *B_im, *C_re, *C_im, *log_dt, *Dskip;
  const __nv_bfloat16 *x, *wqkv, *wo;
  __nv_bfloat16 *uT, *yT;
};

DEVI uint32_t s2u(const void* p) { return (uint32_t)__cvta_generic_to_shared(p); }
DEVI void mbar_init(uint32_t b, uint32_t c) { asm volatile("mbarrier.init.shared::cta.b64 [%0], %1;" ::"r"(b), "r"(c) : "memory"); }
DEVI void mbar_expect_tx(uint32_t b, uint32_t bytes) {
  asm volatile("mbarrier.arrive.expect_tx.shared::cta.b64 _, [%0], %1;" ::"r"(b), "r"(bytes) : "memory");
}
DEVI void mbar_arrive(uint32_t b) { asm volatile("mbarrier.arrive.shared::cta.b64 _, [%0];" ::"r"(b) : "memory"); }
DEVI void mbar_arrive_cluster(uint32_t b, uint32_t cta) {
  asm volatile("{\n.reg .b32 r;\nmapa.shared::cluster.u32 r, %0, %1;\nmbarrier.arrive.shared::cluster.b64 _, [r];\n}"
               ::"r"(b), "r"(cta) : "memory");
}
DEVI void mbar_wait(uint32_t b, uint32_t parity) {
  asm volatile("{\n.reg .pred p;\nLAB_WAIT:\nmbarrier.try_wait.parity.shared::cta.b64 p, [%0], %1;\n@!p bra LAB_WAIT;\n}"
               ::"r"(b), "r"(parity) : "memory");
}
DEVI void mbar_wait_long(uint32_t b, uint32_t parity) {
  asm volatile("{\n.reg .pred p;\nLAB_WAIT:\nmbarrier.try_wait.parity.shared::cta.b64 p, [%0], %1, 0x989680;\n@!p bra LAB_WAIT;\n}"
               ::"r"(b), "r"(parity) : "memory");
}
DEVI void bar_sync(int id, int n) { asm volatile("bar.sync %0, %1;" ::"r"(id), "r"(n) : "memory"); }
DEVI void bar_arrive(int id, int n) { asm volatile("bar.arrive %0, %1;" ::"r"(id), "r"(n) : "memory"); }
DEVI void fence_async_smem() { asm volatile("fence.proxy.async.shared::cta;" ::: "memory"); }
DEVI void fence_async_all() { asm volatile("fence.proxy.async;" ::: "memory"); }
DEVI void cluster_arrive() { asm volatile("barrier.cluster.arrive.relaxed.aligned;" ::: "memory"); }
DEVI void cluster_wait() { asm volatile("barrier.cluster.wait.aligned;" ::: "memory"); }

DEVI void tma_load_2d(uint32_t dst, const CUtensorMap* m, int c0, int c1, uint32_t bar) {
  asm volatile("cp.async.bulk.tensor.2d.shared::cluster.global.mbarrier::complete_tx::bytes [%0], [%1, {%3, %4}], [%2];"
               ::"r"(dst), "l"(m), "r"(bar), "r"(c0), "r"(c1) : "memory");
}
DEVI void tma_load_2d_mc(uint32_t dst, const CUtensorMap* m, int c0, int c1, uint32_t bar, uint16_t mask) {
  asm volatile("cp.async.bulk.tensor.2d.shared::cluster.global.mbarrier::complete_tx::bytes.multicast::cluster [%0], [%1, {%3, %4}], [%2], %5;"
               ::"r"(dst), "l"(m), "r"(bar), "r"(c0), "r"(c1), "h"(mask) : "memory");
}
DEVI void tma_load_3d_mc(uint32_t dst, const CUtensorMap* m, int c0, int c1, int c2, uint32_t bar, uint16_t mask) {
  asm volatile("cp.async.bulk.tensor.3d.shared::cluster.global.mbarrier::complete_tx::bytes.multicast::cluster [%0], [%1, {%3, %4, %5}], [%2], %6;"
               ::"r"(dst), "l"(m), "r"(bar), "r"(c0), "r"(c1), "r"(c2), "h"(mask) : "memory");
}
DEVI void tma_store_2d(const CUtensorMap* m, uint32_t src, int c0, int c1) {
  asm volatile("cp.async.bulk.tensor.2d.global.shared::cta.bulk_group [%0, {%2, %3}], [%1];"
               ::"l"(m), "r"(src), "r"(c0), "r"(c1) : "memory");
}
DEVI void bulk_load(uint32_t dst, const void* src, uint32_t bytes, uint32_t bar) {
  asm volatile("cp.async.bulk.shared::cluster.global.mbarrier::complete_tx::bytes [%0], [%1], %2, [%3];"
               ::"r"(dst), "l"(src), "r"(bytes), "r"(bar) : "memory");
}
DEVI void bulk_store(void* dst, uint32_t src, uint32_t bytes) {
  asm volatile("cp.async.bulk.global.shared::cta.bulk_group [%0], [%1], %2;" ::"l"(dst), "r"(src), "r"(bytes) : "memory");
}
DEVI void bulk_reduce_add_f32(void* dst, uint32_t src, uint32_t bytes) {
  asm volatile("cp.reduce.async.bulk.global.shared::cta.bulk_group.add.f32 [%0], [%1], %2;" ::"l"(dst), "r"(src), "r"(bytes) : "memory");
}
DEVI void bulk_commit() { asm volatile("cp.async.bulk.commit_group;" ::: "memory"); }
DEVI void bulk_wait0() { asm volatile("cp.async.bulk.wait_group 0;" ::: "memory"); }
DEVI void bulk_wait_read0() { asm volatile("cp.async.bulk.wait_group.read 0;" ::: "memory"); }
DEVI void l2_prefetch(const void* p, uint32_t bytes) {
  asm volatile("cp.async.bulk.prefetch.L2.global [%0], %1;" ::"l"(p), "r"(bytes) : "memory");
}
DEVI void prefetch_tmap(const CUtensorMap* m) { asm volatile("prefetch.tensormap [%0];" ::"l"(m) : "memory"); }

DEVI void red_release_add(unsigned* p, unsigned v) {
  asm volatile("red.release.gpu.global.add.u32 [%0], %1;" ::"l"(p), "r"(v) : "memory");
}
DEVI void red_relaxed_add(unsigned* p, unsigned v) {
  asm volatile("red.relaxed.gpu.global.add.u32 [%0], %1;" ::"l"(p), "r"(v) : "memory");
}
DEVI unsigned ld_relaxed(const unsigned* p) {
  unsigned v;
  asm volatile("ld.relaxed.gpu.global.u32 %0, [%1];" : "=r"(v) : "l"(p) : "memory");
  return v;
}
DEVI void wait_counter(const unsigned* p, unsigned target) {
#pragma unroll 1
  for (int it = 0; (int)(ld_relaxed(p) - target) < 0; ++it)
    if (it > (1 << 22)) __trap();
}

DEVI void ldsm_x4(uint32_t (&r)[4], uint32_t a) {
  asm volatile("ldmatrix.sync.aligned.m8n8.x4.shared.b16 {%0,%1,%2,%3}, [%4];"
               : "=r"(r[0]), "=r"(r[1]), "=r"(r[2]), "=r"(r[3]) : "r"(a) : "memory");
}
DEVI void ldsm_x4_t(uint32_t (&r)[4], uint32_t a) {
  asm volatile("ldmatrix.sync.aligned.m8n8.x4.trans.shared.b16 {%0,%1,%2,%3}, [%4];"
               : "=r"(r[0]), "=r"(r[1]), "=r"(r[2]), "=r"(r[3]) : "r"(a) : "memory");
}
DEVI void ldsm_x2_t(uint32_t& r0, uint32_t& r1, uint32_t a) {
  asm volatile("ldmatrix.sync.aligned.m8n8.x2.trans.shared.b16 {%0,%1}, [%2];" : "=r"(r0), "=r"(r1) : "r"(a) : "memory");
}
DEVI void stsm_x4(uint32_t a, uint32_t r0, uint32_t r1, uint32_t r2, uint32_t r3) {
  asm volatile("stmatrix.sync.aligned.m8n8.x4.shared.b16 [%0], {%1,%2,%3,%4};"
               ::"r"(a), "r"(r0), "r"(r1), "r"(r2), "r"(r3) : "memory");
}
DEVI void stsm_x4_t(uint32_t a, uint32_t r0, uint32_t r1, uint32_t r2, uint32_t r3) {
  asm volatile("stmatrix.sync.aligned.m8n8.x4.trans.shared.b16 [%0], {%1,%2,%3,%4};"
               ::"r"(a), "r"(r0), "r"(r1), "r"(r2), "r"(r3) : "memory");
}
DEVI uint32_t lds32(uint32_t a) { uint32_t v; asm volatile("ld.shared.b32 %0, [%1];" : "=r"(v) : "r"(a) : "memory"); return v; }
DEVI float lds_f32(uint32_t a) { float v; asm volatile("ld.shared.f32 %0, [%1];" : "=f"(v) : "r"(a) : "memory"); return v; }
DEVI void sts32(uint32_t a, uint32_t v) { asm volatile("st.shared.b32 [%0], %1;" ::"r"(a), "r"(v) : "memory"); }
DEVI void sts_f32(uint32_t a, float v) { asm volatile("st.shared.f32 [%0], %1;" ::"r"(a), "f"(v) : "memory"); }
DEVI void sts_f32x2(uint32_t a, float x, float y) { asm volatile("st.shared.v2.f32 [%0], {%1,%2};" ::"r"(a), "f"(x), "f"(y) : "memory"); }
DEVI uint4 lds128(uint32_t a) {
  uint4 v;
  asm volatile("ld.shared.v4.b32 {%0,%1,%2,%3}, [%4];" : "=r"(v.x), "=r"(v.y), "=r"(v.z), "=r"(v.w) : "r"(a) : "memory");
  return v;
}
DEVI void sts128(uint32_t a, uint32_t x, uint32_t y, uint32_t z, uint32_t w) {
  asm volatile("st.shared.v4.b32 [%0], {%1,%2,%3,%4};" ::"r"(a), "r"(x), "r"(y), "r"(z), "r"(w) : "memory");
}

DEVI void mma_bf16(float (&d)[4], uint32_t a0, uint32_t a1, uint32_t a2, uint32_t a3, uint32_t b0, uint32_t b1) {
  asm("mma.sync.aligned.m16n8k16.row.col.f32.bf16.bf16.f32 {%0,%1,%2,%3}, {%4,%5,%6,%7}, {%8,%9}, {%0,%1,%2,%3};"
      : "+f"(d[0]), "+f"(d[1]), "+f"(d[2]), "+f"(d[3])
      : "r"(a0), "r"(a1), "r"(a2), "r"(a3), "r"(b0), "r"(b1));
}
DEVI void mma_f16(float (&d)[4], const uint32_t (&a)[4], uint32_t b0, uint32_t b1) {
  asm("mma.sync.aligned.m16n8k16.row.col.f32.f16.f16.f32 {%0,%1,%2,%3}, {%4,%5,%6,%7}, {%8,%9}, {%0,%1,%2,%3};"
      : "+f"(d[0]), "+f"(d[1]), "+f"(d[2]), "+f"(d[3])
      : "r"(a[0]), "r"(a[1]), "r"(a[2]), "r"(a[3]), "r"(b0), "r"(b1));
}
DEVI void mma_bf16v(float (&d)[4], const uint32_t (&a)[4], uint32_t b0, uint32_t b1) {
  asm volatile("mma.sync.aligned.m16n8k16.row.col.f32.bf16.bf16.f32 {%0,%1,%2,%3}, {%4,%5,%6,%7}, {%8,%9}, {%0,%1,%2,%3};"
               : "+f"(d[0]), "+f"(d[1]), "+f"(d[2]), "+f"(d[3])
               : "r"(a[0]), "r"(a[1]), "r"(a[2]), "r"(a[3]), "r"(b0), "r"(b1));
}
DEVI uint32_t pack_bf16(float lo, float hi) {
  uint32_t r;
  asm("cvt.rn.bf16x2.f32 %0, %1, %2;" : "=r"(r) : "f"(hi), "f"(lo));
  return r;
}
DEVI uint32_t pack_f16(float lo, float hi) {
  uint32_t r;
  asm("cvt.rn.f16x2.f32 %0, %1, %2;" : "=r"(r) : "f"(hi), "f"(lo));
  return r;
}
DEVI uint32_t ldg16(const __nv_bfloat16* p) {
  uint32_t v;
  asm volatile("ld.global.nc.u16 %0, [%1];" : "=r"(v) : "l"(p));
  return v;
}
DEVI bool elect_one() {
  uint32_t pred;
  asm volatile("{\n.reg .pred p;\nelect.sync _|p, 0xffffffff;\nselp.u32 %0, 1, 0, p;\n}" : "=r"(pred));
  return pred != 0;
}
DEVI float bf_lo(uint32_t v) { return __uint_as_float(v << 16); }
DEVI float bf_hi(uint32_t v) { return __uint_as_float(v & 0xffff0000u); }
DEVI float bf2f(__nv_bfloat16 v) { return __bfloat162float(v); }
DEVI float round_bf16(float v) { return __bfloat162float(__float2bfloat16_rn(v)); }
DEVI float rcp(float x) { float r; asm("rcp.approx.ftz.f32 %0, %1;" : "=f"(r) : "f"(x)); return r; }
DEVI float ex2(float x) { float r; asm("ex2.approx.ftz.f32 %0, %1;" : "=f"(r) : "f"(x)); return r; }

DEVI void wg_fence() { asm volatile("wgmma.fence.sync.aligned;" ::: "memory"); }
DEVI void wg_commit() { asm volatile("wgmma.commit_group.sync.aligned;" ::: "memory"); }
template <int N> DEVI void wg_wait() { asm volatile("wgmma.wait_group.sync.aligned %0;" ::"n"(N) : "memory"); }
constexpr uint32_t DESC_HI = (1u << 30) | (1024 >> 4);
constexpr uint32_t DESC_HI64 = (2u << 30) | (512 >> 4);
DEVI uint32_t mkdesc(uint32_t saddr, uint32_t lbo) { return ((saddr & 0x3FFFF) >> 4) | ((lbo >> 4) << 16); }

#define R8(b) "%" #b
DEVI void wgmma_n192(float (&d)[96], uint32_t da, uint32_t db, int scale_d) {
  asm volatile(
      "{\n.reg .pred p;\n.reg .b64 da, db;\nsetp.ne.b32 p, %98, 0;\nmov.b64 da, {%96, %100};\nmov.b64 db, {%97, %99};\n"
      "wgmma.mma_async.sync.aligned.m64n192k16.f32.bf16.bf16 "
      "{%0,%1,%2,%3,%4,%5,%6,%7,%8,%9,%10,%11,%12,%13,%14,%15,"
      "%16,%17,%18,%19,%20,%21,%22,%23,%24,%25,%26,%27,%28,%29,%30,%31,"
      "%32,%33,%34,%35,%36,%37,%38,%39,%40,%41,%42,%43,%44,%45,%46,%47,"
      "%48,%49,%50,%51,%52,%53,%54,%55,%56,%57,%58,%59,%60,%61,%62,%63,"
      "%64,%65,%66,%67,%68,%69,%70,%71,%72,%73,%74,%75,%76,%77,%78,%79,"
      "%80,%81,%82,%83,%84,%85,%86,%87,%88,%89,%90,%91,%92,%93,%94,%95}, "
      "da, db, p, 1, 1, 0, 1;\n}"
      : "+f"(d[0]), "+f"(d[1]), "+f"(d[2]), "+f"(d[3]), "+f"(d[4]), "+f"(d[5]), "+f"(d[6]), "+f"(d[7]),
        "+f"(d[8]), "+f"(d[9]), "+f"(d[10]), "+f"(d[11]), "+f"(d[12]), "+f"(d[13]), "+f"(d[14]), "+f"(d[15]),
        "+f"(d[16]), "+f"(d[17]), "+f"(d[18]), "+f"(d[19]), "+f"(d[20]), "+f"(d[21]), "+f"(d[22]), "+f"(d[23]),
        "+f"(d[24]), "+f"(d[25]), "+f"(d[26]), "+f"(d[27]), "+f"(d[28]), "+f"(d[29]), "+f"(d[30]), "+f"(d[31]),
        "+f"(d[32]), "+f"(d[33]), "+f"(d[34]), "+f"(d[35]), "+f"(d[36]), "+f"(d[37]), "+f"(d[38]), "+f"(d[39]),
        "+f"(d[40]), "+f"(d[41]), "+f"(d[42]), "+f"(d[43]), "+f"(d[44]), "+f"(d[45]), "+f"(d[46]), "+f"(d[47]),
        "+f"(d[48]), "+f"(d[49]), "+f"(d[50]), "+f"(d[51]), "+f"(d[52]), "+f"(d[53]), "+f"(d[54]), "+f"(d[55]),
        "+f"(d[56]), "+f"(d[57]), "+f"(d[58]), "+f"(d[59]), "+f"(d[60]), "+f"(d[61]), "+f"(d[62]), "+f"(d[63]),
        "+f"(d[64]), "+f"(d[65]), "+f"(d[66]), "+f"(d[67]), "+f"(d[68]), "+f"(d[69]), "+f"(d[70]), "+f"(d[71]),
        "+f"(d[72]), "+f"(d[73]), "+f"(d[74]), "+f"(d[75]), "+f"(d[76]), "+f"(d[77]), "+f"(d[78]), "+f"(d[79]),
        "+f"(d[80]), "+f"(d[81]), "+f"(d[82]), "+f"(d[83]), "+f"(d[84]), "+f"(d[85]), "+f"(d[86]), "+f"(d[87]),
        "+f"(d[88]), "+f"(d[89]), "+f"(d[90]), "+f"(d[91]), "+f"(d[92]), "+f"(d[93]), "+f"(d[94]), "+f"(d[95])
      : "r"(da), "r"(db), "r"(scale_d), "n"(DESC_HI), "n"(DESC_HI64));
}
DEVI void wgmma_n64(float (&d)[32], uint32_t da, uint32_t db, int scale_d) {
  asm volatile(
      "{\n.reg .pred p;\n.reg .b64 da, db;\nsetp.ne.b32 p, %34, 0;\nmov.b64 da, {%32, %35};\nmov.b64 db, {%33, %35};\n"
      "wgmma.mma_async.sync.aligned.m64n64k16.f32.bf16.bf16 "
      "{%0,%1,%2,%3,%4,%5,%6,%7,%8,%9,%10,%11,%12,%13,%14,%15,"
      "%16,%17,%18,%19,%20,%21,%22,%23,%24,%25,%26,%27,%28,%29,%30,%31}, "
      "da, db, p, 1, 1, 0, 1;\n}"
      : "+f"(d[0]), "+f"(d[1]), "+f"(d[2]), "+f"(d[3]), "+f"(d[4]), "+f"(d[5]), "+f"(d[6]), "+f"(d[7]),
        "+f"(d[8]), "+f"(d[9]), "+f"(d[10]), "+f"(d[11]), "+f"(d[12]), "+f"(d[13]), "+f"(d[14]), "+f"(d[15]),
        "+f"(d[16]), "+f"(d[17]), "+f"(d[18]), "+f"(d[19]), "+f"(d[20]), "+f"(d[21]), "+f"(d[22]), "+f"(d[23]),
        "+f"(d[24]), "+f"(d[25]), "+f"(d[26]), "+f"(d[27]), "+f"(d[28]), "+f"(d[29]), "+f"(d[30]), "+f"(d[31])
      : "r"(da), "r"(db), "r"(scale_d), "n"(DESC_HI));
}

struct C32 { float re, im; };
DEVI C32 csq(C32 a) { return {a.re * a.re - a.im * a.im, 2.f * a.re * a.im}; }
DEVI C32 cmul(C32 a, C32 b) { return {a.re * b.re - a.im * b.im, a.re * b.im + a.im * b.re}; }
DEVI C32 cfresh(float zl, float zi, float m) {
  float mag = ex2(zl * m), ph = zi * m;
  return {mag * __cosf(ph), mag * __sinf(ph)};
}
struct HMul { uint32_t b, bp; };
DEVI HMul mk_mul(float re, float im) { return {pack_f16(re, im), pack_f16(-im, re)}; }
DEVI uint32_t hcmul(uint32_t a, const HMul& m) {
  __half2 ah = *reinterpret_cast<__half2*>(&a);
  __half2 b = *reinterpret_cast<const __half2*>(&m.b), bp = *reinterpret_cast<const __half2*>(&m.bp);
  __half2 r = __hfma2(__high2half2(ah), bp, __hmul2(__low2half2(ah), b));
  return *reinterpret_cast<uint32_t*>(&r);
}
DEVI uint32_t badd(uint32_t a, uint32_t b) {
  __nv_bfloat162 r = __hadd2(*reinterpret_cast<__nv_bfloat162*>(&a), *reinterpret_cast<__nv_bfloat162*>(&b));
  return *reinterpret_cast<uint32_t*>(&r);
}
template <int MU0, int NMU, int DMAX>
DEVI void conv_tail(float (&acc)[16][4], uint32_t p_lane, uint32_t v_base, int back, bool edge, int lane) {
  const int hsel = (lane >> 3) & 1;
  const int row = (lane & 7) + ((lane >> 4) << 3) + PADV - 8 - (back & (hsel ^ 1));
  const uint32_t la = v_base + row * 32 + (((hsel ^ back) ^ ((row >> 2) & 1)) << 4);
  uint32_t M[3][4];
  ldsm_x4_t(M[0], la);
  ldsm_x4_t(M[1], la + 256);
  uint32_t H[2 * NMU];
#pragma unroll
  for (int i = 0; i < 2 * NMU; ++i) H[i ^ 1] = lds32(p_lane + (uint32_t)(MU0 - 1 + i) * 32);
  if (edge) {
    const uint32_t a[4] = {0u, 0u, M[0][0], M[0][1]};
#pragma unroll
    for (int k = 1; k < NMU; ++k) mma_bf16v(acc[MU0 - 2 + 2 * k], a, H[2 * k], H[2 * k + 1]);
  }
#pragma unroll
  for (int delta = -1; delta <= DMAX; ++delta) {
    if (delta + 2 <= DMAX) ldsm_x4_t(M[(delta + 3) % 3], la + (delta + 3) * 256);
#pragma unroll
    for (int k = 0; k < NMU; ++k)
      if (delta + MU0 + 2 * k < 16) mma_bf16v(acc[delta + MU0 + 2 * k], M[(delta + 1) % 3], H[2 * k], H[2 * k + 1]);
  }
}

template <int NB>
DEVI void box_filters(uint32_t sb, uint32_t bars, int idx, int lane) {
  auto swz = [](int k, int pad) { const int r = (k >> 1) + pad; return (uint32_t)(r * 32 + (((k & 1) ^ ((r >> 2) & 1)) << 4)); };
  const uint32_t o0 = swz(lane - 3, 8), o1 = swz(lane - 2, 8), o2 = swz(lane - 1, 8), ow = swz(lane - 2, PADV), oz = swz(lane - 18, PADV);
  const int k = 32 * idx - 2 + lane;
#pragma unroll 1
  for (int c2 = 0; c2 < 4; c2 += NB) {
    uint4 t[NB][3];
#pragma unroll
    for (int b = 0; b < NB; ++b) mbar_wait_long(bars + 8 * (B_UCH + c2 + b), 0);
#pragma unroll
    for (int b = 0; b < NB; ++b) {
      const uint32_t ua = sb + SM_U + (c2 + b) * U_BYTES + idx * 512;
      t[b][0] = lds128(ua + o0); t[b][1] = lds128(ua + o1); t[b][2] = lds128(ua + o2);
    }
#pragma unroll
    for (int b = 0; b < NB; ++b) {
      const uint32_t vb = sb + SM_VV + (c2 + b) * VV_BYTES, aw = vb + idx * 512 + ow;
      const uint32_t E[12] = {t[b][0].x, t[b][0].y, t[b][0].z, t[b][0].w, t[b][1].x, t[b][1].y, t[b][1].z, t[b][1].w,
                              t[b][2].x, t[b][2].y, t[b][2].z, t[b][2].w};
      uint32_t O[8];
#pragma unroll
      for (int j = 0; j < 8; ++j) O[j] = __byte_perm(E[j + 1], E[j + 2], 0x5432);
      uint32_t s3[6], s5[4], s7[4], s9[4];
#pragma unroll
      for (int j = 0; j < 6; ++j) s3[j] = badd(badd(O[j], O[j + 1]), E[j + 2]);
#pragma unroll
      for (int j = 0; j < 4; ++j) {
        s5[j] = badd(s3[j + 2], badd(E[j + 3], E[j + 5]));
        s7[j] = badd(s5[j], badd(O[j + 1], O[j + 4]));
        s9[j] = badd(s7[j], badd(E[j + 2], E[j + 6]));
      }
      if (k < 208) { sts128(aw + VV_U3, s3[0], s3[1], s3[2], s3[3]); sts128(aw + VV_U5, s5[0], s5[1], s5[2], s5[3]); }
      if (k < 144) { sts128(aw + VV_U7, s7[0], s7[1], s7[2], s7[3]); sts128(aw + VV_U9, s9[0], s9[1], s9[2], s9[3]); }
      if (idx == 0 && lane < 16) {
        sts128(vb + oz + VV_U3, 0, 0, 0, 0); sts128(vb + oz + VV_U5, 0, 0, 0, 0);
        sts128(vb + oz + VV_U7, 0, 0, 0, 0); sts128(vb + oz + VV_U9, 0, 0, 0, 0);
      }
    }
  }
}

__global__ void __cluster_dims__(2, 1, 1) __launch_bounds__(NTHREADS, 1)
fused_kernel(const __grid_constant__ Maps maps, const Ptrs p) {
  extern __shared__ __align__(1024) uint8_t smem[];
  const uint32_t sb = s2u(smem);
  const int tid = threadIdx.x, lane = tid & 31;
  const int warp = __shfl_sync(0xffffffffu, tid >> 5, 0);
  const int cta = blockIdx.x;
  const uint32_t rank = cta & 1;
  const int ti = 2 * (cta >> 4) + rank;
  const int tj = (cta >> 1) & 7;
  const int pi = cta >> 3, pj = cta & 7;
  const uint32_t bars = sb + SM_BAR;
#define BAR(i) (bars + 8 * (i))
  const int g = lane >> 2, q = lane & 3;

  auto issue_stage = [&](int ks, int s) {
    const uint32_t st = sb + s * STG_BYTES, fb = BAR(B_FULL + s);
    mbar_expect_tx(fb, STG_BYTES);
    tma_load_2d(st + STG_X, &maps.x, ks * 32, ti * 128, fb);
    tma_load_3d_mc(st + STG_W + rank * 6144, &maps.w, tj * 64, ks * 32 + rank * 16, 0, fb, 3);
  };

  const int kch = warp & 3, krd = warp >> 2;
  float zr, zi, wr, wi;
  unsigned epoch;
  uint32_t r_dskip;
  {
    const size_t po = (size_t)(cta * 4 + kch) * 128 + krd * 32 + lane;
    const uint32_t r_ar = ldg16(p.A_re + po), r_ai = ldg16(p.A_im + po), r_br = ldg16(p.B_re + po), r_bi = ldg16(p.B_im + po);
    const uint32_t r_cr = ldg16(p.C_re + po), r_ci = ldg16(p.C_im + po), r_ldt = ldg16(p.log_dt + cta * 4 + kch);
    epoch = __ldcg(&g_epoch);
    r_dskip = ldg16(p.Dskip + cta * 4 + kch);
    uint4 pt;
    if (tid < 128) pt = __ldg((const uint4*)g_ptab.v + tid);
    if (tid == 384) {
      TS(0);
#pragma unroll
      for (int i = 0; i < B_COUNT; ++i) mbar_init(BAR(i), bar_count(i));
      asm volatile("fence.mbarrier_init.release.cluster;" ::: "memory");
      prefetch_tmap(&maps.x); prefetch_tmap(&maps.w); prefetch_tmap(&maps.u);
    }
    __syncthreads();
    cluster_arrive();
    if (warp >= 12) {
      cluster_wait();
      if (elect_one()) {
        if (warp == 13) {
#define U_POS 0
          if (U_POS == 0) { mbar_expect_tx(BAR(B_TILE), 16384); tma_load_2d(sb + SM_U, &maps.u, tj * 64, ti * 128, BAR(B_TILE)); }
          prefetch_tmap(&maps.uT); prefetch_tmap(&maps.wo); prefetch_tmap(&maps.o); prefetch_tmap(&maps.yT);
          prefetch_tmap(&maps.out); prefetch_tmap(&maps.outh);
        } else {
          if (warp == 12) TS(61);
          { const int ks = warp == 12 ? 0 : warp - 13; issue_stage(ks, ks); }
        }
      }
      __syncwarp();
    }
    if (tid < 128) sts128(sb + SM_PTAB + tid * 16, pt.x, pt.y, pt.z, pt.w);
    const float dt = round_bf16(expf(bf_lo(r_ldt)));
    zr = dt * bf_lo(r_ar); zi = dt * bf_lo(r_ai);
    const float dbr = dt * bf_lo(r_br), dbi = dt * bf_lo(r_bi), cr = bf_lo(r_cr), ci = bf_lo(r_ci);
    wr = cr * dbr - ci * dbi; wi = cr * dbi + ci * dbr;
  }
  {
    const float mz = __uint_as_float(__reduce_max_sync(0xffffffffu, __float_as_uint(fmaxf(zr, 0.f))));
    const int E = min(max((int)(__reduce_max_sync(0xffffffffu, __float_as_uint(fmaxf(fabsf(wr), fabsf(wi)))) >> 23), 1), 252);
    const float sc = __int_as_float((253 - E) << 23), inv = __int_as_float((E + 1) << 23);
    const float zl = (zr - mz) * 1.4426950408889634f;
    const uint32_t tb = sb + SM_VV + kch * VV_BYTES + krd * KG_BYTES;
    const uint32_t sta = tb + (((lane >> 2) << 4) | ((lane & 3) << 2));
    auto put = [&](int r, uint32_t v) { sts32((sta ^ ((r & 7) << 4)) + r * 128, v); };
    const uint32_t lda = tb + ((lane & 7) + (((lane >> 3) & 1) << 3)) * 128;
    const uint32_t ldb = tb + ((lane & 7) + ((lane >> 4) << 3)) * 128;
#define STG_POS 0
#define PF_POS 1
    if (U_POS == 1 && warp == 13 && elect_one()) { mbar_expect_tx(BAR(B_TILE), 16384); tma_load_2d(sb + SM_U, &maps.u, tj * 64, ti * 128, BAR(B_TILE)); }
    if (STG_POS == 0 && warp >= 14 && elect_one()) { issue_stage(warp - 11, warp - 11); issue_stage(warp - 9, warp - 9); }
    if (PF_POS == 0 && warp >= 14 && elect_one()) {
      if (warp == 14) l2_prefetch((const char*)p.wqkv + 224 * 3072 + cta * 6912, 6912);
      else l2_prefetch((const char*)p.x + (size_t)cta * 16384, 16384);
    }
    __syncwarp();
    C32 e1 = cfresh(zl, zi, 1.f), e2 = csq(e1), e4 = csq(e2), e8 = csq(e4);
    C32 e16 = cfresh(zl, zi, 16.f), e32 = csq(e16), e64 = csq(e32), e128 = csq(e64);
    C32 e256 = cfresh(zl, zi, 256.f), e512 = csq(e256), e1024 = csq(e512), e768 = cmul(e512, e256);
    uint32_t XA[2][4][4];
    {
      const HMul m16 = mk_mul(e16.re, e16.im), m32 = mk_mul(e32.re, e32.im), m64 = mk_mul(e64.re, e64.im);
      const HMul m128 = mk_mul(e128.re, e128.im);
      uint32_t X[16];
      X[0] = 0x00003c00u; X[1] = pack_f16(e8.re, e8.im); X[2] = m16.b; X[4] = m32.b; X[8] = m64.b;
      X[3] = hcmul(X[1], m16); X[5] = hcmul(X[1], m32); X[6] = hcmul(X[2], m32); X[7] = hcmul(X[3], m32);
#pragma unroll
      for (int r = 1; r < 8; ++r) X[8 + r] = hcmul(X[r], m64);
#pragma unroll
      for (int h = 0; h < 2; ++h) {
#pragma unroll
        for (int r = 0; r < 16; ++r) put(r, h == 0 ? X[r] : r == 0 ? m128.b : hcmul(X[r], m128));
        __syncwarp();
#pragma unroll
        for (int k = 0; k < 4; ++k) ldsm_x4(XA[h][k], lda + (((2 * k + (lane >> 4)) ^ (lane & 7)) << 4));
        __syncwarp();
      }
    }
    if (U_POS == 2 && warp == 13 && elect_one()) { mbar_expect_tx(BAR(B_TILE), 16384); tma_load_2d(sb + SM_U, &maps.u, tj * 64, ti * 128, BAR(B_TILE)); }
    if (STG_POS == 1 && warp >= 14 && elect_one()) { issue_stage(warp - 11, warp - 11); issue_stage(warp - 9, warp - 9); }
#define PF_MODE 3
    if (PF_POS == 1 && warp >= 14 && elect_one()) {
      if (warp == 14) { if (PF_MODE & 1) l2_prefetch((const char*)p.wqkv + 224 * 3072 + cta * 6912, 6912); }
      else if (PF_MODE & 2) l2_prefetch((const char*)p.x + (size_t)cta * 16384, 16384);
      else if (PF_MODE & 4) {
#pragma unroll 1
        for (int r = 0; r < 16; ++r) l2_prefetch((const char*)p.x + (size_t)(cta * 16 + r) * 1024 + 448, 576);
      }
    }
    __syncwarp();
    float D[2][3][4];
#pragma unroll
    for (int t = 0; t < 6; ++t) D[t / 3][t % 3][0] = D[t / 3][t % 3][1] = D[t / 3][t % 3][2] = D[t / 3][t % 3][3] = 0.f;
    auto contract = [&](int t0, int nt) {
      __syncwarp();
#pragma unroll
      for (int k = 0; k < 4; ++k) {
        uint32_t b[4];
        ldsm_x4(b, ldb + (((2 * k + ((lane >> 3) & 1)) ^ (lane & 7)) << 4));
#pragma unroll
        for (int h = 0; h < 2; ++h) {
          mma_f16(D[h][t0], XA[h][k], b[0], b[1]);
          if (nt == 2) mma_f16(D[h][t0 + 1], XA[h][k], b[2], b[3]);
        }
      }
      __syncwarp();
    };
    const HMul c1 = mk_mul(e1.re, -e1.im), c2 = mk_mul(e2.re, -e2.im), c4 = mk_mul(e4.re, -e4.im);
    const HMul c256 = mk_mul(e256.re, -e256.im), c512 = mk_mul(e512.re, -e512.im), c768 = mk_mul(e768.re, -e768.im);
    const HMul c1024 = mk_mul(e1024.re, -e1024.im);
    uint32_t W[8];
    W[0] = pack_f16(wr * sc, -wi * sc);
    W[1] = hcmul(W[0], c1); W[2] = hcmul(W[0], c2); W[3] = hcmul(W[1], c2);
    W[4] = hcmul(W[0], c4); W[5] = hcmul(W[1], c4); W[6] = hcmul(W[2], c4); W[7] = hcmul(W[3], c4);
#pragma unroll
    for (int i = 0; i < 8; ++i) put(i, W[i]);
#pragma unroll
    for (int i = 0; i < 4; ++i) put(8 + i, hcmul(W[2 * i], c256));
    put(12, hcmul(W[0], c512)); put(13, hcmul(W[4], c512)); put(14, hcmul(W[0], c768)); put(15, hcmul(W[4], c768));
    if (PF_POS == 2 && warp >= 14 && elect_one()) {
      if (warp == 14) l2_prefetch((const char*)p.wqkv + 224 * 3072 + cta * 6912, 6912);
      else l2_prefetch((const char*)p.x + (size_t)cta * 16384, 16384);
    }
    contract(0, 2);
    const uint32_t v0 = hcmul(W[0], c1024);
    put(0, v0); put(1, hcmul(v0, c256)); put(2, hcmul(v0, c512)); put(3, hcmul(v0, c768)); put(4, hcmul(v0, c1024));
    contract(2, 1);
    const uint32_t a = tb + (g * 24 + 2 * q) * 4;
#pragma unroll
    for (int t = 0; t < 6; ++t) {
      const float(&d)[4] = D[t / 3][t % 3];
      sts_f32x2(a + (t / 3) * 1536 + (t % 3) * 32, d[0], d[1]);
      sts_f32x2(a + (t / 3) * 1536 + (t % 3) * 32 + 768, d[2], d[3]);
    }
    if (lane == 0) sts_f32(tb + 3072, inv);
    if (mz > 0.f) {
      __syncwarp();
#pragma unroll 1
      for (int i = lane; i < 768; i += 32) {
        const int r = i / 24, y = i - 24 * r;
        sts_f32(tb + i * 4, lds_f32(tb + i * 4) * ex2(mz * 1.4426950408889634f * (koff(y) + 8 * r)));
      }
    }
  }
  if (tid == 0) TS(2);
  if (warp < 12) cluster_wait();
  __syncthreads();

  if (warp < 4) {
#define A_REGS 200
    asm volatile("setmaxnreg.inc.sync.aligned.u32 %0;" ::"n"(A_REGS));
    if (tid == 0) TS(34);
    const int d = cta * 4 + warp;
    const uint32_t vv = sb + SM_VV + warp * VV_BYTES;
    const uint32_t ub = sb + SM_U + warp * U_BYTES;
    const uint32_t pb = sb + SM_P + warp * P_BYTES;
    const float dskip = bf_lo(r_dskip);
#pragma unroll 1
    for (int pass = 0; pass < 2; ++pass) {
      if (pass == 1) {
        const uint32_t kf = vv;
        const float i0 = lds_f32(kf + 3072), i1 = lds_f32(kf + KG_BYTES + 3072), i2 = lds_f32(kf + 2 * KG_BYTES + 3072);
        const float i3 = lds_f32(kf + 3 * KG_BYTES + 3072);
#pragma unroll 2
        for (int i = 0; i < 6; ++i) {
          const uint32_t a = kf + (i * 32 + lane) * 16;
          const uint4 x0 = lds128(a), x1 = lds128(a + KG_BYTES), x2 = lds128(a + 2 * KG_BYTES), x3 = lds128(a + 3 * KG_BYTES);
          auto s4 = [&](uint32_t a0, uint32_t a1, uint32_t a2, uint32_t a3) {
            return __float_as_uint(fmaf(__uint_as_float(a0), i0, __uint_as_float(a1) * i1) +
                                   fmaf(__uint_as_float(a2), i2, __uint_as_float(a3) * i3));
          };
          sts128(a, s4(x0.x, x1.x, x2.x, x3.x), s4(x0.y, x1.y, x2.y, x3.y), s4(x0.z, x1.z, x2.z, x3.z), s4(x0.w, x1.w, x2.w, x3.w));
        }
        __syncwarp();
        const float k1024 = lds_f32(kf + kidx_c(1024) * 4);
        if (lane == 0) {
          sts_f32(kf + SL_ZERO * 4, 0.f);
          sts_f32(kf + SL_510 * 4, lds_f32(kf + kidx_c(510) * 4) - lds_f32(kf + kidx_c(512) * 4));
          sts_f32(kf + SL_0 * 4, lds_f32(kf) + dskip);
        }
        __syncwarp();
        if (tid == 0) TS(36);
        mbar_wait_long(BAR(B_PFREE), 0);
        if (tid == 0) TS(37);
        {
          float prev = 0.f;
#pragma unroll 1
          for (int i0 = 0; i0 < 16; i0 += 4) {
            uint32_t e[4];
            float a[4], b[4];
#pragma unroll
            for (int i = 0; i < 4; ++i) e[i] = lds32(sb + SM_PTAB + ((i0 + i) * 32 + lane) * 4);
#pragma unroll
            for (int i = 0; i < 4; ++i) { a[i] = lds_f32(kf + (e[i] & 0xffff)); b[i] = lds_f32(kf + (e[i] >> 16)); }
#pragma unroll
            for (int i = 0; i < 4; ++i) {
              const uint32_t w = pb + (31 * lane + 2 * (i0 + i)) * 4;
              if (i0 + i > 0) sts32(w - 4, pack_bf16(a[i], prev));
              sts32(w, pack_bf16(b[i], a[i]));
              prev = b[i];
            }
          }
        }
        __syncwarp();
        if (lane == 0) TS(4);
        const int gq = g - 2 * q;
        uint32_t h127, h128;
        {
          const uint32_t kf2 = pack_bf16(k1024, k1024) ^ 0x80008000u;
          h127 = (gq == 4 ? 0x0000ffffu : gq == 5 ? 0xffffffffu : gq == 6 ? 0xffff0000u : 0u) & kf2;
          h128 = (gq == -4 ? 0x0000ffffu : gq == -3 ? 0xffffffffu : gq == -2 ? 0xffff0000u : 0u) & kf2;
        }
        bar_arrive(7, 384);
        if (lane == 0) TS(6);
        bar_sync(4, 384);
        mbar_wait_long(BAR(B_UCH + warp), 0);
        if (lane == 0) TS(7);
        float acc[16][4];
#pragma unroll
        for (int i = 0; i < 16; ++i) { acc[i][0] = acc[i][1] = acc[i][2] = acc[i][3] = 0.f; }
        {
          const uint32_t pd_lane = pb + (PD_OFF + 16 + gq) * 4;
          const int prow0 = 8 + (lane & 7) + ((lane >> 4) << 3), hs = (lane >> 3) & 1;
          const uint32_t zero = (uint32_t)cta >> 20;
          uint32_t B[2][4][4];
          uint32_t A[4][4];
          const uint32_t la0 = ub + prow0 * 32 + ((hs ^ ((prow0 >> 2) & 1)) << 4);
#pragma unroll
          for (int m2 = 0; m2 < 4; ++m2) ldsm_x4(B[0][m2], la0 + m2 * 512);
#pragma unroll
          for (int i = 0; i < 4; ++i) {
            const uint32_t a = pd_lane + i * 512;
            A[i][0] = lds32(a); A[i][1] = lds32(a + 32); A[i][2] = lds32(a - 32); A[i][3] = lds32(a + zero);
          }
          uint32_t la = la0;
#define UNR_RHO 4
#define UNR_TAIL 4
          constexpr int unr_rho = UNR_RHO, unr_tail = UNR_TAIL;
#pragma unroll unr_rho
          for (int rho = 0; rho < 8; ++rho) {
#pragma unroll
            for (int m2 = 0; m2 < 4; ++m2) ldsm_x4(B[1][m2], la + (4 + m2) * 512);
#pragma unroll
            for (int i = 0; i < 4; ++i)
#pragma unroll
              for (int m = 0; m < 8; ++m) mma_bf16v(acc[m + i], A[i], B[0][m >> 1][2 * (m & 1)], B[0][m >> 1][2 * (m & 1) + 1]);
            const int prow = prow0 - min(rho + 1, 7);
            la = ub + prow * 32 + ((hs ^ ((prow >> 2) & 1)) << 4);
#pragma unroll
            for (int m2 = 0; m2 < 4; ++m2) ldsm_x4(B[0][m2], la + m2 * 512);
            const uint32_t pa = pd_lane + (rho + 1) * 64;
#pragma unroll
            for (int i = 0; i < 4; ++i) {
#pragma unroll
              for (int m = 0; m < 8 - i; ++m)
                mma_bf16v(acc[8 + m + i], A[i], B[1][m >> 1][2 * (m & 1)], B[1][m >> 1][2 * (m & 1) + 1]);
              A[i][0] = lds32(pa + i * 512); A[i][1] = lds32(pa + i * 512 + 32); A[i][2] = lds32(pa + i * 512 - 32);
              A[i][3] = lds32(pa + i * 512 + zero);
            }
          }
          if (lane == 0) TS(40);
          {
            uint32_t b8[4];
            ldsm_x4(b8, la + 4 * 512);
            const uint32_t h63 = lds32(pd_lane + 63 * 32), h64 = lds32(pd_lane + 64 * 32);
            const uint32_t a63[4] = {0u, h127, 0u, 0u}, a32[4] = {h64, 0u, h63, h64}, a64[4] = {h128, 0u, h127, h128};
#pragma unroll
            for (int m2 = 0; m2 < 4; ++m2) ldsm_x4(B[1][m2], la0 + m2 * 512);
#pragma unroll
            for (int m = 0; m < 8; ++m) mma_bf16v(acc[m + 7], a63, B[0][m >> 1][2 * (m & 1)], B[0][m >> 1][2 * (m & 1) + 1]);
#pragma unroll
            for (int m2 = 0; m2 < 2; ++m2) ldsm_x4(B[0][m2], la0 + (4 + m2) * 512);
#pragma unroll
            for (int m = 0; m < 8; ++m) mma_bf16v(acc[m + 4], a32, B[1][m >> 1][2 * (m & 1)], B[1][m >> 1][2 * (m & 1) + 1]);
            mma_bf16v(acc[15], a63, b8[0], b8[1]);
#pragma unroll
            for (int m = 0; m < 8; ++m) mma_bf16v(acc[m + 8], a64, B[1][m >> 1][2 * (m & 1)], B[1][m >> 1][2 * (m & 1) + 1]);
#pragma unroll
            for (int m = 0; m < 4; ++m) mma_bf16v(acc[m + 12], a32, B[0][m >> 1][2 * (m & 1)], B[0][m >> 1][2 * (m & 1) + 1]);
          }
          if (lane == 0) TS(41);
          bar_sync(5, 384);
#pragma unroll unr_tail
          for (int v = 0; v < 4; ++v)
            conv_tail<4, 3, 11>(acc, pb + (P2_OFF + 56 * v + gq - 16) * 4, vv + ((v & 1) ? VV_U3 : VV_U5), v >> 1, v == 0, lane);
          if (lane == 0) TS(42);
#pragma unroll unr_tail
          for (int pi = 0; pi < 2; ++pi)
            conv_tail<8, 5, 7>(acc, pb + (P3_OFF + 88 * pi + gq - 48) * 4, vv + (pi ? VV_U7 : VV_U9), pi, pi == 0, lane);
        }
        if (lane == 0) TS(8);
        __syncwarp();
        {
          const int mt = lane >> 3;
          const uint32_t a = pb + (128 * (mt >> 1) + 16 * (lane & 7) + 8 * (mt & 1)) * 2;
#pragma unroll
          for (int ab = 0; ab < 16; ab += 2)
            stsm_x4_t(a + ab * 256, pack_bf16(acc[ab][0], acc[ab][1]), pack_bf16(acc[ab][2], acc[ab][3]),
                      pack_bf16(acc[ab + 1][0], acc[ab + 1][1]), pack_bf16(acc[ab + 1][2], acc[ab + 1][3]));
        }
        fence_async_smem();
        __syncwarp();
        if (lane < 2) mbar_arrive_cluster(BAR(B_CONVD), lane);
        __syncwarp();
        cluster_arrive();
        bar_arrive(3, 384);
        if (elect_one()) {
          bulk_store(p.yT + (size_t)d * 2048, pb, 4096);
          bulk_commit();
          bulk_wait0();
          red_relaxed_add(&g_cnt[(C_Y + (cta >> 4)) * 32], 1);
          TS(9);
        }
        bar_sync(2, 128);
        if (warp == 0 && elect_one()) {
          wait_counter(&g_cnt[(C_Y + tj) * 32], (epoch + 1) * 64);
          TS(28);
          mbar_expect_tx(BAR(B_TILE), 16384);
          tma_load_2d(sb + SM_U, &maps.yT, ti * 128, tj * 64, BAR(B_TILE));
          tma_load_2d(sb + SM_U + 8192, &maps.yT, ti * 128 + 64, tj * 64, BAR(B_TILE));
        }
        __syncwarp();
      }
      mbar_wait_long(BAR(B_TILE), pass);
      if (lane == 0) TS(26 + 3 * pass);
      {
        const int m = lane >> 3, r = lane & 7;
#pragma unroll 2
        for (int it = 0; it < 8; ++it) {
          const int tb = warp * 4 + (it >> 1), cb = (it & 1) * 4 + m;
          const uint32_t at = (tb * 8 + r) * 128 + ((cb ^ r) << 4);
          const uint32_t ac = (tb >> 3) * 8192 + (cb * 8 + r) * 128 + (((tb & 7) ^ (pass ? 0 : tb >> 3) ^ r) << 4);
          uint32_t v[4];
          ldsm_x4_t(v, sb + SM_U + (pass ? ac : at));
          stsm_x4(sb + SM_P + (pass ? at : ac), v[0], v[1], v[2], v[3]);
        }
      }
      if (pass == 0 && tid == 0) TS(35);
      fence_async_smem();
      if (pass == 0) {
        bar_arrive(6, 160);
      } else {
        bar_sync(2, 128);
        if (warp == 0 && elect_one()) {
          tma_store_2d(&maps.out, sb + SM_P, 64 * tj, 128 * ti);
          bulk_commit();
          bulk_wait_read0();
          TS(30);
        }
      }
    }
  } else if (warp < 12) {
    const int w8 = warp - 4;
    const int row = w8 * 16 + (lane & 7) + (((lane >> 3) & 1) << 3);
    uint32_t pq[16];
    {
      float acc[96];
#pragma unroll 1
      for (int ks = 0, s = 0, ph = 0; ks < 16; ++ks) {
        mbar_wait(BAR(B_FULL + s), ph);
        if (tid == 128 && !(ks & 1)) TSR(16, ks == 0 ? 16 : 9 + (ks >> 1) + (ks > 12 ? 43 : 0));
        const uint32_t st = sb + s * STG_BYTES;
        const uint32_t da = mkdesc(st + STG_X + (w8 >> 2) * 4096, 16);
        const uint32_t db = mkdesc(st + STG_W, 2048);
        wg_fence();
        wgmma_n192(acc, da, db, ks != 0);
        wgmma_n192(acc, da + 2, db + 384, 1);
        wg_commit();
        const uint32_t eprev = BAR(B_EMPTY + (s == 0 ? NSTG - 1 : s - 1));
        if (++s == NSTG) { s = 0; ph ^= 1; }
        if (ks > 0) {
          wg_wait<1>();
          if (lane < 2) mbar_arrive_cluster(eprev, lane);
        }
      }
      wg_wait<0>();
      bar_arrive(4, 384);
      if (tid == 128) TS(17);
      auto phi2 = [](float a, float b) -> uint32_t {
        const uint32_t x = pack_bf16(a, b);
        const uint32_t e = pack_bf16(ex2(a * 1.4426950408889634f), ex2(b * 1.4426950408889634f));
        const uint32_t m = __hgt2_mask(*reinterpret_cast<const __nv_bfloat162*>(&x), __floats2bfloat162_rn(0.f, 0.f));
        return badd((badd(x, 0x3f803f80u) & m) | (e & ~m), 0x35863586u);
      };
      uint32_t pk[16];
#pragma unroll
      for (int i = 0; i < 16; ++i) pk[i] = phi2(acc[32 + 2 * i], acc[33 + 2 * i]);
      if (tid == 128) TS(53);
      bar_sync(1, 256);
#pragma unroll
      for (int i = 0; i < 8; i += 2) {
        const uint32_t off = row * 128 + (((i + (lane >> 4)) ^ (row & 7)) << 4);
        stsm_x4(sb + SM_PK + off, pk[2 * i], pk[2 * i + 1], pk[2 * i + 2], pk[2 * i + 3]);
        stsm_x4(sb + SM_VS + off, pack_bf16(acc[64 + 4 * i], acc[65 + 4 * i]), pack_bf16(acc[66 + 4 * i], acc[67 + 4 * i]),
                pack_bf16(acc[68 + 4 * i], acc[69 + 4 * i]), pack_bf16(acc[70 + 4 * i], acc[71 + 4 * i]));
      }
      bar_sync(1, 256);
      {
        const int hh = w8 >> 1, dtile = w8 & 1;
        float kv[2][4] = {{0.f, 0.f, 0.f, 0.f}, {0.f, 0.f, 0.f, 0.f}}, zz[2][4] = {{0.f, 0.f, 0.f, 0.f}, {0.f, 0.f, 0.f, 0.f}};
        const int m = lane >> 3;
        const uint32_t aa = sb + SM_VS + ((lane & 7) + ((m >> 1) << 3)) * 128 + (((2 * hh + (m & 1)) ^ (lane & 7)) << 4);
        const uint32_t ab = sb + SM_PK + (lane & 15) * 128 + (((2 * hh + dtile) ^ (lane & 7)) << 4);
#pragma unroll
        for (int ks = 0; ks < 8; ++ks) {
          uint32_t a[4], b0, b1;
          ldsm_x4_t(a, aa + ks * 2048);
          ldsm_x2_t(b0, b1, ab + ks * 2048);
          mma_bf16(kv[ks & 1], a[0], a[1], a[2], a[3], b0, b1);
          mma_bf16(zz[ks & 1], 0x3f803f80u, 0x3f803f80u, 0x3f803f80u, 0x3f803f80u, b0, b1);
        }
        const uint32_t kp = sb + SM_KV + hh * 1088;
        sts128(kp + dtile * 512 + lane * 16, __float_as_uint(kv[0][0] + kv[1][0]), __float_as_uint(kv[0][1] + kv[1][1]),
               __float_as_uint(kv[0][2] + kv[1][2]), __float_as_uint(kv[0][3] + kv[1][3]));
        if (g == 0) sts_f32x2(kp + 1024 + dtile * 32 + q * 8, zz[0][0] + zz[1][0], zz[0][1] + zz[1][1]);
        fence_async_smem();
        __syncwarp();
        if (lane == 0) mbar_arrive(BAR(B_KVP));
        if (tid == 128) TS(55);
      }
#pragma unroll
      for (int i = 0; i < 16; ++i) pq[i] = phi2(acc[2 * i], acc[2 * i + 1]);
    }
    if (tid == 128) TS(56);
    if (warp == 4) mbar_wait_long(BAR(B_KVF), 0);
    bar_sync(1, 256);
    if (tid == 128) TS(19);
    {
      uint32_t kb[4][6];
#pragma unroll
      for (int h = 0; h < 4; ++h) {
        const uint32_t kp = sb + SM_KV + h * 1088;
        const uint4 k0 = lds128(kp + lane * 16), k1 = lds128(kp + 512 + lane * 16);
        const uint32_t za = kp + 1024 + q * 8;
        auto pk2 = [](uint32_t x, uint32_t y) { return pack_bf16(__uint_as_float(x), __uint_as_float(y)); };
        kb[h][0] = pk2(k0.x, k0.y); kb[h][1] = pk2(k1.x, k1.y); kb[h][2] = pk2(k0.z, k0.w); kb[h][3] = pk2(k1.z, k1.w);
        kb[h][4] = pack_bf16(lds_f32(za), lds_f32(za + 4)); kb[h][5] = pack_bf16(lds_f32(za + 32), lds_f32(za + 36));
      }
#pragma unroll
      for (int h = 0; h < 4; ++h) {
        float n0[4] = {0.f, 0.f, 0.f, 0.f}, n1[4] = {0.f, 0.f, 0.f, 0.f}, dn[4] = {0.f, 0.f, 0.f, 0.f};
        mma_bf16(n0, pq[4 * h], pq[4 * h + 1], pq[4 * h + 2], pq[4 * h + 3], kb[h][0], kb[h][1]);
        mma_bf16(n1, pq[4 * h], pq[4 * h + 1], pq[4 * h + 2], pq[4 * h + 3], kb[h][2], kb[h][3]);
        mma_bf16(dn, pq[4 * h], pq[4 * h + 1], pq[4 * h + 2], pq[4 * h + 3], kb[h][4], kb[h][5]);
        const float r0 = rcp(dn[0] + 1e-6f), r1 = rcp(dn[2] + 1e-6f);
        stsm_x4(sb + SM_QS + row * 128 + (((2 * h + (lane >> 4)) ^ (row & 7)) << 4),
                pack_bf16(n0[0] * r0, n0[1] * r0), pack_bf16(n0[2] * r1, n0[3] * r1),
                pack_bf16(n1[0] * r0, n1[1] * r0), pack_bf16(n1[2] * r1, n1[3] * r1));
      }
    }
    fence_async_smem();
    __syncwarp();
    if (lane == 0) mbar_arrive(BAR(B_OST));
    if (tid == 128) TS(57);
    bar_sync(7, 384);
    if (w8 < 7) box_filters<4>(sb, bars, w8, lane);
    bar_arrive(5, 384);
    if (tid == 128) TS(6);
    if (warp == 4) mbar_wait_long(BAR(B_WO), 0);
    bar_sync(3, 384);
    {
      float o[32];
#pragma unroll 1
      for (int c = 0; c < 8; ++c) {
        mbar_wait_long(BAR(B_RF + c), 0);
        if (tid == 128) TSR(22, c == 0 ? 22 : 43 + c);
        const uint32_t slot = c < 4 ? SM_QS + c * 16384 : c < 7 ? SM_VV + (c - 4) * 16384 : SM_QS;
        const uint32_t da = mkdesc(sb + slot + (w8 >> 2) * 8192, 16);
        const uint32_t db = mkdesc(sb + SM_WO + c * 8192, 8192);
        wg_fence();
#pragma unroll
        for (int k = 0; k < 4; ++k) wgmma_n64(o, da + 2 * k, db + 128 * k, (c | k) != 0);
        wg_commit();
        if (c == 1) {
          wg_wait<1>();
          if (lane < 2) mbar_arrive_cluster(BAR(B_RE), lane);
          __syncwarp();
          cluster_arrive();
        }
      }
      wg_wait<0>();
      if (tid == 128) TS(51);
#pragma unroll
      for (int i = 0; i < 8; i += 2)
        stsm_x4(sb + SM_BOUT + row * 128 + (((i + (lane >> 4)) ^ (row & 7)) << 4), pack_bf16(o[4 * i], o[4 * i + 1]),
                pack_bf16(o[4 * i + 2], o[4 * i + 3]), pack_bf16(o[4 * i + 4], o[4 * i + 5]), pack_bf16(o[4 * i + 6], o[4 * i + 7]));
      fence_async_smem();
      bar_sync(8 + (w8 >> 2), 128);
      if ((w8 & 3) == 0 && elect_one()) {
        tma_store_2d(&maps.outh, sb + SM_BOUT + (w8 >> 2) * 8192, 512 + 64 * pj, 128 * pi + (w8 >> 2) * 64);
        bulk_commit();
        bulk_wait_read0();
        TS(23);
      }
    }
  } else {
    asm volatile("setmaxnreg.dec.sync.aligned.u32 40;");
    if (warp == 12) {
      if (elect_one()) {
#pragma unroll 1
        for (int ks = NSTG, s = 0, ph = 0; ks < 16; ++ks) {
          mbar_wait(BAR(B_EMPTY + s), ph);
          issue_stage(ks, s);
          if (ks == NSTG) l2_prefetch((const char*)p.wo + (size_t)cta * 4096, 4096);
          if (++s == NSTG) { s = 0; ph ^= 1; }
        }
        mbar_wait(BAR(B_EMPTY + 6), 1);
        mbar_expect_tx(BAR(B_WO), 65536);
        tma_load_2d(sb + SM_WO, &maps.wo, pj * 64, 0, BAR(B_WO));
        tma_load_2d(sb + SM_WO + 32768, &maps.wo, pj * 64, 256, BAR(B_WO));
        float* kvg = &g_kv[epoch & 1][tj][0];
        mbar_wait_long(BAR(B_KVP), 0);
        bulk_reduce_add_f32(kvg, sb + SM_KV, 4352);
        bulk_commit();
        bulk_wait0();
        red_relaxed_add(&g_cnt[(C_KV + tj) * 32], 1);
        TS(18);
        wait_counter(&g_cnt[(C_KV + tj) * 32], (epoch + 1) * 16);
        mbar_expect_tx(BAR(B_KVF), 4352);
        bulk_load(sb + SM_KV, kvg, 4352, BAR(B_KVF));
        mbar_wait_long(BAR(B_OST), 0);
        tma_store_2d(&maps.o, sb + SM_QS, tj * 64, ti * 128);
        tma_store_2d(&maps.o, sb + SM_QS + 8192, tj * 64, ti * 128 + 64);
        bulk_commit();
        bulk_wait0();
        red_relaxed_add(&g_cnt[(C_O + ti) * 32], 1);
        TS(20);
        mbar_arrive_cluster(BAR(B_SLOT), 0);
        mbar_arrive_cluster(BAR(B_SLOT), 1);
        wait_counter(&g_cnt[(C_O + pi) * 32], (epoch + 1) * 8);
        if (cta == 0) g_epoch = epoch + 1;
        mbar_wait(BAR(B_SLOT), 0);
        TS(21);
#pragma unroll 1
        for (int c = 0; c < 8; ++c) {
          if (c == 4) mbar_wait_long(BAR(B_CONVD), 0);
          if (c == 7) mbar_wait(BAR(B_RE), 0);
          const uint32_t slot = c < 4 ? SM_QS + c * 16384 : c < 7 ? SM_VV + (c - 4) * 16384 : SM_QS;
          mbar_expect_tx(BAR(B_RF + c), 16384);
          tma_load_2d_mc(sb + slot + rank * 8192, &maps.o, c * 64, pi * 128 + rank * 64, BAR(B_RF + c), 3);
        }
      }
    } else if (warp == 13) {
      bar_sync(6, 160);
      sts128(sb + SM_U + (lane >> 4) * U_BYTES + (lane & 15) * 16, 0, 0, 0, 0);
      sts128(sb + SM_U + (2 + (lane >> 4)) * U_BYTES + (lane & 15) * 16, 0, 0, 0, 0);
      __syncwarp();
      if (elect_one()) {
        tma_store_2d(&maps.uT, sb + SM_P, ti * 128, tj * 64);
        tma_store_2d(&maps.uT, sb + SM_P + 8192, ti * 128 + 64, tj * 64);
        bulk_commit();
        bulk_wait_read0();
        mbar_arrive(BAR(B_PFREE));
        bulk_wait0();
        red_relaxed_add(&g_cnt[(C_U + tj) * 32], 1);
        TS(27);
        wait_counter(&g_cnt[(C_U + (cta >> 4)) * 32], (epoch + 1) * 16);
#pragma unroll 1
        for (int c = 0; c < 4; ++c) {
          mbar_expect_tx(BAR(B_UCH + c), 4096);
          bulk_load(sb + SM_U + c * U_BYTES + 256, p.uT + (size_t)(cta * 4 + c) * 2048, 4096, BAR(B_UCH + c));
        }
        TS(3);
      }
      __syncwarp();
      if (ti == 0) {
        float4* z = (float4*)&g_kv[(epoch & 1) ^ 1][tj][0];
#pragma unroll 1
        for (int i = lane; i < 272; i += 32) z[i] = make_float4(0.f, 0.f, 0.f, 0.f);
      }
    }
  }
  __syncwarp();
  if (warp >= 12) cluster_arrive();
  cluster_wait();
  if (tid == 0) TS(31);
#undef BAR
}

typedef CUresult (*EncodeFn)(CUtensorMap*, CUtensorMapDataType, cuuint32_t, void*, const cuuint64_t*, const cuuint64_t*,
                             const cuuint32_t*, const cuuint32_t*, CUtensorMapInterleave, CUtensorMapSwizzle,
                             CUtensorMapL2promotion, CUtensorMapFloatOOBfill);

static void make_map(EncodeFn enc, CUtensorMap* m, const void* base, uint64_t inner, uint64_t outer, uint32_t box_in,
                     uint32_t box_out, CUtensorMapSwizzle swz = CU_TENSOR_MAP_SWIZZLE_128B) {
  cuuint64_t gd[2] = {inner, outer};
  cuuint64_t gs[1] = {inner * 2};
  cuuint32_t bd[2] = {box_in, box_out};
  cuuint32_t es[2] = {1, 1};
  enc(m, CU_TENSOR_MAP_DATA_TYPE_BFLOAT16, 2, const_cast<void*>(base), gd, gs, bd, es, CU_TENSOR_MAP_INTERLEAVE_NONE,
      swz, CU_TENSOR_MAP_L2_PROMOTION_L2_128B, CU_TENSOR_MAP_FLOAT_OOB_FILL_NONE);
}

}

extern "C" void kernel_launch(void* const* d_in, const int* in_sizes, int n_in, void* d_out, int out_size) {
  using namespace s4la;
  (void)in_sizes; (void)n_in; (void)out_size;
  static EncodeFn enc = nullptr;
  static void *uT = nullptr, *yT = nullptr, *oS = nullptr;
  if (!enc) {
    void* fn = nullptr;
    cudaDriverEntryPointQueryResult qr;
    cudaGetDriverEntryPoint("cuTensorMapEncodeTiled", &fn, cudaEnableDefault, &qr);
    enc = (EncodeFn)fn;
    cudaGetSymbolAddress(&uT, g_uT);
    cudaGetSymbolAddress(&yT, g_yT);
    cudaGetSymbolAddress(&oS, g_o);
    cudaFuncSetAttribute(fused_kernel, cudaFuncAttributeMaxDynamicSharedMemorySize, SM_TOTAL);
  }
  const __nv_bfloat16* const* in = (const __nv_bfloat16* const*)d_in;
  Maps maps;
  make_map(enc, &maps.x, in[9], 512, 2048, 32, 128, CU_TENSOR_MAP_SWIZZLE_64B);
  {
    cuuint64_t gd[3] = {512, 512, 3};
    cuuint64_t gs[2] = {3072, 1024};
    cuuint32_t bd[3] = {64, 16, 3};
    cuuint32_t es[3] = {1, 1, 1};
    enc(&maps.w, CU_TENSOR_MAP_DATA_TYPE_BFLOAT16, 3, const_cast<__nv_bfloat16*>(in[10]), gd, gs, bd, es,
        CU_TENSOR_MAP_INTERLEAVE_NONE, CU_TENSOR_MAP_SWIZZLE_128B, CU_TENSOR_MAP_L2_PROMOTION_L2_128B,
        CU_TENSOR_MAP_FLOAT_OOB_FILL_NONE);
  }
  make_map(enc, &maps.wo, in[11], 512, 512, 64, 256);
  make_map(enc, &maps.u, in[0], 512, 2048, 64, 128);
  make_map(enc, &maps.uT, uT, 2048, 512, 64, 64);
  make_map(enc, &maps.yT, yT, 2048, 512, 64, 64);
  make_map(enc, &maps.o, oS, 512, 2048, 64, 64);
  make_map(enc, &maps.out, d_out, 1024, 2048, 64, 128);
  make_map(enc, &maps.outh, d_out, 1024, 2048, 64, 64);
  Ptrs p;
  p.A_re = in[1]; p.A_im = in[2]; p.B_re = in[3]; p.B_im = in[4]; p.C_re = in[5]; p.C_im = in[6];
  p.log_dt = in[7]; p.Dskip = in[8]; p.x = in[9]; p.wqkv = in[10]; p.wo = in[11];
  p.uT = (__nv_bfloat16*)uT; p.yT = (__nv_bfloat16*)yT;
  fused_kernel<<<NCTA, NTHREADS, SM_TOTAL, cudaStreamPerThread>>>(maps, p);
}
```

```cpp
#include <cuda_runtime.h>
#include <cuda_bf16.h>
#include <cuda_fp16.h>
#include <cuda.h>
#include <stdint.h>

#define DEVI __device__ __forceinline__

namespace s4la {

constexpr int NTHREADS = 512;
constexpr int NCTA = 128;

constexpr int NSTG = 7;
constexpr uint32_t STG_BYTES = 20480, STG_X = 0, STG_W = 8192;
constexpr uint32_t SM_QS = 0;
constexpr uint32_t SM_PK = SM_QS + 16384, SM_VS = SM_QS + 32768;
constexpr uint32_t SM_WO = 98304;
constexpr uint32_t SM_KV = 81920;
constexpr uint32_t SM_BOUT = 16384;
constexpr uint32_t SM_U = 143360, U_BYTES = 4352;
constexpr uint32_t SM_P = 160768, P_BYTES = 4096;
constexpr uint32_t SM_VV = 177152, VV_BYTES = 12800;
constexpr uint32_t VV_U5 = 0, VV_U3 = 3712, VV_U9 = 7424, VV_U7 = 10112;
constexpr uint32_t KG_BYTES = 3200;
constexpr uint32_t SM_BAR = SM_VV + 4 * VV_BYTES;
constexpr uint32_t SM_PTAB = SM_BAR + 320;
constexpr uint32_t SM_TOTAL = SM_PTAB + 2048;
static_assert(SM_TOTAL <= 232448, "shared memory");
constexpr int PADV = 12;

enum { B_FULL = 0, B_EMPTY = 7, B_TILE = 14, B_UCH = 15, B_KVP = 19, B_KVF = 20, B_OST = 21, B_RF = 22, B_WO = 30, B_RE = 31, B_PFREE = 32, B_CONVD = 33, B_SLOT = 34, B_COUNT = 35 };
__host__ __device__ constexpr int bar_count(int i) {
  return (i >= B_EMPTY && i < B_TILE) ? 16 : (i == B_KVP || i == B_OST || i == B_CONVD) ? 8 : i == B_RE ? 16 : i == B_SLOT ? 2 : 1;
}

constexpr int PD_OFF = 0, P2_OFF = 544, P3_OFF = 768;

constexpr int SL_K2048 = 20, SL_ZERO = 21, SL_510 = 22, SL_0 = 23;
__host__ __device__ constexpr int koff(int y) {
  return y < 8 ? y : y < 12 ? 256 + 2 * (y - 8) : y < 16 ? 512 + 256 * ((y - 12) >> 1) + 4 * (y & 1) : 1024 + 256 * (y - 16);
}
__host__ __device__ constexpr int kidx_c(int l) {
  const int y = l < 256 ? (l & 7) : l < 512 ? 8 + ((l & 7) >> 1) : l < 1024 ? 12 + (((l - 512) >> 8) << 1) + ((l >> 2) & 1)
                                                                            : 16 + ((l - 1024) >> 8);
  return ((l >> 3) & 31) * 24 + y;
}
constexpr int slot_direct(int l) {
  if (l < 0 || l > 510) return SL_ZERO;
  if (l == 510) return SL_510;
  if (l == 0) return SL_0;
  return kidx_c(l < 256 ? l : ((l + ((l >> 1) & 1)) & ~1));
}
constexpr int slot_seg2(int v, int k) { return (k >= 32 && k < 64) ? kidx_c(16 * k + 4 * v) : SL_ZERO; }
constexpr int slot_seg3(int pi, int k) {
  return (k >= 64 && k < 128) ? kidx_c(16 * k + 8 * pi) : ((k == 128 && pi == 0) ? SL_K2048 : SL_ZERO);
}
constexpr int slot_word(int w) {
  return w < 0 ? SL_ZERO : w < 544 ? slot_direct(w - 16) : w < 768 ? slot_seg2((w - 544) / 56, 16 + (w - 544) % 56)
       : w < 944 ? slot_seg3((w - 768) / 88, 48 + (w - 768) % 88) : SL_ZERO;
}
struct PTab { uint32_t v[512]; };
constexpr PTab make_ptab() {
  PTab t{};
  for (int lane = 0; lane < 32; ++lane)
    for (int i = 0; i < 16; ++i)
      t.v[i * 32 + lane] = (slot_word(31 * lane - 1 + 2 * i) * 4) | ((slot_word(31 * lane + 2 * i) * 4) << 16);
  return t;
}
__device__ const PTab g_ptab = make_ptab();

__device__ __nv_bfloat16 g_uT[512 * 2048];
__device__ __nv_bfloat16 g_yT[512 * 2048];
__device__ __nv_bfloat16 g_o[2048 * 512];
__device__ float g_kv[2][8][4 * 272];
__device__ unsigned g_cnt[64 * 32];
__device__ unsigned g_epoch;
#define TS(slot) do { } while (0)
#define TSR(on, slot) do { } while (0)
#define TSD(slot) do { } while (0)
enum { C_U = 0, C_KV = 8, C_O = 16, C_Y = 32 };

struct Maps {
  CUtensorMap x, w, wo, u, uT, yT, o, out, outh;
};
struct Ptrs {
  const __nv_bfloat16 *A_re, *A_im, *B_re, *B_im, *C_re, *C_im, *log_dt, *Dskip;
  const __nv_bfloat16 *x, *wqkv, *wo;
  __nv_bfloat16 *uT, *yT;
};

DEVI uint32_t s2u(const void* p) { return (uint32_t)__cvta_generic_to_shared(p); }
DEVI void mbar_init(uint32_t b, uint32_t c) { asm volatile("mbarrier.init.shared::cta.b64 [%0], %1;" ::"r"(b), "r"(c) : "memory"); }
DEVI void mbar_expect_tx(uint32_t b, uint32_t bytes) {
  asm volatile("mbarrier.arrive.expect_tx.shared::cta.b64 _, [%0], %1;" ::"r"(b), "r"(bytes) : "memory");
}
DEVI void mbar_arrive(uint32_t b) { asm volatile("mbarrier.arrive.shared::cta.b64 _, [%0];" ::"r"(b) : "memory"); }
DEVI void mbar_arrive_cluster(uint32_t b, uint32_t cta) {
  asm volatile("{\n.reg .b32 r;\nmapa.shared::cluster.u32 r, %0, %1;\nmbarrier.arrive.shared::cluster.b64 _, [r];\n}"
               ::"r"(b), "r"(cta) : "memory");
}
DEVI void mbar_wait(uint32_t b, uint32_t parity) {
  asm volatile("{\n.reg .pred p;\nLAB_WAIT:\nmbarrier.try_wait.parity.shared::cta.b64 p, [%0], %1;\n@!p bra LAB_WAIT;\n}"
               ::"r"(b), "r"(parity) : "memory");
}
DEVI void mbar_wait_long(uint32_t b, uint32_t parity) {
  asm volatile("{\n.reg .pred p;\nLAB_WAIT:\nmbarrier.try_wait.parity.shared::cta.b64 p, [%0], %1, 0x989680;\n@!p bra LAB_WAIT;\n}"
               ::"r"(b), "r"(parity) : "memory");
}
DEVI void bar_sync(int id, int n) { asm volatile("bar.sync %0, %1;" ::"r"(id), "r"(n) : "memory"); }
DEVI void bar_arrive(int id, int n) { asm volatile("bar.arrive %0, %1;" ::"r"(id), "r"(n) : "memory"); }
DEVI void fence_async_smem() { asm volatile("fence.proxy.async.shared::cta;" ::: "memory"); }
DEVI void fence_async_all() { asm volatile("fence.proxy.async;" ::: "memory"); }
DEVI void cluster_arrive() { asm volatile("barrier.cluster.arrive.relaxed.aligned;" ::: "memory"); }
DEVI void cluster_wait() { asm volatile("barrier.cluster.wait.aligned;" ::: "memory"); }

DEVI void tma_load_2d(uint32_t dst, const CUtensorMap* m, int c0, int c1, uint32_t bar) {
  asm volatile("cp.async.bulk.tensor.2d.shared::cluster.global.mbarrier::complete_tx::bytes [%0], [%1, {%3, %4}], [%2];"
               ::"r"(dst), "l"(m), "r"(bar), "r"(c0), "r"(c1) : "memory");
}
DEVI void tma_load_2d_mc(uint32_t dst, const CUtensorMap* m, int c0, int c1, uint32_t bar, uint16_t mask) {
  asm volatile("cp.async.bulk.tensor.2d.shared::cluster.global.mbarrier::complete_tx::bytes.multicast::cluster [%0], [%1, {%3, %4}], [%2], %5;"
               ::"r"(dst), "l"(m), "r"(bar), "r"(c0), "r"(c1), "h"(mask) : "memory");
}
DEVI void tma_load_3d_mc(uint32_t dst, const CUtensorMap* m, int c0, int c1, int c2, uint32_t bar, uint16_t mask) {
  asm volatile("cp.async.bulk.tensor.3d.shared::cluster.global.mbarrier::complete_tx::bytes.multicast::cluster [%0], [%1, {%3, %4, %5}], [%2], %6;"
               ::"r"(dst), "l"(m), "r"(bar), "r"(c0), "r"(c1), "r"(c2), "h"(mask) : "memory");
}
DEVI void tma_store_2d(const CUtensorMap* m, uint32_t src, int c0, int c1) {
  asm volatile("cp.async.bulk.tensor.2d.global.shared::cta.bulk_group [%0, {%2, %3}], [%1];"
               ::"l"(m), "r"(src), "r"(c0), "r"(c1) : "memory");
}
DEVI void bulk_load(uint32_t dst, const void* src, uint32_t bytes, uint32_t bar) {
  asm volatile("cp.async.bulk.shared::cluster.global.mbarrier::complete_tx::bytes [%0], [%1], %2, [%3];"
               ::"r"(dst), "l"(src), "r"(bytes), "r"(bar) : "memory");
}
DEVI void bulk_store(void* dst, uint32_t src, uint32_t bytes) {
  asm volatile("cp.async.bulk.global.shared::cta.bulk_group [%0], [%1], %2;" ::"l"(dst), "r"(src), "r"(bytes) : "memory");
}
DEVI void bulk_reduce_add_f32(void* dst, uint32_t src, uint32_t bytes) {
  asm volatile("cp.reduce.async.bulk.global.shared::cta.bulk_group.add.f32 [%0], [%1], %2;" ::"l"(dst), "r"(src), "r"(bytes) : "memory");
}
DEVI void bulk_commit() { asm volatile("cp.async.bulk.commit_group;" ::: "memory"); }
DEVI void bulk_wait0() { asm volatile("cp.async.bulk.wait_group 0;" ::: "memory"); }
DEVI void bulk_wait_read0() { asm volatile("cp.async.bulk.wait_group.read 0;" ::: "memory"); }
DEVI void l2_prefetch(const void* p, uint32_t bytes) {
  asm volatile("cp.async.bulk.prefetch.L2.global [%0], %1;" ::"l"(p), "r"(bytes) : "memory");
}
DEVI void prefetch_tmap(const CUtensorMap* m) { asm volatile("prefetch.tensormap [%0];" ::"l"(m) : "memory"); }

DEVI void red_release_add(unsigned* p, unsigned v) {
  asm volatile("red.release.gpu.global.add.u32 [%0], %1;" ::"l"(p), "r"(v) : "memory");
}
DEVI void red_relaxed_add(unsigned* p, unsigned v) {
  asm volatile("red.relaxed.gpu.global.add.u32 [%0], %1;" ::"l"(p), "r"(v) : "memory");
}
DEVI unsigned ld_relaxed(const unsigned* p) {
  unsigned v;
  asm volatile("ld.relaxed.gpu.global.u32 %0, [%1];" : "=r"(v) : "l"(p) : "memory");
  return v;
}
DEVI void wait_counter(const unsigned* p, unsigned target) {
#pragma unroll 1
  for (int it = 0; (int)(ld_relaxed(p) - target) < 0; ++it)
    if (it > (1 << 22)) __trap();
}

DEVI void ldsm_x4(uint32_t (&r)[4], uint32_t a) {
  asm volatile("ldmatrix.sync.aligned.m8n8.x4.shared.b16 {%0,%1,%2,%3}, [%4];"
               : "=r"(r[0]), "=r"(r[1]), "=r"(r[2]), "=r"(r[3]) : "r"(a) : "memory");
}
DEVI void ldsm_x4_t(uint32_t (&r)[4], uint32_t a) {
  asm volatile("ldmatrix.sync.aligned.m8n8.x4.trans.shared.b16 {%0,%1,%2,%3}, [%4];"
               : "=r"(r[0]), "=r"(r[1]), "=r"(r[2]), "=r"(r[3]) : "r"(a) : "memory");
}
DEVI void ldsm_x2_t(uint32_t& r0, uint32_t& r1, uint32_t a) {
  asm volatile("ldmatrix.sync.aligned.m8n8.x2.trans.shared.b16 {%0,%1}, [%2];" : "=r"(r0), "=r"(r1) : "r"(a) : "memory");
}
DEVI void stsm_x4(uint32_t a, uint32_t r0, uint32_t r1, uint32_t r2, uint32_t r3) {
  asm volatile("stmatrix.sync.aligned.m8n8.x4.shared.b16 [%0], {%1,%2,%3,%4};"
               ::"r"(a), "r"(r0), "r"(r1), "r"(r2), "r"(r3) : "memory");
}
DEVI void stsm_x4_t(uint32_t a, uint32_t r0, uint32_t r1, uint32_t r2, uint32_t r3) {
  asm volatile("stmatrix.sync.aligned.m8n8.x4.trans.shared.b16 [%0], {%1,%2,%3,%4};"
               ::"r"(a), "r"(r0), "r"(r1), "r"(r2), "r"(r3) : "memory");
}
DEVI uint32_t lds32(uint32_t a) { uint32_t v; asm volatile("ld.shared.b32 %0, [%1];" : "=r"(v) : "r"(a) : "memory"); return v; }
DEVI float lds_f32(uint32_t a) { float v; asm volatile("ld.shared.f32 %0, [%1];" : "=f"(v) : "r"(a) : "memory"); return v; }
DEVI void sts32(uint32_t a, uint32_t v) { asm volatile("st.shared.b32 [%0], %1;" ::"r"(a), "r"(v) : "memory"); }
DEVI void sts_f32(uint32_t a, float v) { asm volatile("st.shared.f32 [%0], %1;" ::"r"(a), "f"(v) : "memory"); }
DEVI void sts_f32x2(uint32_t a, float x, float y) { asm volatile("st.shared.v2.f32 [%0], {%1,%2};" ::"r"(a), "f"(x), "f"(y) : "memory"); }
DEVI uint4 lds128(uint32_t a) {
  uint4 v;
  asm volatile("ld.shared.v4.b32 {%0,%1,%2,%3}, [%4];" : "=r"(v.x), "=r"(v.y), "=r"(v.z), "=r"(v.w) : "r"(a) : "memory");
  return v;
}
DEVI void sts128(uint32_t a, uint32_t x, uint32_t y, uint32_t z, uint32_t w) {
  asm volatile("st.shared.v4.b32 [%0], {%1,%2,%3,%4};" ::"r"(a), "r"(x), "r"(y), "r"(z), "r"(w) : "memory");
}

DEVI void mma_bf16(float (&d)[4], uint32_t a0, uint32_t a1, uint32_t a2, uint32_t a3, uint32_t b0, uint32_t b1) {
  asm("mma.sync.aligned.m16n8k16.row.col.f32.bf16.bf16.f32 {%0,%1,%2,%3}, {%4,%5,%6,%7}, {%8,%9}, {%0,%1,%2,%3};"
      : "+f"(d[0]), "+f"(d[1]), "+f"(d[2]), "+f"(d[3])
      : "r"(a0), "r"(a1), "r"(a2), "r"(a3), "r"(b0), "r"(b1));
}
DEVI void mma_f16(float (&d)[4], const uint32_t (&a)[4], uint32_t b0, uint32_t b1) {
  asm("mma.sync.aligned.m16n8k16.row.col.f32.f16.f16.f32 {%0,%1,%2,%3}, {%4,%5,%6,%7}, {%8,%9}, {%0,%1,%2,%3};"
      : "+f"(d[0]), "+f"(d[1]), "+f"(d[2]), "+f"(d[3])
      : "r"(a[0]), "r"(a[1]), "r"(a[2]), "r"(a[3]), "r"(b0), "r"(b1));
}
DEVI void mma_bf16v(float (&d)[4], const uint32_t (&a)[4], uint32_t b0, uint32_t b1) {
  asm volatile("mma.sync.aligned.m16n8k16.row.col.f32.bf16.bf16.f32 {%0,%1,%2,%3}, {%4,%5,%6,%7}, {%8,%9}, {%0,%1,%2,%3};"
               : "+f"(d[0]), "+f"(d[1]), "+f"(d[2]), "+f"(d[3])
               : "r"(a[0]), "r"(a[1]), "r"(a[2]), "r"(a[3]), "r"(b0), "r"(b1));
}
DEVI uint32_t pack_bf16(float lo, float hi) {
  uint32_t r;
  asm("cvt.rn.bf16x2.f32 %0, %1, %2;" : "=r"(r) : "f"(hi), "f"(lo));
  return r;
}
DEVI uint32_t pack_f16(float lo, float hi) {
  uint32_t r;
  asm("cvt.rn.f16x2.f32 %0, %1, %2;" : "=r"(r) : "f"(hi), "f"(lo));
  return r;
}
DEVI uint32_t ldg16(const __nv_bfloat16* p) {
  uint32_t v;
  asm volatile("ld.global.nc.u16 %0, [%1];" : "=r"(v) : "l"(p));
  return v;
}
DEVI bool elect_one() {
  uint32_t pred;
  asm volatile("{\n.reg .pred p;\nelect.sync _|p, 0xffffffff;\nselp.u32 %0, 1, 0, p;\n}" : "=r"(pred));
  return pred != 0;
}
DEVI float bf_lo(uint32_t v) { return __uint_as_float(v << 16); }
DEVI float bf_hi(uint32_t v) { return __uint_as_float(v & 0xffff0000u); }
DEVI float bf2f(__nv_bfloat16 v) { return __bfloat162float(v); }
DEVI float round_bf16(float v) { return __bfloat162float(__float2bfloat16_rn(v)); }
DEVI float rcp(float x) { float r; asm("rcp.approx.ftz.f32 %0, %1;" : "=f"(r) : "f"(x)); return r; }
DEVI float ex2(float x) { float r; asm("ex2.approx.ftz.f32 %0, %1;" : "=f"(r) : "f"(x)); return r; }

DEVI void wg_fence() { asm volatile("wgmma.fence.sync.aligned;" ::: "memory"); }
DEVI void wg_commit() { asm volatile("wgmma.commit_group.sync.aligned;" ::: "memory"); }
template <int N> DEVI void wg_wait() { asm volatile("wgmma.wait_group.sync.aligned %0;" ::"n"(N) : "memory"); }
constexpr uint32_t DESC_HI = (1u << 30) | (1024 >> 4);
constexpr uint32_t DESC_HI64 = (2u << 30) | (512 >> 4);
DEVI uint32_t mkdesc(uint32_t saddr, uint32_t lbo) { return ((saddr & 0x3FFFF) >> 4) | ((lbo >> 4) << 16); }

#define R8(b) "%" #b
DEVI void wgmma_n192(float (&d)[96], uint32_t da, uint32_t db, int scale_d) {
  asm volatile(
      "{\n.reg .pred p;\n.reg .b64 da, db;\nsetp.ne.b32 p, %98, 0;\nmov.b64 da, {%96, %100};\nmov.b64 db, {%97, %99};\n"
      "wgmma.mma_async.sync.aligned.m64n192k16.f32.bf16.bf16 "
      "{%0,%1,%2,%3,%4,%5,%6,%7,%8,%9,%10,%11,%12,%13,%14,%15,"
      "%16,%17,%18,%19,%20,%21,%22,%23,%24,%25,%26,%27,%28,%29,%30,%31,"
      "%32,%33,%34,%35,%36,%37,%38,%39,%40,%41,%42,%43,%44,%45,%46,%47,"
      "%48,%49,%50,%51,%52,%53,%54,%55,%56,%57,%58,%59,%60,%61,%62,%63,"
      "%64,%65,%66,%67,%68,%69,%70,%71,%72,%73,%74,%75,%76,%77,%78,%79,"
      "%80,%81,%82,%83,%84,%85,%86,%87,%88,%89,%90,%91,%92,%93,%94,%95}, "
      "da, db, p, 1, 1, 0, 1;\n}"
      : "+f"(d[0]), "+f"(d[1]), "+f"(d[2]), "+f"(d[3]), "+f"(d[4]), "+f"(d[5]), "+f"(d[6]), "+f"(d[7]),
        "+f"(d[8]), "+f"(d[9]), "+f"(d[10]), "+f"(d[11]), "+f"(d[12]), "+f"(d[13]), "+f"(d[14]), "+f"(d[15]),
        "+f"(d[16]), "+f"(d[17]), "+f"(d[18]), "+f"(d[19]), "+f"(d[20]), "+f"(d[21]), "+f"(d[22]), "+f"(d[23]),
        "+f"(d[24]), "+f"(d[25]), "+f"(d[26]), "+f"(d[27]), "+f"(d[28]), "+f"(d[29]), "+f"(d[30]), "+f"(d[31]),
        "+f"(d[32]), "+f"(d[33]), "+f"(d[34]), "+f"(d[35]), "+f"(d[36]), "+f"(d[37]), "+f"(d[38]), "+f"(d[39]),
        "+f"(d[40]), "+f"(d[41]), "+f"(d[42]), "+f"(d[43]), "+f"(d[44]), "+f"(d[45]), "+f"(d[46]), "+f"(d[47]),
        "+f"(d[48]), "+f"(d[49]), "+f"(d[50]), "+f"(d[51]), "+f"(d[52]), "+f"(d[53]), "+f"(d[54]), "+f"(d[55]),
        "+f"(d[56]), "+f"(d[57]), "+f"(d[58]), "+f"(d[59]), "+f"(d[60]), "+f"(d[61]), "+f"(d[62]), "+f"(d[63]),
        "+f"(d[64]), "+f"(d[65]), "+f"(d[66]), "+f"(d[67]), "+f"(d[68]), "+f"(d[69]), "+f"(d[70]), "+f"(d[71]),
        "+f"(d[72]), "+f"(d[73]), "+f"(d[74]), "+f"(d[75]), "+f"(d[76]), "+f"(d[77]), "+f"(d[78]), "+f"(d[79]),
        "+f"(d[80]), "+f"(d[81]), "+f"(d[82]), "+f"(d[83]), "+f"(d[84]), "+f"(d[85]), "+f"(d[86]), "+f"(d[87]),
        "+f"(d[88]), "+f"(d[89]), "+f"(d[90]), "+f"(d[91]), "+f"(d[92]), "+f"(d[93]), "+f"(d[94]), "+f"(d[95])
      : "r"(da), "r"(db), "r"(scale_d), "n"(DESC_HI), "n"(DESC_HI64));
}
DEVI void wgmma_n64(float (&d)[32], uint32_t da, uint32_t db, int scale_d) {
  asm volatile(
      "{\n.reg .pred p;\n.reg .b64 da, db;\nsetp.ne.b32 p, %34, 0;\nmov.b64 da, {%32, %35};\nmov.b64 db, {%33, %35};\n"
      "wgmma.mma_async.sync.aligned.m64n64k16.f32.bf16.bf16 "
      "{%0,%1,%2,%3,%4,%5,%6,%7,%8,%9,%10,%11,%12,%13,%14,%15,"
      "%16,%17,%18,%19,%20,%21,%22,%23,%24,%25,%26,%27,%28,%29,%30,%31}, "
      "da, db, p, 1, 1, 0, 1;\n}"
      : "+f"(d[0]), "+f"(d[1]), "+f"(d[2]), "+f"(d[3]), "+f"(d[4]), "+f"(d[5]), "+f"(d[6]), "+f"(d[7]),
        "+f"(d[8]), "+f"(d[9]), "+f"(d[10]), "+f"(d[11]), "+f"(d[12]), "+f"(d[13]), "+f"(d[14]), "+f"(d[15]),
        "+f"(d[16]), "+f"(d[17]), "+f"(d[18]), "+f"(d[19]), "+f"(d[20]), "+f"(d[21]), "+f"(d[22]), "+f"(d[23]),
        "+f"(d[24]), "+f"(d[25]), "+f"(d[26]), "+f"(d[27]), "+f"(d[28]), "+f"(d[29]), "+f"(d[30]), "+f"(d[31])
      : "r"(da), "r"(db), "r"(scale_d), "n"(DESC_HI));
}

struct C32 { float re, im; };
DEVI C32 csq(C32 a) { return {a.re * a.re - a.im * a.im, 2.f * a.re * a.im}; }
DEVI C32 cmul(C32 a, C32 b) { return {a.re * b.re - a.im * b.im, a.re * b.im + a.im * b.re}; }
DEVI C32 cfresh(float zl, float zi, float m) {
  float mag = ex2(zl * m), ph = zi * m;
  return {mag * __cosf(ph), mag * __sinf(ph)};
}
struct HMul { uint32_t b, bp; };
DEVI HMul mk_mul(float re, float im) { return {pack_f16(re, im), pack_f16(-im, re)}; }
DEVI uint32_t hcmul(uint32_t a, const HMul& m) {
  __half2 ah = *reinterpret_cast<__half2*>(&a);
  __half2 b = *reinterpret_cast<const __half2*>(&m.b), bp = *reinterpret_cast<const __half2*>(&m.bp);
  __half2 r = __hfma2(__high2half2(ah), bp, __hmul2(__low2half2(ah), b));
  return *reinterpret_cast<uint32_t*>(&r);
}
DEVI uint32_t badd(uint32_t a, uint32_t b) {
  __nv_bfloat162 r = __hadd2(*reinterpret_cast<__nv_bfloat162*>(&a), *reinterpret_cast<__nv_bfloat162*>(&b));
  return *reinterpret_cast<uint32_t*>(&r);
}
template <int MU0, int NMU, int DMAX>
DEVI void conv_tail(float (&acc)[16][4], uint32_t p_lane, uint32_t v_base, int back, bool edge, int lane) {
  const int hsel = (lane >> 3) & 1;
  const int row = (lane & 7) + ((lane >> 4) << 3) + PADV - 8 - (back & (hsel ^ 1));
  const uint32_t la = v_base + row * 32 + (((hsel ^ back) ^ ((row >> 2) & 1)) << 4);
  uint32_t M[3][4];
  ldsm_x4_t(M[0], la);
  ldsm_x4_t(M[1], la + 256);
  uint32_t H[2 * NMU];
#pragma unroll
  for (int i = 0; i < 2 * NMU; ++i) H[i ^ 1] = lds32(p_lane + (uint32_t)(MU0 - 1 + i) * 32);
  if (edge) {
    const uint32_t a[4] = {0u, 0u, M[0][0], M[0][1]};
#pragma unroll
    for (int k = 1; k < NMU; ++k) mma_bf16v(acc[MU0 - 2 + 2 * k], a, H[2 * k], H[2 * k + 1]);
  }
#pragma unroll
  for (int delta = -1; delta <= DMAX; ++delta) {
    if (delta + 2 <= DMAX) ldsm_x4_t(M[(delta + 3) % 3], la + (delta + 3) * 256);
#pragma unroll
    for (int k = 0; k < NMU; ++k)
      if (delta + MU0 + 2 * k < 16) mma_bf16v(acc[delta + MU0 + 2 * k], M[(delta + 1) % 3], H[2 * k], H[2 * k + 1]);
  }
}

template <int NB>
DEVI void box_filters(uint32_t sb, uint32_t bars, int idx, int lane) {
  auto swz = [](int k, int pad) { const int r = (k >> 1) + pad; return (uint32_t)(r * 32 + (((k & 1) ^ ((r >> 2) & 1)) << 4)); };
  const uint32_t o0 = swz(lane - 3, 8), o1 = swz(lane - 2, 8), o2 = swz(lane - 1, 8), ow = swz(lane - 2, PADV), oz = swz(lane - 18, PADV);
  const int k = 32 * idx - 2 + lane;
#pragma unroll 1
  for (int c2 = 0; c2 < 4; c2 += NB) {
    uint4 t[NB][3];
#pragma unroll
    for (int b = 0; b < NB; ++b) mbar_wait_long(bars + 8 * (B_UCH + c2 + b), 0);
#pragma unroll
    for (int b = 0; b < NB; ++b) {
      const uint32_t ua = sb + SM_U + (c2 + b) * U_BYTES + idx * 512;
      t[b][0] = lds128(ua + o0); t[b][1] = lds128(ua + o1); t[b][2] = lds128(ua + o2);
    }
#pragma unroll
    for (int b = 0; b < NB; ++b) {
      const uint32_t vb = sb + SM_VV + (c2 + b) * VV_BYTES, aw = vb + idx * 512 + ow;
      const uint32_t E[12] = {t[b][0].x, t[b][0].y, t[b][0].z, t[b][0].w, t[b][1].x, t[b][1].y, t[b][1].z, t[b][1].w,
                              t[b][2].x, t[b][2].y, t[b][2].z, t[b][2].w};
      uint32_t O[8];
#pragma unroll
      for (int j = 0; j < 8; ++j) O[j] = __byte_perm(E[j + 1], E[j + 2], 0x5432);
      uint32_t s3[6], s5[4], s7[4], s9[4];
#pragma unroll
      for (int j = 0; j < 6; ++j) s3[j] = badd(badd(O[j], O[j + 1]), E[j + 2]);
#pragma unroll
      for (int j = 0; j < 4; ++j) {
        s5[j] = badd(s3[j + 2], badd(E[j + 3], E[j + 5]));
        s7[j] = badd(s5[j], badd(O[j + 1], O[j + 4]));
        s9[j] = badd(s7[j], badd(E[j + 2], E[j + 6]));
      }
      if (k < 208) { sts128(aw + VV_U3, s3[0], s3[1], s3[2], s3[3]); sts128(aw + VV_U5, s5[0], s5[1], s5[2], s5[3]); }
      if (k < 144) { sts128(aw + VV_U7, s7[0], s7[1], s7[2], s7[3]); sts128(aw + VV_U9, s9[0], s9[1], s9[2], s9[3]); }
      if (idx == 0 && lane < 16) {
        sts128(vb + oz + VV_U3, 0, 0, 0, 0); sts128(vb + oz + VV_U5, 0, 0, 0, 0);
        sts128(vb + oz + VV_U7, 0, 0, 0, 0); sts128(vb + oz + VV_U9, 0, 0, 0, 0);
      }
    }
  }
}

DEVI uint32_t o_slot(int c) { return c < 6 ? SM_QS + c * 16384 : SM_VV + (c - 6) * 16384; }
DEVI uint32_t wo_slot(int c) { return c < 5 ? SM_WO + c * 8192 : c < 7 ? SM_VV + 32768 + (c - 5) * 8192 : SM_QS; }

__global__ void __cluster_dims__(2, 1, 1) __launch_bounds__(NTHREADS, 1)
fused_kernel(const __grid_constant__ Maps maps, const Ptrs p) {
  extern __shared__ __align__(1024) uint8_t smem[];
  const uint32_t sb = s2u(smem);
  const int tid = threadIdx.x, lane = tid & 31;
  const int warp = __shfl_sync(0xffffffffu, tid >> 5, 0);
  const int cta = blockIdx.x;
  const uint32_t rank = cta & 1;
  const int ti = 2 * (cta >> 4) + rank;
  const int tj = (cta >> 1) & 7;
  const int pi = cta >> 3, pj = cta & 7;
  const uint32_t bars = sb + SM_BAR;
#define BAR(i) (bars + 8 * (i))
  const int g = lane >> 2, q = lane & 3;

  auto issue_stage = [&](int ks, int s) {
    const uint32_t st = sb + s * STG_BYTES, fb = BAR(B_FULL + s);
    mbar_expect_tx(fb, STG_BYTES);
    tma_load_2d(st + STG_X, &maps.x, ks * 32, ti * 128, fb);
    tma_load_3d_mc(st + STG_W + rank * 6144, &maps.w, tj * 64, ks * 32 + rank * 16, 0, fb, 3);
  };

  const int kch = warp & 3, krd = warp >> 2;
  float zr, zi, wr, wi;
  unsigned epoch;
  uint32_t r_dskip;
  {
    const size_t po = (size_t)(cta * 4 + kch) * 128 + krd * 32 + lane;
    const uint32_t r_ar = ldg16(p.A_re + po), r_ai = ldg16(p.A_im + po), r_br = ldg16(p.B_re + po), r_bi = ldg16(p.B_im + po);
    const uint32_t r_cr = ldg16(p.C_re + po), r_ci = ldg16(p.C_im + po), r_ldt = ldg16(p.log_dt + cta * 4 + kch);
    epoch = __ldcg(&g_epoch);
    r_dskip = ldg16(p.Dskip + cta * 4 + kch);
    uint4 pt;
    if (tid < 128) pt = __ldg((const uint4*)g_ptab.v + tid);
    if (tid == 384) {
      TS(0);
#pragma unroll
      for (int i = 0; i < B_COUNT; ++i) mbar_init(BAR(i), bar_count(i));
      asm volatile("fence.mbarrier_init.release.cluster;" ::: "memory");
      prefetch_tmap(&maps.x); prefetch_tmap(&maps.w); prefetch_tmap(&maps.u);
    }
    __syncthreads();
    cluster_arrive();
    if (warp >= 12) {
      cluster_wait();
      if (elect_one()) {
        if (warp == 13) {
#define U_POS 0
          if (U_POS == 0) { mbar_expect_tx(BAR(B_TILE), 16384); tma_load_2d(sb + SM_U, &maps.u, tj * 64, ti * 128, BAR(B_TILE)); }
          prefetch_tmap(&maps.uT); prefetch_tmap(&maps.wo); prefetch_tmap(&maps.o); prefetch_tmap(&maps.yT);
          prefetch_tmap(&maps.out); prefetch_tmap(&maps.outh);
        } else {
          if (warp == 12) TS(61);
          { const int ks = warp == 12 ? 0 : warp - 13; issue_stage(ks, ks); }
        }
      }
      __syncwarp();
    }
    if (tid < 128) sts128(sb + SM_PTAB + tid * 16, pt.x, pt.y, pt.z, pt.w);
    const float dt = round_bf16(expf(bf_lo(r_ldt)));
    zr = dt * bf_lo(r_ar); zi = dt * bf_lo(r_ai);
    const float dbr = dt * bf_lo(r_br), dbi = dt * bf_lo(r_bi), cr = bf_lo(r_cr), ci = bf_lo(r_ci);
    wr = cr * dbr - ci * dbi; wi = cr * dbi + ci * dbr;
  }
  {
    const float mz = __uint_as_float(__reduce_max_sync(0xffffffffu, __float_as_uint(fmaxf(zr, 0.f))));
    const int E = min(max((int)(__reduce_max_sync(0xffffffffu, __float_as_uint(fmaxf(fabsf(wr), fabsf(wi)))) >> 23), 1), 252);
    const float sc = __int_as_float((253 - E) << 23), inv = __int_as_float((E + 1) << 23);
    const float zl = (zr - mz) * 1.4426950408889634f;
    const uint32_t tb = sb + SM_VV + kch * VV_BYTES + krd * KG_BYTES;
    const uint32_t sta = tb + (((lane >> 2) << 4) | ((lane & 3) << 2));
    auto put = [&](int r, uint32_t v) { sts32((sta ^ ((r & 7) << 4)) + r * 128, v); };
    const uint32_t lda = tb + ((lane & 7) + (((lane >> 3) & 1) << 3)) * 128;
    const uint32_t ldb = tb + ((lane & 7) + ((lane >> 4) << 3)) * 128;
#define STG_POS 0
#define PF_POS 1
    if (U_POS == 1 && warp == 13 && elect_one()) { mbar_expect_tx(BAR(B_TILE), 16384); tma_load_2d(sb + SM_U, &maps.u, tj * 64, ti * 128, BAR(B_TILE)); }
    if (STG_POS == 0 && warp >= 14 && elect_one()) { issue_stage(warp - 11, warp - 11); issue_stage(warp - 9, warp - 9); }
    if (PF_POS == 0 && warp >= 14 && elect_one()) {
      if (warp == 14) l2_prefetch((const char*)p.wqkv + 224 * 3072 + cta * 6912, 6912);
      else l2_prefetch((const char*)p.x + (size_t)cta * 16384, 16384);
    }
    __syncwarp();
    C32 e1 = cfresh(zl, zi, 1.f), e2 = csq(e1), e4 = csq(e2), e8 = csq(e4);
    C32 e16 = cfresh(zl, zi, 16.f), e32 = csq(e16), e64 = csq(e32), e128 = csq(e64);
    C32 e256 = cfresh(zl, zi, 256.f), e512 = csq(e256), e1024 = csq(e512), e768 = cmul(e512, e256);
    uint32_t XA[2][4][4];
    {
      const HMul m16 = mk_mul(e16.re, e16.im), m32 = mk_mul(e32.re, e32.im), m64 = mk_mul(e64.re, e64.im);
      const HMul m128 = mk_mul(e128.re, e128.im);
      uint32_t X[16];
      X[0] = 0x00003c00u; X[1] = pack_f16(e8.re, e8.im); X[2] = m16.b; X[4] = m32.b; X[8] = m64.b;
      X[3] = hcmul(X[1], m16); X[5] = hcmul(X[1], m32); X[6] = hcmul(X[2], m32); X[7] = hcmul(X[3], m32);
#pragma unroll
      for (int r = 1; r < 8; ++r) X[8 + r] = hcmul(X[r], m64);
#pragma unroll
      for (int h = 0; h < 2; ++h) {
#pragma unroll
        for (int r = 0; r < 16; ++r) put(r, h == 0 ? X[r] : r == 0 ? m128.b : hcmul(X[r], m128));
        __syncwarp();
#pragma unroll
        for (int k = 0; k < 4; ++k) ldsm_x4(XA[h][k], lda + (((2 * k + (lane >> 4)) ^ (lane & 7)) << 4));
        __syncwarp();
      }
    }
    if (U_POS == 2 && warp == 13 && elect_one()) { mbar_expect_tx(BAR(B_TILE), 16384); tma_load_2d(sb + SM_U, &maps.u, tj * 64, ti * 128, BAR(B_TILE)); }
    if (STG_POS == 1 && warp >= 14 && elect_one()) { issue_stage(warp - 11, warp - 11); issue_stage(warp - 9, warp - 9); }
#define PF_MODE 3
    if (PF_POS == 1 && warp >= 14 && elect_one()) {
      if (warp == 14) { if (PF_MODE & 1) l2_prefetch((const char*)p.wqkv + 224 * 3072 + cta * 6912, 6912); }
      else if (PF_MODE & 2) l2_prefetch((const char*)p.x + (size_t)cta * 16384, 16384);
      else if (PF_MODE & 4) {
#pragma unroll 1
        for (int r = 0; r < 16; ++r) l2_prefetch((const char*)p.x + (size_t)(cta * 16 + r) * 1024 + 448, 576);
      }
    }
    __syncwarp();
    float D[2][3][4];
#pragma unroll
    for (int t = 0; t < 6; ++t) D[t / 3][t % 3][0] = D[t / 3][t % 3][1] = D[t / 3][t % 3][2] = D[t / 3][t % 3][3] = 0.f;
    auto contract = [&](int t0, int nt) {
      __syncwarp();
#pragma unroll
      for (int k = 0; k < 4; ++k) {
        uint32_t b[4];
        ldsm_x4(b, ldb + (((2 * k + ((lane >> 3) & 1)) ^ (lane & 7)) << 4));
#pragma unroll
        for (int h = 0; h < 2; ++h) {
          mma_f16(D[h][t0], XA[h][k], b[0], b[1]);
          if (nt == 2) mma_f16(D[h][t0 + 1], XA[h][k], b[2], b[3]);
        }
      }
      __syncwarp();
    };
    const HMul c1 = mk_mul(e1.re, -e1.im), c2 = mk_mul(e2.re, -e2.im), c4 = mk_mul(e4.re, -e4.im);
    const HMul c256 = mk_mul(e256.re, -e256.im), c512 = mk_mul(e512.re, -e512.im), c768 = mk_mul(e768.re, -e768.im);
    const HMul c1024 = mk_mul(e1024.re, -e1024.im);
    uint32_t W[8];
    W[0] = pack_f16(wr * sc, -wi * sc);
    W[1] = hcmul(W[0], c1); W[2] = hcmul(W[0], c2); W[3] = hcmul(W[1], c2);
    W[4] = hcmul(W[0], c4); W[5] = hcmul(W[1], c4); W[6] = hcmul(W[2], c4); W[7] = hcmul(W[3], c4);
#pragma unroll
    for (int i = 0; i < 8; ++i) put(i, W[i]);
#pragma unroll
    for (int i = 0; i < 4; ++i) put(8 + i, hcmul(W[2 * i], c256));
    put(12, hcmul(W[0], c512)); put(13, hcmul(W[4], c512)); put(14, hcmul(W[0], c768)); put(15, hcmul(W[4], c768));
    if (PF_POS == 2 && warp >= 14 && elect_one()) {
      if (warp == 14) l2_prefetch((const char*)p.wqkv + 224 * 3072 + cta * 6912, 6912);
      else l2_prefetch((const char*)p.x + (size_t)cta * 16384, 16384);
    }
    contract(0, 2);
    const uint32_t v0 = hcmul(W[0], c1024);
    put(0, v0); put(1, hcmul(v0, c256)); put(2, hcmul(v0, c512)); put(3, hcmul(v0, c768)); put(4, hcmul(v0, c1024));
    contract(2, 1);
    const uint32_t a = tb + (g * 24 + 2 * q) * 4;
#pragma unroll
    for (int t = 0; t < 6; ++t) {
      const float(&d)[4] = D[t / 3][t % 3];
      sts_f32x2(a + (t / 3) * 1536 + (t % 3) * 32, d[0], d[1]);
      sts_f32x2(a + (t / 3) * 1536 + (t % 3) * 32 + 768, d[2], d[3]);
    }
    if (lane == 0) sts_f32(tb + 3072, inv);
    if (mz > 0.f) {
      __syncwarp();
#pragma unroll 1
      for (int i = lane; i < 768; i += 32) {
        const int r = i / 24, y = i - 24 * r;
        sts_f32(tb + i * 4, lds_f32(tb + i * 4) * ex2(mz * 1.4426950408889634f * (koff(y) + 8 * r)));
      }
    }
  }
  if (tid == 0) TS(2);
  if (warp < 12) cluster_wait();
  __syncthreads();

  if (warp < 4) {
#define A_REGS 200
    asm volatile("setmaxnreg.inc.sync.aligned.u32 %0;" ::"n"(A_REGS));
    if (tid == 0) TS(34);
    const int d = cta * 4 + warp;
    const uint32_t vv = sb + SM_VV + warp * VV_BYTES;
    const uint32_t ub = sb + SM_U + warp * U_BYTES;
    const uint32_t pb = sb + SM_P + warp * P_BYTES;
    const float dskip = bf_lo(r_dskip);
#pragma unroll 1
    for (int pass = 0; pass < 2; ++pass) {
      if (pass == 1) {
        const uint32_t kf = vv;
        const float i0 = lds_f32(kf + 3072), i1 = lds_f32(kf + KG_BYTES + 3072), i2 = lds_f32(kf + 2 * KG_BYTES + 3072);
        const float i3 = lds_f32(kf + 3 * KG_BYTES + 3072);
#pragma unroll 2
        for (int i = 0; i < 6; ++i) {
          const uint32_t a = kf + (i * 32 + lane) * 16;
          const uint4 x0 = lds128(a), x1 = lds128(a + KG_BYTES), x2 = lds128(a + 2 * KG_BYTES), x3 = lds128(a + 3 * KG_BYTES);
          auto s4 = [&](uint32_t a0, uint32_t a1, uint32_t a2, uint32_t a3) {
            return __float_as_uint(fmaf(__uint_as_float(a0), i0, __uint_as_float(a1) * i1) +
                                   fmaf(__uint_as_float(a2), i2, __uint_as_float(a3) * i3));
          };
          sts128(a, s4(x0.x, x1.x, x2.x, x3.x), s4(x0.y, x1.y, x2.y, x3.y), s4(x0.z, x1.z, x2.z, x3.z), s4(x0.w, x1.w, x2.w, x3.w));
        }
        __syncwarp();
        const float k1024 = lds_f32(kf + kidx_c(1024) * 4);
        if (lane == 0) {
          sts_f32(kf + SL_ZERO * 4, 0.f);
          sts_f32(kf + SL_510 * 4, lds_f32(kf + kidx_c(510) * 4) - lds_f32(kf + kidx_c(512) * 4));
          sts_f32(kf + SL_0 * 4, lds_f32(kf) + dskip);
        }
        __syncwarp();
        if (tid == 0) TS(36);
        mbar_wait_long(BAR(B_PFREE), 0);
        if (tid == 0) TS(37);
        {
          float prev = 0.f;
#pragma unroll 1
          for (int i0 = 0; i0 < 16; i0 += 4) {
            uint32_t e[4];
            float a[4], b[4];
#pragma unroll
            for (int i = 0; i < 4; ++i) e[i] = lds32(sb + SM_PTAB + ((i0 + i) * 32 + lane) * 4);
#pragma unroll
            for (int i = 0; i < 4; ++i) { a[i] = lds_f32(kf + (e[i] & 0xffff)); b[i] = lds_f32(kf + (e[i] >> 16)); }
#pragma unroll
            for (int i = 0; i < 4; ++i) {
              const uint32_t w = pb + (31 * lane + 2 * (i0 + i)) * 4;
              if (i0 + i > 0) sts32(w - 4, pack_bf16(a[i], prev));
              sts32(w, pack_bf16(b[i], a[i]));
              prev = b[i];
            }
          }
        }
        __syncwarp();
        if (lane == 0) TS(4);
        const int gq = g - 2 * q;
        uint32_t h127, h128;
        {
          const uint32_t kf2 = pack_bf16(k1024, k1024) ^ 0x80008000u;
          h127 = (gq == 4 ? 0x0000ffffu : gq == 5 ? 0xffffffffu : gq == 6 ? 0xffff0000u : 0u) & kf2;
          h128 = (gq == -4 ? 0x0000ffffu : gq == -3 ? 0xffffffffu : gq == -2 ? 0xffff0000u : 0u) & kf2;
        }
        bar_arrive(7, 384);
        if (lane == 0) TS(6);
        bar_sync(4, 384);
        mbar_wait_long(BAR(B_UCH + warp), 0);
        if (lane == 0) TS(7);
        float acc[16][4];
#pragma unroll
        for (int i = 0; i < 16; ++i) { acc[i][0] = acc[i][1] = acc[i][2] = acc[i][3] = 0.f; }
        {
          const uint32_t pd_lane = pb + (PD_OFF + 16 + gq) * 4;
          const int prow0 = 8 + (lane & 7) + ((lane >> 4) << 3), hs = (lane >> 3) & 1;
          const uint32_t zero = (uint32_t)cta >> 20;
          uint32_t B[2][4][4];
          uint32_t A[4][4];
          const uint32_t la0 = ub + prow0 * 32 + ((hs ^ ((prow0 >> 2) & 1)) << 4);
#pragma unroll
          for (int m2 = 0; m2 < 4; ++m2) ldsm_x4(B[0][m2], la0 + m2 * 512);
#pragma unroll
          for (int i = 0; i < 4; ++i) {
            const uint32_t a = pd_lane + i * 512;
            A[i][0] = lds32(a); A[i][1] = lds32(a + 32); A[i][2] = lds32(a - 32); A[i][3] = lds32(a + zero);
          }
          uint32_t la = la0;
#define UNR_RHO 4
#define UNR_TAIL 4
          constexpr int unr_rho = UNR_RHO, unr_tail = UNR_TAIL;
#pragma unroll unr_rho
          for (int rho = 0; rho < 8; ++rho) {
#pragma unroll
            for (int m2 = 0; m2 < 4; ++m2) ldsm_x4(B[1][m2], la + (4 + m2) * 512);
#pragma unroll
            for (int i = 0; i < 4; ++i)
#pragma unroll
              for (int m = 0; m < 8; ++m) mma_bf16v(acc[m + i], A[i], B[0][m >> 1][2 * (m & 1)], B[0][m >> 1][2 * (m & 1) + 1]);
            const int prow = prow0 - min(rho + 1, 7);
            la = ub + prow * 32 + ((hs ^ ((prow >> 2) & 1)) << 4);
#pragma unroll
            for (int m2 = 0; m2 < 4; ++m2) ldsm_x4(B[0][m2], la + m2 * 512);
            const uint32_t pa = pd_lane + (rho + 1) * 64;
#pragma unroll
            for (int i = 0; i < 4; ++i) {
#pragma unroll
              for (int m = 0; m < 8 - i; ++m)
                mma_bf16v(acc[8 + m + i], A[i], B[1][m >> 1][2 * (m & 1)], B[1][m >> 1][2 * (m & 1) + 1]);
              A[i][0] = lds32(pa + i * 512); A[i][1] = lds32(pa + i * 512 + 32); A[i][2] = lds32(pa + i * 512 - 32);
              A[i][3] = lds32(pa + i * 512 + zero);
            }
          }
          if (lane == 0) TS(40);
          {
            uint32_t b8[4];
            ldsm_x4(b8, la + 4 * 512);
            const uint32_t h63 = lds32(pd_lane + 63 * 32), h64 = lds32(pd_lane + 64 * 32);
            const uint32_t a63[4] = {0u, h127, 0u, 0u}, a32[4] = {h64, 0u, h63, h64}, a64[4] = {h128, 0u, h127, h128};
#pragma unroll
            for (int m2 = 0; m2 < 4; ++m2) ldsm_x4(B[1][m2], la0 + m2 * 512);
#pragma unroll
            for (int m = 0; m < 8; ++m) mma_bf16v(acc[m + 7], a63, B[0][m >> 1][2 * (m & 1)], B[0][m >> 1][2 * (m & 1) + 1]);
#pragma unroll
            for (int m2 = 0; m2 < 2; ++m2) ldsm_x4(B[0][m2], la0 + (4 + m2) * 512);
#pragma unroll
            for (int m = 0; m < 8; ++m) mma_bf16v(acc[m + 4], a32, B[1][m >> 1][2 * (m & 1)], B[1][m >> 1][2 * (m & 1) + 1]);
            mma_bf16v(acc[15], a63, b8[0], b8[1]);
#pragma unroll
            for (int m = 0; m < 8; ++m) mma_bf16v(acc[m + 8], a64, B[1][m >> 1][2 * (m & 1)], B[1][m >> 1][2 * (m & 1) + 1]);
#pragma unroll
            for (int m = 0; m < 4; ++m) mma_bf16v(acc[m + 12], a32, B[0][m >> 1][2 * (m & 1)], B[0][m >> 1][2 * (m & 1) + 1]);
          }
          if (lane == 0) TS(41);
          bar_sync(5, 384);
#pragma unroll unr_tail
          for (int v = 0; v < 4; ++v)
            conv_tail<4, 3, 11>(acc, pb + (P2_OFF + 56 * v + gq - 16) * 4, vv + ((v & 1) ? VV_U3 : VV_U5), v >> 1, v == 0, lane);
          if (lane == 0) TS(42);
#pragma unroll unr_tail
          for (int pi = 0; pi < 2; ++pi)
            conv_tail<8, 5, 7>(acc, pb + (P3_OFF + 88 * pi + gq - 48) * 4, vv + (pi ? VV_U7 : VV_U9), pi, pi == 0, lane);
        }
        if (lane == 0) TS(8);
        __syncwarp();
        {
          const int mt = lane >> 3;
          const uint32_t a = pb + (128 * (mt >> 1) + 16 * (lane & 7) + 8 * (mt & 1)) * 2;
#pragma unroll
          for (int ab = 0; ab < 16; ab += 2)
            stsm_x4_t(a + ab * 256, pack_bf16(acc[ab][0], acc[ab][1]), pack_bf16(acc[ab][2], acc[ab][3]),
                      pack_bf16(acc[ab + 1][0], acc[ab + 1][1]), pack_bf16(acc[ab + 1][2], acc[ab + 1][3]));
        }
        fence_async_smem();
        __syncwarp();
        if (lane < 2) mbar_arrive_cluster(BAR(B_CONVD), lane);
        __syncwarp();
        cluster_arrive();
        bar_arrive(3, 384);
        if (elect_one()) {
          bulk_store(p.yT + (size_t)d * 2048, pb, 4096);
          bulk_commit();
          bulk_wait0();
          red_relaxed_add(&g_cnt[(C_Y + (cta >> 4)) * 32], 1);
          TS(9);
        }
        bar_sync(2, 128);
        if (warp == 0 && elect_one()) {
          wait_counter(&g_cnt[(C_Y + tj) * 32], (epoch + 1) * 64);
          TS(28);
          mbar_expect_tx(BAR(B_TILE), 16384);
          tma_load_2d(sb + SM_U, &maps.yT, ti * 128, tj * 64, BAR(B_TILE));
          tma_load_2d(sb + SM_U + 8192, &maps.yT, ti * 128 + 64, tj * 64, BAR(B_TILE));
        }
        __syncwarp();
      }
      mbar_wait_long(BAR(B_TILE), pass);
      if (lane == 0) TS(26 + 3 * pass);
      {
        const int m = lane >> 3, r = lane & 7;
#pragma unroll 2
        for (int it = 0; it < 8; ++it) {
          const int tb = warp * 4 + (it >> 1), cb = (it & 1) * 4 + m;
          const uint32_t at = (tb * 8 + r) * 128 + ((cb ^ r) << 4);
          const uint32_t ac = (tb >> 3) * 8192 + (cb * 8 + r) * 128 + (((tb & 7) ^ (pass ? 0 : tb >> 3) ^ r) << 4);
          uint32_t v[4];
          ldsm_x4_t(v, sb + SM_U + (pass ? ac : at));
          stsm_x4(sb + SM_P + (pass ? at : ac), v[0], v[1], v[2], v[3]);
        }
      }
      if (pass == 0 && tid == 0) TS(35);
      fence_async_smem();
      if (pass == 0) {
        bar_arrive(6, 160);
      } else {
        bar_sync(2, 128);
        if (warp == 0 && elect_one()) {
          tma_store_2d(&maps.out, sb + SM_P, 64 * tj, 128 * ti);
          bulk_commit();
          bulk_wait_read0();
          TS(30);
        }
      }
    }
  } else if (warp < 12) {
    const int w8 = warp - 4;
    const int row = w8 * 16 + (lane & 7) + (((lane >> 3) & 1) << 3);
    uint32_t pq[16];
    {
      float acc[96];
#pragma unroll 1
      for (int ks = 0, s = 0, ph = 0; ks < 16; ++ks) {
        mbar_wait(BAR(B_FULL + s), ph);
        if (tid == 128 && !(ks & 1)) TSR(16, ks == 0 ? 16 : 9 + (ks >> 1) + (ks > 12 ? 43 : 0));
        const uint32_t st = sb + s * STG_BYTES;
        const uint32_t da = mkdesc(st + STG_X + (w8 >> 2) * 4096, 16);
        const uint32_t db = mkdesc(st + STG_W, 2048);
        wg_fence();
        wgmma_n192(acc, da, db, ks != 0);
        wgmma_n192(acc, da + 2, db + 384, 1);
        wg_commit();
        const uint32_t eprev = BAR(B_EMPTY + (s == 0 ? NSTG - 1 : s - 1));
        if (++s == NSTG) { s = 0; ph ^= 1; }
        if (ks > 0) {
          wg_wait<1>();
          if (lane < 2) mbar_arrive_cluster(eprev, lane);
        }
      }
      wg_wait<0>();
      bar_arrive(4, 384);
      if (tid == 128) TS(17);
      auto phi2 = [](float a, float b) -> uint32_t {
        const uint32_t x = pack_bf16(a, b);
        const uint32_t e = pack_bf16(ex2(a * 1.4426950408889634f), ex2(b * 1.4426950408889634f));
        const uint32_t m = __hgt2_mask(*reinterpret_cast<const __nv_bfloat162*>(&x), __floats2bfloat162_rn(0.f, 0.f));
        return badd((badd(x, 0x3f803f80u) & m) | (e & ~m), 0x35863586u);
      };
      uint32_t pk[16];
#pragma unroll
      for (int i = 0; i < 16; ++i) pk[i] = phi2(acc[32 + 2 * i], acc[33 + 2 * i]);
      if (tid == 128) TS(53);
      bar_sync(1, 256);
#pragma unroll
      for (int i = 0; i < 8; i += 2) {
        const uint32_t off = row * 128 + (((i + (lane >> 4)) ^ (row & 7)) << 4);
        stsm_x4(sb + SM_PK + off, pk[2 * i], pk[2 * i + 1], pk[2 * i + 2], pk[2 * i + 3]);
        stsm_x4(sb + SM_VS + off, pack_bf16(acc[64 + 4 * i], acc[65 + 4 * i]), pack_bf16(acc[66 + 4 * i], acc[67 + 4 * i]),
                pack_bf16(acc[68 + 4 * i], acc[69 + 4 * i]), pack_bf16(acc[70 + 4 * i], acc[71 + 4 * i]));
      }
      bar_sync(1, 256);
      {
        const int hh = w8 >> 1, dtile = w8 & 1;
        float kv[2][4] = {{0.f, 0.f, 0.f, 0.f}, {0.f, 0.f, 0.f, 0.f}}, zz[2][4] = {{0.f, 0.f, 0.f, 0.f}, {0.f, 0.f, 0.f, 0.f}};
        const int m = lane >> 3;
        const uint32_t aa = sb + SM_VS + ((lane & 7) + ((m >> 1) << 3)) * 128 + (((2 * hh + (m & 1)) ^ (lane & 7)) << 4);
        const uint32_t ab = sb + SM_PK + (lane & 15) * 128 + (((2 * hh + dtile) ^ (lane & 7)) << 4);
#pragma unroll
        for (int ks = 0; ks < 8; ++ks) {
          uint32_t a[4], b0, b1;
          ldsm_x4_t(a, aa + ks * 2048);
          ldsm_x2_t(b0, b1, ab + ks * 2048);
          mma_bf16(kv[ks & 1], a[0], a[1], a[2], a[3], b0, b1);
          mma_bf16(zz[ks & 1], 0x3f803f80u, 0x3f803f80u, 0x3f803f80u, 0x3f803f80u, b0, b1);
        }
        const uint32_t kp = sb + SM_KV + hh * 1088;
        sts128(kp + dtile * 512 + lane * 16, __float_as_uint(kv[0][0] + kv[1][0]), __float_as_uint(kv[0][1] + kv[1][1]),
               __float_as_uint(kv[0][2] + kv[1][2]), __float_as_uint(kv[0][3] + kv[1][3]));
        if (g == 0) sts_f32x2(kp + 1024 + dtile * 32 + q * 8, zz[0][0] + zz[1][0], zz[0][1] + zz[1][1]);
        fence_async_smem();
        __syncwarp();
        if (lane == 0) mbar_arrive(BAR(B_KVP));
        if (tid == 128) TS(55);
      }
#pragma unroll
      for (int i = 0; i < 16; ++i) pq[i] = phi2(acc[2 * i], acc[2 * i + 1]);
    }
    if (tid == 128) TS(56);
    if (warp == 4) mbar_wait_long(BAR(B_KVF), 0);
    bar_sync(1, 256);
    if (tid == 128) TS(19);
    {
      uint32_t kb[4][6];
#pragma unroll
      for (int h = 0; h < 4; ++h) {
        const uint32_t kp = sb + SM_KV + h * 1088;
        const uint4 k0 = lds128(kp + lane * 16), k1 = lds128(kp + 512 + lane * 16);
        const uint32_t za = kp + 1024 + q * 8;
        auto pk2 = [](uint32_t x, uint32_t y) { return pack_bf16(__uint_as_float(x), __uint_as_float(y)); };
        kb[h][0] = pk2(k0.x, k0.y); kb[h][1] = pk2(k1.x, k1.y); kb[h][2] = pk2(k0.z, k0.w); kb[h][3] = pk2(k1.z, k1.w);
        kb[h][4] = pack_bf16(lds_f32(za), lds_f32(za + 4)); kb[h][5] = pack_bf16(lds_f32(za + 32), lds_f32(za + 36));
      }
#pragma unroll
      for (int h = 0; h < 4; ++h) {
        float n0[4] = {0.f, 0.f, 0.f, 0.f}, n1[4] = {0.f, 0.f, 0.f, 0.f}, dn[4] = {0.f, 0.f, 0.f, 0.f};
        mma_bf16(n0, pq[4 * h], pq[4 * h + 1], pq[4 * h + 2], pq[4 * h + 3], kb[h][0], kb[h][1]);
        mma_bf16(n1, pq[4 * h], pq[4 * h + 1], pq[4 * h + 2], pq[4 * h + 3], kb[h][2], kb[h][3]);
        mma_bf16(dn, pq[4 * h], pq[4 * h + 1], pq[4 * h + 2], pq[4 * h + 3], kb[h][4], kb[h][5]);
        const float r0 = rcp(dn[0] + 1e-6f), r1 = rcp(dn[2] + 1e-6f);
        stsm_x4(sb + SM_QS + row * 128 + (((2 * h + (lane >> 4)) ^ (row & 7)) << 4),
                pack_bf16(n0[0] * r0, n0[1] * r0), pack_bf16(n0[2] * r1, n0[3] * r1),
                pack_bf16(n1[0] * r0, n1[1] * r0), pack_bf16(n1[2] * r1, n1[3] * r1));
      }
    }
    fence_async_smem();
    __syncwarp();
    if (lane == 0) mbar_arrive(BAR(B_OST));
    if (tid == 128) TS(57);
    bar_sync(7, 384);
    if (w8 < 7) box_filters<4>(sb, bars, w8, lane);
    bar_arrive(5, 384);
    if (tid == 128) TS(6);
    bar_sync(3, 384);
    {
      float o[32];
#pragma unroll 1
      for (int c = 0; c < 8; ++c) {
        mbar_wait_long(BAR(B_RF + c), 0);
        if (tid == 128) TSR(22, c == 0 ? 22 : 43 + c);
        const uint32_t da = mkdesc(sb + o_slot(c) + (w8 >> 2) * 8192, 16);
        const uint32_t db = mkdesc(sb + wo_slot(c), 8192);
        wg_fence();
#pragma unroll
        for (int k = 0; k < 4; ++k) wgmma_n64(o, da + 2 * k, db + 128 * k, (c | k) != 0);
        wg_commit();
        if (c == 1) {
          wg_wait<1>();
          if (lane < 2) mbar_arrive_cluster(BAR(B_RE), lane);
          __syncwarp();
          cluster_arrive();
        }
      }
      wg_wait<0>();
      if (tid == 128) TS(51);
#pragma unroll
      for (int i = 0; i < 8; i += 2)
        stsm_x4(sb + SM_BOUT + row * 128 + (((i + (lane >> 4)) ^ (row & 7)) << 4), pack_bf16(o[4 * i], o[4 * i + 1]),
                pack_bf16(o[4 * i + 2], o[4 * i + 3]), pack_bf16(o[4 * i + 4], o[4 * i + 5]), pack_bf16(o[4 * i + 6], o[4 * i + 7]));
      fence_async_smem();
      bar_sync(8 + (w8 >> 2), 128);
      if ((w8 & 3) == 0 && elect_one()) {
        tma_store_2d(&maps.outh, sb + SM_BOUT + (w8 >> 2) * 8192, 512 + 64 * pj, 128 * pi + (w8 >> 2) * 64);
        bulk_commit();
        bulk_wait_read0();
        TS(23);
      }
    }
  } else {
    asm volatile("setmaxnreg.dec.sync.aligned.u32 40;");
    if (warp == 12) {
      if (elect_one()) {
#pragma unroll 1
        for (int ks = NSTG, s = 0, ph = 0; ks < 16; ++ks) {
          mbar_wait(BAR(B_EMPTY + s), ph);
          issue_stage(ks, s);
          if (ks == NSTG) l2_prefetch((const char*)p.wo + (size_t)cta * 4096, 4096);
          if (++s == NSTG) { s = 0; ph ^= 1; }
        }
        mbar_wait(BAR(B_EMPTY + 6), 1);
#pragma unroll 1
        for (int c = 0; c < 5; ++c) {
          mbar_expect_tx(BAR(B_RF + c), 24576);
          tma_load_2d(sb + wo_slot(c), &maps.wo, pj * 64, c * 64, BAR(B_RF + c));
        }
        float* kvg = &g_kv[epoch & 1][tj][0];
        mbar_wait_long(BAR(B_KVP), 0);
        bulk_reduce_add_f32(kvg, sb + SM_KV, 4352);
        bulk_commit();
        bulk_wait0();
        red_relaxed_add(&g_cnt[(C_KV + tj) * 32], 1);
        TS(18);
        wait_counter(&g_cnt[(C_KV + tj) * 32], (epoch + 1) * 16);
        mbar_expect_tx(BAR(B_KVF), 4352);
        bulk_load(sb + SM_KV, kvg, 4352, BAR(B_KVF));
        mbar_wait_long(BAR(B_OST), 0);
        tma_store_2d(&maps.o, sb + SM_QS, tj * 64, ti * 128);
        tma_store_2d(&maps.o, sb + SM_QS + 8192, tj * 64, ti * 128 + 64);
        bulk_commit();
        bulk_wait0();
        red_relaxed_add(&g_cnt[(C_O + ti) * 32], 1);
        TS(20);
        mbar_arrive_cluster(BAR(B_SLOT), 0);
        mbar_arrive_cluster(BAR(B_SLOT), 1);
        wait_counter(&g_cnt[(C_O + pi) * 32], (epoch + 1) * 8);
        if (cta == 0) g_epoch = epoch + 1;
        mbar_wait(BAR(B_SLOT), 0);
        TS(21);
#pragma unroll 1
        for (int c = 0; c < 8; ++c) {
          if (c == 6) mbar_wait_long(BAR(B_CONVD), 0);
          if (c >= 5) mbar_expect_tx(BAR(B_RF + c), 24576);
          tma_load_2d_mc(sb + o_slot(c) + rank * 8192, &maps.o, c * 64, pi * 128 + rank * 64, BAR(B_RF + c), 3);
        }
#pragma unroll 1
        for (int c = 5; c < 8; ++c) {
          if (c == 7) mbar_wait(BAR(B_RE), 0);
          tma_load_2d(sb + wo_slot(c), &maps.wo, pj * 64, c * 64, BAR(B_RF + c));
        }
      }
    } else if (warp == 13) {
      bar_sync(6, 160);
      sts128(sb + SM_U + (lane >> 4) * U_BYTES + (lane & 15) * 16, 0, 0, 0, 0);
      sts128(sb + SM_U + (2 + (lane >> 4)) * U_BYTES + (lane & 15) * 16, 0, 0, 0, 0);
      __syncwarp();
      if (elect_one()) {
        tma_store_2d(&maps.uT, sb + SM_P, ti * 128, tj * 64);
        tma_store_2d(&maps.uT, sb + SM_P + 8192, ti * 128 + 64, tj * 64);
        bulk_commit();
        bulk_wait_read0();
        mbar_arrive(BAR(B_PFREE));
        bulk_wait0();
        red_relaxed_add(&g_cnt[(C_U + tj) * 32], 1);
        TS(27);
        wait_counter(&g_cnt[(C_U + (cta >> 4)) * 32], (epoch + 1) * 16);
#pragma unroll 1
        for (int c = 0; c < 4; ++c) {
          mbar_expect_tx(BAR(B_UCH + c), 4096);
          bulk_load(sb + SM_U + c * U_BYTES + 256, p.uT + (size_t)(cta * 4 + c) * 2048, 4096, BAR(B_UCH + c));
        }
        TS(3);
      }
      __syncwarp();
      if (ti == 0) {
        float4* z = (float4*)&g_kv[(epoch & 1) ^ 1][tj][0];
#pragma unroll 1
        for (int i = lane; i < 272; i += 32) z[i] = make_float4(0.f, 0.f, 0.f, 0.f);
      }
    }
  }
  __syncwarp();
  if (warp >= 12) cluster_arrive();
  cluster_wait();
  if (tid == 0) TS(31);
#undef BAR
}

typedef CUresult (*EncodeFn)(CUtensorMap*, CUtensorMapDataType, cuuint32_t, void*, const cuuint64_t*, const cuuint64_t*,
                             const cuuint32_t*, const cuuint32_t*, CUtensorMapInterleave, CUtensorMapSwizzle,
                             CUtensorMapL2promotion, CUtensorMapFloatOOBfill);

static void make_map(EncodeFn enc, CUtensorMap* m, const void* base, uint64_t inner, uint64_t outer, uint32_t box_in,
                     uint32_t box_out, CUtensorMapSwizzle swz = CU_TENSOR_MAP_SWIZZLE_128B) {
  cuuint64_t gd[2] = {inner, outer};
  cuuint64_t gs[1] = {inner * 2};
  cuuint32_t bd[2] = {box_in, box_out};
  cuuint32_t es[2] = {1, 1};
  enc(m, CU_TENSOR_MAP_DATA_TYPE_BFLOAT16, 2, const_cast<void*>(base), gd, gs, bd, es, CU_TENSOR_MAP_INTERLEAVE_NONE,
      swz, CU_TENSOR_MAP_L2_PROMOTION_L2_128B, CU_TENSOR_MAP_FLOAT_OOB_FILL_NONE);
}

}

extern "C" void kernel_launch(void* const* d_in, const int* in_sizes, int n_in, void* d_out, int out_size) {
  using namespace s4la;
  (void)in_sizes; (void)n_in; (void)out_size;
  static EncodeFn enc = nullptr;
  static void *uT = nullptr, *yT = nullptr, *oS = nullptr;
  if (!enc) {
    void* fn = nullptr;
    cudaDriverEntryPointQueryResult qr;
    cudaGetDriverEntryPoint("cuTensorMapEncodeTiled", &fn, cudaEnableDefault, &qr);
    enc = (EncodeFn)fn;
    cudaGetSymbolAddress(&uT, g_uT);
    cudaGetSymbolAddress(&yT, g_yT);
    cudaGetSymbolAddress(&oS, g_o);
    cudaFuncSetAttribute(fused_kernel, cudaFuncAttributeMaxDynamicSharedMemorySize, SM_TOTAL);
  }
  const __nv_bfloat16* const* in = (const __nv_bfloat16* const*)d_in;
  Maps maps;
  make_map(enc, &maps.x, in[9], 512, 2048, 32, 128, CU_TENSOR_MAP_SWIZZLE_64B);
  {
    cuuint64_t gd[3] = {512, 512, 3};
    cuuint64_t gs[2] = {3072, 1024};
    cuuint32_t bd[3] = {64, 16, 3};
    cuuint32_t es[3] = {1, 1, 1};
    enc(&maps.w, CU_TENSOR_MAP_DATA_TYPE_BFLOAT16, 3, const_cast<__nv_bfloat16*>(in[10]), gd, gs, bd, es,
        CU_TENSOR_MAP_INTERLEAVE_NONE, CU_TENSOR_MAP_SWIZZLE_128B, CU_TENSOR_MAP_L2_PROMOTION_L2_128B,
        CU_TENSOR_MAP_FLOAT_OOB_FILL_NONE);
  }
  make_map(enc, &maps.wo, in[11], 512, 512, 64, 64);
  make_map(enc, &maps.u, in[0], 512, 2048, 64, 128);
  make_map(enc, &maps.uT, uT, 2048, 512, 64, 64);
  make_map(enc, &maps.yT, yT, 2048, 512, 64, 64);
  make_map(enc, &maps.o, oS, 512, 2048, 64, 64);
  make_map(enc, &maps.out, d_out, 1024, 2048, 64, 128);
  make_map(enc, &maps.outh, d_out, 1024, 2048, 64, 64);
  Ptrs p;
  p.A_re = in[1]; p.A_im = in[2]; p.B_re = in[3]; p.B_im = in[4]; p.C_re = in[5]; p.C_im = in[6];
  p.log_dt = in[7]; p.Dskip = in[8]; p.x = in[9]; p.wqkv = in[10]; p.wo = in[11];
  p.uT = (__nv_bfloat16*)uT; p.yT = (__nv_bfloat16*)yT;
  fused_kernel<<<NCTA, NTHREADS, SM_TOTAL, cudaStreamPerThread>>>(maps, p);
}
```

```cpp
#include <cuda_runtime.h>
#include <cuda_bf16.h>
#include <cuda_fp16.h>
#include <cuda.h>
#include <stdint.h>

#define DEVI __device__ __forceinline__

namespace s4la {

constexpr int NTHREADS = 512;
constexpr int NCTA = 128;

constexpr int NSTG = 7;
constexpr uint32_t STG_BYTES = 20480, STG_X = 0, STG_W = 8192;
constexpr uint32_t SM_QS = 0;
constexpr uint32_t SM_PK = SM_QS + 16384, SM_VS = SM_QS + 32768;
constexpr uint32_t SM_WO = 98304;
constexpr uint32_t SM_KV = 81920;
constexpr uint32_t SM_BOUT = 16384;
constexpr uint32_t SM_U = 143360, U_BYTES = 4352;
constexpr uint32_t SM_P = 160768, P_BYTES = 4096;
constexpr uint32_t SM_VV = 177152, VV_BYTES = 12800;
constexpr uint32_t VV_U5 = 0, VV_U3 = 3712, VV_U9 = 7424, VV_U7 = 10112;
constexpr uint32_t KG_BYTES = 3200;
constexpr uint32_t SM_BAR = SM_VV + 4 * VV_BYTES;
constexpr uint32_t SM_PTAB = SM_BAR + 320;
constexpr uint32_t SM_TOTAL = SM_PTAB + 2048;
static_assert(SM_TOTAL <= 232448, "shared memory");
constexpr int PADV = 12;

enum { B_FULL = 0, B_EMPTY = 7, B_TILE = 14, B_UCH = 15, B_KVP = 19, B_KVF = 20, B_OST = 21, B_RF = 22, B_WO = 30, B_RE = 31, B_PFREE = 32, B_CONVD = 33, B_SLOT = 34, B_COUNT = 35 };
__host__ __device__ constexpr int bar_count(int i) {
  return (i >= B_EMPTY && i < B_TILE) ? 16 : (i == B_KVP || i == B_OST || i == B_CONVD) ? 8 : i == B_RE ? 16 : i == B_SLOT ? 2 : 1;
}

constexpr int PD_OFF = 0, P2_OFF = 544, P3_OFF = 768;

constexpr int SL_K2048 = 20, SL_ZERO = 21, SL_510 = 22, SL_0 = 23;
__host__ __device__ constexpr int koff(int y) {
  return y < 8 ? y : y < 12 ? 256 + 2 * (y - 8) : y < 16 ? 512 + 256 * ((y - 12) >> 1) + 4 * (y & 1) : 1024 + 256 * (y - 16);
}
__host__ __device__ constexpr int kidx_c(int l) {
  const int y = l < 256 ? (l & 7) : l < 512 ? 8 + ((l & 7) >> 1) : l < 1024 ? 12 + (((l - 512) >> 8) << 1) + ((l >> 2) & 1)
                                                                            : 16 + ((l - 1024) >> 8);
  return ((l >> 3) & 31) * 24 + y;
}
constexpr int slot_direct(int l) {
  if (l < 0 || l > 510) return SL_ZERO;
  if (l == 510) return SL_510;
  if (l == 0) return SL_0;
  return kidx_c(l < 256 ? l : ((l + ((l >> 1) & 1)) & ~1));
}
constexpr int slot_seg2(int v, int k) { return (k >= 32 && k < 64) ? kidx_c(16 * k + 4 * v) : SL_ZERO; }
constexpr int slot_seg3(int pi, int k) {
  return (k >= 64 && k < 128) ? kidx_c(16 * k + 8 * pi) : ((k == 128 && pi == 0) ? SL_K2048 : SL_ZERO);
}
constexpr int slot_word(int w) {
  return w < 0 ? SL_ZERO : w < 544 ? slot_direct(w - 16) : w < 768 ? slot_seg2((w - 544) / 56, 16 + (w - 544) % 56)
       : w < 944 ? slot_seg3((w - 768) / 88, 48 + (w - 768) % 88) : SL_ZERO;
}
struct PTab { uint32_t v[512]; };
constexpr PTab make_ptab() {
  PTab t{};
  for (int lane = 0; lane < 32; ++lane)
    for (int i = 0; i < 16; ++i)
      t.v[i * 32 + lane] = (slot_word(31 * lane - 1 + 2 * i) * 4) | ((slot_word(31 * lane + 2 * i) * 4) << 16);
  return t;
}
__device__ const PTab g_ptab = make_ptab();

__device__ __nv_bfloat16 g_uT[512 * 2048];
__device__ __nv_bfloat16 g_yT[512 * 2048];
__device__ __nv_bfloat16 g_o[2048 * 512];
__device__ float g_kv[2][8][4 * 272];
__device__ unsigned g_cnt[64 * 32];
__device__ unsigned g_epoch;
#define TS(slot) do { } while (0)
#define TSR(on, slot) do { } while (0)
#define TSD(slot) do { } while (0)
enum { C_U = 0, C_KV = 8, C_O = 16, C_Y = 32 };

struct Maps {
  CUtensorMap x, w, wo, u, uT, yT, o, out, outh;
};
struct Ptrs {
  const __nv_bfloat16 *A_re, *A_im, *B_re, *B_im, *C_re, *C_im, *log_dt, *Dskip;
  const __nv_bfloat16 *x, *wqkv, *wo;
  __nv_bfloat16 *uT, *yT;
};

DEVI uint32_t s2u(const void* p) { return (uint32_t)__cvta_generic_to_shared(p); }
DEVI void mbar_init(uint32_t b, uint32_t c) { asm volatile("mbarrier.init.shared::cta.b64 [%0], %1;" ::"r"(b), "r"(c) : "memory"); }
DEVI void mbar_expect_tx(uint32_t b, uint32_t bytes) {
  asm volatile("mbarrier.arrive.expect_tx.shared::cta.b64 _, [%0], %1;" ::"r"(b), "r"(bytes) : "memory");
}
DEVI void mbar_arrive(uint32_t b) { asm volatile("mbarrier.arrive.shared::cta.b64 _, [%0];" ::"r"(b) : "memory"); }
DEVI void mbar_arrive_cluster(uint32_t b, uint32_t cta) {
  asm volatile("{\n.reg .b32 r;\nmapa.shared::cluster.u32 r, %0, %1;\nmbarrier.arrive.shared::cluster.b64 _, [r];\n}"
               ::"r"(b), "r"(cta) : "memory");
}
DEVI void mbar_wait(uint32_t b, uint32_t parity) {
  asm volatile("{\n.reg .pred p;\nLAB_WAIT:\nmbarrier.try_wait.parity.shared::cta.b64 p, [%0], %1;\n@!p bra LAB_WAIT;\n}"
               ::"r"(b), "r"(parity) : "memory");
}
DEVI void mbar_wait_long(uint32_t b, uint32_t parity) {
  asm volatile("{\n.reg .pred p;\nLAB_WAIT:\nmbarrier.try_wait.parity.shared::cta.b64 p, [%0], %1, 0x989680;\n@!p bra LAB_WAIT;\n}"
               ::"r"(b), "r"(parity) : "memory");
}
DEVI void bar_sync(int id, int n) { asm volatile("bar.sync %0, %1;" ::"r"(id), "r"(n) : "memory"); }
DEVI void bar_arrive(int id, int n) { asm volatile("bar.arrive %0, %1;" ::"r"(id), "r"(n) : "memory"); }
DEVI void fence_async_smem() { asm volatile("fence.proxy.async.shared::cta;" ::: "memory"); }
DEVI void fence_async_all() { asm volatile("fence.proxy.async;" ::: "memory"); }
DEVI void cluster_arrive() { asm volatile("barrier.cluster.arrive.relaxed.aligned;" ::: "memory"); }
DEVI void cluster_wait() { asm volatile("barrier.cluster.wait.aligned;" ::: "memory"); }

DEVI void tma_load_2d(uint32_t dst, const CUtensorMap* m, int c0, int c1, uint32_t bar) {
  asm volatile("cp.async.bulk.tensor.2d.shared::cluster.global.mbarrier::complete_tx::bytes [%0], [%1, {%3, %4}], [%2];"
               ::"r"(dst), "l"(m), "r"(bar), "r"(c0), "r"(c1) : "memory");
}
DEVI void tma_load_2d_mc(uint32_t dst, const CUtensorMap* m, int c0, int c1, uint32_t bar, uint16_t mask) {
  asm volatile("cp.async.bulk.tensor.2d.shared::cluster.global.mbarrier::complete_tx::bytes.multicast::cluster [%0], [%1, {%3, %4}], [%2], %5;"
               ::"r"(dst), "l"(m), "r"(bar), "r"(c0), "r"(c1), "h"(mask) : "memory");
}
DEVI void tma_load_3d_mc(uint32_t dst, const CUtensorMap* m, int c0, int c1, int c2, uint32_t bar, uint16_t mask) {
  asm volatile("cp.async.bulk.tensor.3d.shared::cluster.global.mbarrier::complete_tx::bytes.multicast::cluster [%0], [%1, {%3, %4, %5}], [%2], %6;"
               ::"r"(dst), "l"(m), "r"(bar), "r"(c0), "r"(c1), "r"(c2), "h"(mask) : "memory");
}
DEVI void tma_store_2d(const CUtensorMap* m, uint32_t src, int c0, int c1) {
  asm volatile("cp.async.bulk.tensor.2d.global.shared::cta.bulk_group [%0, {%2, %3}], [%1];"
               ::"l"(m), "r"(src), "r"(c0), "r"(c1) : "memory");
}
DEVI void bulk_load(uint32_t dst, const void* src, uint32_t bytes, uint32_t bar) {
  asm volatile("cp.async.bulk.shared::cluster.global.mbarrier::complete_tx::bytes [%0], [%1], %2, [%3];"
               ::"r"(dst), "l"(src), "r"(bytes), "r"(bar) : "memory");
}
DEVI void bulk_store(void* dst, uint32_t src, uint32_t bytes) {
  asm volatile("cp.async.bulk.global.shared::cta.bulk_group [%0], [%1], %2;" ::"l"(dst), "r"(src), "r"(bytes) : "memory");
}
DEVI void bulk_reduce_add_f32(void* dst, uint32_t src, uint32_t bytes) {
  asm volatile("cp.reduce.async.bulk.global.shared::cta.bulk_group.add.f32 [%0], [%1], %2;" ::"l"(dst), "r"(src), "r"(bytes) : "memory");
}
DEVI void bulk_commit() { asm volatile("cp.async.bulk.commit_group;" ::: "memory"); }
DEVI void bulk_wait0() { asm volatile("cp.async.bulk.wait_group 0;" ::: "memory"); }
DEVI void bulk_wait_read0() { asm volatile("cp.async.bulk.wait_group.read 0;" ::: "memory"); }
DEVI void l2_prefetch(const void* p, uint32_t bytes) {
  asm volatile("cp.async.bulk.prefetch.L2.global [%0], %1;" ::"l"(p), "r"(bytes) : "memory");
}
DEVI void prefetch_tmap(const CUtensorMap* m) { asm volatile("prefetch.tensormap [%0];" ::"l"(m) : "memory"); }

DEVI void red_release_add(unsigned* p, unsigned v) {
  asm volatile("red.release.gpu.global.add.u32 [%0], %1;" ::"l"(p), "r"(v) : "memory");
}
DEVI void red_relaxed_add(unsigned* p, unsigned v) {
  asm volatile("red.relaxed.gpu.global.add.u32 [%0], %1;" ::"l"(p), "r"(v) : "memory");
}
DEVI unsigned ld_relaxed(const unsigned* p) {
  unsigned v;
  asm volatile("ld.relaxed.gpu.global.u32 %0, [%1];" : "=r"(v) : "l"(p) : "memory");
  return v;
}
DEVI void wait_counter(const unsigned* p, unsigned target) {
#pragma unroll 1
  for (int it = 0; (int)(ld_relaxed(p) - target) < 0; ++it)
    if (it > (1 << 22)) __trap();
}

DEVI void ldsm_x4(uint32_t (&r)[4], uint32_t a) {
  asm volatile("ldmatrix.sync.aligned.m8n8.x4.shared.b16 {%0,%1,%2,%3}, [%4];"
               : "=r"(r[0]), "=r"(r[1]), "=r"(r[2]), "=r"(r[3]) : "r"(a) : "memory");
}
DEVI void ldsm_x4_t(uint32_t (&r)[4], uint32_t a) {
  asm volatile("ldmatrix.sync.aligned.m8n8.x4.trans.shared.b16 {%0,%1,%2,%3}, [%4];"
               : "=r"(r[0]), "=r"(r[1]), "=r"(r[2]), "=r"(r[3]) : "r"(a) : "memory");
}
DEVI void ldsm_x2_t(uint32_t& r0, uint32_t& r1, uint32_t a) {
  asm volatile("ldmatrix.sync.aligned.m8n8.x2.trans.shared.b16 {%0,%1}, [%2];" : "=r"(r0), "=r"(r1) : "r"(a) : "memory");
}
DEVI void stsm_x4(uint32_t a, uint32_t r0, uint32_t r1, uint32_t r2, uint32_t r3) {
  asm volatile("stmatrix.sync.aligned.m8n8.x4.shared.b16 [%0], {%1,%2,%3,%4};"
               ::"r"(a), "r"(r0), "r"(r1), "r"(r2), "r"(r3) : "memory");
}
DEVI void stsm_x4_t(uint32_t a, uint32_t r0, uint32_t r1, uint32_t r2, uint32_t r3) {
  asm volatile("stmatrix.sync.aligned.m8n8.x4.trans.shared.b16 [%0], {%1,%2,%3,%4};"
               ::"r"(a), "r"(r0), "r"(r1), "r"(r2), "r"(r3) : "memory");
}
DEVI uint32_t lds32(uint32_t a) { uint32_t v; asm volatile("ld.shared.b32 %0, [%1];" : "=r"(v) : "r"(a) : "memory"); return v; }
DEVI float lds_f32(uint32_t a) { float v; asm volatile("ld.shared.f32 %0, [%1];" : "=f"(v) : "r"(a) : "memory"); return v; }
DEVI void sts32(uint32_t a, uint32_t v) { asm volatile("st.shared.b32 [%0], %1;" ::"r"(a), "r"(v) : "memory"); }
DEVI void sts_f32(uint32_t a, float v) { asm volatile("st.shared.f32 [%0], %1;" ::"r"(a), "f"(v) : "memory"); }
DEVI void sts_f32x2(uint32_t a, float x, float y) { asm volatile("st.shared.v2.f32 [%0], {%1,%2};" ::"r"(a), "f"(x), "f"(y) : "memory"); }
DEVI uint4 lds128(uint32_t a) {
  uint4 v;
  asm volatile("ld.shared.v4.b32 {%0,%1,%2,%3}, [%4];" : "=r"(v.x), "=r"(v.y), "=r"(v.z), "=r"(v.w) : "r"(a) : "memory");
  return v;
}
DEVI void sts128(uint32_t a, uint32_t x, uint32_t y, uint32_t z, uint32_t w) {
  asm volatile("st.shared.v4.b32 [%0], {%1,%2,%3,%4};" ::"r"(a), "r"(x), "r"(y), "r"(z), "r"(w) : "memory");
}

DEVI void mma_bf16(float (&d)[4], uint32_t a0, uint32_t a1, uint32_t a2, uint32_t a3, uint32_t b0, uint32_t b1) {
  asm("mma.sync.aligned.m16n8k16.row.col.f32.bf16.bf16.f32 {%0,%1,%2,%3}, {%4,%5,%6,%7}, {%8,%9}, {%0,%1,%2,%3};"
      : "+f"(d[0]), "+f"(d[1]), "+f"(d[2]), "+f"(d[3])
      : "r"(a0), "r"(a1), "r"(a2), "r"(a3), "r"(b0), "r"(b1));
}
DEVI void mma_f16(float (&d)[4], const uint32_t (&a)[4], uint32_t b0, uint32_t b1) {
  asm("mma.sync.aligned.m16n8k16.row.col.f32.f16.f16.f32 {%0,%1,%2,%3}, {%4,%5,%6,%7}, {%8,%9}, {%0,%1,%2,%3};"
      : "+f"(d[0]), "+f"(d[1]), "+f"(d[2]), "+f"(d[3])
      : "r"(a[0]), "r"(a[1]), "r"(a[2]), "r"(a[3]), "r"(b0), "r"(b1));
}
DEVI void mma_bf16v(float (&d)[4], const uint32_t (&a)[4], uint32_t b0, uint32_t b1) {
  asm volatile("mma.sync.aligned.m16n8k16.row.col.f32.bf16.bf16.f32 {%0,%1,%2,%3}, {%4,%5,%6,%7}, {%8,%9}, {%0,%1,%2,%3};"
               : "+f"(d[0]), "+f"(d[1]), "+f"(d[2]), "+f"(d[3])
               : "r"(a[0]), "r"(a[1]), "r"(a[2]), "r"(a[3]), "r"(b0), "r"(b1));
}
DEVI uint32_t pack_bf16(float lo, float hi) {
  uint32_t r;
  asm("cvt.rn.bf16x2.f32 %0, %1, %2;" : "=r"(r) : "f"(hi), "f"(lo));
  return r;
}
DEVI uint32_t pack_f16(float lo, float hi) {
  uint32_t r;
  asm("cvt.rn.f16x2.f32 %0, %1, %2;" : "=r"(r) : "f"(hi), "f"(lo));
  return r;
}
DEVI uint32_t ldg16(const __nv_bfloat16* p) {
  uint32_t v;
  asm volatile("ld.global.nc.u16 %0, [%1];" : "=r"(v) : "l"(p));
  return v;
}
DEVI bool elect_one() {
  uint32_t pred;
  asm volatile("{\n.reg .pred p;\nelect.sync _|p, 0xffffffff;\nselp.u32 %0, 1, 0, p;\n}" : "=r"(pred));
  return pred != 0;
}
DEVI float bf_lo(uint32_t v) { return __uint_as_float(v << 16); }
DEVI float bf_hi(uint32_t v) { return __uint_as_float(v & 0xffff0000u); }
DEVI float bf2f(__nv_bfloat16 v) { return __bfloat162float(v); }
DEVI float round_bf16(float v) { return __bfloat162float(__float2bfloat16_rn(v)); }
DEVI float rcp(float x) { float r; asm("rcp.approx.ftz.f32 %0, %1;" : "=f"(r) : "f"(x)); return r; }
DEVI float ex2(float x) { float r; asm("ex2.approx.ftz.f32 %0, %1;" : "=f"(r) : "f"(x)); return r; }

DEVI void wg_fence() { asm volatile("wgmma.fence.sync.aligned;" ::: "memory"); }
DEVI void wg_commit() { asm volatile("wgmma.commit_group.sync.aligned;" ::: "memory"); }
template <int N> DEVI void wg_wait() { asm volatile("wgmma.wait_group.sync.aligned %0;" ::"n"(N) : "memory"); }
constexpr uint32_t DESC_HI = (1u << 30) | (1024 >> 4);
constexpr uint32_t DESC_HI64 = (2u << 30) | (512 >> 4);
DEVI uint32_t mkdesc(uint32_t saddr, uint32_t lbo) { return ((saddr & 0x3FFFF) >> 4) | ((lbo >> 4) << 16); }

#define R8(b) "%" #b
DEVI void wgmma_n192(float (&d)[96], uint32_t da, uint32_t db, int scale_d) {
  asm volatile(
      "{\n.reg .pred p;\n.reg .b64 da, db;\nsetp.ne.b32 p, %98, 0;\nmov.b64 da, {%96, %100};\nmov.b64 db, {%97, %99};\n"
      "wgmma.mma_async.sync.aligned.m64n192k16.f32.bf16.bf16 "
      "{%0,%1,%2,%3,%4,%5,%6,%7,%8,%9,%10,%11,%12,%13,%14,%15,"
      "%16,%17,%18,%19,%20,%21,%22,%23,%24,%25,%26,%27,%28,%29,%30,%31,"
      "%32,%33,%34,%35,%36,%37,%38,%39,%40,%41,%42,%43,%44,%45,%46,%47,"
      "%48,%49,%50,%51,%52,%53,%54,%55,%56,%57,%58,%59,%60,%61,%62,%63,"
      "%64,%65,%66,%67,%68,%69,%70,%71,%72,%73,%74,%75,%76,%77,%78,%79,"
      "%80,%81,%82,%83,%84,%85,%86,%87,%88,%89,%90,%91,%92,%93,%94,%95}, "
      "da, db, p, 1, 1, 0, 1;\n}"
      : "+f"(d[0]), "+f"(d[1]), "+f"(d[2]), "+f"(d[3]), "+f"(d[4]), "+f"(d[5]), "+f"(d[6]), "+f"(d[7]),
        "+f"(d[8]), "+f"(d[9]), "+f"(d[10]), "+f"(d[11]), "+f"(d[12]), "+f"(d[13]), "+f"(d[14]), "+f"(d[15]),
        "+f"(d[16]), "+f"(d[17]), "+f"(d[18]), "+f"(d[19]), "+f"(d[20]), "+f"(d[21]), "+f"(d[22]), "+f"(d[23]),
        "+f"(d[24]), "+f"(d[25]), "+f"(d[26]), "+f"(d[27]), "+f"(d[28]), "+f"(d[29]), "+f"(d[30]), "+f"(d[31]),
        "+f"(d[32]), "+f"(d[33]), "+f"(d[34]), "+f"(d[35]), "+f"(d[36]), "+f"(d[37]), "+f"(d[38]), "+f"(d[39]),
        "+f"(d[40]), "+f"(d[41]), "+f"(d[42]), "+f"(d[43]), "+f"(d[44]), "+f"(d[45]), "+f"(d[46]), "+f"(d[47]),
        "+f"(d[48]), "+f"(d[49]), "+f"(d[50]), "+f"(d[51]), "+f"(d[52]), "+f"(d[53]), "+f"(d[54]), "+f"(d[55]),
        "+f"(d[56]), "+f"(d[57]), "+f"(d[58]), "+f"(d[59]), "+f"(d[60]), "+f"(d[61]), "+f"(d[62]), "+f"(d[63]),
        "+f"(d[64]), "+f"(d[65]), "+f"(d[66]), "+f"(d[67]), "+f"(d[68]), "+f"(d[69]), "+f"(d[70]), "+f"(d[71]),
        "+f"(d[72]), "+f"(d[73]), "+f"(d[74]), "+f"(d[75]), "+f"(d[76]), "+f"(d[77]), "+f"(d[78]), "+f"(d[79]),
        "+f"(d[80]), "+f"(d[81]), "+f"(d[82]), "+f"(d[83]), "+f"(d[84]), "+f"(d[85]), "+f"(d[86]), "+f"(d[87]),
        "+f"(d[88]), "+f"(d[89]), "+f"(d[90]), "+f"(d[91]), "+f"(d[92]), "+f"(d[93]), "+f"(d[94]), "+f"(d[95])
      : "r"(da), "r"(db), "r"(scale_d), "n"(DESC_HI), "n"(DESC_HI64));
}
DEVI void wgmma_n64(float (&d)[32], uint32_t da, uint32_t db, int scale_d) {
  asm volatile(
      "{\n.reg .pred p;\n.reg .b64 da, db;\nsetp.ne.b32 p, %34, 0;\nmov.b64 da, {%32, %35};\nmov.b64 db, {%33, %35};\n"
      "wgmma.mma_async.sync.aligned.m64n64k16.f32.bf16.bf16 "
      "{%0,%1,%2,%3,%4,%5,%6,%7,%8,%9,%10,%11,%12,%13,%14,%15,"
      "%16,%17,%18,%19,%20,%21,%22,%23,%24,%25,%26,%27,%28,%29,%30,%31}, "
      "da, db, p, 1, 1, 0, 1;\n}"
      : "+f"(d[0]), "+f"(d[1]), "+f"(d[2]), "+f"(d[3]), "+f"(d[4]), "+f"(d[5]), "+f"(d[6]), "+f"(d[7]),
        "+f"(d[8]), "+f"(d[9]), "+f"(d[10]), "+f"(d[11]), "+f"(d[12]), "+f"(d[13]), "+f"(d[14]), "+f"(d[15]),
        "+f"(d[16]), "+f"(d[17]), "+f"(d[18]), "+f"(d[19]), "+f"(d[20]), "+f"(d[21]), "+f"(d[22]), "+f"(d[23]),
        "+f"(d[24]), "+f"(d[25]), "+f"(d[26]), "+f"(d[27]), "+f"(d[28]), "+f"(d[29]), "+f"(d[30]), "+f"(d[31])
      : "r"(da), "r"(db), "r"(scale_d), "n"(DESC_HI));
}

struct C32 { float re, im; };
DEVI C32 csq(C32 a) { return {a.re * a.re - a.im * a.im, 2.f * a.re * a.im}; }
DEVI C32 cmul(C32 a, C32 b) { return {a.re * b.re - a.im * b.im, a.re * b.im + a.im * b.re}; }
DEVI C32 cfresh(float zl, float zi, float m) {
  float mag = ex2(zl * m), ph = zi * m;
  return {mag * __cosf(ph), mag * __sinf(ph)};
}
struct HMul { uint32_t b, bp; };
DEVI HMul mk_mul(float re, float im) { return {pack_f16(re, im), pack_f16(-im, re)}; }
DEVI uint32_t hcmul(uint32_t a, const HMul& m) {
  __half2 ah = *reinterpret_cast<__half2*>(&a);
  __half2 b = *reinterpret_cast<const __half2*>(&m.b), bp = *reinterpret_cast<const __half2*>(&m.bp);
  __half2 r = __hfma2(__high2half2(ah), bp, __hmul2(__low2half2(ah), b));
  return *reinterpret_cast<uint32_t*>(&r);
}
DEVI uint32_t badd(uint32_t a, uint32_t b) {
  __nv_bfloat162 r = __hadd2(*reinterpret_cast<__nv_bfloat162*>(&a), *reinterpret_cast<__nv_bfloat162*>(&b));
  return *reinterpret_cast<uint32_t*>(&r);
}
template <int MU0, int NMU, int DMAX>
DEVI void conv_tail(float (&acc)[16][4], uint32_t p_lane, uint32_t v_base, int back, bool edge, int lane) {
  const int hsel = (lane >> 3) & 1;
  const int row = (lane & 7) + ((lane >> 4) << 3) + PADV - 8 - (back & (hsel ^ 1));
  const uint32_t la = v_base + row * 32 + (((hsel ^ back) ^ ((row >> 2) & 1)) << 4);
  uint32_t M[3][4];
  ldsm_x4_t(M[0], la);
  ldsm_x4_t(M[1], la + 256);
  uint32_t H[2 * NMU];
#pragma unroll
  for (int i = 0; i < 2 * NMU; ++i) H[i ^ 1] = lds32(p_lane + (uint32_t)(MU0 - 1 + i) * 32);
  if (edge) {
    const uint32_t a[4] = {0u, 0u, M[0][0], M[0][1]};
#pragma unroll
    for (int k = 1; k < NMU; ++k) mma_bf16v(acc[MU0 - 2 + 2 * k], a, H[2 * k], H[2 * k + 1]);
  }
#pragma unroll
  for (int delta = -1; delta <= DMAX; ++delta) {
    if (delta + 2 <= DMAX) ldsm_x4_t(M[(delta + 3) % 3], la + (delta + 3) * 256);
#pragma unroll
    for (int k = 0; k < NMU; ++k)
      if (delta + MU0 + 2 * k < 16) mma_bf16v(acc[delta + MU0 + 2 * k], M[(delta + 1) % 3], H[2 * k], H[2 * k + 1]);
  }
}

template <int NB>
DEVI void box_filters(uint32_t sb, uint32_t bars, int idx, int lane) {
  auto swz = [](int k, int pad) { const int r = (k >> 1) + pad; return (uint32_t)(r * 32 + (((k & 1) ^ ((r >> 2) & 1)) << 4)); };
  const uint32_t o0 = swz(lane - 3, 8), o1 = swz(lane - 2, 8), o2 = swz(lane - 1, 8), ow = swz(lane - 2, PADV), oz = swz(lane - 18, PADV);
  const int k = 32 * idx - 2 + lane;
#pragma unroll 1
  for (int c2 = 0; c2 < 4; c2 += NB) {
    uint4 t[NB][3];
#pragma unroll
    for (int b = 0; b < NB; ++b) mbar_wait_long(bars + 8 * (B_UCH + c2 + b), 0);
#pragma unroll
    for (int b = 0; b < NB; ++b) {
      const uint32_t ua = sb + SM_U + (c2 + b) * U_BYTES + idx * 512;
      t[b][0] = lds128(ua + o0); t[b][1] = lds128(ua + o1); t[b][2] = lds128(ua + o2);
    }
#pragma unroll
    for (int b = 0; b < NB; ++b) {
      const uint32_t vb = sb + SM_VV + (c2 + b) * VV_BYTES, aw = vb + idx * 512 + ow;
      const uint32_t E[12] = {t[b][0].x, t[b][0].y, t[b][0].z, t[b][0].w, t[b][1].x, t[b][1].y, t[b][1].z, t[b][1].w,
                              t[b][2].x, t[b][2].y, t[b][2].z, t[b][2].w};
      uint32_t O[8];
#pragma unroll
      for (int j = 0; j < 8; ++j) O[j] = __byte_perm(E[j + 1], E[j + 2], 0x5432);
      uint32_t s3[6], s5[4], s7[4], s9[4];
#pragma unroll
      for (int j = 0; j < 6; ++j) s3[j] = badd(badd(O[j], O[j + 1]), E[j + 2]);
#pragma unroll
      for (int j = 0; j < 4; ++j) {
        s5[j] = badd(s3[j + 2], badd(E[j + 3], E[j + 5]));
        s7[j] = badd(s5[j], badd(O[j + 1], O[j + 4]));
        s9[j] = badd(s7[j], badd(E[j + 2], E[j + 6]));
      }
      if (k < 208) { sts128(aw + VV_U3, s3[0], s3[1], s3[2], s3[3]); sts128(aw + VV_U5, s5[0], s5[1], s5[2], s5[3]); }
      if (k < 144) { sts128(aw + VV_U7, s7[0], s7[1], s7[2], s7[3]); sts128(aw + VV_U9, s9[0], s9[1], s9[2], s9[3]); }
      if (idx == 0 && lane < 16) {
        sts128(vb + oz + VV_U3, 0, 0, 0, 0); sts128(vb + oz + VV_U5, 0, 0, 0, 0);
        sts128(vb + oz + VV_U7, 0, 0, 0, 0); sts128(vb + oz + VV_U9, 0, 0, 0, 0);
      }
    }
  }
}

DEVI uint32_t o_slot(int c) { return c < 6 ? SM_QS + c * 16384 : SM_VV + (c - 6) * 16384; }
DEVI uint32_t wo_slot(int c) { return c < 5 ? SM_WO + c * 8192 : c < 7 ? SM_VV + 32768 + (c - 5) * 8192 : SM_QS; }

__global__ void __cluster_dims__(2, 1, 1) __launch_bounds__(NTHREADS, 1)
fused_kernel(const __grid_constant__ Maps maps, const Ptrs p) {
  extern __shared__ __align__(1024) uint8_t smem[];
  const uint32_t sb = s2u(smem);
  const int tid = threadIdx.x, lane = tid & 31;
  const int warp = __shfl_sync(0xffffffffu, tid >> 5, 0);
  const int cta = blockIdx.x;
  const uint32_t rank = cta & 1;
  const int ti = 2 * (cta >> 4) + rank;
  const int tj = (cta >> 1) & 7;
  const int pi = cta >> 3, pj = cta & 7;
  const uint32_t bars = sb + SM_BAR;
#define BAR(i) (bars + 8 * (i))
  const int g = lane >> 2, q = lane & 3;

  auto issue_stage = [&](int ks, int s) {
    const uint32_t st = sb + s * STG_BYTES, fb = BAR(B_FULL + s);
    mbar_expect_tx(fb, STG_BYTES);
    tma_load_2d(st + STG_X, &maps.x, ks * 32, ti * 128, fb);
    tma_load_3d_mc(st + STG_W + rank * 6144, &maps.w, tj * 64, ks * 32 + rank * 16, 0, fb, 3);
  };

  const int kch = warp & 3, krd = warp >> 2;
  float zr, zi, wr, wi;
  unsigned epoch;
  uint32_t r_dskip;
  {
    const size_t po = (size_t)(cta * 4 + kch) * 128 + krd * 32 + lane;
    const uint32_t r_ar = ldg16(p.A_re + po), r_ai = ldg16(p.A_im + po), r_br = ldg16(p.B_re + po), r_bi = ldg16(p.B_im + po);
    const uint32_t r_cr = ldg16(p.C_re + po), r_ci = ldg16(p.C_im + po), r_ldt = ldg16(p.log_dt + cta * 4 + kch);
    epoch = __ldcg(&g_epoch);
    r_dskip = ldg16(p.Dskip + cta * 4 + kch);
    uint4 pt;
    if (tid < 128) pt = __ldg((const uint4*)g_ptab.v + tid);
    if (tid == 384) {
      TS(0);
#pragma unroll
      for (int i = 0; i < B_COUNT; ++i) mbar_init(BAR(i), bar_count(i));
      asm volatile("fence.mbarrier_init.release.cluster;" ::: "memory");
      prefetch_tmap(&maps.x); prefetch_tmap(&maps.w); prefetch_tmap(&maps.u);
    }
    __syncthreads();
    cluster_arrive();
    if (warp >= 12) {
      cluster_wait();
      if (elect_one()) {
        if (warp == 13) {
#define U_POS 0
          if (U_POS == 0) { mbar_expect_tx(BAR(B_TILE), 16384); tma_load_2d(sb + SM_U, &maps.u, tj * 64, ti * 128, BAR(B_TILE)); }
          prefetch_tmap(&maps.uT); prefetch_tmap(&maps.wo); prefetch_tmap(&maps.o); prefetch_tmap(&maps.yT);
          prefetch_tmap(&maps.out); prefetch_tmap(&maps.outh);
        } else {
          if (warp == 12) TS(61);
          { const int ks = warp == 12 ? 0 : warp - 13; issue_stage(ks, ks); }
        }
      }
      __syncwarp();
    }
    if (tid < 128) sts128(sb + SM_PTAB + tid * 16, pt.x, pt.y, pt.z, pt.w);
    const float dt = round_bf16(expf(bf_lo(r_ldt)));
    zr = dt * bf_lo(r_ar); zi = dt * bf_lo(r_ai);
    const float dbr = dt * bf_lo(r_br), dbi = dt * bf_lo(r_bi), cr = bf_lo(r_cr), ci = bf_lo(r_ci);
    wr = cr * dbr - ci * dbi; wi = cr * dbi + ci * dbr;
  }
  {
    const float mz = __uint_as_float(__reduce_max_sync(0xffffffffu, __float_as_uint(fmaxf(zr, 0.f))));
    const int E = min(max((int)(__reduce_max_sync(0xffffffffu, __float_as_uint(fmaxf(fabsf(wr), fabsf(wi)))) >> 23), 1), 252);
    const float sc = __int_as_float((253 - E) << 23), inv = __int_as_float((E + 1) << 23);
    const float zl = (zr - mz) * 1.4426950408889634f;
    const uint32_t tb = sb + SM_VV + kch * VV_BYTES + krd * KG_BYTES;
    const uint32_t sta = tb + (((lane >> 2) << 4) | ((lane & 3) << 2));
    auto put = [&](int r, uint32_t v) { sts32((sta ^ ((r & 7) << 4)) + r * 128, v); };
    const uint32_t lda = tb + ((lane & 7) + (((lane >> 3) & 1) << 3)) * 128;
    const uint32_t ldb = tb + ((lane & 7) + ((lane >> 4) << 3)) * 128;
#define STG_POS 0
#define PF_POS 1
    if (U_POS == 1 && warp == 13 && elect_one()) { mbar_expect_tx(BAR(B_TILE), 16384); tma_load_2d(sb + SM_U, &maps.u, tj * 64, ti * 128, BAR(B_TILE)); }
    if (STG_POS == 0 && warp >= 14 && elect_one()) { issue_stage(warp - 11, warp - 11); issue_stage(warp - 9, warp - 9); }
    if (PF_POS == 0 && warp >= 14 && elect_one()) {
      if (warp == 14) l2_prefetch((const char*)p.wqkv + 224 * 3072 + cta * 6912, 6912);
      else l2_prefetch((const char*)p.x + (size_t)cta * 16384, 16384);
    }
    __syncwarp();
    C32 e1 = cfresh(zl, zi, 1.f), e2 = csq(e1), e4 = csq(e2), e8 = csq(e4);
    C32 e16 = cfresh(zl, zi, 16.f), e32 = csq(e16), e64 = csq(e32), e128 = csq(e64);
    C32 e256 = cfresh(zl, zi, 256.f), e512 = csq(e256), e1024 = csq(e512), e768 = cmul(e512, e256);
    uint32_t XA[2][4][4];
    {
      const HMul m16 = mk_mul(e16.re, e16.im), m32 = mk_mul(e32.re, e32.im), m64 = mk_mul(e64.re, e64.im);
      const HMul m128 = mk_mul(e128.re, e128.im);
      uint32_t X[16];
      X[0] = 0x00003c00u; X[1] = pack_f16(e8.re, e8.im); X[2] = m16.b; X[4] = m32.b; X[8] = m64.b;
      X[3] = hcmul(X[1], m16); X[5] = hcmul(X[1], m32); X[6] = hcmul(X[2], m32); X[7] = hcmul(X[3], m32);
#pragma unroll
      for (int r = 1; r < 8; ++r) X[8 + r] = hcmul(X[r], m64);
#pragma unroll
      for (int h = 0; h < 2; ++h) {
#pragma unroll
        for (int r = 0; r < 16; ++r) put(r, h == 0 ? X[r] : r == 0 ? m128.b : hcmul(X[r], m128));
        __syncwarp();
#pragma unroll
        for (int k = 0; k < 4; ++k) ldsm_x4(XA[h][k], lda + (((2 * k + (lane >> 4)) ^ (lane & 7)) << 4));
        __syncwarp();
      }
    }
    if (U_POS == 2 && warp == 13 && elect_one()) { mbar_expect_tx(BAR(B_TILE), 16384); tma_load_2d(sb + SM_U, &maps.u, tj * 64, ti * 128, BAR(B_TILE)); }
    if (STG_POS == 1 && warp >= 14 && elect_one()) { issue_stage(warp - 11, warp - 11); issue_stage(warp - 9, warp - 9); }
#define PF_MODE 3
    if (PF_POS == 1 && warp >= 14 && elect_one()) {
      if (warp == 14) { if (PF_MODE & 1) l2_prefetch((const char*)p.wqkv + 224 * 3072 + cta * 6912, 6912); }
      else if (PF_MODE & 2) l2_prefetch((const char*)p.x + (size_t)cta * 16384, 16384);
      else if (PF_MODE & 4) {
#pragma unroll 1
        for (int r = 0; r < 16; ++r) l2_prefetch((const char*)p.x + (size_t)(cta * 16 + r) * 1024 + 448, 576);
      }
    }
    __syncwarp();
    float D[2][3][4];
#pragma unroll
    for (int t = 0; t < 6; ++t) D[t / 3][t % 3][0] = D[t / 3][t % 3][1] = D[t / 3][t % 3][2] = D[t / 3][t % 3][3] = 0.f;
    auto contract = [&](int t0, int nt) {
      __syncwarp();
#pragma unroll
      for (int k = 0; k < 4; ++k) {
        uint32_t b[4];
        ldsm_x4(b, ldb + (((2 * k + ((lane >> 3) & 1)) ^ (lane & 7)) << 4));
#pragma unroll
        for (int h = 0; h < 2; ++h) {
          mma_f16(D[h][t0], XA[h][k], b[0], b[1]);
          if (nt == 2) mma_f16(D[h][t0 + 1], XA[h][k], b[2], b[3]);
        }
      }
      __syncwarp();
    };
    const HMul c1 = mk_mul(e1.re, -e1.im), c2 = mk_mul(e2.re, -e2.im), c4 = mk_mul(e4.re, -e4.im);
    const HMul c256 = mk_mul(e256.re, -e256.im), c512 = mk_mul(e512.re, -e512.im), c768 = mk_mul(e768.re, -e768.im);
    const HMul c1024 = mk_mul(e1024.re, -e1024.im);
    uint32_t W[8];
    W[0] = pack_f16(wr * sc, -wi * sc);
    W[1] = hcmul(W[0], c1); W[2] = hcmul(W[0], c2); W[3] = hcmul(W[1], c2);
    W[4] = hcmul(W[0], c4); W[5] = hcmul(W[1], c4); W[6] = hcmul(W[2], c4); W[7] = hcmul(W[3], c4);
#pragma unroll
    for (int i = 0; i < 8; ++i) put(i, W[i]);
#pragma unroll
    for (int i = 0; i < 4; ++i) put(8 + i, hcmul(W[2 * i], c256));
    put(12, hcmul(W[0], c512)); put(13, hcmul(W[4], c512)); put(14, hcmul(W[0], c768)); put(15, hcmul(W[4], c768));
    if (PF_POS == 2 && warp >= 14 && elect_one()) {
      if (warp == 14) l2_prefetch((const char*)p.wqkv + 224 * 3072 + cta * 6912, 6912);
      else l2_prefetch((const char*)p.x + (size_t)cta * 16384, 16384);
    }
    contract(0, 2);
    const uint32_t v0 = hcmul(W[0], c1024);
    put(0, v0); put(1, hcmul(v0, c256)); put(2, hcmul(v0, c512)); put(3, hcmul(v0, c768)); put(4, hcmul(v0, c1024));
    contract(2, 1);
    const uint32_t a = tb + (g * 24 + 2 * q) * 4;
#pragma unroll
    for (int t = 0; t < 6; ++t) {
      const float(&d)[4] = D[t / 3][t % 3];
      sts_f32x2(a + (t / 3) * 1536 + (t % 3) * 32, d[0], d[1]);
      sts_f32x2(a + (t / 3) * 1536 + (t % 3) * 32 + 768, d[2], d[3]);
    }
    if (lane == 0) sts_f32(tb + 3072, inv);
    if (mz > 0.f) {
      __syncwarp();
#pragma unroll 1
      for (int i = lane; i < 768; i += 32) {
        const int r = i / 24, y = i - 24 * r;
        sts_f32(tb + i * 4, lds_f32(tb + i * 4) * ex2(mz * 1.4426950408889634f * (koff(y) + 8 * r)));
      }
    }
  }
  if (tid == 0) TS(2);
  if (warp < 12) cluster_wait();
  __syncthreads();

  if (warp < 4) {
#define A_REGS 200
    asm volatile("setmaxnreg.inc.sync.aligned.u32 %0;" ::"n"(A_REGS));
    if (tid == 0) TS(34);
    const int d = cta * 4 + warp;
    const uint32_t vv = sb + SM_VV + warp * VV_BYTES;
    const uint32_t ub = sb + SM_U + warp * U_BYTES;
    const uint32_t pb = sb + SM_P + warp * P_BYTES;
    const float dskip = bf_lo(r_dskip);
#pragma unroll 1
    for (int pass = 0; pass < 2; ++pass) {
      if (pass == 1) {
        const uint32_t kf = vv;
        const float i0 = lds_f32(kf + 3072), i1 = lds_f32(kf + KG_BYTES + 3072), i2 = lds_f32(kf + 2 * KG_BYTES + 3072);
        const float i3 = lds_f32(kf + 3 * KG_BYTES + 3072);
#pragma unroll 2
        for (int i = 0; i < 6; ++i) {
          const uint32_t a = kf + (i * 32 + lane) * 16;
          const uint4 x0 = lds128(a), x1 = lds128(a + KG_BYTES), x2 = lds128(a + 2 * KG_BYTES), x3 = lds128(a + 3 * KG_BYTES);
          auto s4 = [&](uint32_t a0, uint32_t a1, uint32_t a2, uint32_t a3) {
            return __float_as_uint(fmaf(__uint_as_float(a0), i0, __uint_as_float(a1) * i1) +
                                   fmaf(__uint_as_float(a2), i2, __uint_as_float(a3) * i3));
          };
          sts128(a, s4(x0.x, x1.x, x2.x, x3.x), s4(x0.y, x1.y, x2.y, x3.y), s4(x0.z, x1.z, x2.z, x3.z), s4(x0.w, x1.w, x2.w, x3.w));
        }
        __syncwarp();
        const float k1024 = lds_f32(kf + kidx_c(1024) * 4);
        if (lane == 0) {
          sts_f32(kf + SL_ZERO * 4, 0.f);
          sts_f32(kf + SL_510 * 4, lds_f32(kf + kidx_c(510) * 4) - lds_f32(kf + kidx_c(512) * 4));
          sts_f32(kf + SL_0 * 4, lds_f32(kf) + dskip);
        }
        __syncwarp();
        if (tid == 0) TS(36);
        mbar_wait_long(BAR(B_PFREE), 0);
        if (tid == 0) TS(37);
        {
          float prev = 0.f;
#pragma unroll 1
          for (int i0 = 0; i0 < 16; i0 += 4) {
            uint32_t e[4];
            float a[4], b[4];
#pragma unroll
            for (int i = 0; i < 4; ++i) e[i] = lds32(sb + SM_PTAB + ((i0 + i) * 32 + lane) * 4);
#pragma unroll
            for (int i = 0; i < 4; ++i) { a[i] = lds_f32(kf + (e[i] & 0xffff)); b[i] = lds_f32(kf + (e[i] >> 16)); }
#pragma unroll
            for (int i = 0; i < 4; ++i) {
              const uint32_t w = pb + (31 * lane + 2 * (i0 + i)) * 4;
              if (i0 + i > 0) sts32(w - 4, pack_bf16(a[i], prev));
              sts32(w, pack_bf16(b[i], a[i]));
              prev = b[i];
            }
          }
        }
        __syncwarp();
        if (lane == 0) TS(4);
        const int gq = g - 2 * q;
        uint32_t h127, h128;
        {
          const uint32_t kf2 = pack_bf16(k1024, k1024) ^ 0x80008000u;
          h127 = (gq == 4 ? 0x0000ffffu : gq == 5 ? 0xffffffffu : gq == 6 ? 0xffff0000u : 0u) & kf2;
          h128 = (gq == -4 ? 0x0000ffffu : gq == -3 ? 0xffffffffu : gq == -2 ? 0xffff0000u : 0u) & kf2;
        }
        bar_arrive(7, 384);
        if (lane == 0) TS(6);
        bar_sync(4, 384);
        mbar_wait_long(BAR(B_UCH + warp), 0);
        if (lane == 0) TS(7);
        float acc[16][4];
#pragma unroll
        for (int i = 0; i < 16; ++i) { acc[i][0] = acc[i][1] = acc[i][2] = acc[i][3] = 0.f; }
        {
          const uint32_t pd_lane = pb + (PD_OFF + 16 + gq) * 4;
          const int prow0 = 8 + (lane & 7) + ((lane >> 4) << 3), hs = (lane >> 3) & 1;
          const uint32_t zero = (uint32_t)cta >> 20;
          uint32_t B[2][4][4];
          uint32_t A[4][4];
          const uint32_t la0 = ub + prow0 * 32 + ((hs ^ ((prow0 >> 2) & 1)) << 4);
#pragma unroll
          for (int m2 = 0; m2 < 4; ++m2) ldsm_x4(B[0][m2], la0 + m2 * 512);
#pragma unroll
          for (int i = 0; i < 4; ++i) {
            const uint32_t a = pd_lane + i * 512;
            A[i][0] = lds32(a); A[i][1] = lds32(a + 32); A[i][2] = lds32(a - 32); A[i][3] = lds32(a + zero);
          }
          uint32_t la = la0;
#define UNR_RHO 4
#define UNR_TAIL 4
          constexpr int unr_rho = UNR_RHO, unr_tail = UNR_TAIL;
#pragma unroll unr_rho
          for (int rho = 0; rho < 8; ++rho) {
#pragma unroll
            for (int m2 = 0; m2 < 4; ++m2) ldsm_x4(B[1][m2], la + (4 + m2) * 512);
#pragma unroll
            for (int i = 0; i < 4; ++i)
#pragma unroll
              for (int m = 0; m < 8; ++m) mma_bf16v(acc[m + i], A[i], B[0][m >> 1][2 * (m & 1)], B[0][m >> 1][2 * (m & 1) + 1]);
            const int prow = prow0 - min(rho + 1, 7);
            la = ub + prow * 32 + ((hs ^ ((prow >> 2) & 1)) << 4);
#pragma unroll
            for (int m2 = 0; m2 < 4; ++m2) ldsm_x4(B[0][m2], la + m2 * 512);
            const uint32_t pa = pd_lane + (rho + 1) * 64;
#pragma unroll
            for (int i = 0; i < 4; ++i) {
#pragma unroll
              for (int m = 0; m < 8 - i; ++m)
                mma_bf16v(acc[8 + m + i], A[i], B[1][m >> 1][2 * (m & 1)], B[1][m >> 1][2 * (m & 1) + 1]);
              A[i][0] = lds32(pa + i * 512); A[i][1] = lds32(pa + i * 512 + 32); A[i][2] = lds32(pa + i * 512 - 32);
              A[i][3] = lds32(pa + i * 512 + zero);
            }
          }
          if (lane == 0) TS(40);
          {
            uint32_t b8[4];
            ldsm_x4(b8, la + 4 * 512);
            const uint32_t h63 = lds32(pd_lane + 63 * 32), h64 = lds32(pd_lane + 64 * 32);
            const uint32_t a63[4] = {0u, h127, 0u, 0u}, a32[4] = {h64, 0u, h63, h64}, a64[4] = {h128, 0u, h127, h128};
#pragma unroll
            for (int m2 = 0; m2 < 4; ++m2) ldsm_x4(B[1][m2], la0 + m2 * 512);
#pragma unroll
            for (int m = 0; m < 8; ++m) mma_bf16v(acc[m + 7], a63, B[0][m >> 1][2 * (m & 1)], B[0][m >> 1][2 * (m & 1) + 1]);
#pragma unroll
            for (int m2 = 0; m2 < 2; ++m2) ldsm_x4(B[0][m2], la0 + (4 + m2) * 512);
#pragma unroll
            for (int m = 0; m < 8; ++m) mma_bf16v(acc[m + 4], a32, B[1][m >> 1][2 * (m & 1)], B[1][m >> 1][2 * (m & 1) + 1]);
            mma_bf16v(acc[15], a63, b8[0], b8[1]);
#pragma unroll
            for (int m = 0; m < 8; ++m) mma_bf16v(acc[m + 8], a64, B[1][m >> 1][2 * (m & 1)], B[1][m >> 1][2 * (m & 1) + 1]);
#pragma unroll
            for (int m = 0; m < 4; ++m) mma_bf16v(acc[m + 12], a32, B[0][m >> 1][2 * (m & 1)], B[0][m >> 1][2 * (m & 1) + 1]);
          }
          if (lane == 0) TS(41);
          bar_sync(5, 384);
#pragma unroll unr_tail
          for (int v = 0; v < 4; ++v)
            conv_tail<4, 3, 11>(acc, pb + (P2_OFF + 56 * v + gq - 16) * 4, vv + ((v & 1) ? VV_U3 : VV_U5), v >> 1, v == 0, lane);
          if (lane == 0) TS(42);
#pragma unroll unr_tail
          for (int pi = 0; pi < 2; ++pi)
            conv_tail<8, 5, 7>(acc, pb + (P3_OFF + 88 * pi + gq - 48) * 4, vv + (pi ? VV_U7 : VV_U9), pi, pi == 0, lane);
        }
        if (lane == 0) TS(8);
        __syncwarp();
        if (lane < 2) mbar_arrive_cluster(BAR(B_CONVD), lane);
        __syncwarp();
        {
          const int mt = lane >> 3;
          const uint32_t a = pb + (128 * (mt >> 1) + 16 * (lane & 7) + 8 * (mt & 1)) * 2;
#pragma unroll
          for (int ab = 0; ab < 16; ab += 2)
            stsm_x4_t(a + ab * 256, pack_bf16(acc[ab][0], acc[ab][1]), pack_bf16(acc[ab][2], acc[ab][3]),
                      pack_bf16(acc[ab + 1][0], acc[ab + 1][1]), pack_bf16(acc[ab + 1][2], acc[ab + 1][3]));
        }
        fence_async_smem();
        __syncwarp();
        __syncwarp();
        cluster_arrive();
        bar_arrive(3, 384);
        if (elect_one()) {
          bulk_store(p.yT + (size_t)d * 2048, pb, 4096);
          bulk_commit();
          bulk_wait0();
          red_relaxed_add(&g_cnt[(C_Y + (cta >> 4)) * 32], 1);
          TS(9);
        }
        bar_sync(2, 128);
        if (warp == 0 && elect_one()) {
          wait_counter(&g_cnt[(C_Y + tj) * 32], (epoch + 1) * 64);
          TS(28);
          mbar_expect_tx(BAR(B_TILE), 16384);
          tma_load_2d(sb + SM_U, &maps.yT, ti * 128, tj * 64, BAR(B_TILE));
          tma_load_2d(sb + SM_U + 8192, &maps.yT, ti * 128 + 64, tj * 64, BAR(B_TILE));
        }
        __syncwarp();
      }
      mbar_wait_long(BAR(B_TILE), pass);
      if (lane == 0) TS(26 + 3 * pass);
      {
        const int m = lane >> 3, r = lane & 7;
#pragma unroll 2
        for (int it = 0; it < 8; ++it) {
          const int tb = warp * 4 + (it >> 1), cb = (it & 1) * 4 + m;
          const uint32_t at = (tb * 8 + r) * 128 + ((cb ^ r) << 4);
          const uint32_t ac = (tb >> 3) * 8192 + (cb * 8 + r) * 128 + (((tb & 7) ^ (pass ? 0 : tb >> 3) ^ r) << 4);
          uint32_t v[4];
          ldsm_x4_t(v, sb + SM_U + (pass ? ac : at));
          stsm_x4(sb + SM_P + (pass ? at : ac), v[0], v[1], v[2], v[3]);
        }
      }
      if (pass == 0 && tid == 0) TS(35);
      fence_async_smem();
      if (pass == 0) {
        bar_arrive(6, 160);
      } else {
        bar_sync(2, 128);
        if (warp == 0 && elect_one()) {
          tma_store_2d(&maps.out, sb + SM_P, 64 * tj, 128 * ti);
          bulk_commit();
          bulk_wait_read0();
          TS(30);
        }
      }
    }
  } else if (warp < 12) {
    const int w8 = warp - 4;
    const int row = w8 * 16 + (lane & 7) + (((lane >> 3) & 1) << 3);
    uint32_t pq[16];
    {
      float acc[96];
#pragma unroll 1
      for (int ks = 0, s = 0, ph = 0; ks < 16; ++ks) {
        mbar_wait(BAR(B_FULL + s), ph);
        if (tid == 128 && !(ks & 1)) TSR(16, ks == 0 ? 16 : 9 + (ks >> 1) + (ks > 12 ? 43 : 0));
        const uint32_t st = sb + s * STG_BYTES;
        const uint32_t da = mkdesc(st + STG_X + (w8 >> 2) * 4096, 16);
        const uint32_t db = mkdesc(st + STG_W, 2048);
        wg_fence();
        wgmma_n192(acc, da, db, ks != 0);
        wgmma_n192(acc, da + 2, db + 384, 1);
        wg_commit();
        const uint32_t eprev = BAR(B_EMPTY + (s == 0 ? NSTG - 1 : s - 1));
        if (++s == NSTG) { s = 0; ph ^= 1; }
        if (ks > 0) {
          wg_wait<1>();
          if (lane < 2) mbar_arrive_cluster(eprev, lane);
        }
      }
      wg_wait<0>();
      bar_arrive(4, 384);
      if (tid == 128) TS(17);
      auto phi2 = [](float a, float b) -> uint32_t {
        const uint32_t x = pack_bf16(a, b);
        const uint32_t e = pack_bf16(ex2(a * 1.4426950408889634f), ex2(b * 1.4426950408889634f));
        const uint32_t m = __hgt2_mask(*reinterpret_cast<const __nv_bfloat162*>(&x), __floats2bfloat162_rn(0.f, 0.f));
        return badd((badd(x, 0x3f803f80u) & m) | (e & ~m), 0x35863586u);
      };
      uint32_t pk[16];
#pragma unroll
      for (int i = 0; i < 16; ++i) pk[i] = phi2(acc[32 + 2 * i], acc[33 + 2 * i]);
      if (tid == 128) TS(53);
      bar_sync(1, 256);
#pragma unroll
      for (int i = 0; i < 8; i += 2) {
        const uint32_t off = row * 128 + (((i + (lane >> 4)) ^ (row & 7)) << 4);
        stsm_x4(sb + SM_PK + off, pk[2 * i], pk[2 * i + 1], pk[2 * i + 2], pk[2 * i + 3]);
        stsm_x4(sb + SM_VS + off, pack_bf16(acc[64 + 4 * i], acc[65 + 4 * i]), pack_bf16(acc[66 + 4 * i], acc[67 + 4 * i]),
                pack_bf16(acc[68 + 4 * i], acc[69 + 4 * i]), pack_bf16(acc[70 + 4 * i], acc[71 + 4 * i]));
      }
      bar_sync(1, 256);
      {
        const int hh = w8 >> 1, dtile = w8 & 1;
        float kv[2][4] = {{0.f, 0.f, 0.f, 0.f}, {0.f, 0.f, 0.f, 0.f}}, zz[2][4] = {{0.f, 0.f, 0.f, 0.f}, {0.f, 0.f, 0.f, 0.f}};
        const int m = lane >> 3;
        const uint32_t aa = sb + SM_VS + ((lane & 7) + ((m >> 1) << 3)) * 128 + (((2 * hh + (m & 1)) ^ (lane & 7)) << 4);
        const uint32_t ab = sb + SM_PK + (lane & 15) * 128 + (((2 * hh + dtile) ^ (lane & 7)) << 4);
#pragma unroll
        for (int ks = 0; ks < 8; ++ks) {
          uint32_t a[4], b0, b1;
          ldsm_x4_t(a, aa + ks * 2048);
          ldsm_x2_t(b0, b1, ab + ks * 2048);
          mma_bf16(kv[ks & 1], a[0], a[1], a[2], a[3], b0, b1);
          mma_bf16(zz[ks & 1], 0x3f803f80u, 0x3f803f80u, 0x3f803f80u, 0x3f803f80u, b0, b1);
        }
        const uint32_t kp = sb + SM_KV + hh * 1088;
        sts128(kp + dtile * 512 + lane * 16, __float_as_uint(kv[0][0] + kv[1][0]), __float_as_uint(kv[0][1] + kv[1][1]),
               __float_as_uint(kv[0][2] + kv[1][2]), __float_as_uint(kv[0][3] + kv[1][3]));
        if (g == 0) sts_f32x2(kp + 1024 + dtile * 32 + q * 8, zz[0][0] + zz[1][0], zz[0][1] + zz[1][1]);
        fence_async_smem();
        __syncwarp();
        if (lane == 0) mbar_arrive(BAR(B_KVP));
        if (tid == 128) TS(55);
      }
#pragma unroll
      for (int i = 0; i < 16; ++i) pq[i] = phi2(acc[2 * i], acc[2 * i + 1]);
    }
    if (tid == 128) TS(56);
    if (warp == 4) mbar_wait_long(BAR(B_KVF), 0);
    bar_sync(1, 256);
    if (tid == 128) TS(19);
    {
      uint32_t kb[4][6];
#pragma unroll
      for (int h = 0; h < 4; ++h) {
        const uint32_t kp = sb + SM_KV + h * 1088;
        const uint4 k0 = lds128(kp + lane * 16), k1 = lds128(kp + 512 + lane * 16);
        const uint32_t za = kp + 1024 + q * 8;
        auto pk2 = [](uint32_t x, uint32_t y) { return pack_bf16(__uint_as_float(x), __uint_as_float(y)); };
        kb[h][0] = pk2(k0.x, k0.y); kb[h][1] = pk2(k1.x, k1.y); kb[h][2] = pk2(k0.z, k0.w); kb[h][3] = pk2(k1.z, k1.w);
        kb[h][4] = pack_bf16(lds_f32(za), lds_f32(za + 4)); kb[h][5] = pack_bf16(lds_f32(za + 32), lds_f32(za + 36));
      }
#pragma unroll
      for (int h = 0; h < 4; ++h) {
        float n0[4] = {0.f, 0.f, 0.f, 0.f}, n1[4] = {0.f, 0.f, 0.f, 0.f}, dn[4] = {0.f, 0.f, 0.f, 0.f};
        mma_bf16(n0, pq[4 * h], pq[4 * h + 1], pq[4 * h + 2], pq[4 * h + 3], kb[h][0], kb[h][1]);
        mma_bf16(n1, pq[4 * h], pq[4 * h + 1], pq[4 * h + 2], pq[4 * h + 3], kb[h][2], kb[h][3]);
        mma_bf16(dn, pq[4 * h], pq[4 * h + 1], pq[4 * h + 2], pq[4 * h + 3], kb[h][4], kb[h][5]);
        const float r0 = rcp(dn[0] + 1e-6f), r1 = rcp(dn[2] + 1e-6f);
        stsm_x4(sb + SM_QS + row * 128 + (((2 * h + (lane >> 4)) ^ (row & 7)) << 4),
                pack_bf16(n0[0] * r0, n0[1] * r0), pack_bf16(n0[2] * r1, n0[3] * r1),
                pack_bf16(n1[0] * r0, n1[1] * r0), pack_bf16(n1[2] * r1, n1[3] * r1));
      }
    }
    fence_async_smem();
    __syncwarp();
    if (lane == 0) mbar_arrive(BAR(B_OST));
    if (tid == 128) TS(57);
    bar_sync(7, 384);
    if (w8 < 7) box_filters<4>(sb, bars, w8, lane);
    bar_arrive(5, 384);
    if (tid == 128) TS(6);
    bar_sync(3, 384);
    {
      float o[32];
#pragma unroll 1
      for (int c = 0; c < 8; ++c) {
        mbar_wait_long(BAR(B_RF + c), 0);
        if (tid == 128) TSR(22, c == 0 ? 22 : 43 + c);
        const uint32_t da = mkdesc(sb + o_slot(c) + (w8 >> 2) * 8192, 16);
        const uint32_t db = mkdesc(sb + wo_slot(c), 8192);
        wg_fence();
#pragma unroll
        for (int k = 0; k < 4; ++k) wgmma_n64(o, da + 2 * k, db + 128 * k, (c | k) != 0);
        wg_commit();
        if (c == 1) {
          wg_wait<1>();
          if (lane < 2) mbar_arrive_cluster(BAR(B_RE), lane);
          __syncwarp();
          cluster_arrive();
        }
      }
      wg_wait<0>();
      if (tid == 128) TS(51);
#pragma unroll
      for (int i = 0; i < 8; i += 2)
        stsm_x4(sb + SM_BOUT + row * 128 + (((i + (lane >> 4)) ^ (row & 7)) << 4), pack_bf16(o[4 * i], o[4 * i + 1]),
                pack_bf16(o[4 * i + 2], o[4 * i + 3]), pack_bf16(o[4 * i + 4], o[4 * i + 5]), pack_bf16(o[4 * i + 6], o[4 * i + 7]));
      fence_async_smem();
      bar_sync(8 + (w8 >> 2), 128);
      if ((w8 & 3) == 0 && elect_one()) {
        tma_store_2d(&maps.outh, sb + SM_BOUT + (w8 >> 2) * 8192, 512 + 64 * pj, 128 * pi + (w8 >> 2) * 64);
        bulk_commit();
        bulk_wait_read0();
        TS(23);
      }
    }
  } else {
    asm volatile("setmaxnreg.dec.sync.aligned.u32 40;");
    if (warp == 12) {
      if (elect_one()) {
#pragma unroll 1
        for (int ks = NSTG, s = 0, ph = 0; ks < 16; ++ks) {
          mbar_wait(BAR(B_EMPTY + s), ph);
          issue_stage(ks, s);
          if (ks == NSTG) l2_prefetch((const char*)p.wo + (size_t)cta * 4096, 4096);
          if (++s == NSTG) { s = 0; ph ^= 1; }
        }
        mbar_wait(BAR(B_EMPTY + 6), 1);
#pragma unroll 1
        for (int c = 0; c < 5; ++c) {
          mbar_expect_tx(BAR(B_RF + c), 24576);
          tma_load_2d(sb + wo_slot(c), &maps.wo, pj * 64, c * 64, BAR(B_RF + c));
        }
        float* kvg = &g_kv[epoch & 1][tj][0];
        mbar_wait_long(BAR(B_KVP), 0);
        bulk_reduce_add_f32(kvg, sb + SM_KV, 4352);
        bulk_commit();
        bulk_wait0();
        red_relaxed_add(&g_cnt[(C_KV + tj) * 32], 1);
        TS(18);
        wait_counter(&g_cnt[(C_KV + tj) * 32], (epoch + 1) * 16);
        mbar_expect_tx(BAR(B_KVF), 4352);
        bulk_load(sb + SM_KV, kvg, 4352, BAR(B_KVF));
        mbar_wait_long(BAR(B_OST), 0);
        tma_store_2d(&maps.o, sb + SM_QS, tj * 64, ti * 128);
        tma_store_2d(&maps.o, sb + SM_QS + 8192, tj * 64, ti * 128 + 64);
        bulk_commit();
        bulk_wait0();
        red_relaxed_add(&g_cnt[(C_O + ti) * 32], 1);
        TS(20);
        mbar_arrive_cluster(BAR(B_SLOT), 0);
        mbar_arrive_cluster(BAR(B_SLOT), 1);
        wait_counter(&g_cnt[(C_O + pi) * 32], (epoch + 1) * 8);
        if (cta == 0) g_epoch = epoch + 1;
        mbar_wait(BAR(B_SLOT), 0);
        TS(21);
#pragma unroll 1
        for (int c = 0; c < 8; ++c) {
          if (c >= 5) mbar_expect_tx(BAR(B_RF + c), 24576);
          if (c == 6) {
            mbar_wait_long(BAR(B_CONVD), 0);
            tma_load_2d(sb + wo_slot(5), &maps.wo, pj * 64, 5 * 64, BAR(B_RF + 5));
          }
          tma_load_2d_mc(sb + o_slot(c) + rank * 8192, &maps.o, c * 64, pi * 128 + rank * 64, BAR(B_RF + c), 3);
          if (c == 6) tma_load_2d(sb + wo_slot(6), &maps.wo, pj * 64, 6 * 64, BAR(B_RF + 6));
        }
        mbar_wait(BAR(B_RE), 0);
        tma_load_2d(sb + wo_slot(7), &maps.wo, pj * 64, 7 * 64, BAR(B_RF + 7));
      }
    } else if (warp == 13) {
      bar_sync(6, 160);
      sts128(sb + SM_U + (lane >> 4) * U_BYTES + (lane & 15) * 16, 0, 0, 0, 0);
      sts128(sb + SM_U + (2 + (lane >> 4)) * U_BYTES + (lane & 15) * 16, 0, 0, 0, 0);
      __syncwarp();
      if (elect_one()) {
        tma_store_2d(&maps.uT, sb + SM_P, ti * 128, tj * 64);
        tma_store_2d(&maps.uT, sb + SM_P + 8192, ti * 128 + 64, tj * 64);
        bulk_commit();
        bulk_wait_read0();
        mbar_arrive(BAR(B_PFREE));
        bulk_wait0();
        red_relaxed_add(&g_cnt[(C_U + tj) * 32], 1);
        TS(27);
        wait_counter(&g_cnt[(C_U + (cta >> 4)) * 32], (epoch + 1) * 16);
#pragma unroll 1
        for (int c = 0; c < 4; ++c) {
          mbar_expect_tx(BAR(B_UCH + c), 4096);
          bulk_load(sb + SM_U + c * U_BYTES + 256, p.uT + (size_t)(cta * 4 + c) * 2048, 4096, BAR(B_UCH + c));
        }
        TS(3);
      }
      __syncwarp();
      if (ti == 0) {
        float4* z = (float4*)&g_kv[(epoch & 1) ^ 1][tj][0];
#pragma unroll 1
        for (int i = lane; i < 272; i += 32) z[i] = make_float4(0.f, 0.f, 0.f, 0.f);
      }
    }
  }
  __syncwarp();
  if (warp >= 12) cluster_arrive();
  cluster_wait();
  if (tid == 0) TS(31);
#undef BAR
}

typedef CUresult (*EncodeFn)(CUtensorMap*, CUtensorMapDataType, cuuint32_t, void*, const cuuint64_t*, const cuuint64_t*,
                             const cuuint32_t*, const cuuint32_t*, CUtensorMapInterleave, CUtensorMapSwizzle,
                             CUtensorMapL2promotion, CUtensorMapFloatOOBfill);

static void make_map(EncodeFn enc, CUtensorMap* m, const void* base, uint64_t inner, uint64_t outer, uint32_t box_in,
                     uint32_t box_out, CUtensorMapSwizzle swz = CU_TENSOR_MAP_SWIZZLE_128B) {
  cuuint64_t gd[2] = {inner, outer};
  cuuint64_t gs[1] = {inner * 2};
  cuuint32_t bd[2] = {box_in, box_out};
  cuuint32_t es[2] = {1, 1};
  enc(m, CU_TENSOR_MAP_DATA_TYPE_BFLOAT16, 2, const_cast<void*>(base), gd, gs, bd, es, CU_TENSOR_MAP_INTERLEAVE_NONE,
      swz, CU_TENSOR_MAP_L2_PROMOTION_L2_128B, CU_TENSOR_MAP_FLOAT_OOB_FILL_NONE);
}

}

extern "C" void kernel_launch(void* const* d_in, const int* in_sizes, int n_in, void* d_out, int out_size) {
  using namespace s4la;
  (void)in_sizes; (void)n_in; (void)out_size;
  static EncodeFn enc = nullptr;
  static void *uT = nullptr, *yT = nullptr, *oS = nullptr;
  if (!enc) {
    void* fn = nullptr;
    cudaDriverEntryPointQueryResult qr;
    cudaGetDriverEntryPoint("cuTensorMapEncodeTiled", &fn, cudaEnableDefault, &qr);
    enc = (EncodeFn)fn;
    cudaGetSymbolAddress(&uT, g_uT);
    cudaGetSymbolAddress(&yT, g_yT);
    cudaGetSymbolAddress(&oS, g_o);
    cudaFuncSetAttribute(fused_kernel, cudaFuncAttributeMaxDynamicSharedMemorySize, SM_TOTAL);
  }
  const __nv_bfloat16* const* in = (const __nv_bfloat16* const*)d_in;
  Maps maps;
  make_map(enc, &maps.x, in[9], 512, 2048, 32, 128, CU_TENSOR_MAP_SWIZZLE_64B);
  {
    cuuint64_t gd[3] = {512, 512, 3};
    cuuint64_t gs[2] = {3072, 1024};
    cuuint32_t bd[3] = {64, 16, 3};
    cuuint32_t es[3] = {1, 1, 1};
    enc(&maps.w, CU_TENSOR_MAP_DATA_TYPE_BFLOAT16, 3, const_cast<__nv_bfloat16*>(in[10]), gd, gs, bd, es,
        CU_TENSOR_MAP_INTERLEAVE_NONE, CU_TENSOR_MAP_SWIZZLE_128B, CU_TENSOR_MAP_L2_PROMOTION_L2_128B,
        CU_TENSOR_MAP_FLOAT_OOB_FILL_NONE);
  }
  make_map(enc, &maps.wo, in[11], 512, 512, 64, 64);
  make_map(enc, &maps.u, in[0], 512, 2048, 64, 128);
  make_map(enc, &maps.uT, uT, 2048, 512, 64, 64);
  make_map(enc, &maps.yT, yT, 2048, 512, 64, 64);
  make_map(enc, &maps.o, oS, 512, 2048, 64, 64);
  make_map(enc, &maps.out, d_out, 1024, 2048, 64, 128);
  make_map(enc, &maps.outh, d_out, 1024, 2048, 64, 64);
  Ptrs p;
  p.A_re = in[1]; p.A_im = in[2]; p.B_re = in[3]; p.B_im = in[4]; p.C_re = in[5]; p.C_im = in[6];
  p.log_dt = in[7]; p.Dskip = in[8]; p.x = in[9]; p.wqkv = in[10]; p.wo = in[11];
  p.uT = (__nv_bfloat16*)uT; p.yT = (__nv_bfloat16*)yT;
  fused_kernel<<<NCTA, NTHREADS, SM_TOTAL, cudaStreamPerThread>>>(maps, p);
}
```

```cpp
#include <cuda_runtime.h>
#include <cuda_bf16.h>
#include <cuda_fp16.h>
#include <cuda.h>
#include <stdint.h>

#define DEVI __device__ __forceinline__

namespace s4la {

constexpr int NTHREADS = 512;
constexpr int NCTA = 128;

constexpr int NSTG = 7;
constexpr uint32_t STG_BYTES = 20480, STG_X = 0, STG_W = 8192;
constexpr uint32_t SM_QS = 0;
constexpr uint32_t SM_PK = SM_QS + 16384, SM_VS = SM_QS + 32768;
constexpr uint32_t SM_WO = 65536;
constexpr uint32_t SM_KV = 131072;
constexpr uint32_t SM_BOUT = 16384;
constexpr uint32_t SM_U = 143360, U_BYTES = 4352;
constexpr uint32_t SM_P = 160768, P_BYTES = 4096;
constexpr uint32_t SM_VV = 177152, VV_BYTES = 12800;
constexpr uint32_t VV_U5 = 0, VV_U3 = 3712, VV_U9 = 7424, VV_U7 = 10112;
constexpr uint32_t KG_BYTES = 3200;
constexpr uint32_t SM_BAR = SM_VV + 4 * VV_BYTES;
constexpr uint32_t SM_PTAB = SM_BAR + 320;
constexpr uint32_t SM_TOTAL = SM_PTAB + 2048;
static_assert(SM_TOTAL <= 232448, "shared memory");
constexpr int PADV = 12;

enum { B_FULL = 0, B_EMPTY = 7, B_TILE = 14, B_UCH = 15, B_KVP = 19, B_KVF = 20, B_OST = 21, B_RF = 22, B_WO = 30, B_RE = 31, B_PFREE = 32, B_CONVD = 33, B_SLOT = 34, B_COUNT = 35 };
__host__ __device__ constexpr int bar_count(int i) {
  return (i >= B_EMPTY && i < B_TILE) ? 16 : (i == B_KVP || i == B_OST || i == B_CONVD) ? 8 : i == B_RE ? 16 : i == B_SLOT ? 2 : 1;
}

constexpr int PD_OFF = 0, P2_OFF = 544, P3_OFF = 768;

constexpr int SL_K2048 = 20, SL_ZERO = 21, SL_510 = 22, SL_0 = 23;
__host__ __device__ constexpr int koff(int y) {
  return y < 8 ? y : y < 12 ? 256 + 2 * (y - 8) : y < 16 ? 512 + 256 * ((y - 12) >> 1) + 4 * (y & 1) : 1024 + 256 * (y - 16);
}
__host__ __device__ constexpr int kidx_c(int l) {
  const int y = l < 256 ? (l & 7) : l < 512 ? 8 + ((l & 7) >> 1) : l < 1024 ? 12 + (((l - 512) >> 8) << 1) + ((l >> 2) & 1)
                                                                            : 16 + ((l - 1024) >> 8);
  return ((l >> 3) & 31) * 24 + y;
}
constexpr int slot_direct(int l) {
  if (l < 0 || l > 510) return SL_ZERO;
  if (l == 510) return SL_510;
  if (l == 0) return SL_0;
  return kidx_c(l < 256 ? l : ((l + ((l >> 1) & 1)) & ~1));
}
constexpr int slot_seg2(int v, int k) { return (k >= 32 && k < 64) ? kidx_c(16 * k + 4 * v) : SL_ZERO; }
constexpr int slot_seg3(int pi, int k) {
  return (k >= 64 && k < 128) ? kidx_c(16 * k + 8 * pi) : ((k == 128 && pi == 0) ? SL_K2048 : SL_ZERO);
}
constexpr int slot_word(int w) {
  return w < 0 ? SL_ZERO : w < 544 ? slot_direct(w - 16) : w < 768 ? slot_seg2((w - 544) / 56, 16 + (w - 544) % 56)
       : w < 944 ? slot_seg3((w - 768) / 88, 48 + (w - 768) % 88) : SL_ZERO;
}
struct PTab { uint32_t v[512]; };
constexpr PTab make_ptab() {
  PTab t{};
  for (int lane = 0; lane < 32; ++lane)
    for (int i = 0; i < 16; ++i)
      t.v[i * 32 + lane] = (slot_word(31 * lane - 1 + 2 * i) * 4) | ((slot_word(31 * lane + 2 * i) * 4) << 16);
  return t;
}
__device__ const PTab g_ptab = make_ptab();

__device__ __nv_bfloat16 g_uT[512 * 2048];
__device__ __nv_bfloat16 g_yT[512 * 2048];
__device__ __nv_bfloat16 g_o[2048 * 512];
__device__ float g_kv[2][8][4 * 272];
__device__ unsigned g_cnt[64 * 32];
__device__ unsigned g_epoch;
enum { C_U = 0, C_KV = 8, C_O = 16, C_Y = 32 };

struct Maps {
  CUtensorMap x, w, wo, u, uT, yT, o, out, outh;
};
struct Ptrs {
  const __nv_bfloat16 *A_re, *A_im, *B_re, *B_im, *C_re, *C_im, *log_dt, *Dskip;
  const __nv_bfloat16 *x, *wqkv, *wo;
  __nv_bfloat16 *uT, *yT;
};

DEVI uint32_t s2u(const void* p) { return (uint32_t)__cvta_generic_to_shared(p); }
DEVI void mbar_init(uint32_t b, uint32_t c) { asm volatile("mbarrier.init.shared::cta.b64 [%0], %1;" ::"r"(b), "r"(c) : "memory"); }
DEVI void mbar_expect_tx(uint32_t b, uint32_t bytes) {
  asm volatile("mbarrier.arrive.expect_tx.shared::cta.b64 _, [%0], %1;" ::"r"(b), "r"(bytes) : "memory");
}
DEVI void mbar_arrive(uint32_t b) { asm volatile("mbarrier.arrive.shared::cta.b64 _, [%0];" ::"r"(b) : "memory"); }
DEVI void mbar_arrive_cluster(uint32_t b, uint32_t cta) {
  asm volatile("{\n.reg .b32 r;\nmapa.shared::cluster.u32 r, %0, %1;\nmbarrier.arrive.shared::cluster.b64 _, [r];\n}"
               ::"r"(b), "r"(cta) : "memory");
}
DEVI void mbar_wait(uint32_t b, uint32_t parity) {
  asm volatile("{\n.reg .pred p;\nLAB_WAIT:\nmbarrier.try_wait.parity.shared::cta.b64 p, [%0], %1;\n@!p bra LAB_WAIT;\n}"
               ::"r"(b), "r"(parity) : "memory");
}
DEVI void mbar_wait_long(uint32_t b, uint32_t parity) {
  asm volatile("{\n.reg .pred p;\nLAB_WAIT:\nmbarrier.try_wait.parity.shared::cta.b64 p, [%0], %1, 0x989680;\n@!p bra LAB_WAIT;\n}"
               ::"r"(b), "r"(parity) : "memory");
}
DEVI void bar_sync(int id, int n) { asm volatile("bar.sync %0, %1;" ::"r"(id), "r"(n) : "memory"); }
DEVI void bar_arrive(int id, int n) { asm volatile("bar.arrive %0, %1;" ::"r"(id), "r"(n) : "memory"); }
DEVI void fence_async_smem() { asm volatile("fence.proxy.async.shared::cta;" ::: "memory"); }
DEVI void cluster_arrive() { asm volatile("barrier.cluster.arrive.relaxed.aligned;" ::: "memory"); }
DEVI void cluster_wait() { asm volatile("barrier.cluster.wait.aligned;" ::: "memory"); }

DEVI void tma_load_2d(uint32_t dst, const CUtensorMap* m, int c0, int c1, uint32_t bar) {
  asm volatile("cp.async.bulk.tensor.2d.shared::cluster.global.mbarrier::complete_tx::bytes [%0], [%1, {%3, %4}], [%2];"
               ::"r"(dst), "l"(m), "r"(bar), "r"(c0), "r"(c1) : "memory");
}
DEVI void tma_load_2d_mc(uint32_t dst, const CUtensorMap* m, int c0, int c1, uint32_t bar, uint16_t mask) {
  asm volatile("cp.async.bulk.tensor.2d.shared::cluster.global.mbarrier::complete_tx::bytes.multicast::cluster [%0], [%1, {%3, %4}], [%2], %5;"
               ::"r"(dst), "l"(m), "r"(bar), "r"(c0), "r"(c1), "h"(mask) : "memory");
}
DEVI void tma_load_3d_mc(uint32_t dst, const CUtensorMap* m, int c0, int c1, int c2, uint32_t bar, uint16_t mask) {
  asm volatile("cp.async.bulk.tensor.3d.shared::cluster.global.mbarrier::complete_tx::bytes.multicast::cluster [%0], [%1, {%3, %4, %5}], [%2], %6;"
               ::"r"(dst), "l"(m), "r"(bar), "r"(c0), "r"(c1), "r"(c2), "h"(mask) : "memory");
}
DEVI void tma_store_2d(const CUtensorMap* m, uint32_t src, int c0, int c1) {
  asm volatile("cp.async.bulk.tensor.2d.global.shared::cta.bulk_group [%0, {%2, %3}], [%1];"
               ::"l"(m), "r"(src), "r"(c0), "r"(c1) : "memory");
}
DEVI void bulk_load(uint32_t dst, const void* src, uint32_t bytes, uint32_t bar) {
  asm volatile("cp.async.bulk.shared::cluster.global.mbarrier::complete_tx::bytes [%0], [%1], %2, [%3];"
               ::"r"(dst), "l"(src), "r"(bytes), "r"(bar) : "memory");
}
DEVI void bulk_store(void* dst, uint32_t src, uint32_t bytes) {
  asm volatile("cp.async.bulk.global.shared::cta.bulk_group [%0], [%1], %2;" ::"l"(dst), "r"(src), "r"(bytes) : "memory");
}
DEVI void bulk_reduce_add_f32(void* dst, uint32_t src, uint32_t bytes) {
  asm volatile("cp.reduce.async.bulk.global.shared::cta.bulk_group.add.f32 [%0], [%1], %2;" ::"l"(dst), "r"(src), "r"(bytes) : "memory");
}
DEVI void bulk_commit() { asm volatile("cp.async.bulk.commit_group;" ::: "memory"); }
DEVI void bulk_wait0() { asm volatile("cp.async.bulk.wait_group 0;" ::: "memory"); }
DEVI void bulk_wait_read0() { asm volatile("cp.async.bulk.wait_group.read 0;" ::: "memory"); }
DEVI void l2_prefetch(const void* p, uint32_t bytes) {
  asm volatile("cp.async.bulk.prefetch.L2.global [%0], %1;" ::"l"(p), "r"(bytes) : "memory");
}
DEVI void prefetch_tmap(const CUtensorMap* m) { asm volatile("prefetch.tensormap [%0];" ::"l"(m) : "memory"); }

DEVI void red_relaxed_add(unsigned* p, unsigned v) {
  asm volatile("red.relaxed.gpu.global.add.u32 [%0], %1;" ::"l"(p), "r"(v) : "memory");
}
DEVI unsigned ld_relaxed(const unsigned* p) {
  unsigned v;
  asm volatile("ld.relaxed.gpu.global.u32 %0, [%1];" : "=r"(v) : "l"(p) : "memory");
  return v;
}
DEVI void wait_counter(const unsigned* p, unsigned target) {
#pragma unroll 1
  for (int it = 0; (int)(ld_relaxed(p) - target) < 0; ++it)
    if (it > (1 << 22)) __trap();
}

DEVI void ldsm_x4(uint32_t (&r)[4], uint32_t a) {
  asm volatile("ldmatrix.sync.aligned.m8n8.x4.shared.b16 {%0,%1,%2,%3}, [%4];"
               : "=r"(r[0]), "=r"(r[1]), "=r"(r[2]), "=r"(r[3]) : "r"(a) : "memory");
}
DEVI void ldsm_x4_t(uint32_t (&r)[4], uint32_t a) {
  asm volatile("ldmatrix.sync.aligned.m8n8.x4.trans.shared.b16 {%0,%1,%2,%3}, [%4];"
               : "=r"(r[0]), "=r"(r[1]), "=r"(r[2]), "=r"(r[3]) : "r"(a) : "memory");
}
DEVI void ldsm_x2_t(uint32_t& r0, uint32_t& r1, uint32_t a) {
  asm volatile("ldmatrix.sync.aligned.m8n8.x2.trans.shared.b16 {%0,%1}, [%2];" : "=r"(r0), "=r"(r1) : "r"(a) : "memory");
}
DEVI void stsm_x4(uint32_t a, uint32_t r0, uint32_t r1, uint32_t r2, uint32_t r3) {
  asm volatile("stmatrix.sync.aligned.m8n8.x4.shared.b16 [%0], {%1,%2,%3,%4};"
               ::"r"(a), "r"(r0), "r"(r1), "r"(r2), "r"(r3) : "memory");
}
DEVI void stsm_x4_t(uint32_t a, uint32_t r0, uint32_t r1, uint32_t r2, uint32_t r3) {
  asm volatile("stmatrix.sync.aligned.m8n8.x4.trans.shared.b16 [%0], {%1,%2,%3,%4};"
               ::"r"(a), "r"(r0), "r"(r1), "r"(r2), "r"(r3) : "memory");
}
DEVI uint32_t lds32(uint32_t a) { uint32_t v; asm volatile("ld.shared.b32 %0, [%1];" : "=r"(v) : "r"(a) : "memory"); return v; }
DEVI float lds_f32(uint32_t a) { float v; asm volatile("ld.shared.f32 %0, [%1];" : "=f"(v) : "r"(a) : "memory"); return v; }
DEVI void sts32(uint32_t a, uint32_t v) { asm volatile("st.shared.b32 [%0], %1;" ::"r"(a), "r"(v) : "memory"); }
DEVI void sts_f32(uint32_t a, float v) { asm volatile("st.shared.f32 [%0], %1;" ::"r"(a), "f"(v) : "memory"); }
DEVI void sts_f32x2(uint32_t a, float x, float y) { asm volatile("st.shared.v2.f32 [%0], {%1,%2};" ::"r"(a), "f"(x), "f"(y) : "memory"); }
DEVI uint4 lds128(uint32_t a) {
  uint4 v;
  asm volatile("ld.shared.v4.b32 {%0,%1,%2,%3}, [%4];" : "=r"(v.x), "=r"(v.y), "=r"(v.z), "=r"(v.w) : "r"(a) : "memory");
  return v;
}
DEVI void sts128(uint32_t a, uint32_t x, uint32_t y, uint32_t z, uint32_t w) {
  asm volatile("st.shared.v4.b32 [%0], {%1,%2,%3,%4};" ::"r"(a), "r"(x), "r"(y), "r"(z), "r"(w) : "memory");
}

DEVI void mma_bf16(float (&d)[4], uint32_t a0, uint32_t a1, uint32_t a2, uint32_t a3, uint32_t b0, uint32_t b1) {
  asm("mma.sync.aligned.m16n8k16.row.col.f32.bf16.bf16.f32 {%0,%1,%2,%3}, {%4,%5,%6,%7}, {%8,%9}, {%0,%1,%2,%3};"
      : "+f"(d[0]), "+f"(d[1]), "+f"(d[2]), "+f"(d[3])
      : "r"(a0), "r"(a1), "r"(a2), "r"(a3), "r"(b0), "r"(b1));
}
DEVI void mma_f16(float (&d)[4], const uint32_t (&a)[4], uint32_t b0, uint32_t b1) {
  asm("mma.sync.aligned.m16n8k16.row.col.f32.f16.f16.f32 {%0,%1,%2,%3}, {%4,%5,%6,%7}, {%8,%9}, {%0,%1,%2,%3};"
      : "+f"(d[0]), "+f"(d[1]), "+f"(d[2]), "+f"(d[3])
      : "r"(a[0]), "r"(a[1]), "r"(a[2]), "r"(a[3]), "r"(b0), "r"(b1));
}
DEVI void mma_bf16v(float (&d)[4], const uint32_t (&a)[4], uint32_t b0, uint32_t b1) {
  asm volatile("mma.sync.aligned.m16n8k16.row.col.f32.bf16.bf16.f32 {%0,%1,%2,%3}, {%4,%5,%6,%7}, {%8,%9}, {%0,%1,%2,%3};"
               : "+f"(d[0]), "+f"(d[1]), "+f"(d[2]), "+f"(d[3])
               : "r"(a[0]), "r"(a[1]), "r"(a[2]), "r"(a[3]), "r"(b0), "r"(b1));
}
DEVI uint32_t pack_bf16(float lo, float hi) {
  uint32_t r;
  asm("cvt.rn.bf16x2.f32 %0, %1, %2;" : "=r"(r) : "f"(hi), "f"(lo));
  return r;
}
DEVI uint32_t pack_f16(float lo, float hi) {
  uint32_t r;
  asm("cvt.rn.f16x2.f32 %0, %1, %2;" : "=r"(r) : "f"(hi), "f"(lo));
  return r;
}
DEVI uint32_t ldg16(const __nv_bfloat16* p) {
  uint32_t v;
  asm volatile("ld.global.nc.u16 %0, [%1];" : "=r"(v) : "l"(p));
  return v;
}
DEVI bool elect_one() {
  uint32_t pred;
  asm volatile("{\n.reg .pred p;\nelect.sync _|p, 0xffffffff;\nselp.u32 %0, 1, 0, p;\n}" : "=r"(pred));
  return pred != 0;
}
DEVI float bf_lo(uint32_t v) { return __uint_as_float(v << 16); }
DEVI float round_bf16(float v) { return __bfloat162float(__float2bfloat16_rn(v)); }
DEVI float rcp(float x) { float r; asm("rcp.approx.ftz.f32 %0, %1;" : "=f"(r) : "f"(x)); return r; }
DEVI float ex2(float x) { float r; asm("ex2.approx.ftz.f32 %0, %1;" : "=f"(r) : "f"(x)); return r; }

DEVI void wg_fence() { asm volatile("wgmma.fence.sync.aligned;" ::: "memory"); }
DEVI void wg_commit() { asm volatile("wgmma.commit_group.sync.aligned;" ::: "memory"); }
template <int N> DEVI void wg_wait() { asm volatile("wgmma.wait_group.sync.aligned %0;" ::"n"(N) : "memory"); }
constexpr uint32_t DESC_HI = (1u << 30) | (1024 >> 4);
constexpr uint32_t DESC_HI64 = (2u << 30) | (512 >> 4);
DEVI uint32_t mkdesc(uint32_t saddr, uint32_t lbo) { return ((saddr & 0x3FFFF) >> 4) | ((lbo >> 4) << 16); }

DEVI void wgmma_n192(float (&d)[96], uint32_t da, uint32_t db, int scale_d) {
  asm volatile(
      "{\n.reg .pred p;\n.reg .b64 da, db;\nsetp.ne.b32 p, %98, 0;\nmov.b64 da, {%96, %100};\nmov.b64 db, {%97, %99};\n"
      "wgmma.mma_async.sync.aligned.m64n192k16.f32.bf16.bf16 "
      "{%0,%1,%2,%3,%4,%5,%6,%7,%8,%9,%10,%11,%12,%13,%14,%15,"
      "%16,%17,%18,%19,%20,%21,%22,%23,%24,%25,%26,%27,%28,%29,%30,%31,"
      "%32,%33,%34,%35,%36,%37,%38,%39,%40,%41,%42,%43,%44,%45,%46,%47,"
      "%48,%49,%50,%51,%52,%53,%54,%55,%56,%57,%58,%59,%60,%61,%62,%63,"
      "%64,%65,%66,%67,%68,%69,%70,%71,%72,%73,%74,%75,%76,%77,%78,%79,"
      "%80,%81,%82,%83,%84,%85,%86,%87,%88,%89,%90,%91,%92,%93,%94,%95}, "
      "da, db, p, 1, 1, 0, 1;\n}"
      : "+f"(d[0]), "+f"(d[1]), "+f"(d[2]), "+f"(d[3]), "+f"(d[4]), "+f"(d[5]), "+f"(d[6]), "+f"(d[7]),
        "+f"(d[8]), "+f"(d[9]), "+f"(d[10]), "+f"(d[11]), "+f"(d[12]), "+f"(d[13]), "+f"(d[14]), "+f"(d[15]),
        "+f"(d[16]), "+f"(d[17]), "+f"(d[18]), "+f"(d[19]), "+f"(d[20]), "+f"(d[21]), "+f"(d[22]), "+f"(d[23]),
        "+f"(d[24]), "+f"(d[25]), "+f"(d[26]), "+f"(d[27]), "+f"(d[28]), "+f"(d[29]), "+f"(d[30]), "+f"(d[31]),
        "+f"(d[32]), "+f"(d[33]), "+f"(d[34]), "+f"(d[35]), "+f"(d[36]), "+f"(d[37]), "+f"(d[38]), "+f"(d[39]),
        "+f"(d[40]), "+f"(d[41]), "+f"(d[42]), "+f"(d[43]), "+f"(d[44]), "+f"(d[45]), "+f"(d[46]), "+f"(d[47]),
        "+f"(d[48]), "+f"(d[49]), "+f"(d[50]), "+f"(d[51]), "+f"(d[52]), "+f"(d[53]), "+f"(d[54]), "+f"(d[55]),
        "+f"(d[56]), "+f"(d[57]), "+f"(d[58]), "+f"(d[59]), "+f"(d[60]), "+f"(d[61]), "+f"(d[62]), "+f"(d[63]),
        "+f"(d[64]), "+f"(d[65]), "+f"(d[66]), "+f"(d[67]), "+f"(d[68]), "+f"(d[69]), "+f"(d[70]), "+f"(d[71]),
        "+f"(d[72]), "+f"(d[73]), "+f"(d[74]), "+f"(d[75]), "+f"(d[76]), "+f"(d[77]), "+f"(d[78]), "+f"(d[79]),
        "+f"(d[80]), "+f"(d[81]), "+f"(d[82]), "+f"(d[83]), "+f"(d[84]), "+f"(d[85]), "+f"(d[86]), "+f"(d[87]),
        "+f"(d[88]), "+f"(d[89]), "+f"(d[90]), "+f"(d[91]), "+f"(d[92]), "+f"(d[93]), "+f"(d[94]), "+f"(d[95])
      : "r"(da), "r"(db), "r"(scale_d), "n"(DESC_HI), "n"(DESC_HI64));
}
DEVI void wgmma_n64(float (&d)[32], uint32_t da, uint32_t db, int scale_d) {
  asm volatile(
      "{\n.reg .pred p;\n.reg .b64 da, db;\nsetp.ne.b32 p, %34, 0;\nmov.b64 da, {%32, %35};\nmov.b64 db, {%33, %35};\n"
      "wgmma.mma_async.sync.aligned.m64n64k16.f32.bf16.bf16 "
      "{%0,%1,%2,%3,%4,%5,%6,%7,%8,%9,%10,%11,%12,%13,%14,%15,"
      "%16,%17,%18,%19,%20,%21,%22,%23,%24,%25,%26,%27,%28,%29,%30,%31}, "
      "da, db, p, 1, 1, 0, 1;\n}"
      : "+f"(d[0]), "+f"(d[1]), "+f"(d[2]), "+f"(d[3]), "+f"(d[4]), "+f"(d[5]), "+f"(d[6]), "+f"(d[7]),
        "+f"(d[8]), "+f"(d[9]), "+f"(d[10]), "+f"(d[11]), "+f"(d[12]), "+f"(d[13]), "+f"(d[14]), "+f"(d[15]),
        "+f"(d[16]), "+f"(d[17]), "+f"(d[18]), "+f"(d[19]), "+f"(d[20]), "+f"(d[21]), "+f"(d[22]), "+f"(d[23]),
        "+f"(d[24]), "+f"(d[25]), "+f"(d[26]), "+f"(d[27]), "+f"(d[28]), "+f"(d[29]), "+f"(d[30]), "+f"(d[31])
      : "r"(da), "r"(db), "r"(scale_d), "n"(DESC_HI));
}

struct C32 { float re, im; };
DEVI C32 csq(C32 a) { return {a.re * a.re - a.im * a.im, 2.f * a.re * a.im}; }
DEVI C32 cmul(C32 a, C32 b) { return {a.re * b.re - a.im * b.im, a.re * b.im + a.im * b.re}; }
DEVI C32 cfresh(float zl, float zi, float m) {
  float mag = ex2(zl * m), ph = zi * m;
  return {mag * __cosf(ph), mag * __sinf(ph)};
}
struct HMul { uint32_t b, bp; };
DEVI HMul mk_mul(float re, float im) { return {pack_f16(re, im), pack_f16(-im, re)}; }
DEVI uint32_t hcmul(uint32_t a, const HMul& m) {
  __half2 ah = *reinterpret_cast<__half2*>(&a);
  __half2 b = *reinterpret_cast<const __half2*>(&m.b), bp = *reinterpret_cast<const __half2*>(&m.bp);
  __half2 r = __hfma2(__high2half2(ah), bp, __hmul2(__low2half2(ah), b));
  return *reinterpret_cast<uint32_t*>(&r);
}
DEVI uint32_t badd(uint32_t a, uint32_t b) {
  __nv_bfloat162 r = __hadd2(*reinterpret_cast<__nv_bfloat162*>(&a), *reinterpret_cast<__nv_bfloat162*>(&b));
  return *reinterpret_cast<uint32_t*>(&r);
}
template <int MU0, int NMU, int DMAX>
DEVI void conv_tail(float (&acc)[16][4], uint32_t p_lane, uint32_t v_base, int back, bool edge, int lane) {
  const int hsel = (lane >> 3) & 1;
  const int row = (lane & 7) + ((lane >> 4) << 3) + PADV - 8 - (back & (hsel ^ 1));
  const uint32_t la = v_base + row * 32 + (((hsel ^ back) ^ ((row >> 2) & 1)) << 4);
  uint32_t M[3][4];
  ldsm_x4_t(M[0], la);
  ldsm_x4_t(M[1], la + 256);
  uint32_t H[2 * NMU];
#pragma unroll
  for (int i = 0; i < 2 * NMU; ++i) H[i ^ 1] = lds32(p_lane + (uint32_t)(MU0 - 1 + i) * 32);
  if (edge) {
    const uint32_t a[4] = {0u, 0u, M[0][0], M[0][1]};
#pragma unroll
    for (int k = 1; k < NMU; ++k) mma_bf16v(acc[MU0 - 2 + 2 * k], a, H[2 * k], H[2 * k + 1]);
  }
#pragma unroll
  for (int delta = -1; delta <= DMAX; ++delta) {
    if (delta + 2 <= DMAX) ldsm_x4_t(M[(delta + 3) % 3], la + (delta + 3) * 256);
#pragma unroll
    for (int k = 0; k < NMU; ++k)
      if (delta + MU0 + 2 * k < 16) mma_bf16v(acc[delta + MU0 + 2 * k], M[(delta + 1) % 3], H[2 * k], H[2 * k + 1]);
  }
}

template <int NB>
DEVI void box_filters(uint32_t sb, uint32_t bars, int idx, int lane) {
  auto swz = [](int k, int pad) { const int r = (k >> 1) + pad; return (uint32_t)(r * 32 + (((k & 1) ^ ((r >> 2) & 1)) << 4)); };
  const uint32_t o0 = swz(lane - 3, 8), o1 = swz(lane - 2, 8), o2 = swz(lane - 1, 8), ow = swz(lane - 2, PADV), oz = swz(lane - 18, PADV);
  const int k = 32 * idx - 2 + lane;
#pragma unroll 1
  for (int c2 = 0; c2 < 4; c2 += NB) {
    uint4 t[NB][3];
#pragma unroll
    for (int b = 0; b < NB; ++b) mbar_wait_long(bars + 8 * (B_UCH + c2 + b), 0);
#pragma unroll
    for (int b = 0; b < NB; ++b) {
      const uint32_t ua = sb + SM_U + (c2 + b) * U_BYTES + idx * 512;
      t[b][0] = lds128(ua + o0); t[b][1] = lds128(ua + o1); t[b][2] = lds128(ua + o2);
    }
#pragma unroll
    for (int b = 0; b < NB; ++b) {
      const uint32_t vb = sb + SM_VV + (c2 + b) * VV_BYTES, aw = vb + idx * 512 + ow;
      const uint32_t E[12] = {t[b][0].x, t[b][0].y, t[b][0].z, t[b][0].w, t[b][1].x, t[b][1].y, t[b][1].z, t[b][1].w,
                              t[b][2].x, t[b][2].y, t[b][2].z, t[b][2].w};
      uint32_t O[8];
#pragma unroll
      for (int j = 0; j < 8; ++j) O[j] = __byte_perm(E[j + 1], E[j + 2], 0x5432);
      uint32_t s3[6], s5[4], s7[4], s9[4];
#pragma unroll
      for (int j = 0; j < 6; ++j) s3[j] = badd(badd(O[j], O[j + 1]), E[j + 2]);
#pragma unroll
      for (int j = 0; j < 4; ++j) {
        s5[j] = badd(s3[j + 2], badd(E[j + 3], E[j + 5]));
        s7[j] = badd(s5[j], badd(O[j + 1], O[j + 4]));
        s9[j] = badd(s7[j], badd(E[j + 2], E[j + 6]));
      }
      if (k < 208) { sts128(aw + VV_U3, s3[0], s3[1], s3[2], s3[3]); sts128(aw + VV_U5, s5[0], s5[1], s5[2], s5[3]); }
      if (k < 144) { sts128(aw + VV_U7, s7[0], s7[1], s7[2], s7[3]); sts128(aw + VV_U9, s9[0], s9[1], s9[2], s9[3]); }
      if (idx == 0 && lane < 16) {
        sts128(vb + oz + VV_U3, 0, 0, 0, 0); sts128(vb + oz + VV_U5, 0, 0, 0, 0);
        sts128(vb + oz + VV_U7, 0, 0, 0, 0); sts128(vb + oz + VV_U9, 0, 0, 0, 0);
      }
    }
  }
}

__global__ void __cluster_dims__(2, 1, 1) __launch_bounds__(NTHREADS, 1)
fused_kernel(const __grid_constant__ Maps maps, const Ptrs p) {
  extern __shared__ __align__(1024) uint8_t smem[];
  const uint32_t sb = s2u(smem);
  const int tid = threadIdx.x, lane = tid & 31;
  const int warp = __shfl_sync(0xffffffffu, tid >> 5, 0);
  const int cta = blockIdx.x;
  const uint32_t rank = cta & 1;
  const int ti = 2 * (cta >> 4) + rank;
  const int tj = (cta >> 1) & 7;
  const int pi = cta >> 3, pj = cta & 7;
  const uint32_t bars = sb + SM_BAR;
#define BAR(i) (bars + 8 * (i))
  const int g = lane >> 2, q = lane & 3;

  auto issue_stage = [&](int ks, int s) {
    const uint32_t st = sb + s * STG_BYTES, fb = BAR(B_FULL + s);
    mbar_expect_tx(fb, STG_BYTES);
    tma_load_2d(st + STG_X, &maps.x, ks * 32, ti * 128, fb);
    tma_load_3d_mc(st + STG_W + rank * 6144, &maps.w, tj * 64, ks * 32 + rank * 16, 0, fb, 3);
  };

  const int kch = warp & 3, krd = warp >> 2;
  float zr, zi, wr, wi;
  unsigned epoch;
  uint32_t r_dskip;
  {
    const size_t po = (size_t)(cta * 4 + kch) * 128 + krd * 32 + lane;
    const uint32_t r_ar = ldg16(p.A_re + po), r_ai = ldg16(p.A_im + po), r_br = ldg16(p.B_re + po), r_bi = ldg16(p.B_im + po);
    const uint32_t r_cr = ldg16(p.C_re + po), r_ci = ldg16(p.C_im + po), r_ldt = ldg16(p.log_dt + cta * 4 + kch);
    epoch = __ldcg(&g_epoch);
    r_dskip = ldg16(p.Dskip + cta * 4 + kch);
    uint4 pt;
    if (tid < 128) pt = __ldg((const uint4*)g_ptab.v + tid);
    if (tid == 384) {
#pragma unroll
      for (int i = 0; i < B_COUNT; ++i) mbar_init(BAR(i), bar_count(i));
      asm volatile("fence.mbarrier_init.release.cluster;" ::: "memory");
      prefetch_tmap(&maps.x); prefetch_tmap(&maps.w); prefetch_tmap(&maps.u);
    }
    __syncthreads();
    cluster_arrive();
    if (warp >= 12) {
      cluster_wait();
      if (elect_one()) {
        if (warp == 13) {
          mbar_expect_tx(BAR(B_TILE), 16384);
          tma_load_2d(sb + SM_U, &maps.u, tj * 64, ti * 128, BAR(B_TILE));
          prefetch_tmap(&maps.uT); prefetch_tmap(&maps.wo); prefetch_tmap(&maps.o); prefetch_tmap(&maps.yT);
          prefetch_tmap(&maps.out); prefetch_tmap(&maps.outh);
        } else {
          const int ks = warp == 12 ? 0 : warp - 13;
          issue_stage(ks, ks);
        }
      }
      __syncwarp();
    }
    if (tid < 128) sts128(sb + SM_PTAB + tid * 16, pt.x, pt.y, pt.z, pt.w);
    const float dt = round_bf16(expf(bf_lo(r_ldt)));
    zr = dt * bf_lo(r_ar); zi = dt * bf_lo(r_ai);
    const float dbr = dt * bf_lo(r_br), dbi = dt * bf_lo(r_bi), cr = bf_lo(r_cr), ci = bf_lo(r_ci);
    wr = cr * dbr - ci * dbi; wi = cr * dbi + ci * dbr;
  }
  {
    const float mz = __uint_as_float(__reduce_max_sync(0xffffffffu, __float_as_uint(fmaxf(zr, 0.f))));
    const int E = min(max((int)(__reduce_max_sync(0xffffffffu, __float_as_uint(fmaxf(fabsf(wr), fabsf(wi)))) >> 23), 1), 252);
    const float sc = __int_as_float((253 - E) << 23), inv = __int_as_float((E + 1) << 23);
    const float zl = (zr - mz) * 1.4426950408889634f;
    const uint32_t tb = sb + SM_VV + kch * VV_BYTES + krd * KG_BYTES;
    const uint32_t sta = tb + (((lane >> 2) << 4) | ((lane & 3) << 2));
    auto put = [&](int r, uint32_t v) { sts32((sta ^ ((r & 7) << 4)) + r * 128, v); };
    const uint32_t lda = tb + ((lane & 7) + (((lane >> 3) & 1) << 3)) * 128;
    const uint32_t ldb = tb + ((lane & 7) + ((lane >> 4) << 3)) * 128;
    if (warp >= 14 && elect_one()) {
      issue_stage(warp - 11, warp - 11);
      issue_stage(warp - 9, warp - 9);
    }
    __syncwarp();
    C32 e1 = cfresh(zl, zi, 1.f), e2 = csq(e1), e4 = csq(e2), e8 = csq(e4);
    C32 e16 = cfresh(zl, zi, 16.f), e32 = csq(e16), e64 = csq(e32), e128 = csq(e64);
    C32 e256 = cfresh(zl, zi, 256.f), e512 = csq(e256), e1024 = csq(e512), e768 = cmul(e512, e256);
    uint32_t XA[2][4][4];
    {
      const HMul m16 = mk_mul(e16.re, e16.im), m32 = mk_mul(e32.re, e32.im), m64 = mk_mul(e64.re, e64.im);
      const HMul m128 = mk_mul(e128.re, e128.im);
      uint32_t X[16];
      X[0] = 0x00003c00u; X[1] = pack_f16(e8.re, e8.im); X[2] = m16.b; X[4] = m32.b; X[8] = m64.b;
      X[3] = hcmul(X[1], m16); X[5] = hcmul(X[1], m32); X[6] = hcmul(X[2], m32); X[7] = hcmul(X[3], m32);
#pragma unroll
      for (int r = 1; r < 8; ++r) X[8 + r] = hcmul(X[r], m64);
#pragma unroll
      for (int h = 0; h < 2; ++h) {
#pragma unroll
        for (int r = 0; r < 16; ++r) put(r, h == 0 ? X[r] : r == 0 ? m128.b : hcmul(X[r], m128));
        __syncwarp();
#pragma unroll
        for (int k = 0; k < 4; ++k) ldsm_x4(XA[h][k], lda + (((2 * k + (lane >> 4)) ^ (lane & 7)) << 4));
        __syncwarp();
      }
    }
    if (warp >= 14 && elect_one()) {
      if (warp == 14) l2_prefetch((const char*)p.wqkv + 224 * 3072 + cta * 6912, 6912);
      else l2_prefetch((const char*)p.x + (size_t)cta * 16384, 16384);
    }
    __syncwarp();
    float D[2][3][4];
#pragma unroll
    for (int t = 0; t < 6; ++t) D[t / 3][t % 3][0] = D[t / 3][t % 3][1] = D[t / 3][t % 3][2] = D[t / 3][t % 3][3] = 0.f;
    auto contract = [&](int t0, int nt) {
      __syncwarp();
#pragma unroll
      for (int k = 0; k < 4; ++k) {
        uint32_t b[4];
        ldsm_x4(b, ldb + (((2 * k + ((lane >> 3) & 1)) ^ (lane & 7)) << 4));
#pragma unroll
        for (int h = 0; h < 2; ++h) {
          mma_f16(D[h][t0], XA[h][k], b[0], b[1]);
          if (nt == 2) mma_f16(D[h][t0 + 1], XA[h][k], b[2], b[3]);
        }
      }
      __syncwarp();
    };
    const HMul c1 = mk_mul(e1.re, -e1.im), c2 = mk_mul(e2.re, -e2.im), c4 = mk_mul(e4.re, -e4.im);
    const HMul c256 = mk_mul(e256.re, -e256.im), c512 = mk_mul(e512.re, -e512.im), c768 = mk_mul(e768.re, -e768.im);
    const HMul c1024 = mk_mul(e1024.re, -e1024.im);
    uint32_t W[8];
    W[0] = pack_f16(wr * sc, -wi * sc);
    W[1] = hcmul(W[0], c1); W[2] = hcmul(W[0], c2); W[3] = hcmul(W[1], c2);
    W[4] = hcmul(W[0], c4); W[5] = hcmul(W[1], c4); W[6] = hcmul(W[2], c4); W[7] = hcmul(W[3], c4);
#pragma unroll
    for (int i = 0; i < 8; ++i) put(i, W[i]);
#pragma unroll
    for (int i = 0; i < 4; ++i) put(8 + i, hcmul(W[2 * i], c256));
    put(12, hcmul(W[0], c512)); put(13, hcmul(W[4], c512)); put(14, hcmul(W[0], c768)); put(15, hcmul(W[4], c768));
    contract(0, 2);
    const uint32_t v0 = hcmul(W[0], c1024);
    put(0, v0); put(1, hcmul(v0, c256)); put(2, hcmul(v0, c512)); put(3, hcmul(v0, c768)); put(4, hcmul(v0, c1024));
    contract(2, 1);
    const uint32_t a = tb + (g * 24 + 2 * q) * 4;
#pragma unroll
    for (int t = 0; t < 6; ++t) {
      const float(&d)[4] = D[t / 3][t % 3];
      sts_f32x2(a + (t / 3) * 1536 + (t % 3) * 32, d[0], d[1]);
      sts_f32x2(a + (t / 3) * 1536 + (t % 3) * 32 + 768, d[2], d[3]);
    }
    if (lane == 0) sts_f32(tb + 3072, inv);
    if (mz > 0.f) {
      __syncwarp();
#pragma unroll 1
      for (int i = lane; i < 768; i += 32) {
        const int r = i / 24, y = i - 24 * r;
        sts_f32(tb + i * 4, lds_f32(tb + i * 4) * ex2(mz * 1.4426950408889634f * (koff(y) + 8 * r)));
      }
    }
  }
  if (warp < 12) cluster_wait();
  __syncthreads();

  if (warp < 4) {
    asm volatile("setmaxnreg.inc.sync.aligned.u32 200;");
    const int d = cta * 4 + warp;
    const uint32_t vv = sb + SM_VV + warp * VV_BYTES;
    const uint32_t ub = sb + SM_U + warp * U_BYTES;
    const uint32_t pb = sb + SM_P + warp * P_BYTES;
    const float dskip = bf_lo(r_dskip);
#pragma unroll 1
    for (int pass = 0; pass < 2; ++pass) {
      if (pass == 1) {
        const uint32_t kf = vv;
        const float i0 = lds_f32(kf + 3072), i1 = lds_f32(kf + KG_BYTES + 3072), i2 = lds_f32(kf + 2 * KG_BYTES + 3072);
        const float i3 = lds_f32(kf + 3 * KG_BYTES + 3072);
#pragma unroll 2
        for (int i = 0; i < 6; ++i) {
          const uint32_t a = kf + (i * 32 + lane) * 16;
          const uint4 x0 = lds128(a), x1 = lds128(a + KG_BYTES), x2 = lds128(a + 2 * KG_BYTES), x3 = lds128(a + 3 * KG_BYTES);
          auto s4 = [&](uint32_t a0, uint32_t a1, uint32_t a2, uint32_t a3) {
            return __float_as_uint(fmaf(__uint_as_float(a0), i0, __uint_as_float(a1) * i1) +
                                   fmaf(__uint_as_float(a2), i2, __uint_as_float(a3) * i3));
          };
          sts128(a, s4(x0.x, x1.x, x2.x, x3.x), s4(x0.y, x1.y, x2.y, x3.y), s4(x0.z, x1.z, x2.z, x3.z), s4(x0.w, x1.w, x2.w, x3.w));
        }
        __syncwarp();
        const float k1024 = lds_f32(kf + kidx_c(1024) * 4);
        if (lane == 0) {
          sts_f32(kf + SL_ZERO * 4, 0.f);
          sts_f32(kf + SL_510 * 4, lds_f32(kf + kidx_c(510) * 4) - lds_f32(kf + kidx_c(512) * 4));
          sts_f32(kf + SL_0 * 4, lds_f32(kf) + dskip);
        }
        __syncwarp();
        mbar_wait_long(BAR(B_PFREE), 0);
        {
          float prev = 0.f;
#pragma unroll 1
          for (int i0 = 0; i0 < 16; i0 += 4) {
            uint32_t e[4];
            float a[4], b[4];
#pragma unroll
            for (int i = 0; i < 4; ++i) e[i] = lds32(sb + SM_PTAB + ((i0 + i) * 32 + lane) * 4);
#pragma unroll
            for (int i = 0; i < 4; ++i) { a[i] = lds_f32(kf + (e[i] & 0xffff)); b[i] = lds_f32(kf + (e[i] >> 16)); }
#pragma unroll
            for (int i = 0; i < 4; ++i) {
              const uint32_t w = pb + (31 * lane + 2 * (i0 + i)) * 4;
              if (i0 + i > 0) sts32(w - 4, pack_bf16(a[i], prev));
              sts32(w, pack_bf16(b[i], a[i]));
              prev = b[i];
            }
          }
        }
        __syncwarp();
        const int gq = g - 2 * q;
        uint32_t h127, h128;
        {
          const uint32_t kf2 = pack_bf16(k1024, k1024) ^ 0x80008000u;
          h127 = (gq == 4 ? 0x0000ffffu : gq == 5 ? 0xffffffffu : gq == 6 ? 0xffff0000u : 0u) & kf2;
          h128 = (gq == -4 ? 0x0000ffffu : gq == -3 ? 0xffffffffu : gq == -2 ? 0xffff0000u : 0u) & kf2;
        }
        bar_arrive(7, 384);
        bar_sync(4, 384);
        mbar_wait_long(BAR(B_UCH + warp), 0);
        float acc[16][4];
#pragma unroll
        for (int i = 0; i < 16; ++i) { acc[i][0] = acc[i][1] = acc[i][2] = acc[i][3] = 0.f; }
        {
          const uint32_t pd_lane = pb + (PD_OFF + 16 + gq) * 4;
          const int prow0 = 8 + (lane & 7) + ((lane >> 4) << 3), hs = (lane >> 3) & 1;
          const uint32_t zero = (uint32_t)cta >> 20;
          uint32_t B[2][4][4];
          uint32_t A[4][4];
          const uint32_t la0 = ub + prow0 * 32 + ((hs ^ ((prow0 >> 2) & 1)) << 4);
#pragma unroll
          for (int m2 = 0; m2 < 4; ++m2) ldsm_x4(B[0][m2], la0 + m2 * 512);
#pragma unroll
          for (int i = 0; i < 4; ++i) {
            const uint32_t a = pd_lane + i * 512;
            A[i][0] = lds32(a); A[i][1] = lds32(a + 32); A[i][2] = lds32(a - 32); A[i][3] = lds32(a + zero);
          }
          uint32_t la = la0;
#pragma unroll 4
          for (int rho = 0; rho < 8; ++rho) {
#pragma unroll
            for (int m2 = 0; m2 < 4; ++m2) ldsm_x4(B[1][m2], la + (4 + m2) * 512);
#pragma unroll
            for (int i = 0; i < 4; ++i)
#pragma unroll
              for (int m = 0; m < 8; ++m) mma_bf16v(acc[m + i], A[i], B[0][m >> 1][2 * (m & 1)], B[0][m >> 1][2 * (m & 1) + 1]);
            const int prow = prow0 - min(rho + 1, 7);
            la = ub + prow * 32 + ((hs ^ ((prow >> 2) & 1)) << 4);
#pragma unroll
            for (int m2 = 0; m2 < 4; ++m2) ldsm_x4(B[0][m2], la + m2 * 512);
            const uint32_t pa = pd_lane + (rho + 1) * 64;
#pragma unroll
            for (int i = 0; i < 4; ++i) {
#pragma unroll
              for (int m = 0; m < 8 - i; ++m)
                mma_bf16v(acc[8 + m + i], A[i], B[1][m >> 1][2 * (m & 1)], B[1][m >> 1][2 * (m & 1) + 1]);
              A[i][0] = lds32(pa + i * 512); A[i][1] = lds32(pa + i * 512 + 32); A[i][2] = lds32(pa + i * 512 - 32);
              A[i][3] = lds32(pa + i * 512 + zero);
            }
          }
          {
            uint32_t b8[4];
            ldsm_x4(b8, la + 4 * 512);
            const uint32_t h63 = lds32(pd_lane + 63 * 32), h64 = lds32(pd_lane + 64 * 32);
            const uint32_t a63[4] = {0u, h127, 0u, 0u}, a32[4] = {h64, 0u, h63, h64}, a64[4] = {h128, 0u, h127, h128};
#pragma unroll
            for (int m2 = 0; m2 < 4; ++m2) ldsm_x4(B[1][m2], la0 + m2 * 512);
#pragma unroll
            for (int m = 0; m < 8; ++m) mma_bf16v(acc[m + 7], a63, B[0][m >> 1][2 * (m & 1)], B[0][m >> 1][2 * (m & 1) + 1]);
#pragma unroll
            for (int m2 = 0; m2 < 2; ++m2) ldsm_x4(B[0][m2], la0 + (4 + m2) * 512);
#pragma unroll
            for (int m = 0; m < 8; ++m) mma_bf16v(acc[m + 4], a32, B[1][m >> 1][2 * (m & 1)], B[1][m >> 1][2 * (m & 1) + 1]);
            mma_bf16v(acc[15], a63, b8[0], b8[1]);
#pragma unroll
            for (int m = 0; m < 8; ++m) mma_bf16v(acc[m + 8], a64, B[1][m >> 1][2 * (m & 1)], B[1][m >> 1][2 * (m & 1) + 1]);
#pragma unroll
            for (int m = 0; m < 4; ++m) mma_bf16v(acc[m + 12], a32, B[0][m >> 1][2 * (m & 1)], B[0][m >> 1][2 * (m & 1) + 1]);
          }
          bar_sync(5, 384);
#pragma unroll
          for (int v = 0; v < 4; ++v)
            conv_tail<4, 3, 11>(acc, pb + (P2_OFF + 56 * v + gq - 16) * 4, vv + ((v & 1) ? VV_U3 : VV_U5), v >> 1, v == 0, lane);
#pragma unroll
          for (int par = 0; par < 2; ++par)
            conv_tail<8, 5, 7>(acc, pb + (P3_OFF + 88 * par + gq - 48) * 4, vv + (par ? VV_U7 : VV_U9), par, par == 0, lane);
        }
        __syncwarp();
        {
          const int mt = lane >> 3;
          const uint32_t a = pb + (128 * (mt >> 1) + 16 * (lane & 7) + 8 * (mt & 1)) * 2;
#pragma unroll
          for (int ab = 0; ab < 16; ab += 2)
            stsm_x4_t(a + ab * 256, pack_bf16(acc[ab][0], acc[ab][1]), pack_bf16(acc[ab][2], acc[ab][3]),
                      pack_bf16(acc[ab + 1][0], acc[ab + 1][1]), pack_bf16(acc[ab + 1][2], acc[ab + 1][3]));
        }
        fence_async_smem();
        __syncwarp();
        if (lane < 2) mbar_arrive_cluster(BAR(B_CONVD), lane);
        __syncwarp();
        cluster_arrive();
        bar_arrive(3, 384);
        if (elect_one()) {
          bulk_store(p.yT + (size_t)d * 2048, pb, 4096);
          bulk_commit();
          bulk_wait0();
          red_relaxed_add(&g_cnt[(C_Y + (cta >> 4)) * 32], 1);
        }
        bar_sync(2, 128);
        if (warp == 0 && elect_one()) {
          wait_counter(&g_cnt[(C_Y + tj) * 32], (epoch + 1) * 64);
          mbar_expect_tx(BAR(B_TILE), 16384);
          tma_load_2d(sb + SM_U, &maps.yT, ti * 128, tj * 64, BAR(B_TILE));
          tma_load_2d(sb + SM_U + 8192, &maps.yT, ti * 128 + 64, tj * 64, BAR(B_TILE));
        }
        __syncwarp();
      }
      mbar_wait_long(BAR(B_TILE), pass);
      {
        const int m = lane >> 3, r = lane & 7;
#pragma unroll 2
        for (int it = 0; it < 8; ++it) {
          const int tb = warp * 4 + (it >> 1), cb = (it & 1) * 4 + m;
          const uint32_t at = (tb * 8 + r) * 128 + ((cb ^ r) << 4);
          const uint32_t ac = (tb >> 3) * 8192 + (cb * 8 + r) * 128 + (((tb & 7) ^ (pass ? 0 : tb >> 3) ^ r) << 4);
          uint32_t v[4];
          ldsm_x4_t(v, sb + SM_U + (pass ? ac : at));
          stsm_x4(sb + SM_P + (pass ? at : ac), v[0], v[1], v[2], v[3]);
        }
      }
      fence_async_smem();
      if (pass == 0) {
        bar_arrive(6, 160);
      } else {
        bar_sync(2, 128);
        if (warp == 0 && elect_one()) {
          tma_store_2d(&maps.out, sb + SM_P, 64 * tj, 128 * ti);
          bulk_commit();
          bulk_wait_read0();
        }
      }
    }
  } else if (warp < 12) {
    const int w8 = warp - 4;
    const int row = w8 * 16 + (lane & 7) + (((lane >> 3) & 1) << 3);
    uint32_t pq[16];
    {
      float acc[96];
#pragma unroll 1
      for (int ks = 0, s = 0, ph = 0; ks < 16; ++ks) {
        mbar_wait(BAR(B_FULL + s), ph);
        const uint32_t st = sb + s * STG_BYTES;
        const uint32_t da = mkdesc(st + STG_X + (w8 >> 2) * 4096, 16);
        const uint32_t db = mkdesc(st + STG_W, 2048);
        wg_fence();
        wgmma_n192(acc, da, db, ks != 0);
        wgmma_n192(acc, da + 2, db + 384, 1);
        wg_commit();
        const uint32_t eprev = BAR(B_EMPTY + (s == 0 ? NSTG - 1 : s - 1));
        if (++s == NSTG) { s = 0; ph ^= 1; }
        if (ks > 0) {
          wg_wait<1>();
          if (lane < 2) mbar_arrive_cluster(eprev, lane);
        }
      }
      wg_wait<0>();
      bar_arrive(4, 384);
      auto phi2 = [](float a, float b) -> uint32_t {
        const uint32_t x = pack_bf16(a, b);
        const uint32_t e = pack_bf16(ex2(a * 1.4426950408889634f), ex2(b * 1.4426950408889634f));
        const uint32_t m = __hgt2_mask(*reinterpret_cast<const __nv_bfloat162*>(&x), __floats2bfloat162_rn(0.f, 0.f));
        return badd((badd(x, 0x3f803f80u) & m) | (e & ~m), 0x35863586u);
      };
      uint32_t pk[16];
#pragma unroll
      for (int i = 0; i < 16; ++i) pk[i] = phi2(acc[32 + 2 * i], acc[33 + 2 * i]);
      bar_sync(1, 256);
#pragma unroll
      for (int i = 0; i < 8; i += 2) {
        const uint32_t off = row * 128 + (((i + (lane >> 4)) ^ (row & 7)) << 4);
        stsm_x4(sb + SM_PK + off, pk[2 * i], pk[2 * i + 1], pk[2 * i + 2], pk[2 * i + 3]);
        stsm_x4(sb + SM_VS + off, pack_bf16(acc[64 + 4 * i], acc[65 + 4 * i]), pack_bf16(acc[66 + 4 * i], acc[67 + 4 * i]),
                pack_bf16(acc[68 + 4 * i], acc[69 + 4 * i]), pack_bf16(acc[70 + 4 * i], acc[71 + 4 * i]));
      }
      bar_sync(1, 256);
      {
        const int hh = w8 >> 1, dtile = w8 & 1;
        float kv[2][4] = {{0.f, 0.f, 0.f, 0.f}, {0.f, 0.f, 0.f, 0.f}}, zz[2][4] = {{0.f, 0.f, 0.f, 0.f}, {0.f, 0.f, 0.f, 0.f}};
        const int m = lane >> 3;
        const uint32_t aa = sb + SM_VS + ((lane & 7) + ((m >> 1) << 3)) * 128 + (((2 * hh + (m & 1)) ^ (lane & 7)) << 4);
        const uint32_t ab = sb + SM_PK + (lane & 15) * 128 + (((2 * hh + dtile) ^ (lane & 7)) << 4);
#pragma unroll
        for (int ks = 0; ks < 8; ++ks) {
          uint32_t a[4], b0, b1;
          ldsm_x4_t(a, aa + ks * 2048);
          ldsm_x2_t(b0, b1, ab + ks * 2048);
          mma_bf16(kv[ks & 1], a[0], a[1], a[2], a[3], b0, b1);
          mma_bf16(zz[ks & 1], 0x3f803f80u, 0x3f803f80u, 0x3f803f80u, 0x3f803f80u, b0, b1);
        }
        const uint32_t kp = sb + SM_KV + hh * 1088;
        sts128(kp + dtile * 512 + lane * 16, __float_as_uint(kv[0][0] + kv[1][0]), __float_as_uint(kv[0][1] + kv[1][1]),
               __float_as_uint(kv[0][2] + kv[1][2]), __float_as_uint(kv[0][3] + kv[1][3]));
        if (g == 0) sts_f32x2(kp + 1024 + dtile * 32 + q * 8, zz[0][0] + zz[1][0], zz[0][1] + zz[1][1]);
        fence_async_smem();
        __syncwarp();
        if (lane == 0) mbar_arrive(BAR(B_KVP));
      }
#pragma unroll
      for (int i = 0; i < 16; ++i) pq[i] = phi2(acc[2 * i], acc[2 * i + 1]);
    }
    if (warp == 4) mbar_wait_long(BAR(B_KVF), 0);
    bar_sync(1, 256);
    {
      uint32_t kb[4][6];
#pragma unroll
      for (int h = 0; h < 4; ++h) {
        const uint32_t kp = sb + SM_KV + h * 1088;
        const uint4 k0 = lds128(kp + lane * 16), k1 = lds128(kp + 512 + lane * 16);
        const uint32_t za = kp + 1024 + q * 8;
        auto pk2 = [](uint32_t x, uint32_t y) { return pack_bf16(__uint_as_float(x), __uint_as_float(y)); };
        kb[h][0] = pk2(k0.x, k0.y); kb[h][1] = pk2(k1.x, k1.y); kb[h][2] = pk2(k0.z, k0.w); kb[h][3] = pk2(k1.z, k1.w);
        kb[h][4] = pack_bf16(lds_f32(za), lds_f32(za + 4)); kb[h][5] = pack_bf16(lds_f32(za + 32), lds_f32(za + 36));
      }
#pragma unroll
      for (int h = 0; h < 4; ++h) {
        float n0[4] = {0.f, 0.f, 0.f, 0.f}, n1[4] = {0.f, 0.f, 0.f, 0.f}, dn[4] = {0.f, 0.f, 0.f, 0.f};
        mma_bf16(n0, pq[4 * h], pq[4 * h + 1], pq[4 * h + 2], pq[4 * h + 3], kb[h][0], kb[h][1]);
        mma_bf16(n1, pq[4 * h], pq[4 * h + 1], pq[4 * h + 2], pq[4 * h + 3], kb[h][2], kb[h][3]);
        mma_bf16(dn, pq[4 * h], pq[4 * h + 1], pq[4 * h + 2], pq[4 * h + 3], kb[h][4], kb[h][5]);
        const float r0 = rcp(dn[0] + 1e-6f), r1 = rcp(dn[2] + 1e-6f);
        stsm_x4(sb + SM_QS + row * 128 + (((2 * h + (lane >> 4)) ^ (row & 7)) << 4),
                pack_bf16(n0[0] * r0, n0[1] * r0), pack_bf16(n0[2] * r1, n0[3] * r1),
                pack_bf16(n1[0] * r0, n1[1] * r0), pack_bf16(n1[2] * r1, n1[3] * r1));
      }
    }
    fence_async_smem();
    __syncwarp();
    if (lane == 0) mbar_arrive(BAR(B_OST));
    bar_sync(7, 384);
    if (w8 < 7) box_filters<4>(sb, bars, w8, lane);
    bar_arrive(5, 384);
    if (warp == 4) mbar_wait_long(BAR(B_WO), 0);
    bar_sync(3, 384);
    {
      float o[32];
#pragma unroll 1
      for (int c = 0; c < 8; ++c) {
        mbar_wait_long(BAR(B_RF + c), 0);
        const uint32_t slot = c < 4 ? SM_QS + c * 16384 : c < 7 ? SM_VV + (c - 4) * 16384 : SM_QS;
        const uint32_t da = mkdesc(sb + slot + (w8 >> 2) * 8192, 16);
        const uint32_t db = mkdesc(sb + SM_WO + c * 8192, 8192);
        wg_fence();
#pragma unroll
        for (int k = 0; k < 4; ++k) wgmma_n64(o, da + 2 * k, db + 128 * k, (c | k) != 0);
        wg_commit();
        if (c == 1) {
          wg_wait<1>();
          if (lane < 2) mbar_arrive_cluster(BAR(B_RE), lane);
          __syncwarp();
          cluster_arrive();
        }
      }
      wg_wait<0>();
#pragma unroll
      for (int i = 0; i < 8; i += 2)
        stsm_x4(sb + SM_BOUT + row * 128 + (((i + (lane >> 4)) ^ (row & 7)) << 4), pack_bf16(o[4 * i], o[4 * i + 1]),
                pack_bf16(o[4 * i + 2], o[4 * i + 3]), pack_bf16(o[4 * i + 4], o[4 * i + 5]), pack_bf16(o[4 * i + 6], o[4 * i + 7]));
      fence_async_smem();
      bar_sync(8 + (w8 >> 2), 128);
      if ((w8 & 3) == 0 && elect_one()) {
        tma_store_2d(&maps.outh, sb + SM_BOUT + (w8 >> 2) * 8192, 512 + 64 * pj, 128 * pi + (w8 >> 2) * 64);
        bulk_commit();
        bulk_wait_read0();
      }
    }
  } else {
    asm volatile("setmaxnreg.dec.sync.aligned.u32 40;");
    if (warp == 12) {
      if (elect_one()) {
#pragma unroll 1
        for (int ks = NSTG, s = 0, ph = 0; ks < 16; ++ks) {
          mbar_wait(BAR(B_EMPTY + s), ph);
          issue_stage(ks, s);
          if (ks == NSTG) l2_prefetch((const char*)p.wo + (size_t)cta * 4096, 4096);
          if (++s == NSTG) { s = 0; ph ^= 1; }
        }
        mbar_wait(BAR(B_EMPTY + 6), 1);
        mbar_expect_tx(BAR(B_WO), 65536);
        tma_load_2d(sb + SM_WO, &maps.wo, pj * 64, 0, BAR(B_WO));
        tma_load_2d(sb + SM_WO + 32768, &maps.wo, pj * 64, 256, BAR(B_WO));
        float* kvg = &g_kv[epoch & 1][tj][0];
        mbar_wait_long(BAR(B_KVP), 0);
        bulk_reduce_add_f32(kvg, sb + SM_KV, 4352);
        bulk_commit();
        bulk_wait0();
        red_relaxed_add(&g_cnt[(C_KV + tj) * 32], 1);
        wait_counter(&g_cnt[(C_KV + tj) * 32], (epoch + 1) * 16);
        mbar_expect_tx(BAR(B_KVF), 4352);
        bulk_load(sb + SM_KV, kvg, 4352, BAR(B_KVF));
        mbar_wait_long(BAR(B_OST), 0);
        tma_store_2d(&maps.o, sb + SM_QS, tj * 64, ti * 128);
        tma_store_2d(&maps.o, sb + SM_QS + 8192, tj * 64, ti * 128 + 64);
        bulk_commit();
        bulk_wait0();
        red_relaxed_add(&g_cnt[(C_O + ti) * 32], 1);
        mbar_arrive_cluster(BAR(B_SLOT), 0);
        mbar_arrive_cluster(BAR(B_SLOT), 1);
        wait_counter(&g_cnt[(C_O + pi) * 32], (epoch + 1) * 8);
        if (cta == 0) g_epoch = epoch + 1;
        mbar_wait(BAR(B_SLOT), 0);
#pragma unroll 1
        for (int c = 0; c < 8; ++c) {
          if (c == 4) mbar_wait_long(BAR(B_CONVD), 0);
          if (c == 7) mbar_wait(BAR(B_RE), 0);
          const uint32_t slot = c < 4 ? SM_QS + c * 16384 : c < 7 ? SM_VV + (c - 4) * 16384 : SM_QS;
          mbar_expect_tx(BAR(B_RF + c), 16384);
          tma_load_2d_mc(sb + slot + rank * 8192, &maps.o, c * 64, pi * 128 + rank * 64, BAR(B_RF + c), 3);
        }
      }
    } else if (warp == 13) {
      bar_sync(6, 160);
      sts128(sb + SM_U + (lane >> 4) * U_BYTES + (lane & 15) * 16, 0, 0, 0, 0);
      sts128(sb + SM_U + (2 + (lane >> 4)) * U_BYTES + (lane & 15) * 16, 0, 0, 0, 0);
      __syncwarp();
      if (elect_one()) {
        tma_store_2d(&maps.uT, sb + SM_P, ti * 128, tj * 64);
        tma_store_2d(&maps.uT, sb + SM_P + 8192, ti * 128 + 64, tj * 64);
        bulk_commit();
        bulk_wait_read0();
        mbar_arrive(BAR(B_PFREE));
        bulk_wait0();
        red_relaxed_add(&g_cnt[(C_U + tj) * 32], 1);
        wait_counter(&g_cnt[(C_U + (cta >> 4)) * 32], (epoch + 1) * 16);
#pragma unroll 1
        for (int c = 0; c < 4; ++c) {
          mbar_expect_tx(BAR(B_UCH + c), 4096);
          bulk_load(sb + SM_U + c * U_BYTES + 256, p.uT + (size_t)(cta * 4 + c) * 2048, 4096, BAR(B_UCH + c));
        }
      }
      __syncwarp();
      if (ti == 0) {
        float4* z = (float4*)&g_kv[(epoch & 1) ^ 1][tj][0];
#pragma unroll 1
        for (int i = lane; i < 272; i += 32) z[i] = make_float4(0.f, 0.f, 0.f, 0.f);
      }
    }
  }
  __syncwarp();
  if (warp >= 12) cluster_arrive();
  cluster_wait();
#undef BAR
}

typedef CUresult (*EncodeFn)(CUtensorMap*, CUtensorMapDataType, cuuint32_t, void*, const cuuint64_t*, const cuuint64_t*,
                             const cuuint32_t*, const cuuint32_t*, CUtensorMapInterleave, CUtensorMapSwizzle,
                             CUtensorMapL2promotion, CUtensorMapFloatOOBfill);

static void make_map(EncodeFn enc, CUtensorMap* m, const void* base, uint64_t inner, uint64_t outer, uint32_t box_in,
                     uint32_t box_out, CUtensorMapSwizzle swz = CU_TENSOR_MAP_SWIZZLE_128B) {
  cuuint64_t gd[2] = {inner, outer};
  cuuint64_t gs[1] = {inner * 2};
  cuuint32_t bd[2] = {box_in, box_out};
  cuuint32_t es[2] = {1, 1};
  enc(m, CU_TENSOR_MAP_DATA_TYPE_BFLOAT16, 2, const_cast<void*>(base), gd, gs, bd, es, CU_TENSOR_MAP_INTERLEAVE_NONE,
      swz, CU_TENSOR_MAP_L2_PROMOTION_L2_128B, CU_TENSOR_MAP_FLOAT_OOB_FILL_NONE);
}

}

extern "C" void kernel_launch(void* const* d_in, const int* in_sizes, int n_in, void* d_out, int out_size) {
  using namespace s4la;
  (void)in_sizes; (void)n_in; (void)out_size;
  static EncodeFn enc = nullptr;
  static void *uT = nullptr, *yT = nullptr, *oS = nullptr;
  if (!enc) {
    void* fn = nullptr;
    cudaDriverEntryPointQueryResult qr;
    cudaGetDriverEntryPoint("cuTensorMapEncodeTiled", &fn, cudaEnableDefault, &qr);
    enc = (EncodeFn)fn;
    cudaGetSymbolAddress(&uT, g_uT);
    cudaGetSymbolAddress(&yT, g_yT);
    cudaGetSymbolAddress(&oS, g_o);
    cudaFuncSetAttribute(fused_kernel, cudaFuncAttributeMaxDynamicSharedMemorySize, SM_TOTAL);
  }
  const __nv_bfloat16* const* in = (const __nv_bfloat16* const*)d_in;
  Maps maps;
  make_map(enc, &maps.x, in[9], 512, 2048, 32, 128, CU_TENSOR_MAP_SWIZZLE_64B);
  {
    cuuint64_t gd[3] = {512, 512, 3};
    cuuint64_t gs[2] = {3072, 1024};
    cuuint32_t bd[3] = {64, 16, 3};
    cuuint32_t es[3] = {1, 1, 1};
    enc(&maps.w, CU_TENSOR_MAP_DATA_TYPE_BFLOAT16, 3, const_cast<__nv_bfloat16*>(in[10]), gd, gs, bd, es,
        CU_TENSOR_MAP_INTERLEAVE_NONE, CU_TENSOR_MAP_SWIZZLE_128B, CU_TENSOR_MAP_L2_PROMOTION_L2_128B,
        CU_TENSOR_MAP_FLOAT_OOB_FILL_NONE);
  }
  make_map(enc, &maps.wo, in[11], 512, 512, 64, 256);
  make_map(enc, &maps.u, in[0], 512, 2048, 64, 128);
  make_map(enc, &maps.uT, uT, 2048, 512, 64, 64);
  make_map(enc, &maps.yT, yT, 2048, 512, 64, 64);
  make_map(enc, &maps.o, oS, 512, 2048, 64, 64);
  make_map(enc, &maps.out, d_out, 1024, 2048, 64, 128);
  make_map(enc, &maps.outh, d_out, 1024, 2048, 64, 64);
  Ptrs p;
  p.A_re = in[1]; p.A_im = in[2]; p.B_re = in[3]; p.B_im = in[4]; p.C_re = in[5]; p.C_im = in[6];
  p.log_dt = in[7]; p.Dskip = in[8]; p.x = in[9]; p.wqkv = in[10]; p.wo = in[11];
  p.uT = (__nv_bfloat16*)uT; p.yT = (__nv_bfloat16*)yT;
  fused_kernel<<<NCTA, NTHREADS, SM_TOTAL, cudaStreamPerThread>>>(maps, p);
}
```
